```python
import torch

def _softmax(x, axis=-1):
    return torch.softmax(x, dim=axis)
def _gelu(x):
    return torch.nn.functional.gelu(x, approximate="tanh")
def _silu(x):
    return torch.nn.functional.silu(x)
def _sigmoid(x):
    return torch.sigmoid(x)
def _layernorm(x, axis=-1, eps=1e-5):
    m = x.mean(dim=axis, keepdim=True)
    v = x.var(dim=axis, keepdim=True, unbiased=False)
    return (x - m) / torch.sqrt(v + eps)
def _scatter_add(tgt, idx, src, axis=0):
    return tgt.clone().index_add_(axis, idx, src)
def _segment_sum(src, seg, n):
    out = torch.zeros((n,) + src.shape[1:], dtype=src.dtype)
    return out.index_add_(0, seg, src)
def _pad(x, pw):
    flat = tuple(v for pair in reversed(pw) for v in pair)
    return torch.nn.functional.pad(x, flat)

kernel_name = 'sequential_preLN__sliding_local_dilated__mixer_token_mlp__prompt'

def setup_inputs():

    _w = (lambda a: (lambda t: t.to(torch.bfloat16) if t.is_floating_point() else t)(torch.as_tensor(a)))
    def _A_setup():
        B, S, D = 1, 2048, 448
        return {
            "x": _w((lambda *s: torch.randn(*s, dtype=torch.bfloat16) * 0.05)(B, S, D)),
            "wqkv": _w((lambda *s: torch.randn(*s, dtype=torch.bfloat16) * 0.05)(D, 3 * D)),
            "wo": _w((lambda *s: torch.randn(*s, dtype=torch.bfloat16) * 0.05)(D, D)),
        }
    _A_in = _A_setup()

    def _B_setup():
        B, S, D, F = 1, 2048, 448, 1792
        return {
            "x": _w((lambda *s: torch.randn(*s, dtype=torch.bfloat16) * 0.05)(B, S, D)),
            "w1": _w((lambda *s: torch.randn(*s, dtype=torch.bfloat16) * 1.6)(S, F) * (S ** -0.5)),
            "b1": _w((lambda *s: torch.randn(*s, dtype=torch.bfloat16) * 12.8)(F) * 0.02),
            "w2": _w((lambda *s: torch.randn(*s, dtype=torch.bfloat16) * 0.4)(F, S) * (F ** -0.5)),
            "b2": _w((lambda *s: torch.randn(*s, dtype=torch.bfloat16) * 6.4)(S) * 0.02),
        }
    _B_in = _B_setup()

    return {
        "A_x": _A_in["x"],
        "A_wqkv": _A_in["wqkv"],
        "A_wo": _A_in["wo"],
        "B_x": _B_in["x"],
        "B_w1": _B_in["w1"],
        "B_b1": _B_in["b1"],
        "B_w2": _B_in["w2"],
        "B_b2": _B_in["b2"],
    }

def reference(A_x, A_wqkv, A_wo, B_x, B_w1, B_b1, B_w2, B_b2):
    def _A_ref(x, wqkv, wo):
        B, S, D = x.shape
        H = 16; Dh = D // H
        W, dil = 8, 2
        qkv = (lambda x, *d: x.permute(*d))((x @ wqkv).reshape(B, S, 3, H, Dh), 2, 0, 3, 1, 4)
        q, k, v = qkv[0], qkv[1], qkv[2]
        scale = Dh ** -0.5
        pos = torch.arange(S)
        off = torch.arange(W) * dil
        idx = pos[:, None] - off[None, :]
        mask = idx >= 0
        idx_c = torch.where(mask, idx, 0).reshape(-1)
        kg = k[:, :, idx_c, :].reshape(B, H, S, W, Dh)
        vg = v[:, :, idx_c, :].reshape(B, H, S, W, Dh)
        logits = torch.einsum("bhsd,bhswd->bhsw", q, kg) * scale
        logits = torch.where(mask[None, None, :, :], logits, -1e9)
        attn = _softmax(logits, axis=-1)
        o = torch.einsum("bhsw,bhswd->bhsd", attn, vg)
        return (lambda x, *d: x.permute(*d))(o, 0, 2, 1, 3).reshape(B, S, D) @ wo

    def _B_ref(x, w1, b1, w2, b2):
        B, S, D = x.shape
        h = _layernorm(x, axis=-1)
        u = torch.einsum("bsd,sf->bdf", h, w1) + b1
        u = _gelu(u)
        y = torch.einsum("bdf,fs->bds", u, w2) + b2
        return (lambda x, *d: x.permute(*d))(y, 0, 2, 1)

    x = A_x
    h = x + _A_ref(_layernorm(x, axis=-1), A_wqkv, A_wo)
    h2 = h + _B_ref(_layernorm(h, axis=-1), B_w1, B_b1, B_w2, B_b2)
    return h2
```

```cpp
#include <cuda_runtime.h>
#include <cuda_bf16.h>
#include <cuda.h>
#include <stdint.h>

namespace {

constexpr int D_ = 448;
constexpr float LN_EPS = 1e-5f;

__device__ __align__(1024) uint32_t g_o[32 * 57344 / 4];
__device__ __align__(1024) uint32_t g_hn[4 * 32 * 14336 / 4];
__device__ __align__(1024) uint32_t g_u[4 * 28 * 14336 / 4];
__device__ __align__(1024) uint4 g_halo[128 * 2 * 7 * 32];
__device__ __align__(1024) uint4 g_stats[32 * 4 * 64];
__device__ __align__(1024) uint2 g_cs[1344];
__device__ __align__(1024) uint32_t g_cnt_o[32 * 32];
__device__ __align__(1024) uint32_t g_flag_h[4 * 32];
__device__ __align__(1024) uint32_t g_flag_u[4 * 32];
__device__ __align__(1024) uint32_t g_epoch[160];
#define STAMP(i) do {} while (0)

constexpr uint32_t SB = 1024;
constexpr int SM_STAGE = 32768;
constexpr int SM_HALO = 196608;
constexpr int SM_CS = SM_HALO + 16384;
#define NA_SLOTS 6
#define NB_SLOTS 8
constexpr int SM_ARING = 0;
constexpr int SM_BRING = NA_SLOTS * 16384;
constexpr int SM_H = 217088;
static_assert(SM_BRING + NB_SLOTS * 14336 <= SM_H, "smem");
constexpr int SM_BAR = 231424;
constexpr int SM_TOTAL = 232448;
constexpr int B_FULL1 = 0;
constexpr int B_DONE1 = 7;
constexpr int B_FULLQ = 14;
constexpr int B_DONEQ = 16;
constexpr int B_FULLWO = 17;
constexpr int B_FULLO = 18;
constexpr int B_DONEO = 22;
constexpr int B_CS = 23;
constexpr int B_FULLA = 24;
constexpr int B_FULLB = 40;
constexpr int B_DONE = 72;
constexpr int B_END = 104;
constexpr int N_BARS = 105;

constexpr long long WD_CLKS = 2000000000ll;

__device__ __forceinline__ uint32_t smem_u32(const void* p) { return (uint32_t)__cvta_generic_to_shared(p); }
__device__ __forceinline__ void mbar_init(uint32_t bar, uint32_t cnt) { asm volatile("mbarrier.init.shared::cta.b64 [%0], %1;" :: "r"(bar), "r"(cnt) : "memory"); }
__device__ __forceinline__ void mbar_expect(uint32_t bar, uint32_t bytes) { asm volatile("mbarrier.arrive.expect_tx.shared::cta.b64 _, [%0], %1;" :: "r"(bar), "r"(bytes) : "memory"); }
__device__ __forceinline__ void mbar_arrive(uint32_t bar) { asm volatile("mbarrier.arrive.shared::cta.b64 _, [%0];" :: "r"(bar) : "memory"); }
__device__ __forceinline__ bool mbar_try(uint32_t bar, uint32_t parity) {
    uint32_t ok;
    asm volatile("{\n.reg .pred p;\nmbarrier.try_wait.parity.shared::cta.b64 p, [%1], %2;\nselp.u32 %0, 1, 0, p;\n}" : "=r"(ok) : "r"(bar), "r"(parity) : "memory");
    return ok;
}
__device__ __forceinline__ void mbar_wait(uint32_t bar, uint32_t parity) {
    asm volatile("{\n.reg .pred p;\n"
                 "WAIT_LOOP:\n"
                 "mbarrier.try_wait.parity.shared::cta.b64 p, [%0], %1;\n"
                 "@!p bra WAIT_LOOP;\n}" :: "r"(bar), "r"(parity) : "memory");
}
__device__ __forceinline__ void mbar_wait_wd(uint32_t bar, uint32_t parity) {
    const long long t0 = clock64();
    while (!mbar_try(bar, parity)) { if (clock64() - t0 > WD_CLKS) __trap(); }
}
__device__ __forceinline__ bool elect() { uint32_t p; asm volatile("{\n.reg .pred P;\nelect.sync _|P, 0xffffffff;\nselp.u32 %0, 1, 0, P;\n}" : "=r"(p)); return p; }
__device__ __forceinline__ void tma2d(uint32_t dst, const CUtensorMap* tm, int c0, int c1, uint32_t bar) {
    asm volatile("cp.async.bulk.tensor.2d.shared::cluster.global.mbarrier::complete_tx::bytes [%0], [%1, {%3, %4}], [%2];" :: "r"(dst), "l"(tm), "r"(bar), "r"(c0), "r"(c1) : "memory");
}
__device__ __forceinline__ void tma3d(uint32_t dst, const CUtensorMap* tm, int c0, int c1, int c2, uint32_t bar) {
    asm volatile("cp.async.bulk.tensor.3d.shared::cluster.global.mbarrier::complete_tx::bytes [%0], [%1, {%3, %4, %5}], [%2];" :: "r"(dst), "l"(tm), "r"(bar), "r"(c0), "r"(c1), "r"(c2) : "memory");
}
__device__ __forceinline__ void tma2d_store(const CUtensorMap* tm, int c0, int c1, uint32_t src) {
    asm volatile("cp.async.bulk.tensor.2d.global.shared::cta.bulk_group [%0, {%2, %3}], [%1];" :: "l"(tm), "r"(src), "r"(c0), "r"(c1) : "memory");
}
__device__ __forceinline__ void bulk_ld(uint32_t dst, const void* src, uint32_t bytes, uint32_t bar) {
    asm volatile("cp.async.bulk.shared::cluster.global.mbarrier::complete_tx::bytes [%0], [%1], %2, [%3];" :: "r"(dst), "l"(src), "r"(bytes), "r"(bar) : "memory");
}
__device__ __forceinline__ void bulk_prefetch(const void* src, uint32_t bytes) { asm volatile("cp.async.bulk.prefetch.L2.global [%0], %1;" :: "l"(src), "r"(bytes) : "memory"); }
__device__ __forceinline__ void fence_async_global() { asm volatile("fence.proxy.async.global;" ::: "memory"); }
__device__ __forceinline__ void fence_async_smem() { asm volatile("fence.proxy.async.shared::cta;" ::: "memory"); }
__device__ __forceinline__ uint32_t ld_acquire(const uint32_t* p) { uint32_t v; asm volatile("ld.acquire.gpu.global.u32 %0, [%1];" : "=r"(v) : "l"(p) : "memory"); return v; }
__device__ __forceinline__ void red_release(uint32_t* p) { asm volatile("red.release.gpu.global.add.u32 [%0], 1;" :: "l"(p) : "memory"); }
__device__ __forceinline__ uint4 ld_relaxed4(const uint4* p) { uint4 v; asm volatile("ld.relaxed.gpu.global.v4.u32 {%0,%1,%2,%3}, [%4];" : "=r"(v.x), "=r"(v.y), "=r"(v.z), "=r"(v.w) : "l"(p) : "memory"); return v; }
__device__ __forceinline__ uint2 ld_relaxed2(const uint2* p) { uint2 v; asm volatile("ld.relaxed.gpu.global.v2.u32 {%0,%1}, [%2];" : "=r"(v.x), "=r"(v.y) : "l"(p) : "memory"); return v; }
__device__ __forceinline__ void st_relaxed4(uint4* p, uint32_t a, uint32_t b, uint32_t c, uint32_t d) { asm volatile("st.relaxed.gpu.global.v4.u32 [%0], {%1,%2,%3,%4};" :: "l"(p), "r"(a), "r"(b), "r"(c), "r"(d) : "memory"); }
__device__ __forceinline__ void st_relaxed2(uint2* p, uint32_t a, uint32_t b) { asm volatile("st.relaxed.gpu.global.v2.u32 [%0], {%1,%2};" :: "l"(p), "r"(a), "r"(b) : "memory"); }
__device__ __forceinline__ uint32_t ld_volatile(const uint32_t* p) { uint32_t v; asm volatile("ld.volatile.global.u32 %0, [%1];" : "=r"(v) : "l"(p) : "memory"); return v; }
__device__ __forceinline__ void named_arrive(int id, int n) { asm volatile("bar.arrive %0, %1;" :: "r"(id), "r"(n) : "memory"); }
__device__ __forceinline__ void named_sync(int id, int n) { asm volatile("bar.sync %0, %1;" :: "r"(id), "r"(n) : "memory"); }
__device__ __forceinline__ void wg_fence() { asm volatile("wgmma.fence.sync.aligned;" ::: "memory"); }
__device__ __forceinline__ void wg_commit() { asm volatile("wgmma.commit_group.sync.aligned;" ::: "memory"); }
template<int N> __device__ __forceinline__ void wg_wait() { asm volatile("wgmma.wait_group.sync.aligned %0;" :: "n"(N) : "memory"); }
template<int N> __device__ __forceinline__ void reg_fence(float (&d)[N]) {
    #pragma unroll
    for (int i = 0; i < N; i++) asm volatile("" : "+f"(d[i]) :: "memory");
}
__device__ __forceinline__ constexpr uint64_t mkdesc(uint32_t addr, uint32_t lbo, uint32_t sbo, uint32_t sw) {
    return (uint64_t)((addr & 0x3FFFF) >> 4) | ((uint64_t)(lbo >> 4) << 16) | ((uint64_t)(sbo >> 4) << 32) | ((uint64_t)sw << 62);
}
__device__ __forceinline__ void ldsm4(uint32_t (&r)[4], uint32_t addr) {
    asm volatile("ldmatrix.sync.aligned.m8n8.x4.shared.b16 {%0,%1,%2,%3}, [%4];" : "=r"(r[0]), "=r"(r[1]), "=r"(r[2]), "=r"(r[3]) : "r"(addr) : "memory");
}
__device__ __forceinline__ void stsm4(uint32_t addr, uint32_t r0, uint32_t r1, uint32_t r2, uint32_t r3) {
    asm volatile("stmatrix.sync.aligned.m8n8.x4.shared.b16 [%0], {%1,%2,%3,%4};" :: "r"(addr), "r"(r0), "r"(r1), "r"(r2), "r"(r3) : "memory");
}
__device__ __forceinline__ uint32_t movtrans(uint32_t a) { uint32_t d; asm volatile("movmatrix.sync.aligned.m8n8.trans.b16 %0, %1;" : "=r"(d) : "r"(a)); return d; }
__device__ __forceinline__ uint32_t pack_bf16(float lo, float hi) { uint32_t r; asm("cvt.rn.bf16x2.f32 %0, %1, %2;" : "=r"(r) : "f"(hi), "f"(lo)); return r; }
__device__ __forceinline__ float bf_lo(uint32_t v) { return __uint_as_float(v << 16); }
__device__ __forceinline__ float bf_hi(uint32_t v) { return __uint_as_float(v & 0xffff0000u); }
__device__ __forceinline__ void mma16816(float (&c)[4], uint32_t a0, uint32_t a1, uint32_t a2, uint32_t a3, uint32_t b0, uint32_t b1) {
    asm volatile("mma.sync.aligned.m16n8k16.row.col.f32.bf16.bf16.f32 {%0,%1,%2,%3}, {%4,%5,%6,%7}, {%8,%9}, {%0,%1,%2,%3};"
        : "+f"(c[0]), "+f"(c[1]), "+f"(c[2]), "+f"(c[3]) : "r"(a0), "r"(a1), "r"(a2), "r"(a3), "r"(b0), "r"(b1));
}
__device__ __forceinline__ void mma1688(float (&c)[4], uint32_t a0, uint32_t a1, uint32_t b0) {
    asm volatile("mma.sync.aligned.m16n8k8.row.col.f32.bf16.bf16.f32 {%0,%1,%2,%3}, {%4,%5}, {%6}, {%0,%1,%2,%3};"
        : "+f"(c[0]), "+f"(c[1]), "+f"(c[2]), "+f"(c[3]) : "r"(a0), "r"(a1), "r"(b0));
}
__device__ __forceinline__ float quad_sum(float v) { v += __shfl_xor_sync(0xffffffffu, v, 1); v += __shfl_xor_sync(0xffffffffu, v, 2); return v; }
__device__ __forceinline__ float quad_max(float v) { v = fmaxf(v, __shfl_xor_sync(0xffffffffu, v, 1)); v = fmaxf(v, __shfl_xor_sync(0xffffffffu, v, 2)); return v; }
__device__ __forceinline__ float ex2(float x) { float y; asm("ex2.approx.ftz.f32 %0, %1;" : "=f"(y) : "f"(x)); return y; }
__device__ __forceinline__ float rcp_approx(float x) { float y; asm("rcp.approx.ftz.f32 %0, %1;" : "=f"(y) : "f"(x)); return y; }
__device__ __forceinline__ float gelu_tanh(float x) {
    float z = x * fmaf(x * x, 0.044715f * 0.7978845608028654f, 0.7978845608028654f);
    float t; asm("tanh.approx.f32 %0, %1;" : "=f"(t) : "f"(z));
    float hx = 0.5f * x;
    return fmaf(hx, t, hx);
}

template<int TB> __device__ __forceinline__ void wgmma_rs56(float (&d)[28], const uint32_t (&a)[4], uint64_t db, int sc) {
    asm volatile("{\n.reg .pred p;\nsetp.ne.b32 p, %33, 0;\n"
        "wgmma.mma_async.sync.aligned.m64n56k16.f32.bf16.bf16 {%0, %1, %2, %3, %4, %5, %6, %7, %8, %9, %10, %11, %12, %13, %14, %15, %16, %17, %18, %19, %20, %21, %22, %23, %24, %25, %26, %27}, {%28, %29, %30, %31}, %32, p, 1, 1, %34;\n}\n"
        : "+f"(d[0]), "+f"(d[1]), "+f"(d[2]), "+f"(d[3]), "+f"(d[4]), "+f"(d[5]), "+f"(d[6]), "+f"(d[7]), "+f"(d[8]), "+f"(d[9]), "+f"(d[10]), "+f"(d[11]), "+f"(d[12]), "+f"(d[13]), "+f"(d[14]), "+f"(d[15]), "+f"(d[16]), "+f"(d[17]), "+f"(d[18]), "+f"(d[19]), "+f"(d[20]), "+f"(d[21]), "+f"(d[22]), "+f"(d[23]), "+f"(d[24]), "+f"(d[25]), "+f"(d[26]), "+f"(d[27])
        : "r"(a[0]), "r"(a[1]), "r"(a[2]), "r"(a[3]), "l"(db), "r"(sc), "n"(TB));
}

template<int TA, int TB> __device__ __forceinline__ void wgmma_ss112(float (&d)[56], uint64_t da, uint64_t db, int sc) {
    asm volatile("{\n.reg .pred p;\nsetp.ne.b32 p, %58, 0;\n"
        "wgmma.mma_async.sync.aligned.m64n112k16.f32.bf16.bf16 {%0, %1, %2, %3, %4, %5, %6, %7, %8, %9, %10, %11, %12, %13, %14, %15, %16, %17, %18, %19, %20, %21, %22, %23, %24, %25, %26, %27, %28, %29, %30, %31, %32, %33, %34, %35, %36, %37, %38, %39, %40, %41, %42, %43, %44, %45, %46, %47, %48, %49, %50, %51, %52, %53, %54, %55}, %56, %57, p, 1, 1, %59, %60;\n}\n"
        : "+f"(d[0]), "+f"(d[1]), "+f"(d[2]), "+f"(d[3]), "+f"(d[4]), "+f"(d[5]), "+f"(d[6]), "+f"(d[7]), "+f"(d[8]), "+f"(d[9]), "+f"(d[10]), "+f"(d[11]), "+f"(d[12]), "+f"(d[13]), "+f"(d[14]), "+f"(d[15]), "+f"(d[16]), "+f"(d[17]), "+f"(d[18]), "+f"(d[19]), "+f"(d[20]), "+f"(d[21]), "+f"(d[22]), "+f"(d[23]), "+f"(d[24]), "+f"(d[25]), "+f"(d[26]), "+f"(d[27]), "+f"(d[28]), "+f"(d[29]), "+f"(d[30]), "+f"(d[31]), "+f"(d[32]), "+f"(d[33]), "+f"(d[34]), "+f"(d[35]), "+f"(d[36]), "+f"(d[37]), "+f"(d[38]), "+f"(d[39]), "+f"(d[40]), "+f"(d[41]), "+f"(d[42]), "+f"(d[43]), "+f"(d[44]), "+f"(d[45]), "+f"(d[46]), "+f"(d[47]), "+f"(d[48]), "+f"(d[49]), "+f"(d[50]), "+f"(d[51]), "+f"(d[52]), "+f"(d[53]), "+f"(d[54]), "+f"(d[55])
        : "l"(da), "l"(db), "r"(sc), "n"(TA), "n"(TB));
}

template<int NKB, bool PERM>
__device__ __forceinline__ void mix_mainloop(float (&acc)[56], uint32_t par, bool leader) {
    constexpr uint32_t sb = SB, bars = sb + SM_BAR;
    int bslot = 0, aslot = 0;
    #pragma unroll
    for (int i = 0; i < 56; i++) acc[i] = 0.f;
    #pragma unroll 1
    for (int i = 0; i < NKB / 2; i++) {
        mbar_wait(bars + 8 * (B_FULLA + i), par);
        const uint64_t adesc = mkdesc(sb + SM_ARING, 8192, 1024, 1) + (uint32_t)(aslot * 1024);
        aslot = aslot == NA_SLOTS - 1 ? 0 : aslot + 1;
        #pragma unroll
        for (int jj = 0; jj < 2; jj++) {
            const int j = 2 * i + jj;
            mbar_wait(bars + 8 * (B_FULLB + j), par);
            const uint64_t bdesc = mkdesc(sb + SM_BRING, 1792, 128, 0) + (uint32_t)(bslot * 896);
            bslot = bslot == NB_SLOTS - 1 ? 0 : bslot + 1;
            wg_fence();
            #pragma unroll
            for (int s = 0; s < 4; s++) {
                const uint32_t aoff = PERM ? (s & 1) * 8192 + (jj * 32 + (s >> 1) * 16) * 128 : jj * 8192 + s * 2048;
                wgmma_ss112<1, 1>(acc, adesc + (aoff >> 4), bdesc + s * 224, 1);
            }
            wg_commit();
            wg_wait<1>();
            if (j > 0 && leader) mbar_arrive(bars + 8 * (B_DONE + j - 1));
        }
    }
    wg_wait<0>();
    reg_fence(acc);
    if (leader) mbar_arrive(bars + 8 * (B_DONE + NKB - 1));
}

template<int NKB>
__device__ __forceinline__ void mix_producer_b(uint32_t par, const uint32_t* flags, uint32_t target, const uint32_t* src, int lane) {
    constexpr uint32_t sb = SB, bars = sb + SM_BAR;
    uint32_t ready = 0;
    int bslot = 0;
    #pragma unroll 1
    for (int j = 0; j < NKB; j++) {
        if (!((ready >> j) & 1)) {
            do {
                uint32_t v = ld_acquire(flags + lane);
                ready = __ballot_sync(0xffffffffu, (int)(v - target) >= 0);
            } while (!((ready >> j) & 1));
            fence_async_global();
        }
        if (j >= NB_SLOTS) mbar_wait(bars + 8 * (B_DONE + j - NB_SLOTS), par);
        if (elect()) {
            mbar_expect(bars + 8 * (B_FULLB + j), 14336);
            bulk_ld(sb + SM_BRING + bslot * 14336, src + j * 3584, 14336, bars + 8 * (B_FULLB + j));
        }
        bslot = bslot == NB_SLOTS - 1 ? 0 : bslot + 1;
    }
}

__global__ void __launch_bounds__(384, 1)
fused_kernel(const __grid_constant__ CUtensorMap tm_x, const __grid_constant__ CUtensorMap tm_wqkv,
             const __grid_constant__ CUtensorMap tm_wo64, const __grid_constant__ CUtensorMap tm_wo48,
             const __grid_constant__ CUtensorMap tm_w1, const __grid_constant__ CUtensorMap tm_w2,
             const __grid_constant__ CUtensorMap tm_out,
             const __nv_bfloat16* __restrict__ x, const __nv_bfloat16* __restrict__ wqkv, const __nv_bfloat16* __restrict__ wo,
             const __nv_bfloat16* __restrict__ w1, const __nv_bfloat16* __restrict__ b1,
             const __nv_bfloat16* __restrict__ w2, const __nv_bfloat16* __restrict__ b2, int use_smid) {
    extern __shared__ __align__(1024) uint8_t smem_raw[];
    constexpr uint32_t sb = SB;
    constexpr uint32_t bars = sb + SM_BAR;
    const int tid = threadIdx.x, lane = tid & 31;
    const int warp = __shfl_sync(0xffffffffu, tid >> 5, 0), wg = warp >> 2;
    int slot;
    {
        uint32_t smid; asm volatile("mov.u32 %0, %%smid;" : "=r"(smid));
        if (!use_smid) slot = blockIdx.x;
        else if (smid < 64) slot = ((smid & 15) >> 1) * 16 + (smid >> 4) * 2 + (smid & 1);
        else if (smid < 120) { int u = smid - 64; slot = (1 + (u % 14) / 2) * 16 + 8 + (u / 14) * 2 + (u & 1); }
        else if (smid < 128) slot = 8 + (smid - 120);
        else slot = smid;
    }
    const int G = slot >> 4, mi = slot & 15;
    const int tb = 4 * (G >> 1) + (mi & 3), hp = 4 * (G & 1) + (mi >> 2);
    const int wcol = (hp * 56) & ~15;
    if (warp == 8 && slot < 128) {
        if (elect()) {
            #pragma unroll
            for (int kb = 0; kb < 7; kb++) mbar_init(bars + 8 * (B_FULL1 + kb), 1);
            asm volatile("fence.mbarrier_init.release.cluster;" ::: "memory");
            mbar_expect(bars + 8 * B_FULL1, 32768);
            tma3d(sb, &tm_x, 0, 0, tb * 64, bars + 8 * B_FULL1);
            tma2d(sb + 16384, &tm_wqkv, 448 + wcol, 0, bars + 8 * B_FULL1);
            tma2d(sb + 24576, &tm_wqkv, 896 + wcol, 0, bars + 8 * B_FULL1);
            tma3d(sb + 8192, &tm_x, 0, 1, tb * 64, bars + 8 * B_FULL1);
        }
    }
    if (slot >= 128) {
        if (tid == 0) {
            const uint32_t ep = g_epoch[slot] + 1;
            const long long t0 = clock64();
            while ((int)(ld_acquire(&g_flag_u[0]) - 4 * ep) < 0) { __nanosleep(500); if (clock64() - t0 > WD_CLKS) __trap(); }
            g_epoch[slot] = ep;
        }
        return;
    }
    const int q = mi & 3, tt2 = 4 * G + (mi >> 2), ft = 4 * (G - 1) + (mi >> 2);
    const bool has_b1 = G > 0;
    if (warp < 8) {
        if (elect()) {
            #pragma unroll 1
            for (int i = B_DONE1 + warp; i < N_BARS; i += 8) mbar_init(bars + 8 * i, (i < B_FULLQ || i == B_DONEQ) ? 2 : i == B_CS ? 3 : 1);
            asm volatile("fence.mbarrier_init.release.cluster;" ::: "memory");
        }
    }

    if (wg == 2) {
        asm volatile("setmaxnreg.dec.sync.aligned.u32 56;");
        if (warp == 8) {
            __syncthreads();
            #pragma unroll 1
            for (int kb = 1; kb < 7; kb++) {
                if (kb == 6) mbar_wait(bars + 8 * (B_DONE1 + 0), 0);
                if (elect()) {
                    const uint32_t st = sb + (kb == 6 ? 0 : kb) * SM_STAGE, bar = bars + 8 * (B_FULL1 + kb);
                    mbar_expect(bar, 32768);
                    tma3d(st, &tm_x, kb * 64, 0, tb * 64, bar);
                    tma2d(st + 16384, &tm_wqkv, 448 + wcol, kb * 64, bar);
                    tma2d(st + 24576, &tm_wqkv, 896 + wcol, kb * 64, bar);
                    tma3d(st + 8192, &tm_x, kb * 64, 1, tb * 64, bar);
                }
            }
            if (smem_u32(smem_raw) != SB) __trap();
            const uint32_t ep = ld_volatile(&g_epoch[slot]) + 1;
            #pragma unroll 1
            for (int h = 0; h < 2; h++) {
                mbar_wait(bars + 8 * (B_DONE1 + 1 + h), 0);
                if (elect()) {
                    const uint32_t bar = bars + 8 * (B_FULLQ + h);
                    mbar_expect(bar, (4 - h) * 8192);
                    #pragma unroll 1
                    for (int kb = 4 * h; kb < 4 + 3 * h; kb++) tma2d(sb + SM_STAGE + kb * 8192, &tm_wqkv, wcol, kb * 64, bar);
                }
            }
            #pragma unroll 1
            for (int pr = 0; pr < 4; pr++) {
                mbar_wait(bars + 8 * (B_DONE1 + 3 + pr), 0);
                if (elect()) {
                    const uint32_t bar = bars + 8 * B_FULLWO;
                    if (pr == 0) mbar_expect(bar, 448 * 112 * 2);
                    const uint32_t st = sb + ((pr + 3) % 6) * SM_STAGE;
                    tma2d(st, &tm_wo64, q * 112, pr * 128, bar);
                    tma2d(st + 8192, &tm_wo48, q * 112 + 64, pr * 128, bar);
                    if (pr < 3) {
                        tma2d(st + 16384, &tm_wo64, q * 112, pr * 128 + 64, bar);
                        tma2d(st + 24576, &tm_wo48, q * 112 + 64, pr * 128 + 64, bar);
                    }
                }
            }
            mbar_wait(bars + 8 * B_DONEQ, 0);
            {
                uint32_t issued = 0;
                while (issued != 15u) {
                    uint32_t v = ld_acquire(&g_cnt_o[tt2 * 32 + (lane & 3)]);
                    uint32_t ready = __ballot_sync(0xffffffffu, (int)(v - 8 * ep) >= 0) & 15u & ~issued;
                    if (ready) {
                        fence_async_global();
                        if (lane < 4 && ((ready >> lane) & 1)) {
                            const uint32_t bar = bars + 8 * (B_FULLO + lane);
                            mbar_expect(bar, 14336);
                            bulk_ld(sb + SM_STAGE + lane * 14336, g_o + tt2 * 14336 + lane * 3584, 14336, bar);
                        }
                        issued |= ready;
                    }
                    }
                __syncwarp();
            }
            if (lane == 0) STAMP(20);
            mbar_wait(bars + 8 * B_DONEO, 0);
            if (has_b1) {
                mix_producer_b<32>(0, g_flag_h + q * 32, 4 * ep, g_hn + q * 32 * 3584, lane);
                mbar_wait(bars + 8 * (B_DONE + 31), 0);
            }
            mix_producer_b<28>(has_b1, g_flag_u + q * 32, 4 * ep, g_u + q * 28 * 3584, lane);
        } else {
            float* csf = (float*)(smem_raw + SM_CS);
            const int u = tid - 288;
            float a8[8];
            if (slot < 84) {
                const int half = u & 1, rg = u >> 1;
                const uint4* src = (const uint4*)(wqkv + slot * 16 + half * 8) + rg * 168;
                uint4 v[10];
                #pragma unroll
                for (int i = 0; i < 10; i++) v[i] = (i < 9 || rg < 16) ? __ldg(src + 48 * 168 * i) : make_uint4(0, 0, 0, 0);
                __syncthreads();
                #pragma unroll
                for (int i = 0; i < 8; i++) a8[i] = 0.f;
                #pragma unroll
                for (int i = 0; i < 10; i++) {
                    a8[0] += bf_lo(v[i].x); a8[1] += bf_hi(v[i].x); a8[2] += bf_lo(v[i].y); a8[3] += bf_hi(v[i].y);
                    a8[4] += bf_lo(v[i].z); a8[5] += bf_hi(v[i].z); a8[6] += bf_lo(v[i].w); a8[7] += bf_hi(v[i].w);
                }
            } else __syncthreads();
            const uint32_t ep = ld_volatile(&g_epoch[slot]) + 1;
            if (slot < 84) {
                #pragma unroll
                for (int i = 0; i < 8; i++) {
                    #pragma unroll
                    for (int m = 2; m < 32; m <<= 1) a8[i] += __shfl_xor_sync(0xffffffffu, a8[i], m);
                }
                if (lane < 2) {
                    #pragma unroll
                    for (int i = 0; i < 8; i++) csf[192 + (warp - 9) * 16 + lane * 8 + i] = a8[i];
                }
                named_sync(3, 96);
                if (warp == 10 && lane < 16) st_relaxed2(&g_cs[slot * 16 + lane], __float_as_uint(csf[192 + lane] + csf[208 + lane] + csf[224 + lane]), ep);
            }
            if (warp == 11 && lane == 0) bulk_prefetch((const char*)wo + slot * 3136, 3136);
            if (lane < 28) {
                const uint4* p = (const uint4*)g_cs + (warp - 9) * 224 + hp * 28 + lane;
                uint4 v = ld_relaxed4(p);
                while (v.y != ep || v.w != ep) { __nanosleep(100); v = ld_relaxed4(p); }
                *(float2*)(csf + (warp - 9) * 56 + 2 * lane) = make_float2(__uint_as_float(v.x), __uint_as_float(v.z));
            }
            __syncwarp();
            if (lane == 0) mbar_arrive(bars + 8 * B_CS);
            if (warp == 10) {
                if (lane == 0) STAMP(21);
            } else if (warp == 11) {
                if (lane == 0) {
                    mbar_wait_wd(bars + 8 * (B_FULL1 + 5), 0);
                    long long t = clock64();
                    #pragma unroll 1
                    for (int i = 0; i < 28; i++) {
                        const char* src = (i < 14 ? (const char*)w1 : (const char*)w2 - 57344) + slot * 57344 + i * 4096;
                        bulk_prefetch(src, 4096);
                        t += 330;
                        while (clock64() < t) __nanosleep(40);
                    }
                    mbar_wait_wd(bars + 8 * B_END, 0);
                }
            } else {
                mbar_wait(bars + 8 * B_DONEO, 0);
                int aslot = 0;
                if (has_b1) {
                    #pragma unroll 1
                    for (int i = 0; i < 16; i++) {
                        if (i >= NA_SLOTS) mbar_wait(bars + 8 * (B_DONE + 1 + ((i - NA_SLOTS) * 22) / (15 - NA_SLOTS)), 0);
                        if (elect()) {
                            const uint32_t bar = bars + 8 * (B_FULLA + i), dst = sb + SM_ARING + aslot * 16384;
                            mbar_expect(bar, 16384);
                            tma3d(dst, &tm_w1, ft * 64, 0, i * 64, bar);
                            tma3d(dst + 8192, &tm_w1, ft * 64, 1, i * 64, bar);
                        }
                        aslot = aslot == NA_SLOTS - 1 ? 0 : aslot + 1;
                    }
                }
                aslot = 0;
                #pragma unroll 1
                for (int i = 0; i < 14; i++) {
                    if (i >= NA_SLOTS) mbar_wait(bars + 8 * (B_DONE + 1 + ((i - NA_SLOTS) * 18) / (13 - NA_SLOTS)), has_b1);
                    else if (has_b1) {
                        const int last = i + NA_SLOTS * ((15 - i) / NA_SLOTS);
                        mbar_wait(bars + 8 * (B_DONE + max(2 * last + 1, 32 - NB_SLOTS)), 0);
                    }
                    if (i == NA_SLOTS - 1 && has_b1) mbar_wait(bars + 8 * (B_DONE + 31), 0);
                    if (elect()) {
                        const uint32_t bar = bars + 8 * (B_FULLA + i);
                        mbar_expect(bar, 16384);
                        tma2d(sb + SM_ARING + aslot * 16384, &tm_w2, tt2 * 64, i * 128, bar);
                    }
                    aslot = aslot == NA_SLOTS - 1 ? 0 : aslot + 1;
                }
            }
        }
    } else {
        __syncthreads();
        asm volatile("setmaxnreg.inc.sync.aligned.u32 224;");
        const uint32_t ep = ld_volatile(&g_epoch[slot]) + 1;
        const int w = warp & 3, g = lane >> 2, t = lane & 3;
        const bool leader = (tid & 127) == 0;
        {
            uint32_t a[28][4];
            float accK[28], accV[28], accQ[28];
            float s0 = 0.f, s1 = 0.f, q0 = 0.f, q1 = 0.f;
            const int lrow = 16 * w + (lane & 7) + (lane & 8);
            const uint32_t lbase = sb + wg * 8192 + lrow * 128;
            const uint32_t lx = (lane >> 4) ^ (lane & 7);
            const uint32_t wofs = hp & 1;
            auto stats = [&](int kb) {
                #pragma unroll
                for (int s = 0; s < 4; s++) {
                    #pragma unroll
                    for (int r = 0; r < 4; r++) {
                        const float lo = bf_lo(a[4 * kb + s][r]), hi = bf_hi(a[4 * kb + s][r]);
                        if (r & 1) { s1 += lo; q1 = fmaf(lo, lo, q1); s1 += hi; q1 = fmaf(hi, hi, q1); }
                        else       { s0 += lo; q0 = fmaf(lo, lo, q0); s0 += hi; q0 = fmaf(hi, hi, q0); }
                    }
                }
                asm volatile("" : "+f"(s0), "+f"(s1), "+f"(q0), "+f"(q1));
            };
            #pragma unroll
            for (int kb = 0; kb < 7; kb++) {
                const uint32_t st = (kb % 6) * SM_STAGE;
                mbar_wait(bars + 8 * (B_FULL1 + kb), 0);
                if (kb == 0 && tid == 0) STAMP(0);
                #pragma unroll
                for (int s = 0; s < 4; s++) ldsm4(a[4 * kb + s], lbase + st + ((lx ^ (2 * s)) << 4));
                wg_fence();
                #pragma unroll
                for (int s = 0; s < 4; s++) {
                    wgmma_rs56<1>(accK, a[4 * kb + s], mkdesc(sb + st + 16384 + s * 2048, 8192, 1024, 1) + wofs, (kb | s) != 0);
                    wgmma_rs56<1>(accV, a[4 * kb + s], mkdesc(sb + st + 24576 + s * 2048, 8192, 1024, 1) + wofs, (kb | s) != 0);
                }
                wg_commit();
                if (kb > 0) {
                    wg_wait<1>();
                    if (leader) mbar_arrive(bars + 8 * (B_DONE1 + kb - 1));
                    stats(kb - 1);
                }
            }
            if (tid == 0) STAMP(1);
            mbar_wait(bars + 8 * (B_FULLQ + 0), 0);
            wg_fence();
            #pragma unroll
            for (int s = 0; s < 16; s++) wgmma_rs56<1>(accQ, a[s], mkdesc(sb + SM_STAGE + s * 2048, 8192, 1024, 1) + wofs, s != 0);
            wg_commit();
            wg_wait<1>();
            reg_fence(accK); reg_fence(accV);
            if (leader) mbar_arrive(bars + 8 * (B_DONE1 + 6));
            if (tid == 0) STAMP(2);
            stats(6);
            mbar_wait(bars + 8 * (B_FULLQ + 1), 0);
            wg_fence();
            #pragma unroll
            for (int s = 16; s < 28; s++) wgmma_rs56<1>(accQ, a[s], mkdesc(sb + SM_STAGE + s * 2048, 8192, 1024, 1) + wofs, 1);
            wg_commit();
            s0 = quad_sum(s0); s1 = quad_sum(s1); q0 = quad_sum(q0); q1 = quad_sum(q1);
            const float m0 = s0 * (1.f / D_), m1 = s1 * (1.f / D_);
            const float r0 = rsqrtf(fmaxf(q0 * (1.f / D_) - m0 * m0, 0.f) + LN_EPS), r1 = rsqrtf(fmaxf(q1 * (1.f / D_) - m1 * m1, 0.f) + LN_EPS);
            mbar_wait(bars + 8 * B_CS, 0);
            const float2* cs2 = (const float2*)(smem_raw + SM_CS);
            uint32_t Kb[7], Kc[7], Vb[7], Vc[7];
            #pragma unroll
            for (int j = 0; j < 7; j++) {
                const float2 ck = cs2[28 + 4 * j + t], cv = cs2[56 + 4 * j + t];
                Kb[j] = pack_bf16((accK[4 * j] - m0 * ck.x) * r0, (accK[4 * j + 1] - m0 * ck.y) * r0);
                Kc[j] = pack_bf16((accK[4 * j + 2] - m1 * ck.x) * r1, (accK[4 * j + 3] - m1 * ck.y) * r1);
                Vb[j] = movtrans(pack_bf16((accV[4 * j] - m0 * cv.x) * r0, (accV[4 * j + 1] - m0 * cv.y) * r0));
                Vc[j] = movtrans(pack_bf16((accV[4 * j + 2] - m1 * cv.x) * r1, (accV[4 * j + 3] - m1 * cv.y) * r1));
            }
            uint2* hs = (uint2*)(smem_raw + SM_HALO) + warp * 256 + lane;
            if (w < 3) {
                #pragma unroll
                for (int j = 0; j < 7; j++) hs[j * 32] = make_uint2(Kc[j], Vc[j]);
            } else if (tb < 15) {
                uint4* hg = g_halo + (((tb + 1) * 8 + hp) * 2 + wg) * 224 + lane;
                #pragma unroll
                for (int j = 0; j < 7; j++) st_relaxed4(hg + j * 32, Kc[j], ep, Vc[j], ep);
            }
            named_sync(1 + wg, 128);
            uint32_t Ka[7], Va[7];
            if (w > 0) {
                #pragma unroll
                for (int j = 0; j < 7; j++) { const uint2 v = hs[j * 32 - 256]; Ka[j] = v.x; Va[j] = v.y; }
            } else if (tb > 0) {
                const uint4* hg = g_halo + ((tb * 8 + hp) * 2 + wg) * 224 + lane;
                bool ok;
                do {
                    ok = true;
                    #pragma unroll
                    for (int j = 0; j < 7; j++) { const uint4 v = ld_relaxed4(hg + j * 32); Ka[j] = v.x; Va[j] = v.z; ok = ok && v.y == ep && v.w == ep; }
                    } while (!ok);
                __syncwarp();
            } else {
                #pragma unroll
                for (int j = 0; j < 7; j++) { Ka[j] = 0; Va[j] = 0; }
            }
            if (tid == 0) STAMP(3);
            wg_wait<0>();
            reg_fence(accQ);
            if (leader) mbar_arrive(bars + 8 * B_DONEQ);
            if (tid == 0) STAMP(4);
            uint32_t Q0[7], Q1[7];
            #pragma unroll
            for (int j = 0; j < 7; j++) {
                const float2 cq = cs2[4 * j + t];
                Q0[j] = pack_bf16((accQ[4 * j] - m0 * cq.x) * r0, (accQ[4 * j + 1] - m0 * cq.y) * r0);
                Q1[j] = pack_bf16((accQ[4 * j + 2] - m1 * cq.x) * r1, (accQ[4 * j + 3] - m1 * cq.y) * r1);
            }
            const bool first = (tb == 0 && w == 0);
            const float sc = 0.1889822365046136f * 1.4426950408889634f;
            float o[8][4];
            #pragma unroll
            for (int h = 0; h < 2; h++) {
                const int j0 = 3 * h;
                const bool own3 = (t >= 2) == (h == 1);
                uint32_t qa[4], qb[4];
                #pragma unroll
                for (int j = 0; j < 4; j++) {
                    qa[j] = (j0 + j == 3 && !own3) ? 0u : Q0[j0 + j];
                    qb[j] = (j0 + j == 3 && !own3) ? 0u : Q1[j0 + j];
                }
                float sA[4] = {0.f, 0.f, 0.f, 0.f}, sB[4] = {0.f, 0.f, 0.f, 0.f}, sC[4] = {0.f, 0.f, 0.f, 0.f};
                #pragma unroll
                for (int k = 0; k < 2; k++) {
                    mma16816(sA, qa[2 * k], qb[2 * k], qa[2 * k + 1], qb[2 * k + 1], Ka[j0 + 2 * k], Ka[j0 + 2 * k + 1]);
                    mma16816(sB, qa[2 * k], qb[2 * k], qa[2 * k + 1], qb[2 * k + 1], Kb[j0 + 2 * k], Kb[j0 + 2 * k + 1]);
                    mma16816(sC, qa[2 * k], qb[2 * k], qa[2 * k + 1], qb[2 * k + 1], Kc[j0 + 2 * k], Kc[j0 + 2 * k + 1]);
                }
                const bool n0 = 2 * t <= g, n1 = 2 * t + 1 <= g;
                float l00 = n0 ? sB[0] : (first ? -1e30f : sA[0]), l01 = n1 ? sB[1] : (first ? -1e30f : sA[1]);
                float l10 = n0 ? sC[2] : sB[2], l11 = n1 ? sC[3] : sB[3];
                const float x0 = quad_max(fmaxf(l00, l01)), x1 = quad_max(fmaxf(l10, l11));
                const float e00 = ex2((l00 - x0) * sc), e01 = ex2((l01 - x0) * sc), e10 = ex2((l10 - x1) * sc), e11 = ex2((l11 - x1) * sc);
                const float i0 = rcp_approx(quad_sum(e00 + e01)), i1 = rcp_approx(quad_sum(e10 + e11));
                const float p00 = e00 * i0, p01 = e01 * i0, p10 = e10 * i1, p11 = e11 * i1;
                const uint32_t pA = pack_bf16(n0 ? 0.f : p00, n1 ? 0.f : p01), pB0 = pack_bf16(n0 ? p00 : 0.f, n1 ? p01 : 0.f);
                const uint32_t pC = pack_bf16(n0 ? p10 : 0.f, n1 ? p11 : 0.f), pB1 = pack_bf16(n0 ? 0.f : p10, n1 ? 0.f : p11);
                #pragma unroll
                for (int j = 0; j < 4; j++) {
                    float (&oo)[4] = o[4 * h + j];
                    oo[0] = oo[1] = oo[2] = oo[3] = 0.f;
                    mma16816(oo, pA, 0u, 0u, pC, Va[j0 + j], Vc[j0 + j]);
                    mma1688(oo, pB0, pB1, Vb[j0 + j]);
                }
            }
            const int tt = 2 * tb + (w >> 1);
            uint32_t* od = g_o + tt * 14336 + (7 * hp) * 256 + (2 * (2 * (w & 1) + wg)) * 32 + lane;
            #pragma unroll
            for (int j = 0; j < 7; j++) {
                float v[4];
                #pragma unroll
                for (int c = 0; c < 4; c++) v[c] = j < 3 ? o[j][c] : j > 3 ? o[j + 1][c] : (t < 2 ? o[3][c] : o[4][c]);
                od[j * 256] = pack_bf16(v[0], v[1]);
                od[j * 256 + 32] = pack_bf16(v[2], v[3]);
            }
            if (tid == 0) STAMP(5);
            __syncwarp();
            if (lane == 0) red_release(&g_cnt_o[tt * 32 + (hp >> 1)]);
            if (tid == 0) STAMP(6);
        }
        if (wg == 0) {
            const uint32_t rb10 = has_b1 ? __ldg((const unsigned short*)b1 + ft * 64 + 16 * w + g) : 0, rb11 = has_b1 ? __ldg((const unsigned short*)b1 + ft * 64 + 16 * w + g + 8) : 0;
            const uint32_t rb20 = __ldg((const unsigned short*)b2 + tt2 * 64 + 16 * w + g), rb21 = __ldg((const unsigned short*)b2 + tt2 * 64 + 16 * w + g + 8);
            {
                float acc[56];
                uint32_t xr[28];
                const int tok = 64 * tt2 + 32 * (w >> 1) + 2 * g + (w & 1);
                const uint32_t* xp = (const uint32_t*)(x + tok * D_ + q * 112) + t;
                #pragma unroll
                for (int j = 0; j < 14; j++) { xr[2 * j] = __ldg(xp + 4 * j); xr[2 * j + 1] = __ldg(xp + 4 * j + 16 * (D_ / 2)); }
                mbar_wait(bars + 8 * B_FULLWO, 0);
                #pragma unroll
                for (int i = 0; i < 4; i++) {
                    mbar_wait(bars + 8 * (B_FULLO + i), 0);
                    if (i == 0 && tid == 0) STAMP(7);
                    wg_fence();
                    #pragma unroll
                    for (int ss = 0; ss < 7; ss++) {
                        const int s = 7 * i + ss, kb = s >> 2;
                        wgmma_ss112<0, 1>(acc, mkdesc(sb + SM_STAGE + s * 2048, 1024, 128, 0),
                                          mkdesc(sb + (((kb >> 1) + 3) % 6) * SM_STAGE + (kb & 1) * 16384 + (s & 3) * 2048, 8192, 1024, 1), s != 0);
                    }
                    wg_commit();
                }
                wg_wait<0>();
                reg_fence(acc);
                if (leader) mbar_arrive(bars + 8 * B_DONEO);
                if (tid == 0) STAMP(8);
                float s0 = 0.f, s1 = 0.f, q0 = 0.f, q1 = 0.f;
                #pragma unroll
                for (int j = 0; j < 14; j++) {
                    xr[2 * j] = pack_bf16(bf_lo(xr[2 * j]) + acc[4 * j], bf_hi(xr[2 * j]) + acc[4 * j + 1]);
                    xr[2 * j + 1] = pack_bf16(bf_lo(xr[2 * j + 1]) + acc[4 * j + 2], bf_hi(xr[2 * j + 1]) + acc[4 * j + 3]);
                    acc[4 * j] = bf_lo(xr[2 * j]); acc[4 * j + 1] = bf_hi(xr[2 * j]);
                    acc[4 * j + 2] = bf_lo(xr[2 * j + 1]); acc[4 * j + 3] = bf_hi(xr[2 * j + 1]);
                    s0 += acc[4 * j] + acc[4 * j + 1]; q0 = fmaf(acc[4 * j], acc[4 * j], fmaf(acc[4 * j + 1], acc[4 * j + 1], q0));
                    s1 += acc[4 * j + 2] + acc[4 * j + 3]; q1 = fmaf(acc[4 * j + 2], acc[4 * j + 2], fmaf(acc[4 * j + 3], acc[4 * j + 3], q1));
                }
                s0 = quad_sum(s0); s1 = quad_sum(s1); q0 = quad_sum(q0); q1 = quad_sum(q1);
                uint4* sp = g_stats + tt2 * 256 + 16 * w + g;
                if (t < 2) st_relaxed4(sp + q * 64 + 8 * t, __float_as_uint(t ? s1 : s0), ep, __float_as_uint(t ? q1 : q0), ep);
                if (tid == 0) STAMP(9);
                {
                    const int mrow = 32 * (w >> 1) + 2 * ((lane & 7) + (lane & 8)) + (w & 1);
                    #pragma unroll
                    for (int jp = 0; jp < 7; jp++) {
                        const int j = 2 * jp + (lane >> 4);
                        stsm4(sb + SM_H + mrow * 224 + j * 16, xr[4 * jp], xr[4 * jp + 1], xr[4 * jp + 2], xr[4 * jp + 3]);
                    }
                }
                if (t != q) {
                    uint4 v0, v1;
                    do {
                        v0 = ld_relaxed4(sp + t * 64); v1 = ld_relaxed4(sp + t * 64 + 8);
                            } while (v0.y != ep || v0.w != ep || v1.y != ep || v1.w != ep);
                    s0 = __uint_as_float(v0.x); q0 = __uint_as_float(v0.z); s1 = __uint_as_float(v1.x); q1 = __uint_as_float(v1.z);
                }
                __syncwarp();
                if (tid == 0) STAMP(10);
                s0 = quad_sum(s0); s1 = quad_sum(s1); q0 = quad_sum(q0); q1 = quad_sum(q1);
                const float m0 = s0 * (1.f / D_), m1 = s1 * (1.f / D_);
                const float v0 = fmaxf(q0 * (1.f / D_) - m0 * m0, 0.f), v1 = fmaxf(q1 * (1.f / D_) - m1 * m1, 0.f);
                float r0 = rsqrtf(v0 + LN_EPS), r1 = rsqrtf(v1 + LN_EPS);
                r0 *= rsqrtf(fmaf(v0 * r0, r0, LN_EPS)); r1 *= rsqrtf(fmaf(v1 * r1, r1, LN_EPS));
                uint32_t* hd = g_hn + (q * 32 + tt2) * 3584 + (2 * w) * 448 + lane;
                #pragma unroll
                for (int j = 0; j < 14; j++) {
                    hd[j * 32] = pack_bf16((acc[4 * j] - m0) * r0, (acc[4 * j + 1] - m0) * r0);
                    hd[j * 32 + 448] = pack_bf16((acc[4 * j + 2] - m1) * r1, (acc[4 * j + 3] - m1) * r1);
                }
                if (tid == 0) STAMP(11);
                __syncwarp();
                if (lane == 0) red_release(&g_flag_h[q * 32 + tt2]);
                if (tid == 0) STAMP(12);
            }
            if (has_b1) {
                float acc[56];
                const float bb0 = bf_lo(rb10), bb1 = bf_lo(rb11);
                mix_mainloop<32, true>(acc, 0, leader);
                if (tid == 0) STAMP(14);
                uint32_t* ud = g_u + (q * 28 + ft) * 3584 + (2 * w) * 448 + lane;
                #pragma unroll
                for (int j = 0; j < 14; j++) {
                    ud[j * 32] = pack_bf16(gelu_tanh(acc[4 * j] + bb0), gelu_tanh(acc[4 * j + 1] + bb0));
                    ud[j * 32 + 448] = pack_bf16(gelu_tanh(acc[4 * j + 2] + bb1), gelu_tanh(acc[4 * j + 3] + bb1));
                }
                if (tid == 0) STAMP(15);
                __syncwarp();
                if (lane == 0) red_release(&g_flag_u[q * 32 + ft]);
                if (tid == 0) STAMP(16);
            }
            {
                float acc[56];
                const float bb0 = bf_lo(rb20), bb1 = bf_lo(rb21);
                named_sync(1, 128);
                mix_mainloop<28, false>(acc, has_b1, leader);
                if (leader) mbar_arrive(bars + 8 * B_END);
                if (tid == 0) STAMP(18);
                const int mrow = 16 * w + (lane & 7) + (lane & 8);
                #pragma unroll
                for (int jp = 0; jp < 7; jp++) {
                    const int j = 2 * jp + (lane >> 4);
                    const uint32_t ad = sb + SM_H + mrow * 224 + j * 16;
                    uint32_t hh[4];
                    ldsm4(hh, ad);
                    stsm4(ad, pack_bf16(bf_lo(hh[0]) + (acc[8 * jp] + bb0), bf_hi(hh[0]) + (acc[8 * jp + 1] + bb0)),
                              pack_bf16(bf_lo(hh[1]) + (acc[8 * jp + 2] + bb1), bf_hi(hh[1]) + (acc[8 * jp + 3] + bb1)),
                              pack_bf16(bf_lo(hh[2]) + (acc[8 * jp + 4] + bb0), bf_hi(hh[2]) + (acc[8 * jp + 5] + bb0)),
                              pack_bf16(bf_lo(hh[3]) + (acc[8 * jp + 6] + bb1), bf_hi(hh[3]) + (acc[8 * jp + 7] + bb1)));
                }
                fence_async_smem();
                __syncwarp();
                if (elect()) {
                    tma2d_store(&tm_out, q * 112, tt2 * 64 + 16 * w, sb + SM_H + w * 3584);
                    asm volatile("cp.async.bulk.commit_group;" ::: "memory");
                    asm volatile("cp.async.bulk.wait_group.read 0;" ::: "memory");
                }
                if (tid == 0) { g_epoch[slot] = ep; STAMP(19); }
            }
        }
    }
}

typedef CUresult (*EncodeFn)(CUtensorMap*, CUtensorMapDataType, cuuint32_t, void*, const cuuint64_t*, const cuuint64_t*, const cuuint32_t*,
                             const cuuint32_t*, CUtensorMapInterleave, CUtensorMapSwizzle, CUtensorMapL2promotion, CUtensorMapFloatOOBfill);

void make_map(EncodeFn fn, CUtensorMap* tm, const void* ptr, int rank, const cuuint64_t* dims, const cuuint64_t* strides, const cuuint32_t* box, CUtensorMapSwizzle sw) {
    cuuint32_t es[3] = {1, 1, 1};
    fn(tm, CU_TENSOR_MAP_DATA_TYPE_BFLOAT16, rank, const_cast<void*>(ptr), dims, strides, box, es, CU_TENSOR_MAP_INTERLEAVE_NONE, sw,
       CU_TENSOR_MAP_L2_PROMOTION_NONE, CU_TENSOR_MAP_FLOAT_OOB_FILL_NONE);
}

}

extern "C" void kernel_launch(void* const* d_in, const int* in_sizes, int n_in, void* d_out, int out_size) {
    const __nv_bfloat16* x = (const __nv_bfloat16*)d_in[0];
    const __nv_bfloat16* wqkv = (const __nv_bfloat16*)d_in[1];
    const __nv_bfloat16* wo = (const __nv_bfloat16*)d_in[2];
    const __nv_bfloat16* w1 = (const __nv_bfloat16*)d_in[4];
    const __nv_bfloat16* b1 = (const __nv_bfloat16*)d_in[5];
    const __nv_bfloat16* w2 = (const __nv_bfloat16*)d_in[6];
    const __nv_bfloat16* b2 = (const __nv_bfloat16*)d_in[7];

    void* fnp = nullptr; cudaDriverEntryPointQueryResult qr;
    cudaGetDriverEntryPoint("cuTensorMapEncodeTiled", &fnp, cudaEnableDefault, &qr);
    EncodeFn fn = (EncodeFn)fnp;
    CUtensorMap tx, twqkv, two64, two48, tw1, tw2, tout;
    { cuuint64_t d[3] = {448, 2, 1024}, s[2] = {896, 1792}; cuuint32_t b[3] = {64, 1, 64}; make_map(fn, &tx, x, 3, d, s, b, CU_TENSOR_MAP_SWIZZLE_128B); }
    { cuuint64_t d[2] = {1344, 448}, s[1] = {2688}; cuuint32_t b[2] = {64, 64}; make_map(fn, &twqkv, wqkv, 2, d, s, b, CU_TENSOR_MAP_SWIZZLE_128B); }
    { cuuint64_t d[2] = {448, 448}, s[1] = {896}; cuuint32_t b[2] = {64, 64}; make_map(fn, &two64, wo, 2, d, s, b, CU_TENSOR_MAP_SWIZZLE_128B); }
    { cuuint64_t d[2] = {448, 448}, s[1] = {896}; cuuint32_t b[2] = {48, 64}; make_map(fn, &two48, wo, 2, d, s, b, CU_TENSOR_MAP_SWIZZLE_128B); }
    { cuuint64_t d[3] = {1792, 2, 1024}, s[2] = {3584, 7168}; cuuint32_t b[3] = {64, 1, 64}; make_map(fn, &tw1, w1, 3, d, s, b, CU_TENSOR_MAP_SWIZZLE_128B); }
    { cuuint64_t d[2] = {2048, 1792}, s[1] = {4096}; cuuint32_t b[2] = {64, 128}; make_map(fn, &tw2, w2, 2, d, s, b, CU_TENSOR_MAP_SWIZZLE_128B); }
    { cuuint64_t d[2] = {448, 2048}, s[1] = {896}; cuuint32_t b[2] = {112, 16}; make_map(fn, &tout, d_out, 2, d, s, b, CU_TENSOR_MAP_SWIZZLE_NONE); }

    int dev = 0, sms = 0;
    cudaGetDevice(&dev);
    cudaDeviceGetAttribute(&sms, cudaDevAttrMultiProcessorCount, dev);
    cudaFuncSetAttribute(fused_kernel, cudaFuncAttributeMaxDynamicSharedMemorySize, SM_TOTAL);
    const int use_smid = (sms == 132);
    fused_kernel<<<use_smid ? 132 : 128, 384, SM_TOTAL>>>(tx, twqkv, two64, two48, tw1, tw2, tout, x, wqkv, wo, w1, b1, w2, b2, use_smid);
}
```

```cpp
#include <cuda_runtime.h>
#include <cuda_bf16.h>
#include <cuda.h>
#include <stdint.h>

namespace {

constexpr int D_ = 448;
constexpr float LN_EPS = 1e-5f;

struct Scratch {
    uint32_t o[32 * 57344 / 4];
    uint32_t hn[4 * 32 * 14336 / 4];
    uint32_t u[4 * 28 * 14336 / 4];
    uint4 halo[128 * 2 * 7 * 32];
    uint4 stats[32 * 4 * 64];
    uint2 cs[6 * 1344];
    uint32_t cnt_o[32 * 32];
    uint32_t flag_h[4 * 32];
    uint32_t flag_u[4 * 32];
    uint32_t epoch[160];
};
__device__ __align__(1024) Scratch g_scratch;
#define STAMP(i) do {} while (0)

constexpr uint32_t SB = 1024;
constexpr int SM_STAGE = 32768;
constexpr int SM_HALO = 196608;
constexpr int SM_CS = SM_HALO + 16384;
#define NA_SLOTS 6
#define NB_SLOTS 8
constexpr int SM_ARING = 0;
constexpr int SM_BRING = NA_SLOTS * 16384;
constexpr int SM_H = 217088;
static_assert(SM_BRING + NB_SLOTS * 14336 <= SM_H, "smem");
constexpr int SM_BAR = 231424;
constexpr int SM_TOTAL = 232448;
constexpr int B_FULL1 = 0;
constexpr int B_FQ = 7;
constexpr int B_CSBOX = 11;
constexpr int B_DONE1 = 12;
constexpr int B_DONEQ = 19;
constexpr int B_CS = 20;
constexpr int B_ONE = 21;
constexpr int B_FULLWO = 21;
constexpr int B_FULLO = 22;
constexpr int B_DONEO = 26;
constexpr int B_END = 27;
constexpr int B_FULLA = 29;
constexpr int B_FULLB = 45;
constexpr int B_DONE = 77;
constexpr int N_BARS = 109;

constexpr long long WD_CLKS = 2000000000ll;

__device__ __forceinline__ uint32_t smem_u32(const void* p) { return (uint32_t)__cvta_generic_to_shared(p); }
__device__ __forceinline__ void mbar_init(uint32_t bar, uint32_t cnt) { asm volatile("mbarrier.init.shared::cta.b64 [%0], %1;" :: "r"(bar), "r"(cnt) : "memory"); }
__device__ __forceinline__ void mbar_expect(uint32_t bar, uint32_t bytes) { asm volatile("mbarrier.arrive.expect_tx.shared::cta.b64 _, [%0], %1;" :: "r"(bar), "r"(bytes) : "memory"); }
__device__ __forceinline__ void mbar_arrive(uint32_t bar) { asm volatile("mbarrier.arrive.shared::cta.b64 _, [%0];" :: "r"(bar) : "memory"); }
__device__ __forceinline__ bool mbar_try(uint32_t bar, uint32_t parity) {
    uint32_t ok;
    asm volatile("{\n.reg .pred p;\nmbarrier.try_wait.parity.shared::cta.b64 p, [%1], %2;\nselp.u32 %0, 1, 0, p;\n}" : "=r"(ok) : "r"(bar), "r"(parity) : "memory");
    return ok;
}
__device__ __forceinline__ void mbar_wait(uint32_t bar, uint32_t parity) {
    asm volatile("{\n.reg .pred p;\n"
                 "WAIT_LOOP:\n"
                 "mbarrier.try_wait.parity.shared::cta.b64 p, [%0], %1;\n"
                 "@!p bra WAIT_LOOP;\n}" :: "r"(bar), "r"(parity) : "memory");
}
__device__ __forceinline__ void mbar_wait_wd(uint32_t bar, uint32_t parity) {
    const long long t0 = clock64();
    while (!mbar_try(bar, parity)) { if (clock64() - t0 > WD_CLKS) __trap(); }
}
__device__ __forceinline__ bool elect() { uint32_t p; asm volatile("{\n.reg .pred P;\nelect.sync _|P, 0xffffffff;\nselp.u32 %0, 1, 0, P;\n}" : "=r"(p)); return p; }
__device__ __forceinline__ void tma2d(uint32_t dst, const CUtensorMap* tm, int c0, int c1, uint32_t bar) {
    asm volatile("cp.async.bulk.tensor.2d.shared::cluster.global.mbarrier::complete_tx::bytes [%0], [%1, {%3, %4}], [%2];" :: "r"(dst), "l"(tm), "r"(bar), "r"(c0), "r"(c1) : "memory");
}
__device__ __forceinline__ void tma3d(uint32_t dst, const CUtensorMap* tm, int c0, int c1, int c2, uint32_t bar) {
    asm volatile("cp.async.bulk.tensor.3d.shared::cluster.global.mbarrier::complete_tx::bytes [%0], [%1, {%3, %4, %5}], [%2];" :: "r"(dst), "l"(tm), "r"(bar), "r"(c0), "r"(c1), "r"(c2) : "memory");
}
__device__ __forceinline__ void tma2d_store(const CUtensorMap* tm, int c0, int c1, uint32_t src) {
    asm volatile("cp.async.bulk.tensor.2d.global.shared::cta.bulk_group [%0, {%2, %3}], [%1];" :: "l"(tm), "r"(src), "r"(c0), "r"(c1) : "memory");
}
__device__ __forceinline__ void bulk_ld(uint32_t dst, const void* src, uint32_t bytes, uint32_t bar) {
    asm volatile("cp.async.bulk.shared::cluster.global.mbarrier::complete_tx::bytes [%0], [%1], %2, [%3];" :: "r"(dst), "l"(src), "r"(bytes), "r"(bar) : "memory");
}
__device__ __forceinline__ void bulk_prefetch(const void* src, uint32_t bytes) { asm volatile("cp.async.bulk.prefetch.L2.global [%0], %1;" :: "l"(src), "r"(bytes) : "memory"); }
__device__ __forceinline__ void fence_async_global() { asm volatile("fence.proxy.async.global;" ::: "memory"); }
__device__ __forceinline__ void fence_async_smem() { asm volatile("fence.proxy.async.shared::cta;" ::: "memory"); }
__device__ __forceinline__ uint32_t ld_acquire(const uint32_t* p) { uint32_t v; asm volatile("ld.acquire.gpu.global.u32 %0, [%1];" : "=r"(v) : "l"(p) : "memory"); return v; }
__device__ __forceinline__ void red_release(uint32_t* p) { asm volatile("red.release.gpu.global.add.u32 [%0], 1;" :: "l"(p) : "memory"); }
__device__ __forceinline__ uint4 ld_relaxed4(const uint4* p) { uint4 v; asm volatile("ld.relaxed.gpu.global.v4.u32 {%0,%1,%2,%3}, [%4];" : "=r"(v.x), "=r"(v.y), "=r"(v.z), "=r"(v.w) : "l"(p) : "memory"); return v; }
__device__ __forceinline__ void st_relaxed4(uint4* p, uint32_t a, uint32_t b, uint32_t c, uint32_t d) { asm volatile("st.relaxed.gpu.global.v4.u32 [%0], {%1,%2,%3,%4};" :: "l"(p), "r"(a), "r"(b), "r"(c), "r"(d) : "memory"); }
__device__ __forceinline__ void st_relaxed2(uint2* p, uint32_t a, uint32_t b) { asm volatile("st.relaxed.gpu.global.v2.u32 [%0], {%1,%2};" :: "l"(p), "r"(a), "r"(b) : "memory"); }
__device__ __forceinline__ uint32_t ld_volatile(const uint32_t* p) { uint32_t v; asm volatile("ld.volatile.global.u32 %0, [%1];" : "=r"(v) : "l"(p) : "memory"); return v; }
__device__ __forceinline__ void named_arrive(int id, int n) { asm volatile("bar.arrive %0, %1;" :: "r"(id), "r"(n) : "memory"); }
__device__ __forceinline__ void named_sync(int id, int n) { asm volatile("bar.sync %0, %1;" :: "r"(id), "r"(n) : "memory"); }
__device__ __forceinline__ void wg_fence() { asm volatile("wgmma.fence.sync.aligned;" ::: "memory"); }
__device__ __forceinline__ void wg_commit() { asm volatile("wgmma.commit_group.sync.aligned;" ::: "memory"); }
template<int N> __device__ __forceinline__ void wg_wait() { asm volatile("wgmma.wait_group.sync.aligned %0;" :: "n"(N) : "memory"); }
template<int N> __device__ __forceinline__ void reg_fence(float (&d)[N]) {
    #pragma unroll
    for (int i = 0; i < N; i++) asm volatile("" : "+f"(d[i]) :: "memory");
}
__device__ __forceinline__ constexpr uint64_t mkdesc(uint32_t addr, uint32_t lbo, uint32_t sbo, uint32_t sw) {
    return (uint64_t)((addr & 0x3FFFF) >> 4) | ((uint64_t)(lbo >> 4) << 16) | ((uint64_t)(sbo >> 4) << 32) | ((uint64_t)sw << 62);
}
__device__ __forceinline__ void ldsm4(uint32_t (&r)[4], uint32_t addr) {
    asm volatile("ldmatrix.sync.aligned.m8n8.x4.shared.b16 {%0,%1,%2,%3}, [%4];" : "=r"(r[0]), "=r"(r[1]), "=r"(r[2]), "=r"(r[3]) : "r"(addr) : "memory");
}
__device__ __forceinline__ void stsm4(uint32_t addr, uint32_t r0, uint32_t r1, uint32_t r2, uint32_t r3) {
    asm volatile("stmatrix.sync.aligned.m8n8.x4.shared.b16 [%0], {%1,%2,%3,%4};" :: "r"(addr), "r"(r0), "r"(r1), "r"(r2), "r"(r3) : "memory");
}
__device__ __forceinline__ uint32_t movtrans(uint32_t a) { uint32_t d; asm volatile("movmatrix.sync.aligned.m8n8.trans.b16 %0, %1;" : "=r"(d) : "r"(a)); return d; }
__device__ __forceinline__ uint32_t pack_bf16(float lo, float hi) { uint32_t r; asm("cvt.rn.bf16x2.f32 %0, %1, %2;" : "=r"(r) : "f"(hi), "f"(lo)); return r; }
__device__ __forceinline__ float bf_lo(uint32_t v) { return __uint_as_float(v << 16); }
__device__ __forceinline__ float bf_hi(uint32_t v) { return __uint_as_float(v & 0xffff0000u); }
__device__ __forceinline__ void mma16816(float (&c)[4], uint32_t a0, uint32_t a1, uint32_t a2, uint32_t a3, uint32_t b0, uint32_t b1) {
    asm volatile("mma.sync.aligned.m16n8k16.row.col.f32.bf16.bf16.f32 {%0,%1,%2,%3}, {%4,%5,%6,%7}, {%8,%9}, {%0,%1,%2,%3};"
        : "+f"(c[0]), "+f"(c[1]), "+f"(c[2]), "+f"(c[3]) : "r"(a0), "r"(a1), "r"(a2), "r"(a3), "r"(b0), "r"(b1));
}
__device__ __forceinline__ void mma1688(float (&c)[4], uint32_t a0, uint32_t a1, uint32_t b0) {
    asm volatile("mma.sync.aligned.m16n8k8.row.col.f32.bf16.bf16.f32 {%0,%1,%2,%3}, {%4,%5}, {%6}, {%0,%1,%2,%3};"
        : "+f"(c[0]), "+f"(c[1]), "+f"(c[2]), "+f"(c[3]) : "r"(a0), "r"(a1), "r"(b0));
}
__device__ __forceinline__ float quad_sum(float v) { v += __shfl_xor_sync(0xffffffffu, v, 1); v += __shfl_xor_sync(0xffffffffu, v, 2); return v; }
__device__ __forceinline__ float quad_max(float v) { v = fmaxf(v, __shfl_xor_sync(0xffffffffu, v, 1)); v = fmaxf(v, __shfl_xor_sync(0xffffffffu, v, 2)); return v; }
__device__ __forceinline__ float ex2(float x) { float y; asm("ex2.approx.ftz.f32 %0, %1;" : "=f"(y) : "f"(x)); return y; }
__device__ __forceinline__ float rsqrt_approx(float x) { float y; asm("rsqrt.approx.ftz.f32 %0, %1;" : "=f"(y) : "f"(x)); return y; }
__device__ __forceinline__ float rcp_approx(float x) { float y; asm("rcp.approx.ftz.f32 %0, %1;" : "=f"(y) : "f"(x)); return y; }
__device__ __forceinline__ float gelu_half(float hx) {
    const float z = hx * fmaf(hx * hx, 8.f * 0.044715f * 0.7978845608028654f, 2.f * 0.7978845608028654f);
    float t; asm("tanh.approx.f32 %0, %1;" : "=f"(t) : "f"(z));
    return fmaf(hx, t, hx);
}
__device__ __forceinline__ uint32_t clock32() { uint32_t t; asm volatile("mov.u32 %0, %%clock;" : "=r"(t)); return t; }
#define CS_AT 1
#define PF_PACE 450
#define PACE 0

template<int TB> __device__ __forceinline__ void wgmma_rs56(float (&d)[28], const uint32_t (&a)[4], uint64_t db, int sc) {
    asm volatile("{\n.reg .pred p;\nsetp.ne.b32 p, %33, 0;\n"
        "wgmma.mma_async.sync.aligned.m64n56k16.f32.bf16.bf16 {%0, %1, %2, %3, %4, %5, %6, %7, %8, %9, %10, %11, %12, %13, %14, %15, %16, %17, %18, %19, %20, %21, %22, %23, %24, %25, %26, %27}, {%28, %29, %30, %31}, %32, p, 1, 1, %34;\n}\n"
        : "+f"(d[0]), "+f"(d[1]), "+f"(d[2]), "+f"(d[3]), "+f"(d[4]), "+f"(d[5]), "+f"(d[6]), "+f"(d[7]), "+f"(d[8]), "+f"(d[9]), "+f"(d[10]), "+f"(d[11]), "+f"(d[12]), "+f"(d[13]), "+f"(d[14]), "+f"(d[15]), "+f"(d[16]), "+f"(d[17]), "+f"(d[18]), "+f"(d[19]), "+f"(d[20]), "+f"(d[21]), "+f"(d[22]), "+f"(d[23]), "+f"(d[24]), "+f"(d[25]), "+f"(d[26]), "+f"(d[27])
        : "r"(a[0]), "r"(a[1]), "r"(a[2]), "r"(a[3]), "l"(db), "r"(sc), "n"(TB));
}

template<int TA, int TB> __device__ __forceinline__ void wgmma_ss112(float (&d)[56], uint64_t da, uint64_t db, int sc) {
    asm volatile("{\n.reg .pred p;\nsetp.ne.b32 p, %58, 0;\n"
        "wgmma.mma_async.sync.aligned.m64n112k16.f32.bf16.bf16 {%0, %1, %2, %3, %4, %5, %6, %7, %8, %9, %10, %11, %12, %13, %14, %15, %16, %17, %18, %19, %20, %21, %22, %23, %24, %25, %26, %27, %28, %29, %30, %31, %32, %33, %34, %35, %36, %37, %38, %39, %40, %41, %42, %43, %44, %45, %46, %47, %48, %49, %50, %51, %52, %53, %54, %55}, %56, %57, p, 1, 1, %59, %60;\n}\n"
        : "+f"(d[0]), "+f"(d[1]), "+f"(d[2]), "+f"(d[3]), "+f"(d[4]), "+f"(d[5]), "+f"(d[6]), "+f"(d[7]), "+f"(d[8]), "+f"(d[9]), "+f"(d[10]), "+f"(d[11]), "+f"(d[12]), "+f"(d[13]), "+f"(d[14]), "+f"(d[15]), "+f"(d[16]), "+f"(d[17]), "+f"(d[18]), "+f"(d[19]), "+f"(d[20]), "+f"(d[21]), "+f"(d[22]), "+f"(d[23]), "+f"(d[24]), "+f"(d[25]), "+f"(d[26]), "+f"(d[27]), "+f"(d[28]), "+f"(d[29]), "+f"(d[30]), "+f"(d[31]), "+f"(d[32]), "+f"(d[33]), "+f"(d[34]), "+f"(d[35]), "+f"(d[36]), "+f"(d[37]), "+f"(d[38]), "+f"(d[39]), "+f"(d[40]), "+f"(d[41]), "+f"(d[42]), "+f"(d[43]), "+f"(d[44]), "+f"(d[45]), "+f"(d[46]), "+f"(d[47]), "+f"(d[48]), "+f"(d[49]), "+f"(d[50]), "+f"(d[51]), "+f"(d[52]), "+f"(d[53]), "+f"(d[54]), "+f"(d[55])
        : "l"(da), "l"(db), "r"(sc), "n"(TA), "n"(TB));
}

template<int NKB, bool PERM>
__device__ __forceinline__ void mix_mainloop(float (&acc)[56], uint32_t par, bool leader) {
    constexpr uint32_t sb = SB, bars = sb + SM_BAR;
    int bslot = 0, aslot = 0;
    reg_fence(acc);
    #pragma unroll 1
    for (int i = 0; i < NKB / 2; i++) {
        mbar_wait(bars + 8 * (B_FULLA + i), par);
        const uint64_t adesc = mkdesc(sb + SM_ARING, 8192, 1024, 1) + (uint32_t)(aslot * 1024);
        aslot = aslot == NA_SLOTS - 1 ? 0 : aslot + 1;
        #pragma unroll
        for (int jj = 0; jj < 2; jj++) {
            const int j = 2 * i + jj;
            mbar_wait(bars + 8 * (B_FULLB + j), par);
            const uint64_t bdesc = mkdesc(sb + SM_BRING, 1792, 128, 0) + (uint32_t)(bslot * 896);
            bslot = bslot == NB_SLOTS - 1 ? 0 : bslot + 1;
            wg_fence();
            #pragma unroll
            for (int s = 0; s < 4; s++) {
                const uint32_t aoff = PERM ? (s & 1) * 8192 + (jj * 32 + (s >> 1) * 16) * 128 : jj * 8192 + s * 2048;
                wgmma_ss112<1, 1>(acc, adesc + (aoff >> 4), bdesc + s * 224, 1);
            }
            wg_commit();
            wg_wait<1>();
            if (j > 0 && leader) mbar_arrive(bars + 8 * (B_DONE + j - 1));
        }
    }
    wg_wait<0>();
    reg_fence(acc);
    if (leader) mbar_arrive(bars + 8 * (B_DONE + NKB - 1));
}

template<int NKB>
__device__ __forceinline__ void mix_producer_b(uint32_t par, const uint32_t* flags, uint32_t target, const uint32_t* src, int lane) {
    constexpr uint32_t sb = SB, bars = sb + SM_BAR;
    uint32_t ready = 0;
    int bslot = 0;
    #pragma unroll 1
    for (int j = 0; j < NKB; j++) {
        if (!((ready >> j) & 1)) {
            do {
                uint32_t v = ld_acquire(flags + lane);
                ready = __ballot_sync(0xffffffffu, (int)(v - target) >= 0);
            } while (!((ready >> j) & 1));
            fence_async_global();
        }
        if (j >= NB_SLOTS) mbar_wait(bars + 8 * (B_DONE + j - NB_SLOTS), par);
        if (elect()) {
            mbar_expect(bars + 8 * (B_FULLB + j), 14336);
            bulk_ld(sb + SM_BRING + bslot * 14336, src + j * 3584, 14336, bars + 8 * (B_FULLB + j));
        }
        bslot = bslot == NB_SLOTS - 1 ? 0 : bslot + 1;
    }
}

template<bool USE_SMID>
__global__ void __launch_bounds__(384, 1)
fused_kernel(Scratch* __restrict__ sc, const __nv_bfloat16* __restrict__ x, const __nv_bfloat16* __restrict__ wo,
             const __nv_bfloat16* __restrict__ w1, const __nv_bfloat16* __restrict__ b1,
             const __nv_bfloat16* __restrict__ w2, const __nv_bfloat16* __restrict__ b2,
             const __grid_constant__ CUtensorMap tm_x, const __grid_constant__ CUtensorMap tm_wqkv,
             const __grid_constant__ CUtensorMap tm_wo64, const __grid_constant__ CUtensorMap tm_wo48,
             const __grid_constant__ CUtensorMap tm_w1, const __grid_constant__ CUtensorMap tm_w2,
             const __grid_constant__ CUtensorMap tm_out, const __grid_constant__ CUtensorMap tm_wcs) {
    extern __shared__ __align__(1024) uint8_t smem_raw[];
    constexpr uint32_t sb = SB;
    constexpr uint32_t bars = sb + SM_BAR;
    const int tid = threadIdx.x, lane = tid & 31;
    const int warp = __shfl_sync(0xffffffffu, tid >> 5, 0), wg = warp >> 2;
    int slot;
    if (USE_SMID) {
        asm("{\n.reg .u32 s, t, u, d, a, b, c;\n.reg .pred p, r;\n"
            "mov.u32 s, %%smid;\nshr.u32 t, s, 1;\nsub.u32 u, t, 32;\nmul.lo.u32 d, u, 37;\nshr.u32 d, d, 8;\n"
            "and.b32 a, t, 7;\nshl.b32 a, a, 3;\nshr.u32 c, t, 3;\nadd.u32 a, a, c;\n"
            "mad.lo.u32 b, d, -55, 12;\nshl.b32 c, u, 3;\nadd.u32 b, b, c;\n"
            "setp.lt.u32 p, t, 32;\nselp.u32 a, a, b, p;\n"
            "setp.lt.u32 r, t, 64;\nselp.u32 c, 56, 0, r;\nsub.u32 c, t, c;\nsetp.lt.u32 p, t, 60;\nselp.u32 a, a, c, p;\n"
            "and.b32 s, s, 1;\nshl.b32 a, a, 1;\nadd.u32 %0, a, s;\n}" : "=r"(slot));
    } else slot = blockIdx.x;
    const int G = slot >> 4, mi = slot & 15;
    const int tb = 4 * (G >> 1) + (mi >> 2), hp = 2 * (mi & 3) + (G & 1);
    const int wcol = (hp * 56) & ~15;
    const bool odd = G & 1;
    if (__builtin_expect(slot >= 128, 0)) {
        if (tid == 0) {
            const uint32_t ep = sc->epoch[slot] + 1;
            const long long t0 = clock64();
            while ((int)(ld_acquire(&sc->flag_u[0]) - 4 * ep) < 0) { __nanosleep(500); if (clock64() - t0 > WD_CLKS) __trap(); }
            sc->epoch[slot] = ep;
        }
        return;
    }
    const int q = mi & 3, tt2 = 4 * G + (mi >> 2), ft = 4 * (G - 1) + (mi >> 2);
    const bool has_b1 = G > 0;

    if (__builtin_expect(wg == 2, 1)) {
        asm volatile("setmaxnreg.dec.sync.aligned.u32 56;");
        if (__builtin_expect(warp == 8, 1)) {
            if (elect()) {
                constexpr uint32_t bar = bars + 8 * B_FULL1;
                #pragma unroll
                for (int i = 0; i < B_DONE1; i++) mbar_init(bars + 8 * i, 1);
                asm volatile("fence.mbarrier_init.release.cluster;" ::: "memory");
                mbar_expect(bar, 32768);
                if (!odd) { tma3d(sb, &tm_x, 0, 0, tb * 64, bar); tma3d(sb + 8192, &tm_x, 0, 1, tb * 64, bar); }
                tma2d(sb + 16384, &tm_wqkv, 448 + wcol, 0, bar);
                tma2d(sb + 24576, &tm_wqkv, 896 + wcol, 0, bar);
                if (odd) { tma3d(sb, &tm_x, 0, 0, tb * 64, bar); tma3d(sb + 8192, &tm_x, 0, 1, tb * 64, bar); }
                STAMP(22);
            }
            named_arrive(0, 384);
            #pragma unroll 1
            for (int kb = 1; kb < 7; kb++) {
                if (kb == 5) named_sync(4, 64);
                if (kb >= 5) mbar_wait(bars + 8 * (B_DONE1 + kb - 5), 0);
                if (elect()) {
                    const uint32_t st = sb + (kb >= 5 ? kb - 5 : kb) * SM_STAGE, bar = bars + 8 * (B_FULL1 + kb);
                    mbar_expect(bar, 32768 + (kb & 1) * 8192);
                    if (odd) tma2d(st + 16384, &tm_wqkv, 448 + wcol, kb * 64, bar);
                    if (kb & 1) tma2d(sb + 5 * SM_STAGE + (kb >> 1) * 8192, &tm_wqkv, wcol, (kb >> 1) * 64, bar);
                    if (odd) tma2d(st + 24576, &tm_wqkv, 896 + wcol, kb * 64, bar);
                    tma3d(st, &tm_x, kb * 64, 0, tb * 64, bar); tma3d(st + 8192, &tm_x, kb * 64, 1, tb * 64, bar);
                    if (!odd) { tma2d(st + 16384, &tm_wqkv, 448 + wcol, kb * 64, bar); tma2d(st + 24576, &tm_wqkv, 896 + wcol, kb * 64, bar); }
                    if (kb == CS_AT && slot < 126) {
                        mbar_expect(bars + 8 * B_CSBOX, 9600);
                        tma2d(sb + SM_H, &tm_wcs, (slot % 21) * 64, (slot / 21) * 75, bars + 8 * B_CSBOX);
                    }
                }
            }
            mbar_wait(bars + 8 * (B_DONE1 + 2), 0);
            if (elect()) {
                mbar_expect(bars + 8 * (B_FQ + 3), 32768);
                #pragma unroll 1
                for (int i = 0; i < 4; i++) { const int j = i ^ (int)odd; tma2d(sb + 2 * SM_STAGE + j * 8192, &tm_wqkv, wcol, (3 + j) * 64, bars + 8 * (B_FQ + 3)); }
            }
            if (smem_u32(smem_raw) != SB) __trap();
            const uint32_t ep = ld_volatile(&sc->epoch[slot]) + 1;
            #pragma unroll 1
            for (int pr = 0; pr < 4; pr++) {
                mbar_wait(bars + 8 * (B_DONE1 + 3 + pr), 0);
                if (elect()) {
                    const uint32_t bar = bars + 8 * B_FULLWO;
                    if (pr == 0) mbar_expect(bar, 448 * 112 * 2);
                    const uint32_t st = sb + (pr < 2 ? pr + 3 : pr - 2) * SM_STAGE;
                    tma2d(st, &tm_wo64, q * 112, pr * 128, bar);
                    tma2d(st + 8192, &tm_wo48, q * 112 + 64, pr * 128, bar);
                    if (pr < 3) {
                        tma2d(st + 16384, &tm_wo64, q * 112, pr * 128 + 64, bar);
                        tma2d(st + 24576, &tm_wo48, q * 112 + 64, pr * 128 + 64, bar);
                    }
                }
            }
            mbar_wait(bars + 8 * B_DONEQ, 0);
            {
                uint32_t issued = 0;
                while (issued != 15u) {
                    uint32_t v = ld_acquire(&sc->cnt_o[tt2 * 32 + (lane & 3)]);
                    uint32_t ready = __ballot_sync(0xffffffffu, (int)(v - 8 * ep) >= 0) & 15u & ~issued;
                    if (ready) {
                        fence_async_global();
                        if (lane < 4 && ((ready >> lane) & 1)) {
                            const uint32_t bar = bars + 8 * (B_FULLO + lane);
                            mbar_expect(bar, 14336);
                            bulk_ld(sb + (lane < 2 ? 2 : 5) * SM_STAGE + (lane & 1) * 14336, sc->o + tt2 * 14336 + lane * 3584, 14336, bar);
                        }
                        issued |= ready;
                    }
                    }
                __syncwarp();
            }
            if (lane == 0) STAMP(20);
            mbar_wait(bars + 8 * B_DONEO, 0);
            if (has_b1) {
                mix_producer_b<32>(0, sc->flag_h + q * 32, 4 * ep, sc->hn + q * 32 * 3584, lane);
                mbar_wait(bars + 8 * (B_DONE + 31), 0);
            }
            mix_producer_b<28>(has_b1, sc->flag_u + q * 32, 4 * ep, sc->u + q * 28 * 3584, lane);
        } else {
            if (warp == 9 && elect()) {
                #pragma unroll
                for (int i = B_DONE1; i < B_ONE; i++) mbar_init(bars + 8 * i, i == B_CS ? 3 : 2);
                asm volatile("fence.mbarrier_init.release.cluster;" ::: "memory");
            }
            named_sync(0, 384);
            if (warp == 9) named_arrive(4, 64);
            float* csf = (float*)(smem_raw + SM_CS);
            const uint32_t ep = ld_volatile(&sc->epoch[slot]) + 1;
            if (warp == 11 && lane == 0) bulk_prefetch((const char*)wo + slot * 3136, 3136);
            if (slot < 126) {
                float a8[8];
                #pragma unroll
                for (int i = 0; i < 8; i++) a8[i] = 0.f;
                const uint4* src = (const uint4*)(smem_raw + SM_H) + (warp - 9) * 200 + lane;
                mbar_wait(bars + 8 * B_CSBOX, 0);
                #pragma unroll
                for (int i = 0; i < 7; i++) {
                    const uint4 v = (i < 6 || lane < 8) ? src[32 * i] : make_uint4(0, 0, 0, 0);
                    a8[0] += bf_lo(v.x); a8[1] += bf_hi(v.x); a8[2] += bf_lo(v.y); a8[3] += bf_hi(v.y);
                    a8[4] += bf_lo(v.z); a8[5] += bf_hi(v.z); a8[6] += bf_lo(v.w); a8[7] += bf_hi(v.w);
                }
                float4* part = (float4*)(csf + 192) + (tid - 288) * 2;
                part[0] = make_float4(a8[0], a8[1], a8[2], a8[3]); part[1] = make_float4(a8[4], a8[5], a8[6], a8[7]);
                named_sync(3, 96);
                if (warp < 11) {
                    const int c = tid - 288;
                    float sum = 0.f;
                    #pragma unroll
                    for (int i = 0; i < 12; i++) sum += csf[192 + i * 64 + c];
                    st_relaxed2(&sc->cs[(slot / 21) * 1344 + (slot % 21) * 64 + c], __float_as_uint(sum), ep);
                }
                if (tid == 288) STAMP(24);
            }
            {
                const uint4* p = (const uint4*)sc->cs + (warp - 9) * 224 + hp * 28 + min(lane, 27);
                float c0, c1; bool ok;
                do {
                    c0 = c1 = 0.f; ok = true;
                    uint4 v[6];
                    #pragma unroll
                    for (int i = 0; i < 6; i++) v[i] = ld_relaxed4(p + i * 672);
                    #pragma unroll
                    for (int i = 0; i < 6; i++) { c0 += __uint_as_float(v[i].x); c1 += __uint_as_float(v[i].z); ok = ok && v[i].y == ep && v[i].w == ep; }
                } while (!__all_sync(0xffffffffu, ok));
                if (lane < 28) *(float2*)(csf + (warp - 9) * 56 + 2 * lane) = make_float2(c0, c1);
            }
            if (tid == 383) csf[168] = __uint_as_float(ep);
            __syncwarp();
            if (lane == 0) mbar_arrive(bars + 8 * B_CS);
            if (warp == 10) {
                if (lane == 0) STAMP(21);
            } else if (warp == 11) {
                if (lane == 0) {
                    mbar_wait_wd(bars + 8 * (B_FULL1 + 5), 0);
                    long long t = clock64();
                    #pragma unroll 1
                    for (int i = 0; i < 28; i++) {
                        const char* src = (i < 14 ? (const char*)w1 : (const char*)w2 - 14 * 524288) + i * 524288 + slot * 4096;
                        bulk_prefetch(src, 4096);
                        t += PF_PACE;
                        while (clock64() < t) __nanosleep(40);
                    }
                    mbar_wait_wd(bars + 8 * B_END, 0);
                }
            } else {
                mbar_wait(bars + 8 * B_DONEO, 0);
                int aslot = 0;
                if (has_b1) {
                    #pragma unroll 1
                    for (int i = 0; i < 16; i++) {
                        if (i >= NA_SLOTS) mbar_wait(bars + 8 * (B_DONE + 1 + ((i - NA_SLOTS) * 22) / (15 - NA_SLOTS)), 0);
                        if (elect()) {
                            const uint32_t bar = bars + 8 * (B_FULLA + i), dst = sb + SM_ARING + aslot * 16384;
                            mbar_expect(bar, 16384);
                            tma3d(dst, &tm_w1, ft * 64, 0, i * 64, bar);
                            tma3d(dst + 8192, &tm_w1, ft * 64, 1, i * 64, bar);
                        }
                        aslot = aslot == NA_SLOTS - 1 ? 0 : aslot + 1;
                    }
                }
                aslot = 0;
                #pragma unroll 1
                for (int i = 0; i < 14; i++) {
                    if (i >= NA_SLOTS) mbar_wait(bars + 8 * (B_DONE + 1 + ((i - NA_SLOTS) * 18) / (13 - NA_SLOTS)), has_b1);
                    else if (has_b1) {
                        const int last = i + NA_SLOTS * ((15 - i) / NA_SLOTS);
                        mbar_wait(bars + 8 * (B_DONE + max(2 * last + 1, 32 - NB_SLOTS)), 0);
                    }
                    if (i == NA_SLOTS - 1 && has_b1) mbar_wait(bars + 8 * (B_DONE + 31), 0);
                    if (elect()) {
                        const uint32_t bar = bars + 8 * (B_FULLA + i);
                        mbar_expect(bar, 16384);
                        tma2d(sb + SM_ARING + aslot * 16384, &tm_w2, tt2 * 64, i * 128, bar);
                    }
                    aslot = aslot == NA_SLOTS - 1 ? 0 : aslot + 1;
                }
            }
        }
    } else {
        if (elect()) {
            #pragma unroll
            for (int i = 0; i < 11; i++) mbar_init(bars + 8 * (B_ONE + i) + warp * 88, 1);
            asm volatile("fence.mbarrier_init.release.cluster;" ::: "memory");
        }
        named_sync(0, 384);
        asm volatile("setmaxnreg.inc.sync.aligned.u32 224;");
        uint32_t ep;
        const int w = warp & 3, g = lane >> 2, t = lane & 3;
        const bool leader = (tid & 127) == 0;
        {
            uint32_t a[28][4];
            float accK[28], accV[28], accQ[28];
            float s0 = 0.f, s1 = 0.f, q0 = 0.f, q1 = 0.f;
            const int lrow = 16 * w + (lane & 7) + (lane & 8);
            const uint32_t lbase = sb + wg * 8192 + lrow * 128;
            const uint32_t lx = (lane >> 4) ^ (lane & 7);
            const uint32_t never = gridDim.y - 1;
            const uint32_t wofs = hp & 1;
            auto stats = [&](int sa, int sb_) {
                #pragma unroll
                for (int s = sa; s < sb_; s++) {
                    #pragma unroll
                    for (int r = 0; r < 4; r++) {
                        const float lo = bf_lo(a[s][r]), hi = bf_hi(a[s][r]);
                        if (r & 1) { s1 += lo; q1 = fmaf(lo, lo, q1); s1 += hi; q1 = fmaf(hi, hi, q1); }
                        else       { s0 += lo; q0 = fmaf(lo, lo, q0); s0 += hi; q0 = fmaf(hi, hi, q0); }
                    }
                }
                asm volatile("{\n.reg .pred p;\nsetp.ne.u32 p, %4, 0;\n@p st.shared.v4.f32 [%5], {%0,%1,%2,%3};\n}" :: "f"(s0), "f"(s1), "f"(q0), "f"(q1), "r"(never), "r"(sb) : "memory");
            };
            auto qmma = [&](int sa, int sb_) {
                #pragma unroll
                for (int s = sa; s < sb_; s++)
                    wgmma_rs56<1>(accQ, a[s], mkdesc(sb + (s < 12 ? 5 * SM_STAGE + s * 2048 : 2 * SM_STAGE + (s - 12) * 2048), 8192, 1024, 1) + wofs, s != 0);
            };
            auto qsteps = [&](int sa, int sb_) { wg_fence(); qmma(sa, sb_); wg_commit(); wg_wait<1>(); };
            auto loadx = [&](int kb) {
                mbar_wait(bars + 8 * (B_FULL1 + kb), 0);
                #pragma unroll
                for (int s = 0; s < 4; s++) ldsm4(a[4 * kb + s], lbase + (kb % 5) * SM_STAGE + ((lx ^ (2 * s)) << 4));
            };
            loadx(0);
            if (tid == 0) STAMP(0);
            #pragma unroll
            for (int kb = 0; kb < 7; kb++) {
                const uint32_t st = (kb % 5) * SM_STAGE;
                if (kb > 0 && kb < 6) loadx(kb + 1);
                if (kb == 1 && tid == 0) STAMP(25);
                if (kb == 3 && tid == 0) STAMP(26);
                if (kb == 5 && tid == 0) STAMP(27);
                wg_fence();
                if (kb > 0) qmma(2 * kb - 2, 2 * kb);
                #pragma unroll
                for (int s = 0; s < 4; s++) {
                    wgmma_rs56<1>(accK, a[4 * kb + s], mkdesc(sb + st + 16384 + s * 2048, 8192, 1024, 1) + wofs, (kb | s) != 0);
                    wgmma_rs56<1>(accV, a[4 * kb + s], mkdesc(sb + st + 24576 + s * 2048, 8192, 1024, 1) + wofs, (kb | s) != 0);
                }
                wg_commit();
                if (kb > 0) {
                    wg_wait<1>();
                    if (leader) mbar_arrive(bars + 8 * (B_DONE1 + kb - 1));
                }
                stats(4 * kb, 4 * kb + 4);
                if (kb == 0) loadx(1);
            }
            if (tid == 0) STAMP(1);
            s0 = quad_sum(s0); s1 = quad_sum(s1); q0 = quad_sum(q0); q1 = quad_sum(q1);
            const float m0 = s0 * (1.f / D_), m1 = s1 * (1.f / D_);
            const float r0 = rsqrt_approx(fmaxf(q0 * (1.f / D_) - m0 * m0, 0.f) + LN_EPS), r1 = rsqrt_approx(fmaxf(q1 * (1.f / D_) - m1 * m1, 0.f) + LN_EPS);
            mbar_wait(bars + 8 * (B_FQ + 3), 0);
            qsteps(12, 18);
            reg_fence(accK); reg_fence(accV);
            if (leader) mbar_arrive(bars + 8 * (B_DONE1 + 6));
            if (tid == 0) STAMP(2);
            mbar_wait(bars + 8 * B_CS, 0);
            const float2* cs2 = (const float2*)(smem_raw + SM_CS);
            ep = __float_as_uint(cs2[84].x);
            uint32_t Kb[7], Kc[7], Vb[7], Vc[7];
            #pragma unroll
            for (int j = 0; j < 7; j++) {
                const float2 ck = cs2[28 + 4 * j + t], cv = cs2[56 + 4 * j + t];
                Kc[j] = pack_bf16((accK[4 * j + 2] - m1 * ck.x) * r1, (accK[4 * j + 3] - m1 * ck.y) * r1);
                Vc[j] = movtrans(pack_bf16((accV[4 * j + 2] - m1 * cv.x) * r1, (accV[4 * j + 3] - m1 * cv.y) * r1));
            }
            uint2* hs = (uint2*)(smem_raw + SM_HALO) + warp * 256 + lane;
            if (w < 3) {
                #pragma unroll
                for (int j = 0; j < 7; j++) hs[j * 32] = make_uint2(Kc[j], Vc[j]);
            } else if (tb < 15) {
                uint4* hg = sc->halo + (((tb + 1) * 8 + hp) * 2 + wg) * 224 + lane;
                #pragma unroll
                for (int j = 0; j < 7; j++) st_relaxed4(hg + j * 32, Kc[j], ep, Vc[j], ep);
            }
            if (tid == 0) STAMP(23);
            qsteps(18, 23);
            #pragma unroll
            for (int j = 0; j < 7; j++) {
                const float2 ck = cs2[28 + 4 * j + t], cv = cs2[56 + 4 * j + t];
                Kb[j] = pack_bf16((accK[4 * j] - m0 * ck.x) * r0, (accK[4 * j + 1] - m0 * ck.y) * r0);
                Vb[j] = movtrans(pack_bf16((accV[4 * j] - m0 * cv.x) * r0, (accV[4 * j + 1] - m0 * cv.y) * r0));
                asm volatile("" : "+r"(Kb[j]));
            }
            qsteps(23, 28);
            named_sync(1 + wg, 128);
            uint32_t Ka[7], Va[7];
            if (w > 0) {
                #pragma unroll
                for (int j = 0; j < 7; j++) { const uint2 v = hs[j * 32 - 256]; Ka[j] = v.x; Va[j] = v.y; }
            } else if (tb > 0) {
                const uint4* hg = sc->halo + ((tb * 8 + hp) * 2 + wg) * 224 + lane;
                bool ok;
                do {
                    ok = true;
                    #pragma unroll
                    for (int j = 0; j < 7; j++) { const uint4 v = ld_relaxed4(hg + j * 32); Ka[j] = v.x; Va[j] = v.z; ok = ok && v.y == ep && v.w == ep; }
                    } while (!__all_sync(0xffffffffu, ok));
            } else {
                #pragma unroll
                for (int j = 0; j < 7; j++) { Ka[j] = 0; Va[j] = 0; }
            }
            if (tid == 0) STAMP(3);
            wg_wait<0>();
            reg_fence(accQ);
            if (leader) mbar_arrive(bars + 8 * B_DONEQ);
            if (tid == 0) STAMP(4);
            uint32_t Q0[7], Q1[7];
            #pragma unroll
            for (int j = 0; j < 7; j++) {
                const float2 cq = cs2[4 * j + t];
                Q0[j] = pack_bf16((accQ[4 * j] - m0 * cq.x) * r0, (accQ[4 * j + 1] - m0 * cq.y) * r0);
                Q1[j] = pack_bf16((accQ[4 * j + 2] - m1 * cq.x) * r1, (accQ[4 * j + 3] - m1 * cq.y) * r1);
            }
            const bool first = (tb == 0 && w == 0);
            const float lsc = 0.1889822365046136f * 1.4426950408889634f;
            float o[8][4];
            #pragma unroll
            for (int h = 0; h < 2; h++) {
                const int j0 = 3 * h;
                const bool own3 = (t >= 2) == (h == 1);
                uint32_t qa[4], qb[4];
                #pragma unroll
                for (int j = 0; j < 4; j++) {
                    qa[j] = (j0 + j == 3 && !own3) ? 0u : Q0[j0 + j];
                    qb[j] = (j0 + j == 3 && !own3) ? 0u : Q1[j0 + j];
                }
                float sA[4] = {0.f, 0.f, 0.f, 0.f}, sB[4] = {0.f, 0.f, 0.f, 0.f}, sC[4] = {0.f, 0.f, 0.f, 0.f};
                #pragma unroll
                for (int k = 0; k < 2; k++) {
                    mma16816(sA, qa[2 * k], qb[2 * k], qa[2 * k + 1], qb[2 * k + 1], Ka[j0 + 2 * k], Ka[j0 + 2 * k + 1]);
                    mma16816(sB, qa[2 * k], qb[2 * k], qa[2 * k + 1], qb[2 * k + 1], Kb[j0 + 2 * k], Kb[j0 + 2 * k + 1]);
                    mma16816(sC, qa[2 * k], qb[2 * k], qa[2 * k + 1], qb[2 * k + 1], Kc[j0 + 2 * k], Kc[j0 + 2 * k + 1]);
                }
                const bool n0 = 2 * t <= g, n1 = 2 * t + 1 <= g;
                float l00 = n0 ? sB[0] : (first ? -1e30f : sA[0]), l01 = n1 ? sB[1] : (first ? -1e30f : sA[1]);
                float l10 = n0 ? sC[2] : sB[2], l11 = n1 ? sC[3] : sB[3];
                const float x0 = quad_max(fmaxf(l00, l01)), x1 = quad_max(fmaxf(l10, l11));
                const float e00 = ex2((l00 - x0) * lsc), e01 = ex2((l01 - x0) * lsc), e10 = ex2((l10 - x1) * lsc), e11 = ex2((l11 - x1) * lsc);
                const float i0 = rcp_approx(quad_sum(e00 + e01)), i1 = rcp_approx(quad_sum(e10 + e11));
                const float p00 = e00 * i0, p01 = e01 * i0, p10 = e10 * i1, p11 = e11 * i1;
                const uint32_t pA = pack_bf16(n0 ? 0.f : p00, n1 ? 0.f : p01), pB0 = pack_bf16(n0 ? p00 : 0.f, n1 ? p01 : 0.f);
                const uint32_t pC = pack_bf16(n0 ? p10 : 0.f, n1 ? p11 : 0.f), pB1 = pack_bf16(n0 ? 0.f : p10, n1 ? 0.f : p11);
                #pragma unroll
                for (int j = 0; j < 4; j++) {
                    float (&oo)[4] = o[4 * h + j];
                    oo[0] = oo[1] = oo[2] = oo[3] = 0.f;
                    mma16816(oo, pA, 0u, 0u, pC, Va[j0 + j], Vc[j0 + j]);
                    mma1688(oo, pB0, pB1, Vb[j0 + j]);
                }
            }
            const int tt = 2 * tb + (w >> 1);
            uint32_t* od = sc->o + tt * 14336 + (7 * hp) * 256 + (2 * (2 * (w & 1) + wg)) * 32 + lane;
            #pragma unroll
            for (int j = 0; j < 7; j++) {
                float v[4];
                #pragma unroll
                for (int c = 0; c < 4; c++) v[c] = j < 3 ? o[j][c] : j > 3 ? o[j + 1][c] : (t < 2 ? o[3][c] : o[4][c]);
                od[j * 256] = pack_bf16(v[0], v[1]);
                od[j * 256 + 32] = pack_bf16(v[2], v[3]);
            }
            if (tid == 0) STAMP(5);
            __syncwarp();
            if (elect()) red_release(&sc->cnt_o[tt * 32 + (hp >> 1)]);
            if (tid == 0) STAMP(6);
        }
        if (wg == 0) {
            const uint32_t rb10 = has_b1 ? __ldg((const unsigned short*)b1 + ft * 64 + 16 * w + g) : 0, rb11 = has_b1 ? __ldg((const unsigned short*)b1 + ft * 64 + 16 * w + g + 8) : 0;
            const uint32_t rb20 = __ldg((const unsigned short*)b2 + tt2 * 64 + 16 * w + g), rb21 = __ldg((const unsigned short*)b2 + tt2 * 64 + 16 * w + g + 8);
            {
                float acc[56];
                uint32_t xr[28];
                const int tok = 64 * tt2 + 32 * (w >> 1) + 2 * g + (w & 1);
                const uint32_t* xp = (const uint32_t*)(x + tok * D_ + q * 112) + t;
                #pragma unroll
                for (int j = 0; j < 14; j++) { xr[2 * j] = __ldg(xp + 4 * j); xr[2 * j + 1] = __ldg(xp + 4 * j + 16 * (D_ / 2)); }
                #pragma unroll
                for (int j = 0; j < 28; j++) { acc[2 * j] = bf_lo(xr[j]); acc[2 * j + 1] = bf_hi(xr[j]); }
                reg_fence(acc);
                mbar_wait(bars + 8 * B_FULLWO, 0);
                #pragma unroll
                for (int i = 0; i < 4; i++) {
                    mbar_wait(bars + 8 * (B_FULLO + i), 0);
                    if (i == 0 && tid == 0) STAMP(7);
                    wg_fence();
                    #pragma unroll
                    for (int ss = 0; ss < 7; ss++) {
                        const int s = 7 * i + ss, kb = s >> 2;
                        wgmma_ss112<0, 1>(acc, mkdesc(sb + (i < 2 ? 2 * SM_STAGE + s * 2048 : 5 * SM_STAGE + (s - 14) * 2048), 1024, 128, 0),
                                          mkdesc(sb + (((kb >> 1) + 3) % 5) * SM_STAGE + (kb & 1) * 16384 + (s & 3) * 2048, 8192, 1024, 1), 1);
                    }
                    wg_commit();
                }
                wg_wait<0>();
                reg_fence(acc);
                if (tid == 0) STAMP(8);
                float s0 = 0.f, s1 = 0.f, q0 = 0.f, q1 = 0.f, s2 = 0.f, s3 = 0.f, q2 = 0.f, q3 = 0.f;
                #pragma unroll
                for (int j = 0; j < 14; j++) {
                    s0 += acc[4 * j]; s2 += acc[4 * j + 1]; q0 = fmaf(acc[4 * j], acc[4 * j], q0); q2 = fmaf(acc[4 * j + 1], acc[4 * j + 1], q2);
                    s1 += acc[4 * j + 2]; s3 += acc[4 * j + 3]; q1 = fmaf(acc[4 * j + 2], acc[4 * j + 2], q1); q3 = fmaf(acc[4 * j + 3], acc[4 * j + 3], q3);
                }
                s0 = quad_sum(s0 + s2); s1 = quad_sum(s1 + s3); q0 = quad_sum(q0 + q2); q1 = quad_sum(q1 + q3);
                uint4* sp = sc->stats + tt2 * 256 + 16 * w + g;
                if (t < 2) st_relaxed4(sp + q * 64 + 8 * t, __float_as_uint(t ? s1 : s0), ep, __float_as_uint(t ? q1 : q0), ep);
                if (tid == 0) STAMP(9);
                {
                    const int mrow = 32 * (w >> 1) + 2 * ((lane & 7) + (lane & 8)) + (w & 1);
                    #pragma unroll
                    for (int jp = 0; jp < 7; jp++)
                        stsm4(sb + SM_H + mrow * 224 + (2 * jp + (lane >> 4)) * 16, pack_bf16(acc[8 * jp], acc[8 * jp + 1]), pack_bf16(acc[8 * jp + 2], acc[8 * jp + 3]),
                              pack_bf16(acc[8 * jp + 4], acc[8 * jp + 5]), pack_bf16(acc[8 * jp + 6], acc[8 * jp + 7]));
                }
                {
                    uint4 v0, v1;
                    do {
                        v0 = ld_relaxed4(sp + t * 64); v1 = ld_relaxed4(sp + t * 64 + 8);
                    } while (__any_sync(0xffffffffu, t != q && (v0.y != ep || v0.w != ep || v1.y != ep || v1.w != ep)));
                    if (t != q) { s0 = __uint_as_float(v0.x); q0 = __uint_as_float(v0.z); s1 = __uint_as_float(v1.x); q1 = __uint_as_float(v1.z); }
                }
                if (leader) mbar_arrive(bars + 8 * B_DONEO);
                if (tid == 0) STAMP(10);
                s0 = quad_sum(s0); s1 = quad_sum(s1); q0 = quad_sum(q0); q1 = quad_sum(q1);
                const float m0 = s0 * (1.f / D_), m1 = s1 * (1.f / D_);
                const float v0 = fmaxf(q0 * (1.f / D_) - m0 * m0, 0.f), v1 = fmaxf(q1 * (1.f / D_) - m1 * m1, 0.f);
                float r0 = rsqrt_approx(v0 + LN_EPS), r1 = rsqrt_approx(v1 + LN_EPS);
                r0 *= 0.5f * rsqrt_approx(fmaf(v0 * r0, r0, LN_EPS)); r1 *= 0.5f * rsqrt_approx(fmaf(v1 * r1, r1, LN_EPS));
                const float c0 = -m0 * r0, c1 = -m1 * r1;
                uint32_t* hd = sc->hn + (q * 32 + tt2) * 3584 + (2 * w) * 448 + lane;
                #pragma unroll
                for (int j = 0; j < 14; j++) {
                    hd[j * 32] = pack_bf16(fmaf(acc[4 * j], r0, c0), fmaf(acc[4 * j + 1], r0, c0));
                    hd[j * 32 + 448] = pack_bf16(fmaf(acc[4 * j + 2], r1, c1), fmaf(acc[4 * j + 3], r1, c1));
                }
                if (tid == 0) STAMP(11);
                __syncwarp();
                if (elect()) red_release(&sc->flag_h[q * 32 + tt2]);
                if (tid == 0) STAMP(12);
            }
            if (has_b1) {
                float acc[56];
                #pragma unroll
                for (int j = 0; j < 56; j++) acc[j] = 0.5f * bf_lo((j & 2) ? rb11 : rb10);
                mix_mainloop<32, true>(acc, 0, leader);
                if (tid == 0) STAMP(14);
                uint32_t* ud = sc->u + (q * 28 + ft) * 3584 + (2 * w) * 448 + lane;
                #pragma unroll
                for (int j = 0; j < 14; j++) {
                    ud[j * 32] = pack_bf16(gelu_half(acc[4 * j]), gelu_half(acc[4 * j + 1]));
                    ud[j * 32 + 448] = pack_bf16(gelu_half(acc[4 * j + 2]), gelu_half(acc[4 * j + 3]));
                }
                if (tid == 0) STAMP(15);
                __syncwarp();
                if (elect()) red_release(&sc->flag_u[q * 32 + ft]);
                if (tid == 0) STAMP(16);
            }
            {
                float acc[56];
                const float bb0 = bf_lo(rb20), bb1 = bf_lo(rb21);
                named_sync(1, 128);
                const uint32_t ad = sb + SM_H + (16 * w + (lane & 7) + (lane & 8)) * 224 + (lane >> 4) * 16;
                #pragma unroll
                for (int jp = 0; jp < 7; jp++) {
                    uint32_t hh[4];
                    ldsm4(hh, ad + jp * 32);
                    #pragma unroll
                    for (int r = 0; r < 4; r++) { acc[8 * jp + 2 * r] = bf_lo(hh[r]) + ((r & 1) ? bb1 : bb0); acc[8 * jp + 2 * r + 1] = bf_hi(hh[r]) + ((r & 1) ? bb1 : bb0); }
                }
                mix_mainloop<28, false>(acc, has_b1, leader);
                if (leader) mbar_arrive(bars + 8 * B_END);
                if (tid == 0) STAMP(18);
                #pragma unroll
                for (int jp = 0; jp < 7; jp++)
                    stsm4(ad + jp * 32, pack_bf16(acc[8 * jp], acc[8 * jp + 1]), pack_bf16(acc[8 * jp + 2], acc[8 * jp + 3]),
                          pack_bf16(acc[8 * jp + 4], acc[8 * jp + 5]), pack_bf16(acc[8 * jp + 6], acc[8 * jp + 7]));
                fence_async_smem();
                __syncwarp();
                if (elect()) {
                    tma2d_store(&tm_out, q * 112, tt2 * 64 + 16 * w, sb + SM_H + w * 3584);
                    asm volatile("cp.async.bulk.commit_group;" ::: "memory");
                    asm volatile("cp.async.bulk.wait_group.read 0;" ::: "memory");
                }
                if (tid == 0) { sc->epoch[slot] = ep; STAMP(19); }
            }
        }
    }
}

typedef CUresult (*EncodeFn)(CUtensorMap*, CUtensorMapDataType, cuuint32_t, void*, const cuuint64_t*, const cuuint64_t*, const cuuint32_t*,
                             const cuuint32_t*, CUtensorMapInterleave, CUtensorMapSwizzle, CUtensorMapL2promotion, CUtensorMapFloatOOBfill);

void make_map(EncodeFn fn, CUtensorMap* tm, const void* ptr, int rank, const cuuint64_t* dims, const cuuint64_t* strides, const cuuint32_t* box, CUtensorMapSwizzle sw) {
    cuuint32_t es[3] = {1, 1, 1};
    fn(tm, CU_TENSOR_MAP_DATA_TYPE_BFLOAT16, rank, const_cast<void*>(ptr), dims, strides, box, es, CU_TENSOR_MAP_INTERLEAVE_NONE, sw,
       CU_TENSOR_MAP_L2_PROMOTION_NONE, CU_TENSOR_MAP_FLOAT_OOB_FILL_NONE);
}

}

extern "C" void kernel_launch(void* const* d_in, const int* in_sizes, int n_in, void* d_out, int out_size) {
    const __nv_bfloat16* x = (const __nv_bfloat16*)d_in[0];
    const __nv_bfloat16* wqkv = (const __nv_bfloat16*)d_in[1];
    const __nv_bfloat16* wo = (const __nv_bfloat16*)d_in[2];
    const __nv_bfloat16* w1 = (const __nv_bfloat16*)d_in[4];
    const __nv_bfloat16* b1 = (const __nv_bfloat16*)d_in[5];
    const __nv_bfloat16* w2 = (const __nv_bfloat16*)d_in[6];
    const __nv_bfloat16* b2 = (const __nv_bfloat16*)d_in[7];

    void* fnp = nullptr; cudaDriverEntryPointQueryResult qr;
    cudaGetDriverEntryPoint("cuTensorMapEncodeTiled", &fnp, cudaEnableDefault, &qr);
    EncodeFn fn = (EncodeFn)fnp;
    CUtensorMap tx, twqkv, two64, two48, tw1, tw2, tout, twcs;
    { cuuint64_t d[2] = {1344, 448}, s[1] = {2688}; cuuint32_t b[2] = {64, 75}; make_map(fn, &twcs, wqkv, 2, d, s, b, CU_TENSOR_MAP_SWIZZLE_NONE); }
    { cuuint64_t d[3] = {448, 2, 1024}, s[2] = {896, 1792}; cuuint32_t b[3] = {64, 1, 64}; make_map(fn, &tx, x, 3, d, s, b, CU_TENSOR_MAP_SWIZZLE_128B); }
    { cuuint64_t d[2] = {1344, 448}, s[1] = {2688}; cuuint32_t b[2] = {64, 64}; make_map(fn, &twqkv, wqkv, 2, d, s, b, CU_TENSOR_MAP_SWIZZLE_128B); }
    { cuuint64_t d[2] = {448, 448}, s[1] = {896}; cuuint32_t b[2] = {64, 64}; make_map(fn, &two64, wo, 2, d, s, b, CU_TENSOR_MAP_SWIZZLE_128B); }
    { cuuint64_t d[2] = {448, 448}, s[1] = {896}; cuuint32_t b[2] = {48, 64}; make_map(fn, &two48, wo, 2, d, s, b, CU_TENSOR_MAP_SWIZZLE_128B); }
    { cuuint64_t d[3] = {1792, 2, 1024}, s[2] = {3584, 7168}; cuuint32_t b[3] = {64, 1, 64}; make_map(fn, &tw1, w1, 3, d, s, b, CU_TENSOR_MAP_SWIZZLE_128B); }
    { cuuint64_t d[2] = {2048, 1792}, s[1] = {4096}; cuuint32_t b[2] = {64, 128}; make_map(fn, &tw2, w2, 2, d, s, b, CU_TENSOR_MAP_SWIZZLE_128B); }
    { cuuint64_t d[2] = {448, 2048}, s[1] = {896}; cuuint32_t b[2] = {112, 16}; make_map(fn, &tout, d_out, 2, d, s, b, CU_TENSOR_MAP_SWIZZLE_NONE); }

    void* scv = nullptr;
    cudaGetSymbolAddress(&scv, g_scratch);
    Scratch* scp = (Scratch*)scv;
    int dev = 0, sms = 0;
    cudaGetDevice(&dev);
    cudaDeviceGetAttribute(&sms, cudaDevAttrMultiProcessorCount, dev);
    if (sms == 132) {
        cudaFuncSetAttribute(fused_kernel<true>, cudaFuncAttributeMaxDynamicSharedMemorySize, SM_TOTAL);
        fused_kernel<true><<<132, 384, SM_TOTAL>>>(scp, x, wo, w1, b1, w2, b2, tx, twqkv, two64, two48, tw1, tw2, tout, twcs);
    } else {
        cudaFuncSetAttribute(fused_kernel<false>, cudaFuncAttributeMaxDynamicSharedMemorySize, SM_TOTAL);
        fused_kernel<false><<<128, 384, SM_TOTAL>>>(scp, x, wo, w1, b1, w2, b2, tx, twqkv, two64, two48, tw1, tw2, tout, twcs);
    }
}
```

```cpp
#include <cuda_runtime.h>
#include <cuda_bf16.h>
#include <cuda.h>
#include <stdint.h>

namespace {

constexpr int D_ = 448;
constexpr float LN_EPS = 1e-5f;

struct Scratch {
    uint32_t o[32 * 57344 / 4];
    uint32_t hn[4 * 32 * 14336 / 4];
    uint32_t u[4 * 28 * 14336 / 4];
    uint4 halo[128 * 2 * 2 * 3 * 32];
    uint4 stats[32 * 4 * 64];
    uint4 hint_o[32 * 32 * 2];
    uint4 hint_h[4 * 32 * 2];
    uint4 hint_u[4 * 32 * 2];
    uint32_t epoch[160];
};
__device__ __align__(1024) Scratch g_scratch;
#define STAMP(i) do {} while (0)
#define TSARG
#define TSVAL

constexpr uint32_t SB = 1024;
constexpr int SM_SLOT = 16384;
__device__ __forceinline__ constexpr uint32_t slot_x(int kb) { return (kb ? 6 + kb : 0) * SM_SLOT; }
__device__ __forceinline__ constexpr uint32_t slot_kv(int kb) { return (kb < 5 ? 2 + kb : 6 - kb) * SM_SLOT; }
__device__ __forceinline__ constexpr uint32_t slot_wo(int kb) { return (kb < 6 ? 2 + kb : 12) * SM_SLOT; }
constexpr int SM_QO = 8 * SM_SLOT;
constexpr int SM_HALOK = SM_QO + 57344, SM_HALOV = 1 * SM_SLOT;
constexpr int NA_SLOTS = 6, NB_SLOTS = 8;
constexpr int SM_ARING = 0;
constexpr int SM_BRING = NA_SLOTS * 16384;
constexpr int SM_MISC = 212992;
constexpr int SM_H = 217088;
constexpr int SM_BAR = 231424;
constexpr int SM_TOTAL = 232448;
constexpr int B_FULLX = 0;
constexpr int B_FULLKV = 7;
constexpr int B_FQ = 14;
constexpr int B_DONE1 = 16;
constexpr int B_DONEX = 23;
constexpr int B_DONEQ = 24;
constexpr int B_DONEO = 25;
constexpr int B_FULLO = 29;
constexpr int B_FULLWO = 33;
constexpr int B_END = 34;
constexpr int B_HALO = 35;
constexpr int B_FULLA = 39;
constexpr int B_FULLB = 55;
constexpr int B_DONE = 87;
constexpr int B_RAW = 119;
constexpr int B_CLR = 127;

constexpr long long WD_CLKS = 2000000000ll;

__device__ __forceinline__ uint32_t smem_u32(const void* p) { return (uint32_t)__cvta_generic_to_shared(p); }
__device__ __forceinline__ void mbar_init(uint32_t bar, uint32_t cnt) { asm volatile("mbarrier.init.shared::cta.b64 [%0], %1;" :: "r"(bar), "r"(cnt) : "memory"); }
__device__ __forceinline__ void mbar_expect(uint32_t bar, uint32_t bytes) { asm volatile("mbarrier.arrive.expect_tx.shared::cta.b64 _, [%0], %1;" :: "r"(bar), "r"(bytes) : "memory"); }
__device__ __forceinline__ void mbar_arrive(uint32_t bar) { asm volatile("mbarrier.arrive.shared::cta.b64 _, [%0];" :: "r"(bar) : "memory"); }
__device__ __forceinline__ bool mbar_try(uint32_t bar, uint32_t parity) {
    uint32_t ok;
    asm volatile("{\n.reg .pred p;\nmbarrier.try_wait.parity.shared::cta.b64 p, [%1], %2;\nselp.u32 %0, 1, 0, p;\n}" : "=r"(ok) : "r"(bar), "r"(parity) : "memory");
    return ok;
}
__device__ __forceinline__ void mbar_wait(uint32_t bar, uint32_t parity) {
    asm volatile("{\n.reg .pred p;\n"
                 "WAIT_LOOP:\n"
                 "mbarrier.try_wait.parity.shared::cta.b64 p, [%0], %1;\n"
                 "@!p bra WAIT_LOOP;\n}" :: "r"(bar), "r"(parity) : "memory");
}
__device__ __forceinline__ void mbar_wait_wd(uint32_t bar, uint32_t parity) {
    const long long t0 = clock64();
    while (!mbar_try(bar, parity)) { if (clock64() - t0 > WD_CLKS) __trap(); }
}
__device__ __forceinline__ bool elect() { uint32_t p; asm volatile("{\n.reg .pred P;\nelect.sync _|P, 0xffffffff;\nselp.u32 %0, 1, 0, P;\n}" : "=r"(p)); return p; }
__device__ __forceinline__ void tma2d(uint32_t dst, const CUtensorMap* tm, int c0, int c1, uint32_t bar) {
    asm volatile("cp.async.bulk.tensor.2d.shared::cluster.global.mbarrier::complete_tx::bytes [%0], [%1, {%3, %4}], [%2];" :: "r"(dst), "l"(tm), "r"(bar), "r"(c0), "r"(c1) : "memory");
}
__device__ __forceinline__ void tma3d(uint32_t dst, const CUtensorMap* tm, int c0, int c1, int c2, uint32_t bar) {
    asm volatile("cp.async.bulk.tensor.3d.shared::cluster.global.mbarrier::complete_tx::bytes [%0], [%1, {%3, %4, %5}], [%2];" :: "r"(dst), "l"(tm), "r"(bar), "r"(c0), "r"(c1), "r"(c2) : "memory");
}
__device__ __forceinline__ void tma2d_store(const CUtensorMap* tm, int c0, int c1, uint32_t src) {
    asm volatile("cp.async.bulk.tensor.2d.global.shared::cta.bulk_group [%0, {%2, %3}], [%1];" :: "l"(tm), "r"(src), "r"(c0), "r"(c1) : "memory");
}
__device__ __forceinline__ void bulk_ld(uint32_t dst, const void* src, uint32_t bytes, uint32_t bar) {
    asm volatile("cp.async.bulk.shared::cluster.global.mbarrier::complete_tx::bytes [%0], [%1], %2, [%3];" :: "r"(dst), "l"(src), "r"(bytes), "r"(bar) : "memory");
}
__device__ __forceinline__ void bulk_prefetch(const void* src, uint32_t bytes) { asm volatile("cp.async.bulk.prefetch.L2.global [%0], %1;" :: "l"(src), "r"(bytes) : "memory"); }
__device__ __forceinline__ void fence_async_smem() { asm volatile("fence.proxy.async.shared::cta;" ::: "memory"); }
__device__ __forceinline__ uint32_t ld_relaxed(const void* p) { uint32_t v; asm volatile("ld.relaxed.gpu.global.u32 %0, [%1];" : "=r"(v) : "l"(p) : "memory"); return v; }
__device__ __forceinline__ uint4 ld_relaxed4(const uint4* p) { uint4 v; asm volatile("ld.relaxed.gpu.global.v4.u32 {%0,%1,%2,%3}, [%4];" : "=r"(v.x), "=r"(v.y), "=r"(v.z), "=r"(v.w) : "l"(p) : "memory"); return v; }
__device__ __forceinline__ void st_relaxed4(uint4* p, uint32_t a, uint32_t b, uint32_t c, uint32_t d) { asm volatile("st.relaxed.gpu.global.v4.u32 [%0], {%1,%2,%3,%4};" :: "l"(p), "r"(a), "r"(b), "r"(c), "r"(d) : "memory"); }
__device__ __forceinline__ uint32_t ld_volatile(const uint32_t* p) { uint32_t v; asm volatile("ld.volatile.global.u32 %0, [%1];" : "=r"(v) : "l"(p) : "memory"); return v; }
__device__ __forceinline__ void named_arrive(int id, int n) { asm volatile("bar.arrive %0, %1;" :: "r"(id), "r"(n) : "memory"); }
__device__ __forceinline__ void named_sync(int id, int n) { asm volatile("bar.sync %0, %1;" :: "r"(id), "r"(n) : "memory"); }
__device__ __forceinline__ void wg_fence() { asm volatile("wgmma.fence.sync.aligned;" ::: "memory"); }
__device__ __forceinline__ void wg_commit() { asm volatile("wgmma.commit_group.sync.aligned;" ::: "memory"); }
template<int N> __device__ __forceinline__ void wg_wait() { asm volatile("wgmma.wait_group.sync.aligned %0;" :: "n"(N) : "memory"); }
template<int N> __device__ __forceinline__ void reg_fence(float (&d)[N]) {
    #pragma unroll
    for (int i = 0; i < N; i++) asm volatile("" : "+f"(d[i]) :: "memory");
}
__device__ __forceinline__ constexpr uint64_t mkdesc(uint32_t addr, uint32_t lbo, uint32_t sbo, uint32_t sw) {
    return (uint64_t)((addr & 0x3FFFF) >> 4) | ((uint64_t)(lbo >> 4) << 16) | ((uint64_t)(sbo >> 4) << 32) | ((uint64_t)sw << 62);
}
__device__ __forceinline__ void ldsm4(uint32_t (&r)[4], uint32_t addr) {
    asm volatile("ldmatrix.sync.aligned.m8n8.x4.shared.b16 {%0,%1,%2,%3}, [%4];" : "=r"(r[0]), "=r"(r[1]), "=r"(r[2]), "=r"(r[3]) : "r"(addr) : "memory");
}
__device__ __forceinline__ void stsm4(uint32_t addr, uint32_t r0, uint32_t r1, uint32_t r2, uint32_t r3) {
    asm volatile("stmatrix.sync.aligned.m8n8.x4.shared.b16 [%0], {%1,%2,%3,%4};" :: "r"(addr), "r"(r0), "r"(r1), "r"(r2), "r"(r3) : "memory");
}
__device__ __forceinline__ uint32_t movtrans(uint32_t a) { uint32_t d; asm volatile("movmatrix.sync.aligned.m8n8.trans.b16 %0, %1;" : "=r"(d) : "r"(a)); return d; }
__device__ __forceinline__ uint32_t pack_bf16(float lo, float hi) { uint32_t r; asm("cvt.rn.bf16x2.f32 %0, %1, %2;" : "=r"(r) : "f"(hi), "f"(lo)); return r; }
__device__ __forceinline__ void sub_bf16x2(uint32_t& a, uint32_t b) { asm volatile("sub.rn.bf16x2 %0, %0, %1;" : "+r"(a) : "r"(b)); }
__device__ __forceinline__ float bf_lo(uint32_t v) { return __uint_as_float(v << 16); }
__device__ __forceinline__ float bf_hi(uint32_t v) { return __uint_as_float(v & 0xffff0000u); }
__device__ __forceinline__ void mma16816(float (&c)[4], uint32_t a0, uint32_t a1, uint32_t a2, uint32_t a3, uint32_t b0, uint32_t b1) {
    asm volatile("mma.sync.aligned.m16n8k16.row.col.f32.bf16.bf16.f32 {%0,%1,%2,%3}, {%4,%5,%6,%7}, {%8,%9}, {%0,%1,%2,%3};"
        : "+f"(c[0]), "+f"(c[1]), "+f"(c[2]), "+f"(c[3]) : "r"(a0), "r"(a1), "r"(a2), "r"(a3), "r"(b0), "r"(b1));
}
__device__ __forceinline__ void mma1688(float (&c)[4], uint32_t a0, uint32_t a1, uint32_t b0) {
    asm volatile("mma.sync.aligned.m16n8k8.row.col.f32.bf16.bf16.f32 {%0,%1,%2,%3}, {%4,%5}, {%6}, {%0,%1,%2,%3};"
        : "+f"(c[0]), "+f"(c[1]), "+f"(c[2]), "+f"(c[3]) : "r"(a0), "r"(a1), "r"(b0));
}
__device__ __forceinline__ float quad_sum(float v) { v += __shfl_xor_sync(0xffffffffu, v, 1); v += __shfl_xor_sync(0xffffffffu, v, 2); return v; }
__device__ __forceinline__ float quad_max(float v) { v = fmaxf(v, __shfl_xor_sync(0xffffffffu, v, 1)); v = fmaxf(v, __shfl_xor_sync(0xffffffffu, v, 2)); return v; }
__device__ __forceinline__ float ex2(float x) { float y; asm("ex2.approx.ftz.f32 %0, %1;" : "=f"(y) : "f"(x)); return y; }
__device__ __forceinline__ float rsqrt_approx(float x) { float y; asm("rsqrt.approx.ftz.f32 %0, %1;" : "=f"(y) : "f"(x)); return y; }
__device__ __forceinline__ float rcp_approx(float x) { float y; asm("rcp.approx.ftz.f32 %0, %1;" : "=f"(y) : "f"(x)); return y; }
__device__ __forceinline__ float gelu_half(float hx) {
    const float z = hx * fmaf(hx * hx, 8.f * 0.044715f * 0.7978845608028654f, 2.f * 0.7978845608028654f);
    float t; asm("tanh.approx.f32 %0, %1;" : "=f"(t) : "f"(z));
    return fmaf(hx, t, hx);
}
__device__ __forceinline__ uint32_t clock32() { uint32_t t; asm volatile("mov.u32 %0, %%clock;" : "=r"(t)); return t; }
#define PF_PACE 400

#define PF_AT 4000
#define NSQ 3
#define HALO_AT 3
#define WO_AT 0
#define WO_PACE 0
#define PF_N 12
#define HINT_H 14
#define HINT_U 14
#define CLR_MODE 2
#define FULLCLR 0
#define SP_AT 2000
#define SP_N 0
#define MAP8 0
#define WO_HOLD 7
#define A_SCHED 0x322188
template<int TB> __device__ __forceinline__ void wgmma_rs56(float (&d)[28], const uint32_t (&a)[4], uint64_t db, int sc) {
    asm volatile("{\n.reg .pred p;\nsetp.ne.b32 p, %33, 0;\n"
        "wgmma.mma_async.sync.aligned.m64n56k16.f32.bf16.bf16 {%0, %1, %2, %3, %4, %5, %6, %7, %8, %9, %10, %11, %12, %13, %14, %15, %16, %17, %18, %19, %20, %21, %22, %23, %24, %25, %26, %27}, {%28, %29, %30, %31}, %32, p, 1, 1, %34;\n}\n"
        : "+f"(d[0]), "+f"(d[1]), "+f"(d[2]), "+f"(d[3]), "+f"(d[4]), "+f"(d[5]), "+f"(d[6]), "+f"(d[7]), "+f"(d[8]), "+f"(d[9]), "+f"(d[10]), "+f"(d[11]), "+f"(d[12]), "+f"(d[13]), "+f"(d[14]), "+f"(d[15]), "+f"(d[16]), "+f"(d[17]), "+f"(d[18]), "+f"(d[19]), "+f"(d[20]), "+f"(d[21]), "+f"(d[22]), "+f"(d[23]), "+f"(d[24]), "+f"(d[25]), "+f"(d[26]), "+f"(d[27])
        : "r"(a[0]), "r"(a[1]), "r"(a[2]), "r"(a[3]), "l"(db), "r"(sc), "n"(TB));
}

template<int TA, int TB> __device__ __forceinline__ void wgmma_ss112(float (&d)[56], uint64_t da, uint64_t db, int sc) {
    asm volatile("{\n.reg .pred p;\nsetp.ne.b32 p, %58, 0;\n"
        "wgmma.mma_async.sync.aligned.m64n112k16.f32.bf16.bf16 {%0, %1, %2, %3, %4, %5, %6, %7, %8, %9, %10, %11, %12, %13, %14, %15, %16, %17, %18, %19, %20, %21, %22, %23, %24, %25, %26, %27, %28, %29, %30, %31, %32, %33, %34, %35, %36, %37, %38, %39, %40, %41, %42, %43, %44, %45, %46, %47, %48, %49, %50, %51, %52, %53, %54, %55}, %56, %57, p, 1, 1, %59, %60;\n}\n"
        : "+f"(d[0]), "+f"(d[1]), "+f"(d[2]), "+f"(d[3]), "+f"(d[4]), "+f"(d[5]), "+f"(d[6]), "+f"(d[7]), "+f"(d[8]), "+f"(d[9]), "+f"(d[10]), "+f"(d[11]), "+f"(d[12]), "+f"(d[13]), "+f"(d[14]), "+f"(d[15]), "+f"(d[16]), "+f"(d[17]), "+f"(d[18]), "+f"(d[19]), "+f"(d[20]), "+f"(d[21]), "+f"(d[22]), "+f"(d[23]), "+f"(d[24]), "+f"(d[25]), "+f"(d[26]), "+f"(d[27]), "+f"(d[28]), "+f"(d[29]), "+f"(d[30]), "+f"(d[31]), "+f"(d[32]), "+f"(d[33]), "+f"(d[34]), "+f"(d[35]), "+f"(d[36]), "+f"(d[37]), "+f"(d[38]), "+f"(d[39]), "+f"(d[40]), "+f"(d[41]), "+f"(d[42]), "+f"(d[43]), "+f"(d[44]), "+f"(d[45]), "+f"(d[46]), "+f"(d[47]), "+f"(d[48]), "+f"(d[49]), "+f"(d[50]), "+f"(d[51]), "+f"(d[52]), "+f"(d[53]), "+f"(d[54]), "+f"(d[55])
        : "l"(da), "l"(db), "r"(sc), "n"(TA), "n"(TB));
}

template<int NKB, bool PERM>
__device__ __forceinline__ void mix_mainloop(float (&acc)[56], uint32_t par, bool leader) {
    constexpr uint32_t sb = SB, bars = sb + SM_BAR;
    int bslot = 0, aslot = 0;
    reg_fence(acc);
    #pragma unroll 1
    for (int i = 0; i < NKB / 2; i++) {
        mbar_wait(bars + 8 * (B_FULLA + i), par);
        const uint64_t adesc = mkdesc(sb + SM_ARING, 8192, 1024, 1) + (uint32_t)(aslot * 1024);
        aslot = aslot == NA_SLOTS - 1 ? 0 : aslot + 1;
        #pragma unroll
        for (int jj = 0; jj < 2; jj++) {
            const int j = 2 * i + jj;
            mbar_wait(bars + 8 * (B_FULLB + j), par);
            const uint64_t bdesc = mkdesc(sb + SM_BRING, 1792, 128, 0) + (uint32_t)(bslot * 896);
            bslot = bslot == NB_SLOTS - 1 ? 0 : bslot + 1;
            wg_fence();
            #pragma unroll
            for (int s = 0; s < 4; s++) {
                const uint32_t aoff = PERM ? (s & 1) * 8192 + (jj * 32 + (s >> 1) * 16) * 128 : jj * 8192 + s * 2048;
                wgmma_ss112<1, 1>(acc, adesc + (aoff >> 4), bdesc + s * 224, 1);
            }
            wg_commit();
            wg_wait<1>();
            if (j > 0 && leader) mbar_arrive(bars + 8 * (B_DONE + j - 1));
        }
    }
    wg_wait<0>();
    reg_fence(acc);
    if (leader) mbar_arrive(bars + 8 * (B_DONE + NKB - 1));
}

constexpr uint32_t EMPTY = 0xFFFFFFFFu;
__device__ __forceinline__ void post_hint(uint4* p, uint32_t ep, int lane) { if (lane < 2) st_relaxed4(p + lane, ep, ep, ep, ep); }
__device__ __forceinline__ void post_hint_wg(uint4* p, uint32_t ep, int w, int lane) {
    if (w < 3) named_arrive(5, 128); else { named_sync(5, 128); post_hint(p, ep, lane); }
}

template<int NKB>
__device__ __forceinline__ void mix_producer_b(TSARG uint32_t par, const uint4* hints, uint32_t ep, const uint32_t* src, int lane) {
    constexpr uint32_t sb = SB, bars = sb + SM_BAR;
    uint32_t ready = 0;
    #pragma unroll 1
    for (int j = 0; j < NKB; j++) {
        while (!((ready >> j) & 1)) ready = __ballot_sync(0xffffffffu, ld_relaxed(hints + 2 * lane) == ep);
        if (j >= NB_SLOTS) mbar_wait(bars + 8 * (B_DONE + j - NB_SLOTS), par);
        if (j == 0 && lane == 0) STAMP(NKB == 32 ? 29 : 30);
        if (j == 7 && lane == 0) STAMP(NKB == 32 ? 35 : 36);
        if (elect()) {
            mbar_expect(bars + 8 * (B_RAW + (j & 7)), 14336);
            bulk_ld(sb + SM_BRING + (j & 7) * 14336, src + j * 3584, 14336, bars + 8 * (B_RAW + (j & 7)));
        }
    }
}
__device__ __forceinline__ void check_tiles(TSARG int n, int w, int lane, uint32_t& ph, uint32_t dst, const uint32_t* src, int full) {
    constexpr uint32_t bars = SB + SM_BAR;
    #pragma unroll 1
    for (int j = w; j < n; j += 4) {
        const uint32_t raw = bars + 8 * (B_RAW + (j & 7)), d = dst + (j & 7) * 14336, a = d + lane * 128 + (lane & 3) * 32 + (lane >> 2) * 4;
        bool bad;
        do {
            mbar_wait(raw, (ph >> (j & 4)) & 1);
            ph ^= 1u << (j & 4);
            if (j == 0 && lane == 0) STAMP(n == 4 ? 6 : n == 32 ? 31 : 32);
            uint32_t v0, v1, v2, v3;
            asm volatile("ld.shared.u32 %0, [%4];\nld.shared.u32 %1, [%4+4096];\nld.shared.u32 %2, [%4+8192];\nld.shared.u32 %3, [%4+10240];"
                         : "=r"(v0), "=r"(v1), "=r"(v2), "=r"(v3) : "r"(a) : "memory");
            bad = __any_sync(0xffffffffu, max(max(v0, v1), max(v2, v3)) == EMPTY);
            if (elect() && bad) {
                mbar_expect(raw, 14336); bulk_ld(d, src + j * 3584, 14336, raw);
            }
        } while (bad);
        if (lane == 0) mbar_arrive(bars + 8 * (full + j));
    }
}

__device__ __forceinline__ constexpr int sq_cut(int p) { return 4 * NSQ + (28 - 4 * NSQ) * (p == 1 ? 0 : p == 2 ? 2 : p == 6 ? 16 : 4 * p - 7) / 16; }

template<bool USE_SMID>
__global__ void __launch_bounds__(384, 1)
fused_kernel(Scratch* __restrict__ sc, const __nv_bfloat16* __restrict__ wo,
             const __nv_bfloat16* __restrict__ w1, const __nv_bfloat16* __restrict__ b1,
             const __nv_bfloat16* __restrict__ w2, const __nv_bfloat16* __restrict__ b2,
             const __grid_constant__ CUtensorMap tm_x, const __grid_constant__ CUtensorMap tm_wqkv,
             const __grid_constant__ CUtensorMap tm_wo64, const __grid_constant__ CUtensorMap tm_wo48,
             const __grid_constant__ CUtensorMap tm_w1, const __grid_constant__ CUtensorMap tm_w2,
             const __grid_constant__ CUtensorMap tm_out, const __grid_constant__ CUtensorMap tm_xr) {
    extern __shared__ __align__(1024) uint8_t smem_raw[];
    constexpr uint32_t sb = SB;
    constexpr uint32_t bars = sb + SM_BAR;
    const int tid = threadIdx.x, lane = tid & 31;
    const int warp = __shfl_sync(0xffffffffu, tid >> 5, 0);
    int slot;
    if (USE_SMID) {
        asm("{\n.reg .u32 s, t, u, d, a, b, c;\n.reg .pred p, r;\n"
            "mov.u32 s, %%smid;\nshr.u32 t, s, 1;\nsub.u32 u, t, 32;\nmul.lo.u32 d, u, 37;\nshr.u32 d, d, 8;\n"
            "and.b32 a, t, 7;\nshl.b32 a, a, 3;\nshr.u32 c, t, 3;\nadd.u32 a, a, c;\n"
            "mad.lo.u32 b, d, -55, 12;\nshl.b32 c, u, 3;\nadd.u32 b, b, c;\n"
            "setp.lt.u32 p, t, 32;\nselp.u32 a, a, b, p;\n"
            "setp.lt.u32 r, t, 64;\nselp.u32 c, 56, 0, r;\nsub.u32 c, t, c;\nsetp.lt.u32 p, t, 60;\nselp.u32 a, a, c, p;\n"
            "and.b32 s, s, 1;\nshl.b32 a, a, 1;\nadd.u32 %0, a, s;\n}" : "=r"(slot));
    } else slot = blockIdx.x;
    const int G = slot >> 4, mi = slot & 15;
    const int tb = MAP8 ? 8 * (G >> 2) + (mi >> 1) : 4 * (G >> 1) + (mi >> 2), hp = MAP8 ? (G & 3) + 4 * (mi & 1) : 2 * (mi & 3) + (G & 1);
    const int wcol = (hp * 56) & ~15;
    const bool odd = G & 1;
    if (slot >= 128) {
        if (tid == 0) {
            const uint32_t ep = sc->epoch[slot] + 1;
            const long long t0 = clock64();
            while (clock64() - t0 < SP_AT) {}
            #pragma unroll 1
            for (int i = 0; i < 7; i++) bulk_prefetch((const char*)wo + (i * 4 + mi) * 14336, 14336);
            #pragma unroll 1
            for (int i = 0; i < SP_N; i++) bulk_prefetch((const char*)w1 + (i * 4 + mi) * 14336, 14336);
            while (ld_relaxed(sc->hint_u) != ep) { __nanosleep(500); if (clock64() - t0 > WD_CLKS) __trap(); }
            sc->epoch[slot] = ep;
        }
        return;
    }
    const int q = mi & 3, tt2 = 4 * G + (mi >> 2), ft = 4 * (G - 1) + (mi >> 2);
    const bool has_b1 = G > 0;

    if (warp < 8) {
        named_sync(0, 384);
        asm volatile("setmaxnreg.inc.sync.aligned.u32 232;");
        int tid; asm volatile("mov.u32 %0, %%tid.x;" : "=r"(tid));
        const int lane = tid & 31, warp = __shfl_sync(0xffffffffu, tid >> 5, 0), wg = warp >> 2;
        const uint32_t ep = ld_volatile(&sc->epoch[slot]) + 1;
        const int w = warp & 3, g = lane >> 2, t = lane & 3;
        const bool leader = (tid & 127) == 0;
        {
            uint32_t a[28][4];
            float accK[28], accV[28], accQ[28];
            const int lrow = 16 * w + (lane & 7) + (lane & 8);
            const uint32_t lbase = sb + wg * 8192 + lrow * 128;
            const uint32_t lx = (lane >> 4) ^ (lane & 7);
            const uint32_t never = gridDim.y - 1;
            const uint32_t wofs = hp & 1;
            float cS[2][4] = {}, cA[4] = {}, cB[4] = {}, p0, p1;
            #pragma unroll
            for (int kb = 0; kb < 8; kb++) {
                if (kb < 7) {
                    mbar_wait(bars + 8 * (B_FULLX + kb), 0);
                    if (kb == 0 && tid == 0) STAMP(0);
                    if (kb == 6 && tid == 0) STAMP(25);
                    #pragma unroll
                    for (int s = 4 * kb; s < 4 * kb + 4; s++) ldsm4(a[s], lbase + slot_x(kb) + ((lx ^ (2 * (s & 3))) << 4));
                }
                if (kb == 0) continue;
                if (kb - 1 == NSQ) { p0 = cS[0][0] + cS[1][0]; p1 = cS[0][2] + cS[1][2]; }
                #pragma unroll
                for (int s = 4 * kb - 4; s < 4 * kb; s++) {
                    mma16816(cS[s & 1], a[s][0], a[s][1], a[s][2], a[s][3], 0x3F803F80u, 0x3F803F80u);
                    if (kb - 1 < NSQ) {
                        mma16816(cA, a[s][0], a[s][1], a[s][2], a[s][3], a[s][0], a[s][2]);
                        mma16816(cB, a[s][0], a[s][1], a[s][2], a[s][3], a[s][1], a[s][3]);
                    }
                }
            }
            const float m0 = (cS[0][0] + cS[1][0]) * (1.f / D_), m1 = (cS[0][2] + cS[1][2]) * (1.f / D_);
            const uint32_t mm0 = pack_bf16(m0, m0), mm1 = pack_bf16(m1, m1);
            if (lane == 0) mbar_arrive(bars + 8 * B_DONEX);
            auto center = [&](int kb) {
                #pragma unroll
                for (int s = 4 * kb; s < 4 * kb + 4; s++) { sub_bf16x2(a[s][0], mm0); sub_bf16x2(a[s][1], mm1); sub_bf16x2(a[s][2], mm0); sub_bf16x2(a[s][3], mm1); }
            };
            float q0, q1;
            auto sumsq = [&](int sa, int sb_) {
                if (sa == 4 * NSQ) {
                    const float c0 = bf_hi(mm0), c1 = bf_hi(mm1);
                    q0 = t == (g >> 1) ? fmaf(c0, fmaf(c0, 64.f * NSQ, -2.f * p0), (g & 1) ? cA[1] : cA[0]) - D_ * (m0 - c0) * (m0 - c0) : 0.f;
                    q1 = t == (g >> 1) ? fmaf(c1, fmaf(c1, 64.f * NSQ, -2.f * p1), (g & 1) ? cB[3] : cB[2]) - D_ * (m1 - c1) * (m1 - c1) : 0.f;
                }
                #pragma unroll
                for (int s = 0; s < 28; s++) {
                    if (s < sa || s >= sb_) continue;
                    #pragma unroll
                    for (int r = 0; r < 4; r++) {
                        const float lo = bf_lo(a[s][r]), hi = bf_hi(a[s][r]);
                        if (r & 1) q1 = fmaf(hi, hi, fmaf(lo, lo, q1)); else q0 = fmaf(hi, hi, fmaf(lo, lo, q0));
                    }
                }
                asm volatile("{\n.reg .pred p;\nsetp.ne.u32 p, %2, 0;\n@p st.shared.v2.f32 [%3], {%0,%1};\n}" :: "f"(q0), "f"(q1), "r"(never), "r"(sb) : "memory");
            };
            auto qsteps = [&](int sa, int sb_) {
                wg_fence();
                #pragma unroll
                for (int s = sa; s < sb_; s++) wgmma_rs56<1>(accQ, a[s], mkdesc(sb + SM_QO + s * 2048, 8192, 1024, 1) + wofs, s != 0);
                wg_commit();
                wg_wait<1>();
            };
            auto hand_over = [&](const uint32_t (&v)[7], int kv) {
                if (w < 3) {
                    uint4* hs = (uint4*)(smem_raw + (kv ? SM_HALOV : SM_HALOK)) + warp * 64 + lane;
                    hs[0] = make_uint4(v[0], v[1], v[2], v[3]); hs[32] = make_uint4(v[4], v[5], v[6], 0);
                } else if (tb < 15) {
                    uint4* hg = sc->halo + ((((tb + 1) * 8 + hp) * 2 + wg) * 2 + kv) * 96 + lane;
                    st_relaxed4(hg, v[0], v[1], v[2], ep); st_relaxed4(hg + 32, v[3], v[4], v[5], ep); st_relaxed4(hg + 64, v[6], ep, ep, ep);
                }
            };
            auto take_over = [&](uint32_t (&v)[7], int kv) {
                if (w == 0) mbar_wait(bars + 8 * (B_HALO + 2 * kv + wg), 0);
                const uint4* hs = (const uint4*)(smem_raw + (kv ? SM_HALOV : SM_HALOK)) + (w ? warp - 1 : warp + 3) * 64 + lane;
                const uint4 u0 = hs[0], u1 = hs[32];
                v[0] = u0.x; v[1] = u0.y; v[2] = u0.z; v[3] = u0.w; v[4] = u1.x; v[5] = u1.y; v[6] = u1.z;
            };
            uint32_t Ka[7], Kb[7], Kc[7], Va[7], Vb[7], Vc[7];
            float r0, r1;
            center(0);
            #pragma unroll
            for (int p = 0; p < 7; p++) {
                mbar_wait(bars + 8 * (B_FULLKV + p), 0);
                if (p == 0 && tid == 0) STAMP(26);
                if (p == 3 && tid == 0) STAMP(27);
                wg_fence();
                #pragma unroll
                for (int s = 8 * p; s < 8 * p + 8; s++) {
                    if (s == 4) { center(1); wg_fence(); }
                    const uint64_t desc = mkdesc(sb + slot_kv(p) + (s & 7) * 2048, 8192, 1024, 1) + wofs;
                    if (s < 28) wgmma_rs56<1>(accK, a[s], desc, s != 0); else wgmma_rs56<1>(accV, a[s - 28], desc, s != 28);
                }
                wg_commit();
                if (p > 0) {
                    wg_wait<1>();
                    if (leader) mbar_arrive(bars + 8 * (B_DONE1 + p - 1));
                }
                if (p < 3) center(2 * p + 2);
                if (p < 2) center(2 * p + 3);
                if (p > 0 && p < 6) sumsq(sq_cut(p), sq_cut(p + 1));
                if (p == 6) {
                    q0 = quad_sum(q0); q1 = quad_sum(q1);
                    r0 = rsqrt_approx(fmaxf(q0 * (1.f / D_), 0.f) + LN_EPS); r1 = rsqrt_approx(fmaxf(q1 * (1.f / D_), 0.f) + LN_EPS);
                    reg_fence(accK);
                    #pragma unroll
                    for (int j = 0; j < 7; j++) Kc[j] = pack_bf16(accK[4 * j + 2] * r1, accK[4 * j + 3] * r1);
                    hand_over(Kc, 0);
                }
            }
            if (tid == 0) STAMP(1);
            mbar_wait(bars + 8 * B_FQ, 0);
            qsteps(0, 7);
            reg_fence(accV);
            if (leader) mbar_arrive(bars + 8 * (B_DONE1 + 6));
            if (tid == 0) STAMP(2);
            #pragma unroll
            for (int j = 0; j < 7; j++) Vc[j] = movtrans(pack_bf16(accV[4 * j + 2] * r1, accV[4 * j + 3] * r1));
            if (w < 3) mbar_wait(bars + 8 * (B_DONE1 + 5), 0);
            hand_over(Vc, 1);
            if (tid == 96) STAMP(23);
            qsteps(7, 14);
            #pragma unroll
            for (int j = 0; j < 7; j++) {
                Kb[j] = pack_bf16(accK[4 * j] * r0, accK[4 * j + 1] * r0);
                Vb[j] = movtrans(pack_bf16(accV[4 * j] * r0, accV[4 * j + 1] * r0));
                asm volatile("" : "+r"(Kb[j]));
            }
            mbar_wait(bars + 8 * (B_FQ + 1), 0);
            qsteps(14, 21);
            qsteps(21, 28);
            named_sync(1 + wg, 128);
            take_over(Ka, 0);
            if (tid == 0) STAMP(3);
            wg_wait<0>();
            reg_fence(accQ);
            if (tid == 0) STAMP(4);
            uint32_t Q0[7], Q1[7];
            #pragma unroll
            for (int j = 0; j < 7; j++) { Q0[j] = pack_bf16(accQ[4 * j], accQ[4 * j + 1]); Q1[j] = pack_bf16(accQ[4 * j + 2], accQ[4 * j + 3]); }
            const bool first = (tb == 0 && w == 0);
            const float lsc = 0.1889822365046136f * 1.4426950408889634f;
            const float ls0 = lsc * r0, ls1 = lsc * r1;
            uint32_t pA[2], pB0[2], pB1[2], pC[2];
            #pragma unroll
            for (int h = 0; h < 2; h++) {
                const int j0 = 3 * h;
                const bool own3 = (t >= 2) == (h == 1);
                uint32_t qa[4], qb[4];
                #pragma unroll
                for (int j = 0; j < 4; j++) {
                    qa[j] = (j0 + j == 3 && !own3) ? 0u : Q0[j0 + j];
                    qb[j] = (j0 + j == 3 && !own3) ? 0u : Q1[j0 + j];
                }
                float sA[4] = {0.f, 0.f, 0.f, 0.f}, sB[4] = {0.f, 0.f, 0.f, 0.f}, sC[4] = {0.f, 0.f, 0.f, 0.f};
                #pragma unroll
                for (int k = 0; k < 2; k++) {
                    mma16816(sA, qa[2 * k], qb[2 * k], qa[2 * k + 1], qb[2 * k + 1], Ka[j0 + 2 * k], Ka[j0 + 2 * k + 1]);
                    mma16816(sB, qa[2 * k], qb[2 * k], qa[2 * k + 1], qb[2 * k + 1], Kb[j0 + 2 * k], Kb[j0 + 2 * k + 1]);
                    mma16816(sC, qa[2 * k], qb[2 * k], qa[2 * k + 1], qb[2 * k + 1], Kc[j0 + 2 * k], Kc[j0 + 2 * k + 1]);
                }
                const bool n0 = 2 * t <= g, n1 = 2 * t + 1 <= g;
                float l00 = n0 ? sB[0] : (first ? -INFINITY : sA[0]), l01 = n1 ? sB[1] : (first ? -INFINITY : sA[1]);
                float l10 = n0 ? sC[2] : sB[2], l11 = n1 ? sC[3] : sB[3];
                const float x0 = quad_max(fmaxf(l00, l01)), x1 = quad_max(fmaxf(l10, l11));
                const float e00 = ex2((l00 - x0) * ls0), e01 = ex2((l01 - x0) * ls0), e10 = ex2((l10 - x1) * ls1), e11 = ex2((l11 - x1) * ls1);
                const float i0 = rcp_approx(quad_sum(e00 + e01)), i1 = rcp_approx(quad_sum(e10 + e11));
                const float p00 = e00 * i0, p01 = e01 * i0, p10 = e10 * i1, p11 = e11 * i1;
                pA[h] = pack_bf16(n0 ? 0.f : p00, n1 ? 0.f : p01); pB0[h] = pack_bf16(n0 ? p00 : 0.f, n1 ? p01 : 0.f);
                pC[h] = pack_bf16(n0 ? p10 : 0.f, n1 ? p11 : 0.f); pB1[h] = pack_bf16(n0 ? 0.f : p10, n1 ? 0.f : p11);
            }
            float o[8][4];
            #pragma unroll
            for (int j = 0; j < 8; j++) {
                o[j][0] = o[j][1] = o[j][2] = o[j][3] = 0.f;
                mma16816(o[j], pB0[j >> 2], pB1[j >> 2], 0u, pC[j >> 2], Vb[j - (j >> 2)], Vc[j - (j >> 2)]);
            }
            if (tid == 0) STAMP(12);
            take_over(Va, 1);
            if (lane == 0) mbar_arrive(bars + 8 * B_DONEQ);
            if (tid == 0) STAMP(16);
            #pragma unroll
            for (int j = 0; j < 8; j++) mma1688(o[j], pA[j >> 2], 0u, Va[j - (j >> 2)]);
            const int tt = 2 * tb + (w >> 1);
            mbar_wait(bars + 8 * B_CLR, 0);
            uint32_t* od = sc->o + tt * 14336 + (7 * hp) * 256 + (2 * (2 * (w & 1) + wg)) * 32 + lane;
            #pragma unroll
            for (int j = 0; j < 7; j++) {
                float v[4];
                #pragma unroll
                for (int c = 0; c < 4; c++) v[c] = j < 3 ? o[j][c] : j > 3 ? o[j + 1][c] : (t < 2 ? o[3][c] : o[4][c]);
                od[j * 256] = pack_bf16(v[0], v[1]);
                od[j * 256 + 32] = pack_bf16(v[2], v[3]);
            }
            if (tid == 0) STAMP(5);
            post_hint(sc->hint_o + (tt * 32 + hp * 4 + (w & 1) * 2 + wg) * 2, ep, lane);
        }
        if (wg == 1) {
            uint32_t ph = 0;
            check_tiles(TSVAL 4, w, lane, ph, sb + SM_QO, sc->o + tt2 * 14336, B_FULLO);
            if (has_b1) check_tiles(TSVAL 32, w, lane, ph, sb + SM_BRING, sc->hn + q * 32 * 3584, B_FULLB);
            check_tiles(TSVAL 28, w, lane, ph, sb + SM_BRING, sc->u + q * 28 * 3584, B_FULLB);
        } else {
            const uint32_t rb10 = has_b1 ? __ldg((const unsigned short*)b1 + ft * 64 + 16 * w + g) : 0, rb11 = has_b1 ? __ldg((const unsigned short*)b1 + ft * 64 + 16 * w + g + 8) : 0;
            const uint32_t rb20 = __ldg((const unsigned short*)b2 + tt2 * 64 + 16 * w + g), rb21 = __ldg((const unsigned short*)b2 + tt2 * 64 + 16 * w + g + 8);
            {
                float acc[56];
                const uint32_t ha = sb + SM_H + (32 * (w >> 1) + 2 * ((lane & 7) + (lane & 8)) + (w & 1)) * 224 + (lane >> 4) * 16;
                mbar_wait(bars + 8 * B_FULLWO, 0);
                #pragma unroll
                for (int jp = 0; jp < 7; jp++) {
                    uint32_t xx[4];
                    ldsm4(xx, ha + jp * 32);
                    #pragma unroll
                    for (int r = 0; r < 4; r++) { acc[8 * jp + 2 * r] = bf_lo(xx[r]); acc[8 * jp + 2 * r + 1] = bf_hi(xx[r]); }
                }
                reg_fence(acc);
                #pragma unroll
                for (int i = 0; i < 4; i++) {
                    mbar_wait(bars + 8 * (B_FULLO + i), 0);
                    if (i == 0 && tid == 0) STAMP(7);
                    wg_fence();
                    #pragma unroll
                    for (int ss = 0; ss < 7; ss++) {
                        const int s = 7 * i + ss, kb = s >> 2;
                        wgmma_ss112<0, 1>(acc, mkdesc(sb + SM_QO + s * 2048, 1024, 128, 0),
                                          mkdesc(sb + slot_wo(kb) + (s & 3) * 2048, 8192, 1024, 1), 1);
                    }
                    wg_commit();
                    if (i > 0) {
                        wg_wait<1>();
                        if (leader) mbar_arrive(bars + 8 * (B_DONEO + i - 1));
                    }
                }
                wg_wait<0>();
                reg_fence(acc);
                if (leader) mbar_arrive(bars + 8 * (B_DONEO + 3));
                if (tid == 0) STAMP(8);
                float s0 = 0.f, s1 = 0.f, q0 = 0.f, q1 = 0.f, s2 = 0.f, s3 = 0.f, q2 = 0.f, q3 = 0.f;
                #pragma unroll
                for (int j = 0; j < 14; j++) {
                    s0 += acc[4 * j]; s2 += acc[4 * j + 1]; q0 = fmaf(acc[4 * j], acc[4 * j], q0); q2 = fmaf(acc[4 * j + 1], acc[4 * j + 1], q2);
                    s1 += acc[4 * j + 2]; s3 += acc[4 * j + 3]; q1 = fmaf(acc[4 * j + 2], acc[4 * j + 2], q1); q3 = fmaf(acc[4 * j + 3], acc[4 * j + 3], q3);
                }
                s0 = quad_sum(s0 + s2); s1 = quad_sum(s1 + s3); q0 = quad_sum(q0 + q2); q1 = quad_sum(q1 + q3);
                uint4* sp = sc->stats + tt2 * 256 + 16 * w + g;
                if (t < 2) st_relaxed4(sp + q * 64 + 8 * t, __float_as_uint(t ? s1 : s0), ep, __float_as_uint(t ? q1 : q0), ep);
                if (tid == 0) STAMP(9);
                #pragma unroll
                for (int jp = 0; jp < 7; jp++)
                    stsm4(ha + jp * 32, pack_bf16(acc[8 * jp], acc[8 * jp + 1]), pack_bf16(acc[8 * jp + 2], acc[8 * jp + 3]),
                          pack_bf16(acc[8 * jp + 4], acc[8 * jp + 5]), pack_bf16(acc[8 * jp + 6], acc[8 * jp + 7]));
                {
                    uint4 v0, v1;
                    do {
                        v0 = ld_relaxed4(sp + t * 64); v1 = ld_relaxed4(sp + t * 64 + 8);
                    } while (__any_sync(0xffffffffu, t != q && (v0.y != ep || v0.w != ep || v1.y != ep || v1.w != ep)));
                    if (t != q) { s0 = __uint_as_float(v0.x); q0 = __uint_as_float(v0.z); s1 = __uint_as_float(v1.x); q1 = __uint_as_float(v1.z); }
                }
                if (tid == 0) STAMP(10);
                s0 = quad_sum(s0); s1 = quad_sum(s1); q0 = quad_sum(q0); q1 = quad_sum(q1);
                const float m0 = s0 * (1.f / D_), m1 = s1 * (1.f / D_);
                const float v0 = fmaxf(q0 * (1.f / D_) - m0 * m0, 0.f), v1 = fmaxf(q1 * (1.f / D_) - m1 * m1, 0.f);
                float r0 = rsqrt_approx(v0 + LN_EPS), r1 = rsqrt_approx(v1 + LN_EPS);
                r0 *= 0.5f * rsqrt_approx(fmaf(v0 * r0, r0, LN_EPS)); r1 *= 0.5f * rsqrt_approx(fmaf(v1 * r1, r1, LN_EPS));
                const float c0 = -m0 * r0, c1 = -m1 * r1;
                uint32_t* hd = sc->hn + (q * 32 + tt2) * 3584 + (2 * w) * 448 + lane;
                #pragma unroll
                for (int j = 0; j < 14; j++) {
                    if (j == HINT_H) post_hint_wg(sc->hint_h + (q * 32 + tt2) * 2, ep, w, lane);
                    hd[j * 32] = pack_bf16(fmaf(acc[4 * j], r0, c0), fmaf(acc[4 * j + 1], r0, c0));
                    hd[j * 32 + 448] = pack_bf16(fmaf(acc[4 * j + 2], r1, c1), fmaf(acc[4 * j + 3], r1, c1));
                }
                if (tid == 0) STAMP(11);
                if (HINT_H == 14) post_hint_wg(sc->hint_h + (q * 32 + tt2) * 2, ep, w, lane);
                if (tid == 96) STAMP(33);
            }
            if (has_b1) {
                float acc[56];
                #pragma unroll
                for (int j = 0; j < 56; j++) acc[j] = 0.5f * bf_lo((j & 2) ? rb11 : rb10);
                mix_mainloop<32, true>(acc, 0, leader);
                if (tid == 0) STAMP(14);
                mbar_wait(bars + 8 * B_CLR, 1);
                uint32_t* ud = sc->u + (q * 28 + ft) * 3584 + (2 * w) * 448 + lane;
                #pragma unroll
                for (int j = 0; j < 14; j++) {
                    if (j == HINT_U) post_hint_wg(sc->hint_u + (q * 32 + ft) * 2, ep, w, lane);
                    ud[j * 32] = pack_bf16(gelu_half(acc[4 * j]), gelu_half(acc[4 * j + 1]));
                    ud[j * 32 + 448] = pack_bf16(gelu_half(acc[4 * j + 2]), gelu_half(acc[4 * j + 3]));
                }
                if (tid == 0) STAMP(15);
                if (HINT_U == 14) post_hint_wg(sc->hint_u + (q * 32 + ft) * 2, ep, w, lane);
                if (tid == 96) STAMP(34);
            }
            {
                float acc[56];
                const float bb0 = bf_lo(rb20), bb1 = bf_lo(rb21);
                named_sync(1, 128);
                const uint32_t ad = sb + SM_H + (16 * w + (lane & 7) + (lane & 8)) * 224 + (lane >> 4) * 16;
                #pragma unroll
                for (int jp = 0; jp < 7; jp++) {
                    uint32_t hh[4];
                    ldsm4(hh, ad + jp * 32);
                    #pragma unroll
                    for (int r = 0; r < 4; r++) { acc[8 * jp + 2 * r] = bf_lo(hh[r]) + ((r & 1) ? bb1 : bb0); acc[8 * jp + 2 * r + 1] = bf_hi(hh[r]) + ((r & 1) ? bb1 : bb0); }
                }
                mix_mainloop<28, false>(acc, has_b1, leader);
                if (leader) mbar_arrive(bars + 8 * B_END);
                if (tid == 0) STAMP(18);
                #pragma unroll
                for (int jp = 0; jp < 7; jp++)
                    stsm4(ad + jp * 32, pack_bf16(acc[8 * jp], acc[8 * jp + 1]), pack_bf16(acc[8 * jp + 2], acc[8 * jp + 3]),
                          pack_bf16(acc[8 * jp + 4], acc[8 * jp + 5]), pack_bf16(acc[8 * jp + 6], acc[8 * jp + 7]));
                fence_async_smem();
                __syncwarp();
                if (elect()) {
                    tma2d_store(&tm_out, q * 112, tt2 * 64 + 16 * w, sb + SM_H + w * 3584);
                    asm volatile("cp.async.bulk.commit_group;" ::: "memory");
                    asm volatile("cp.async.bulk.wait_group.read 0;" ::: "memory");
                }
                if (tid == 0) { sc->epoch[slot] = ep; STAMP(19); }
            }
        }
    } else {
        asm volatile("setmaxnreg.dec.sync.aligned.u32 40;");
        int warp2; asm("mov.u32 %0, %1;" : "=r"(warp2) : "r"(warp));
        if (warp2 > 8) {
            const int l0 = lane >> 1, wo_ = (l0 & 3) * 2 + (lane & 1);
            auto clear_o = [&]() {
                if (FULLCLR & 1) {
                    uint4* po = (uint4*)sc->o + 2 * tb * 3584 + hp * 448 + lane;
                    #pragma unroll 2
                    for (int i = 0; i < 14; i++) { st_relaxed4(po + i * 32, EMPTY, EMPTY, EMPTY, EMPTY); st_relaxed4(po + i * 32 + 3584, EMPTY, EMPTY, EMPTY, EMPTY); }
                } else {
                    uint4* po = (uint4*)sc->o + 2 * tb * 3584 + hp * 448 + wo_;
                    #pragma unroll
                    for (int i = 0; i < 7; i++) { const int l = l0 + 16 * i; st_relaxed4(po + (l < 56 ? l * 8 : l * 8 + 3584 - 448), EMPTY, EMPTY, EMPTY, EMPTY); }
                }
            };
            auto clear_h = [&]() {
                if (FULLCLR & 2) {
                    uint4* ph = (uint4*)sc->hn + (q * 32 + tt2) * 896 + lane;
                    #pragma unroll 4
                    for (int i = 0; i < 28; i++) st_relaxed4(ph + i * 32, EMPTY, EMPTY, EMPTY, EMPTY);
                } else {
                    uint4* ph = (uint4*)sc->hn + (q * 32 + tt2) * 896 + l0 * 8 + wo_;
                    #pragma unroll
                    for (int i = 0; i < 7; i++) st_relaxed4(ph + i * 128, EMPTY, EMPTY, EMPTY, EMPTY);
                }
            };
            if (warp == 11) { if (CLR_MODE == 0 || CLR_MODE == 3) clear_o(); if (CLR_MODE == 0) clear_h(); }
            if (elect()) {
                if (warp == 9) {
                    #pragma unroll
                    for (int i = B_DONE1; i < B_DONEO; i++) mbar_init(bars + 8 * i, i < B_DONEX ? 2 : 8);
                    mbar_init(bars + 8 * B_CLR, 1);
                }
                #pragma unroll
                for (int i = 0; i < 34; i++) mbar_init(bars + 8 * (B_DONEO + i) + (warp - 9) * 272, 1);
                asm volatile("fence.mbarrier_init.release.cluster;" ::: "memory");
            }
            named_sync(0, 384);
            if (warp == 9) named_arrive(4, 64);
            if (warp < 11) {
                const uint32_t ep = ld_volatile(&sc->epoch[slot]) + 1;
                mbar_wait(bars + 8 * (B_DONE1 + HALO_AT), 0);
                #pragma unroll 1
                for (int kv = 0; kv < 2; kv++) {
                    uint4 v0 = {}, v1 = {}, v2 = {};
                    if (tb > 0) {
                        const uint4* hg = sc->halo + (((tb * 8 + hp) * 2 + warp - 9) * 2 + kv) * 96 + lane;
                        do { v0 = ld_relaxed4(hg); v1 = ld_relaxed4(hg + 32); v2 = ld_relaxed4(hg + 64); } while (!__all_sync(0xffffffffu, v0.w == ep && v1.w == ep && v2.w == ep));
                    }
                    if (kv) mbar_wait(bars + 8 * (B_DONE1 + 5), 0);
                    uint4* hs = (uint4*)(smem_raw + (kv ? SM_HALOV : SM_HALOK)) + (4 * warp - 33) * 64 + lane;
                    hs[0] = make_uint4(v0.x, v0.y, v0.z, v1.x); hs[32] = make_uint4(v1.y, v1.z, v2.x, 0);
                    __syncwarp();
                    if (lane == 0) mbar_arrive(bars + 8 * (B_HALO + 2 * kv + warp - 9));
                }
                if (tid == 288) STAMP(21);
            }
            if (warp == 10) {
                if (!has_b1 && lane == 0) {
                    mbar_wait(bars + 8 * (B_DONEO + 3), 0);
                    uint32_t t = clock32() + PF_AT;
                    #pragma unroll 1
                    for (int i = 0; i < PF_N; i++) {
                        while ((int)(clock32() - t) < 0) __nanosleep(40);
                        bulk_prefetch((const char*)w2 + (i * 16 + mi) * 16384, 16384);
                        t += PF_PACE;
                    }
                }
            } else if (warp == 11) {
                if (CLR_MODE == 1) { clear_o(); clear_h(); }
                if (CLR_MODE == 2) { mbar_wait_wd(bars + 8 * (B_FULLKV + 2), 0); clear_o(); mbar_wait_wd(bars + 8 * (B_FULLKV + 4), 0); clear_h(); }
                if (CLR_MODE == 3) { mbar_wait_wd(bars + 8 * (B_FULLKV + 4), 0); clear_h(); }
                asm volatile("fence.acq_rel.gpu;" ::: "memory");
                __syncwarp();
                if (lane == 0) mbar_arrive(bars + 8 * B_CLR);
                if (lane == 0) STAMP(24);
                if (has_b1) {
                    uint4* pu = (uint4*)sc->u + (q * 28 + ft) * 896 + l0 * 8 + wo_;
                    if (FULLCLR & 4) {
                        pu = (uint4*)sc->u + (q * 28 + ft) * 896 + lane;
                        #pragma unroll 1
                        for (int i = 0; i < 14; i++) { mbar_wait_wd(bars + 8 * (B_DONE + 2 + i), 0); st_relaxed4(pu + i * 64, EMPTY, EMPTY, EMPTY, EMPTY); st_relaxed4(pu + i * 64 + 32, EMPTY, EMPTY, EMPTY, EMPTY); }
                    } else {
                        #pragma unroll 1
                        for (int i = 0; i < 7; i++) { mbar_wait_wd(bars + 8 * (B_DONE + 2 * i), 0); st_relaxed4(pu + i * 128, EMPTY, EMPTY, EMPTY, EMPTY); }
                    }
                    asm volatile("fence.acq_rel.gpu;" ::: "memory");
                    __syncwarp();
                    if (lane == 0) mbar_arrive(bars + 8 * B_CLR);
                }
                if (lane == 0) {
                    mbar_wait_wd(bars + 8 * B_END, 0);
                }
            } else {
                int aslot = 0;
                if (has_b1) {
                    #pragma unroll 1
                    for (int i = 0; i < 16; i++) {
                        mbar_wait(bars + 8 * (i < NA_SLOTS ? B_DONEQ + ((A_SCHED >> (4 * i)) & 15) : B_DONE + 1 + ((i - NA_SLOTS) * 22) / (15 - NA_SLOTS)), 0);
                        if (elect()) {
                            const uint32_t bar = bars + 8 * (B_FULLA + i), dst = sb + SM_ARING + aslot * 16384;
                            mbar_expect(bar, 16384);
                            tma3d(dst, &tm_w1, ft * 64, 0, i * 64, bar);
                            tma3d(dst + 8192, &tm_w1, ft * 64, 1, i * 64, bar);
                        }
                        aslot = aslot == NA_SLOTS - 1 ? 0 : aslot + 1;
                    }
                }
                aslot = 0;
                #pragma unroll 1
                for (int i = 0; i < 14; i++) {
                    if (i >= NA_SLOTS) mbar_wait(bars + 8 * (B_DONE + 1 + ((i - NA_SLOTS) * 18) / (13 - NA_SLOTS)), has_b1);
                    else if (has_b1) {
                        const int last = i + NA_SLOTS * ((15 - i) / NA_SLOTS);
                        mbar_wait(bars + 8 * (B_DONE + max(2 * last + 1, 32 - NB_SLOTS)), 0);
                    } else if (i == 0) { mbar_wait(bars + 8 * (B_DONEO + 3), 0); const uint32_t t = clock32() + PF_AT + 12 * PF_PACE; while ((int)(clock32() - t) < 0) __nanosleep(100); }
                    if (i == NA_SLOTS - 1 && has_b1) mbar_wait(bars + 8 * (B_DONE + 31), 0);
                    if (elect()) {
                        const uint32_t bar = bars + 8 * (B_FULLA + i);
                        mbar_expect(bar, 16384);
                        tma2d(sb + SM_ARING + aslot * 16384, &tm_w2, tt2 * 64, i * 128, bar);
                    }
                    aslot = aslot == NA_SLOTS - 1 ? 0 : aslot + 1;
                }
            }
        } else {
            if (elect()) {
                #pragma unroll
                for (int i = 0; i < 7; i++) mbar_init(bars + 8 * i, 1);
                asm volatile("fence.mbarrier_init.release.cluster;" ::: "memory");
                #pragma unroll 1
                for (int kb = 0; kb < 7; kb++) {
                    const uint32_t st = sb + slot_x(kb), bar = bars + 8 * (B_FULLX + kb);
                    mbar_expect(bar, 16384);
                    tma3d(st, &tm_x, kb * 64, 0, tb * 64, bar); tma3d(st + 8192, &tm_x, kb * 64, 1, tb * 64, bar);
                }
                #pragma unroll
                for (int i = 7; i < B_DONE1; i++) mbar_init(bars + 8 * i, 1);
                asm volatile("fence.mbarrier_init.release.cluster;" ::: "memory");
            }
            named_arrive(0, 384);
            #pragma unroll 1
            for (int kb = 0; kb < 7; kb++) {
                if (kb == 6) { named_sync(4, 64); mbar_wait(bars + 8 * B_DONEX, 0); }
                if (elect()) {
                    const uint32_t st = sb + slot_kv(kb), bar = bars + 8 * (B_FULLKV + kb);
                    mbar_expect(bar, 16384);
                    #pragma unroll
                    for (int i = 0; i < 2; i++) {
                        const int n = 2 * kb + (i ^ (int)odd);
                        tma2d(st + (n & 1) * 8192, &tm_wqkv, (n < 7 ? 448 : 896) + wcol, (n < 7 ? n : n - 7) * 64, bar);
                    }
                }
            }
            if (elect()) {
                mbar_expect(bars + 8 * B_FQ, 32768);
                mbar_expect(bars + 8 * (B_FQ + 1), 24576);
                #pragma unroll 1
                for (int i = 0; i < 7; i++) { const int j = i < 6 ? i ^ (int)odd : i; tma2d(sb + SM_QO + j * 8192, &tm_wqkv, wcol, j * 64, bars + 8 * (B_FQ + (i >> 2))); }
                mbar_expect(bars + 8 * B_FULLWO, 512 * 112 * 2);
                tma2d(sb + SM_H, &tm_xr, q * 112, tt2 * 64, bars + 8 * B_FULLWO);
            }
            #pragma unroll 1
            for (int i = 0; i < 7; i++) {
                const int kb = i < 2 ? 5 + i : i - 2;
                if (kb < 5) mbar_wait(bars + 8 * (B_DONE1 + kb), 0);
                if (i == WO_HOLD) { mbar_wait(bars + 8 * (B_HALO + 2), 0); mbar_wait(bars + 8 * (B_HALO + 3), 0); }
                if (elect()) {
                    tma2d(sb + slot_wo(kb), &tm_wo64, q * 112, kb * 64, bars + 8 * B_FULLWO);
                    tma2d(sb + slot_wo(kb) + 8192, &tm_wo48, q * 112 + 64, kb * 64, bars + 8 * B_FULLWO);
                }
            }
            if (smem_u32(smem_raw) != SB) __trap();
            const uint32_t ep = ld_volatile(&sc->epoch[slot]) + 1;
            mbar_wait(bars + 8 * B_DONEQ, 0);
            {
                uint32_t issued = 0;
                while (issued != 0x01010101u) {
                    uint32_t m = __ballot_sync(0xffffffffu, ld_relaxed(sc->hint_o + (tt2 * 32 + lane) * 2) == ep);
                    m &= m >> 4; m &= m >> 2; m &= m >> 1; m &= 0x01010101u & ~issued;
                    if ((m >> lane) & 1) {
                        const uint32_t bar = bars + 8 * B_RAW + lane;
                        mbar_expect(bar, 14336);
                        bulk_ld(sb + SM_QO + lane * 1792, sc->o + tt2 * 14336 + lane * 448, 14336, bar);
                    }
                    issued |= m;
                }
                __syncwarp();
            }
            if (lane == 0) STAMP(20);
            mbar_wait(bars + 8 * (B_DONEO + 3), 0);
            if (has_b1) {
                mix_producer_b<32>(TSVAL 0, sc->hint_h + q * 64, ep, sc->hn + q * 32 * 3584, lane);
                mbar_wait(bars + 8 * (B_DONE + 31), 0);
            }
            mix_producer_b<28>(TSVAL has_b1, sc->hint_u + q * 64, ep, sc->u + q * 28 * 3584, lane);
        }
    }
}

typedef CUresult (*EncodeFn)(CUtensorMap*, CUtensorMapDataType, cuuint32_t, void*, const cuuint64_t*, const cuuint64_t*, const cuuint32_t*,
                             const cuuint32_t*, CUtensorMapInterleave, CUtensorMapSwizzle, CUtensorMapL2promotion, CUtensorMapFloatOOBfill);

void make_map(EncodeFn fn, CUtensorMap* tm, const void* ptr, int rank, const cuuint64_t* dims, const cuuint64_t* strides, const cuuint32_t* box, CUtensorMapSwizzle sw) {
    cuuint32_t es[3] = {1, 1, 1};
    fn(tm, CU_TENSOR_MAP_DATA_TYPE_BFLOAT16, rank, const_cast<void*>(ptr), dims, strides, box, es, CU_TENSOR_MAP_INTERLEAVE_NONE, sw,
       CU_TENSOR_MAP_L2_PROMOTION_NONE, CU_TENSOR_MAP_FLOAT_OOB_FILL_NONE);
}

}

extern "C" void kernel_launch(void* const* d_in, const int* in_sizes, int n_in, void* d_out, int out_size) {
    const __nv_bfloat16* x = (const __nv_bfloat16*)d_in[0];
    const __nv_bfloat16* wqkv = (const __nv_bfloat16*)d_in[1];
    const __nv_bfloat16* wo = (const __nv_bfloat16*)d_in[2];
    const __nv_bfloat16* w1 = (const __nv_bfloat16*)d_in[4];
    const __nv_bfloat16* b1 = (const __nv_bfloat16*)d_in[5];
    const __nv_bfloat16* w2 = (const __nv_bfloat16*)d_in[6];
    const __nv_bfloat16* b2 = (const __nv_bfloat16*)d_in[7];

    void* fnp = nullptr; cudaDriverEntryPointQueryResult qr;
    cudaGetDriverEntryPoint("cuTensorMapEncodeTiled", &fnp, cudaEnableDefault, &qr);
    EncodeFn fn = (EncodeFn)fnp;
    CUtensorMap tx, twqkv, two64, two48, tw1, tw2, tout, txr;
    { cuuint64_t d[3] = {448, 2, 1024}, s[2] = {896, 1792}; cuuint32_t b[3] = {64, 1, 64}; make_map(fn, &tx, x, 3, d, s, b, CU_TENSOR_MAP_SWIZZLE_128B); }
    { cuuint64_t d[2] = {1344, 448}, s[1] = {2688}; cuuint32_t b[2] = {64, 64}; make_map(fn, &twqkv, wqkv, 2, d, s, b, CU_TENSOR_MAP_SWIZZLE_128B); }
    { cuuint64_t d[2] = {448, 448}, s[1] = {896}; cuuint32_t b[2] = {64, 64}; make_map(fn, &two64, wo, 2, d, s, b, CU_TENSOR_MAP_SWIZZLE_128B); }
    { cuuint64_t d[2] = {448, 448}, s[1] = {896}; cuuint32_t b[2] = {48, 64}; make_map(fn, &two48, wo, 2, d, s, b, CU_TENSOR_MAP_SWIZZLE_128B); }
    { cuuint64_t d[3] = {1792, 2, 1024}, s[2] = {3584, 7168}; cuuint32_t b[3] = {64, 1, 64}; make_map(fn, &tw1, w1, 3, d, s, b, CU_TENSOR_MAP_SWIZZLE_128B); }
    { cuuint64_t d[2] = {2048, 1792}, s[1] = {4096}; cuuint32_t b[2] = {64, 128}; make_map(fn, &tw2, w2, 2, d, s, b, CU_TENSOR_MAP_SWIZZLE_128B); }
    { cuuint64_t d[2] = {448, 2048}, s[1] = {896}; cuuint32_t b[2] = {112, 16}; make_map(fn, &tout, d_out, 2, d, s, b, CU_TENSOR_MAP_SWIZZLE_NONE); }

    { cuuint64_t d[2] = {448, 2048}, s[1] = {896}; cuuint32_t b[2] = {112, 64}; make_map(fn, &txr, x, 2, d, s, b, CU_TENSOR_MAP_SWIZZLE_NONE); }

    void* scv = nullptr;
    cudaGetSymbolAddress(&scv, g_scratch);
    Scratch* scp = (Scratch*)scv;
    int dev = 0, sms = 0;
    cudaGetDevice(&dev);
    cudaDeviceGetAttribute(&sms, cudaDevAttrMultiProcessorCount, dev);
    if (sms == 132) {
        cudaFuncSetAttribute(fused_kernel<true>, cudaFuncAttributeMaxDynamicSharedMemorySize, SM_TOTAL);
        fused_kernel<true><<<132, 384, SM_TOTAL>>>(scp, wo, w1, b1, w2, b2, tx, twqkv, two64, two48, tw1, tw2, tout, txr);
    } else {
        cudaFuncSetAttribute(fused_kernel<false>, cudaFuncAttributeMaxDynamicSharedMemorySize, SM_TOTAL);
        fused_kernel<false><<<132, 384, SM_TOTAL>>>(scp, wo, w1, b1, w2, b2, tx, twqkv, two64, two48, tw1, tw2, tout, txr);
    }
}
```

```cpp
#include <cuda_runtime.h>
#include <cuda_bf16.h>
#include <cuda.h>
#include <stdint.h>

namespace {

constexpr int D_ = 448;
constexpr float LN_EPS = 1e-5f;

struct Scratch {
    uint32_t o[32 * 57344 / 4];
    uint32_t hn[4 * 32 * 14336 / 4];
    uint32_t u[4 * 28 * 14336 / 4];
    uint4 halo[128 * 2 * 2 * 3 * 32];
    uint4 stats[32 * 4 * 64];
    uint4 hint_o[32 * 32 * 2];
    uint4 hint_h[4 * 32 * 2];
    uint4 hint_u[4 * 32 * 2];
    uint32_t epoch[160];
};
__device__ __align__(1024) Scratch g_scratch;
#define STAMP(i) do {} while (0)
#define TSARG
#define TSVAL

constexpr uint32_t SB = 1024;
constexpr int SM_SLOT = 16384;
__device__ __forceinline__ constexpr uint32_t slot_x(int kb) { return (kb ? 6 + kb : 0) * SM_SLOT; }
__device__ __forceinline__ constexpr uint32_t slot_kv(int kb) { return (kb < 5 ? 2 + kb : 6 - kb) * SM_SLOT; }
__device__ __forceinline__ constexpr uint32_t slot_wo(int kb) { return (kb < 6 ? 2 + kb : 12) * SM_SLOT; }
constexpr int SM_QO = 8 * SM_SLOT;
constexpr int SM_HALOK = SM_QO + 57344, SM_HALOV = 1 * SM_SLOT;
constexpr int NA_SLOTS = 6, NB_SLOTS = 8;
constexpr int SM_ARING = 0;
constexpr int SM_BRING = NA_SLOTS * 16384;
constexpr int SM_H = 212992;
constexpr int SM_MISC = 229376;
constexpr int SM_BAR = 231424;
constexpr int SM_TOTAL = 232448;
constexpr int B_FULLX = 0;
constexpr int B_FULLKV = 7;
constexpr int B_FQ = 14;
constexpr int B_DONE1 = 16;
constexpr int B_DONEX = 23;
constexpr int B_DONEQ = 24;
constexpr int B_DONEO = 25;
constexpr int B_FULLO = 29;
constexpr int B_FULLWO = 33;
constexpr int B_END = 34;
constexpr int B_HALO = 35;
constexpr int B_FULLA = 39;
constexpr int B_FULLB = 55;
constexpr int B_DONE = 87;
constexpr int B_RAW = 119;
constexpr int B_CLR = 127;

constexpr long long WD_CLKS = 2000000000ll;

__device__ __forceinline__ uint32_t smem_u32(const void* p) { return (uint32_t)__cvta_generic_to_shared(p); }
__device__ __forceinline__ void mbar_init(uint32_t bar, uint32_t cnt) { asm volatile("mbarrier.init.shared::cta.b64 [%0], %1;" :: "r"(bar), "r"(cnt) : "memory"); }
__device__ __forceinline__ void mbar_expect(uint32_t bar, uint32_t bytes) { asm volatile("mbarrier.arrive.expect_tx.shared::cta.b64 _, [%0], %1;" :: "r"(bar), "r"(bytes) : "memory"); }
__device__ __forceinline__ void mbar_arrive(uint32_t bar) { asm volatile("mbarrier.arrive.shared::cta.b64 _, [%0];" :: "r"(bar) : "memory"); }
__device__ __forceinline__ bool mbar_try(uint32_t bar, uint32_t parity) {
    uint32_t ok;
    asm volatile("{\n.reg .pred p;\nmbarrier.try_wait.parity.shared::cta.b64 p, [%1], %2;\nselp.u32 %0, 1, 0, p;\n}" : "=r"(ok) : "r"(bar), "r"(parity) : "memory");
    return ok;
}
__device__ __forceinline__ void mbar_wait(uint32_t bar, uint32_t parity) {
    asm volatile("{\n.reg .pred p;\n"
                 "WAIT_LOOP:\n"
                 "mbarrier.try_wait.parity.shared::cta.b64 p, [%0], %1;\n"
                 "@!p bra WAIT_LOOP;\n}" :: "r"(bar), "r"(parity) : "memory");
}
__device__ __forceinline__ void mbar_wait_wd(uint32_t bar, uint32_t parity) {
    const long long t0 = clock64();
    while (!mbar_try(bar, parity)) { if (clock64() - t0 > WD_CLKS) __trap(); }
}
__device__ __forceinline__ bool elect() { uint32_t p; asm volatile("{\n.reg .pred P;\nelect.sync _|P, 0xffffffff;\nselp.u32 %0, 1, 0, P;\n}" : "=r"(p)); return p; }
__device__ __forceinline__ void tma2d(uint32_t dst, const CUtensorMap* tm, int c0, int c1, uint32_t bar) {
    asm volatile("cp.async.bulk.tensor.2d.shared::cluster.global.mbarrier::complete_tx::bytes [%0], [%1, {%3, %4}], [%2];" :: "r"(dst), "l"(tm), "r"(bar), "r"(c0), "r"(c1) : "memory");
}
__device__ __forceinline__ void tma3d(uint32_t dst, const CUtensorMap* tm, int c0, int c1, int c2, uint32_t bar) {
    asm volatile("cp.async.bulk.tensor.3d.shared::cluster.global.mbarrier::complete_tx::bytes [%0], [%1, {%3, %4, %5}], [%2];" :: "r"(dst), "l"(tm), "r"(bar), "r"(c0), "r"(c1), "r"(c2) : "memory");
}
__device__ __forceinline__ void tma2d_store(const CUtensorMap* tm, int c0, int c1, uint32_t src) {
    asm volatile("cp.async.bulk.tensor.2d.global.shared::cta.bulk_group [%0, {%2, %3}], [%1];" :: "l"(tm), "r"(src), "r"(c0), "r"(c1) : "memory");
}
__device__ __forceinline__ void bulk_ld(uint32_t dst, const void* src, uint32_t bytes, uint32_t bar) {
    asm volatile("cp.async.bulk.shared::cluster.global.mbarrier::complete_tx::bytes [%0], [%1], %2, [%3];" :: "r"(dst), "l"(src), "r"(bytes), "r"(bar) : "memory");
}
__device__ __forceinline__ void bulk_prefetch(const void* src, uint32_t bytes) { asm volatile("cp.async.bulk.prefetch.L2.global [%0], %1;" :: "l"(src), "r"(bytes) : "memory"); }
__device__ __forceinline__ void fence_async_smem() { asm volatile("fence.proxy.async.shared::cta;" ::: "memory"); }
__device__ __forceinline__ uint32_t ld_relaxed(const void* p) { uint32_t v; asm volatile("ld.relaxed.gpu.global.u32 %0, [%1];" : "=r"(v) : "l"(p) : "memory"); return v; }
__device__ __forceinline__ uint4 ld_relaxed4(const uint4* p) {
    uint4 v;
    asm volatile("{\n.reg .b128 t;\n.reg .b64 a, b;\nld.relaxed.gpu.global.b128 t, [%4];\nmov.b128 {a, b}, t;\nmov.b64 {%0, %1}, a;\nmov.b64 {%2, %3}, b;\n}" : "=r"(v.x), "=r"(v.y), "=r"(v.z), "=r"(v.w) : "l"(p) : "memory");
    return v;
}
__device__ __forceinline__ void st_relaxed4(uint4* p, uint32_t a, uint32_t b, uint32_t c, uint32_t d) {
    asm volatile("{\n.reg .b128 t;\n.reg .b64 a, b;\nmov.b64 a, {%1, %2};\nmov.b64 b, {%3, %4};\nmov.b128 t, {a, b};\nst.relaxed.gpu.global.b128 [%0], t;\n}" :: "l"(p), "r"(a), "r"(b), "r"(c), "r"(d) : "memory");
}
__device__ __forceinline__ uint32_t ld_volatile(const uint32_t* p) { uint32_t v; asm volatile("ld.volatile.global.u32 %0, [%1];" : "=r"(v) : "l"(p) : "memory"); return v; }
__device__ __forceinline__ void named_arrive(int id, int n) { asm volatile("bar.arrive %0, %1;" :: "r"(id), "r"(n) : "memory"); }
__device__ __forceinline__ void named_sync(int id, int n) { asm volatile("bar.sync %0, %1;" :: "r"(id), "r"(n) : "memory"); }
__device__ __forceinline__ void wg_fence() { asm volatile("wgmma.fence.sync.aligned;" ::: "memory"); }
__device__ __forceinline__ void wg_commit() { asm volatile("wgmma.commit_group.sync.aligned;" ::: "memory"); }
template<int N> __device__ __forceinline__ void wg_wait() { asm volatile("wgmma.wait_group.sync.aligned %0;" :: "n"(N) : "memory"); }
template<int N> __device__ __forceinline__ void reg_fence(float (&d)[N]) {
    #pragma unroll
    for (int i = 0; i < N; i++) asm volatile("" : "+f"(d[i]) :: "memory");
}
__device__ __forceinline__ constexpr uint64_t mkdesc(uint32_t addr, uint32_t lbo, uint32_t sbo, uint32_t sw) {
    return (uint64_t)((addr & 0x3FFFF) >> 4) | ((uint64_t)(lbo >> 4) << 16) | ((uint64_t)(sbo >> 4) << 32) | ((uint64_t)sw << 62);
}
__device__ __forceinline__ void ldsm4(uint32_t (&r)[4], uint32_t addr) {
    asm volatile("ldmatrix.sync.aligned.m8n8.x4.shared.b16 {%0,%1,%2,%3}, [%4];" : "=r"(r[0]), "=r"(r[1]), "=r"(r[2]), "=r"(r[3]) : "r"(addr) : "memory");
}
__device__ __forceinline__ void stsm4(uint32_t addr, uint32_t r0, uint32_t r1, uint32_t r2, uint32_t r3) {
    asm volatile("stmatrix.sync.aligned.m8n8.x4.shared.b16 [%0], {%1,%2,%3,%4};" :: "r"(addr), "r"(r0), "r"(r1), "r"(r2), "r"(r3) : "memory");
}
__device__ __forceinline__ uint32_t movtrans(uint32_t a) { uint32_t d; asm volatile("movmatrix.sync.aligned.m8n8.trans.b16 %0, %1;" : "=r"(d) : "r"(a)); return d; }
__device__ __forceinline__ uint32_t pack_bf16(float lo, float hi) { uint32_t r; asm("cvt.rn.bf16x2.f32 %0, %1, %2;" : "=r"(r) : "f"(hi), "f"(lo)); return r; }
__device__ __forceinline__ void sub_bf16x2(uint32_t& a, uint32_t b) { asm volatile("sub.rn.bf16x2 %0, %0, %1;" : "+r"(a) : "r"(b)); }
__device__ __forceinline__ float bf_lo(uint32_t v) { return __uint_as_float(v << 16); }
__device__ __forceinline__ float bf_hi(uint32_t v) { return __uint_as_float(v & 0xffff0000u); }
__device__ __forceinline__ void mma16816(float (&c)[4], uint32_t a0, uint32_t a1, uint32_t a2, uint32_t a3, uint32_t b0, uint32_t b1) {
    asm volatile("mma.sync.aligned.m16n8k16.row.col.f32.bf16.bf16.f32 {%0,%1,%2,%3}, {%4,%5,%6,%7}, {%8,%9}, {%0,%1,%2,%3};"
        : "+f"(c[0]), "+f"(c[1]), "+f"(c[2]), "+f"(c[3]) : "r"(a0), "r"(a1), "r"(a2), "r"(a3), "r"(b0), "r"(b1));
}
__device__ __forceinline__ void mma1688(float (&c)[4], uint32_t a0, uint32_t a1, uint32_t b0) {
    asm volatile("mma.sync.aligned.m16n8k8.row.col.f32.bf16.bf16.f32 {%0,%1,%2,%3}, {%4,%5}, {%6}, {%0,%1,%2,%3};"
        : "+f"(c[0]), "+f"(c[1]), "+f"(c[2]), "+f"(c[3]) : "r"(a0), "r"(a1), "r"(b0));
}
__device__ __forceinline__ float quad_sum(float v) { v += __shfl_xor_sync(0xffffffffu, v, 1); v += __shfl_xor_sync(0xffffffffu, v, 2); return v; }
__device__ __forceinline__ float quad_max(float v) { v = fmaxf(v, __shfl_xor_sync(0xffffffffu, v, 1)); v = fmaxf(v, __shfl_xor_sync(0xffffffffu, v, 2)); return v; }
__device__ __forceinline__ float ex2(float x) { float y; asm("ex2.approx.ftz.f32 %0, %1;" : "=f"(y) : "f"(x)); return y; }
__device__ __forceinline__ float rsqrt_approx(float x) { float y; asm("rsqrt.approx.ftz.f32 %0, %1;" : "=f"(y) : "f"(x)); return y; }
__device__ __forceinline__ float rcp_approx(float x) { float y; asm("rcp.approx.ftz.f32 %0, %1;" : "=f"(y) : "f"(x)); return y; }
__device__ __forceinline__ float gelu_half(float hx) {
    const float z = hx * fmaf(hx * hx, 8.f * 0.044715f * 0.7978845608028654f, 2.f * 0.7978845608028654f);
    float t; asm("tanh.approx.f32 %0, %1;" : "=f"(t) : "f"(z));
    return fmaf(hx, t, hx);
}
__device__ __forceinline__ uint32_t clock32() { uint32_t t; asm volatile("mov.u32 %0, %%clock;" : "=r"(t)); return t; }
#define PF_PACE 400

#define PF_AT 4000
#define NSQ 3
#define HALO_AT 3
#define WO_AT 0
#define WO_PACE 0
#define PF_N 12
#define HINT_H 14
#define HINT_U 14
#define CLR_MODE 2
#define FULLCLR 0
#define SP_AT 2000
#define SP_N 0
#define MAP8 0
#define WO_HOLD 7
#define A_SCHED 0x322188
#define WO_ORD0 0x4321065
#define WO_ORD1 0x3465210
#define XR_HOLD 1
template<int TB> __device__ __forceinline__ void wgmma_rs56(float (&d)[28], const uint32_t (&a)[4], uint64_t db, int sc) {
    asm volatile("{\n.reg .pred p;\nsetp.ne.b32 p, %33, 0;\n"
        "wgmma.mma_async.sync.aligned.m64n56k16.f32.bf16.bf16 {%0, %1, %2, %3, %4, %5, %6, %7, %8, %9, %10, %11, %12, %13, %14, %15, %16, %17, %18, %19, %20, %21, %22, %23, %24, %25, %26, %27}, {%28, %29, %30, %31}, %32, p, 1, 1, %34;\n}\n"
        : "+f"(d[0]), "+f"(d[1]), "+f"(d[2]), "+f"(d[3]), "+f"(d[4]), "+f"(d[5]), "+f"(d[6]), "+f"(d[7]), "+f"(d[8]), "+f"(d[9]), "+f"(d[10]), "+f"(d[11]), "+f"(d[12]), "+f"(d[13]), "+f"(d[14]), "+f"(d[15]), "+f"(d[16]), "+f"(d[17]), "+f"(d[18]), "+f"(d[19]), "+f"(d[20]), "+f"(d[21]), "+f"(d[22]), "+f"(d[23]), "+f"(d[24]), "+f"(d[25]), "+f"(d[26]), "+f"(d[27])
        : "r"(a[0]), "r"(a[1]), "r"(a[2]), "r"(a[3]), "l"(db), "r"(sc), "n"(TB));
}

template<int TA, int TB> __device__ __forceinline__ void wgmma_ss112(float (&d)[56], uint64_t da, uint64_t db, int sc) {
    asm volatile("{\n.reg .pred p;\nsetp.ne.b32 p, %58, 0;\n"
        "wgmma.mma_async.sync.aligned.m64n112k16.f32.bf16.bf16 {%0, %1, %2, %3, %4, %5, %6, %7, %8, %9, %10, %11, %12, %13, %14, %15, %16, %17, %18, %19, %20, %21, %22, %23, %24, %25, %26, %27, %28, %29, %30, %31, %32, %33, %34, %35, %36, %37, %38, %39, %40, %41, %42, %43, %44, %45, %46, %47, %48, %49, %50, %51, %52, %53, %54, %55}, %56, %57, p, 1, 1, %59, %60;\n}\n"
        : "+f"(d[0]), "+f"(d[1]), "+f"(d[2]), "+f"(d[3]), "+f"(d[4]), "+f"(d[5]), "+f"(d[6]), "+f"(d[7]), "+f"(d[8]), "+f"(d[9]), "+f"(d[10]), "+f"(d[11]), "+f"(d[12]), "+f"(d[13]), "+f"(d[14]), "+f"(d[15]), "+f"(d[16]), "+f"(d[17]), "+f"(d[18]), "+f"(d[19]), "+f"(d[20]), "+f"(d[21]), "+f"(d[22]), "+f"(d[23]), "+f"(d[24]), "+f"(d[25]), "+f"(d[26]), "+f"(d[27]), "+f"(d[28]), "+f"(d[29]), "+f"(d[30]), "+f"(d[31]), "+f"(d[32]), "+f"(d[33]), "+f"(d[34]), "+f"(d[35]), "+f"(d[36]), "+f"(d[37]), "+f"(d[38]), "+f"(d[39]), "+f"(d[40]), "+f"(d[41]), "+f"(d[42]), "+f"(d[43]), "+f"(d[44]), "+f"(d[45]), "+f"(d[46]), "+f"(d[47]), "+f"(d[48]), "+f"(d[49]), "+f"(d[50]), "+f"(d[51]), "+f"(d[52]), "+f"(d[53]), "+f"(d[54]), "+f"(d[55])
        : "l"(da), "l"(db), "r"(sc), "n"(TA), "n"(TB));
}

template<int NKB, bool PERM>
__device__ __forceinline__ void mix_mainloop(float (&acc)[56], uint32_t par, bool leader) {
    constexpr uint32_t sb = SB, bars = sb + SM_BAR;
    int bslot = 0, aslot = 0;
    reg_fence(acc);
    #pragma unroll 1
    for (int i = 0; i < NKB / 2; i++) {
        mbar_wait(bars + 8 * (B_FULLA + i), par);
        const uint64_t adesc = mkdesc(sb + SM_ARING, 8192, 1024, 1) + (uint32_t)(aslot * 1024);
        aslot = aslot == NA_SLOTS - 1 ? 0 : aslot + 1;
        #pragma unroll
        for (int jj = 0; jj < 2; jj++) {
            const int j = 2 * i + jj;
            mbar_wait(bars + 8 * (B_FULLB + j), par);
            const uint64_t bdesc = mkdesc(sb + SM_BRING, 1792, 128, 0) + (uint32_t)(bslot * 896);
            bslot = bslot == NB_SLOTS - 1 ? 0 : bslot + 1;
            wg_fence();
            #pragma unroll
            for (int s = 0; s < 4; s++) {
                const uint32_t aoff = PERM ? (s & 1) * 8192 + (jj * 32 + (s >> 1) * 16) * 128 : jj * 8192 + s * 2048;
                wgmma_ss112<1, 1>(acc, adesc + (aoff >> 4), bdesc + s * 224, 1);
            }
            wg_commit();
            wg_wait<1>();
            if (j > 0 && leader) mbar_arrive(bars + 8 * (B_DONE + j - 1));
        }
    }
    wg_wait<0>();
    reg_fence(acc);
    if (leader) mbar_arrive(bars + 8 * (B_DONE + NKB - 1));
}

constexpr uint32_t EMPTY = 0xFFFFFFFFu;
__device__ __forceinline__ void post_hint(uint4* p, uint32_t ep, int lane) { if (lane < 2) st_relaxed4(p + lane, ep, ep, ep, ep); }
__device__ __forceinline__ void post_hint_wg(uint4* p, uint32_t ep, int w, int lane) {
    if (w < 3) named_arrive(5, 128); else { named_sync(5, 128); post_hint(p, ep, lane); }
}

template<int NKB>
__device__ __forceinline__ void mix_producer_b(TSARG uint32_t par, const uint4* hints, uint32_t ep, const uint32_t* src, int lane) {
    constexpr uint32_t sb = SB, bars = sb + SM_BAR;
    uint32_t ready = 0;
    #pragma unroll 1
    for (int j = 0; j < NKB; j++) {
        while (!((ready >> j) & 1)) ready = __ballot_sync(0xffffffffu, ld_relaxed(hints + 2 * lane) == ep);
        if (j >= NB_SLOTS) mbar_wait(bars + 8 * (B_DONE + j - NB_SLOTS), par);
        if (j == 0 && lane == 0) STAMP(NKB == 32 ? 29 : 30);
        if (j == 7 && lane == 0) STAMP(NKB == 32 ? 35 : 36);
        if (elect()) {
            mbar_expect(bars + 8 * (B_RAW + (j & 7)), 14336);
            bulk_ld(sb + SM_BRING + (j & 7) * 14336, src + j * 3584, 14336, bars + 8 * (B_RAW + (j & 7)));
        }
    }
}
__device__ __forceinline__ void check_tiles(TSARG int n, int w, int lane, uint32_t& ph, uint32_t dst, const uint32_t* src, int full) {
    constexpr uint32_t bars = SB + SM_BAR;
    #pragma unroll 1
    for (int j = w; j < n; j += 4) {
        const uint32_t raw = bars + 8 * (B_RAW + (j & 7)), d = dst + (j & 7) * 14336, a = d + lane * 128 + (lane & 3) * 32 + (lane >> 2) * 4;
        bool bad;
        do {
            mbar_wait(raw, (ph >> (j & 4)) & 1);
            ph ^= 1u << (j & 4);
            if (j == 0 && lane == 0) STAMP(n == 4 ? 6 : n == 32 ? 31 : 32);
            uint32_t v0, v1, v2, v3;
            asm volatile("ld.shared.u32 %0, [%4];\nld.shared.u32 %1, [%4+4096];\nld.shared.u32 %2, [%4+8192];\nld.shared.u32 %3, [%4+10240];"
                         : "=r"(v0), "=r"(v1), "=r"(v2), "=r"(v3) : "r"(a) : "memory");
            bad = __any_sync(0xffffffffu, max(max(v0, v1), max(v2, v3)) == EMPTY);
            if (elect() && bad) {
                mbar_expect(raw, 14336); bulk_ld(d, src + j * 3584, 14336, raw);
            }
        } while (bad);
        if (lane == 0) mbar_arrive(bars + 8 * (full + j));
    }
}

__device__ __forceinline__ constexpr int sq_cut(int p) { return 4 * NSQ + (28 - 4 * NSQ) * (p == 1 ? 0 : p == 2 ? 2 : p == 6 ? 16 : 4 * p - 7) / 16; }

__device__ __forceinline__ uint32_t hcol(uint32_t a, int jp) { return (a ^ ((jp & 3) << 5)) + (jp >> 2) * 8192; }

template<bool USE_SMID>
__global__ void __launch_bounds__(384, 1)
fused_kernel(Scratch* __restrict__ sc, const __nv_bfloat16* __restrict__ wo,
             const __nv_bfloat16* __restrict__ w1, const __nv_bfloat16* __restrict__ b1,
             const __nv_bfloat16* __restrict__ w2, const __nv_bfloat16* __restrict__ b2,
             const __grid_constant__ CUtensorMap tm_x, const __grid_constant__ CUtensorMap tm_wqkv,
             const __grid_constant__ CUtensorMap tm_wo64, const __grid_constant__ CUtensorMap tm_wo48,
             const __grid_constant__ CUtensorMap tm_w1, const __grid_constant__ CUtensorMap tm_w2,
             const __grid_constant__ CUtensorMap tm_xr64, const __grid_constant__ CUtensorMap tm_xr48,
             const __grid_constant__ CUtensorMap tm_out64, const __grid_constant__ CUtensorMap tm_out48) {
    extern __shared__ __align__(1024) uint8_t smem_raw[];
    constexpr uint32_t sb = SB;
    constexpr uint32_t bars = sb + SM_BAR;
    const int tid = threadIdx.x, lane = tid & 31;
    const int warp = __shfl_sync(0xffffffffu, tid >> 5, 0);
    int slot;
    if (USE_SMID) {
        asm("{\n.reg .u32 s, t, u, d, a, b, c;\n.reg .pred p, r;\n"
            "mov.u32 s, %%smid;\nshr.u32 t, s, 1;\nsub.u32 u, t, 32;\nmul.lo.u32 d, u, 37;\nshr.u32 d, d, 8;\n"
            "and.b32 a, t, 7;\nshl.b32 a, a, 3;\nshr.u32 c, t, 3;\nadd.u32 a, a, c;\n"
            "mad.lo.u32 b, d, -55, 12;\nshl.b32 c, u, 3;\nadd.u32 b, b, c;\n"
            "setp.lt.u32 p, t, 32;\nselp.u32 a, a, b, p;\n"
            "setp.lt.u32 r, t, 64;\nselp.u32 c, 56, 0, r;\nsub.u32 c, t, c;\nsetp.lt.u32 p, t, 60;\nselp.u32 a, a, c, p;\n"
            "and.b32 s, s, 1;\nshl.b32 a, a, 1;\nadd.u32 %0, a, s;\n}" : "=r"(slot));
    } else slot = blockIdx.x;
    const int G = slot >> 4, mi = slot & 15;
    const int tb = MAP8 ? 8 * (G >> 2) + (mi >> 1) : 4 * (G >> 1) + (mi >> 2), hp = MAP8 ? (G & 3) + 4 * (mi & 1) : 2 * (mi & 3) + (G & 1);
    const int wcol = (hp * 56) & ~15;
    if (slot >= 128) {
        if (tid == 0) {
            const uint32_t ep = sc->epoch[slot] + 1;
            const long long t0 = clock64();
            while (clock64() - t0 < SP_AT) {}
            #pragma unroll 1
            for (int i = 0; i < 7; i++) bulk_prefetch((const char*)wo + (i * 4 + mi) * 14336, 14336);
            #pragma unroll 1
            for (int i = 0; i < SP_N; i++) bulk_prefetch((const char*)w1 + (i * 4 + mi) * 14336, 14336);
            while (ld_relaxed(sc->hint_u) != ep) { __nanosleep(500); if (clock64() - t0 > WD_CLKS) __trap(); }
            sc->epoch[slot] = ep;
        }
        return;
    }
    const int q = mi & 3, tt2 = 4 * G + (mi >> 2), ft = 4 * (G - 1) + (mi >> 2);
    const bool has_b1 = G > 0;
    const int c64 = 64 * q, c48 = 256 + 48 * q;

    if (warp < 8) {
        named_sync(0, 384);
        asm volatile("setmaxnreg.inc.sync.aligned.u32 232;");
        int tid; asm volatile("mov.u32 %0, %%tid.x;" : "=r"(tid));
        const int lane = tid & 31, warp = __shfl_sync(0xffffffffu, tid >> 5, 0), wg = warp >> 2;
        const uint32_t ep = ld_volatile(&sc->epoch[slot]) + 1;
        const int w = warp & 3, g = lane >> 2, t = lane & 3;
        const bool leader = (tid & 127) == 0;
        {
            uint32_t a[28][4];
            float accK[28], accV[28], accQ[28];
            const int lrow = 16 * w + (lane & 7) + (lane & 8);
            const uint32_t lbase = sb + wg * 8192 + lrow * 128;
            const uint32_t lx = (lane >> 4) ^ (lane & 7);
            const uint32_t never = gridDim.y - 1;
            const uint32_t wofs = hp & 1;
            float cS[2][4] = {}, cA[4] = {}, cB[4] = {}, p0, p1;
            #pragma unroll
            for (int kb = 0; kb < 8; kb++) {
                if (kb < 7) {
                    mbar_wait(bars + 8 * (B_FULLX + kb), 0);
                    if (kb == 0 && tid == 0) STAMP(0);
                    if (kb == 6 && tid == 0) STAMP(25);
                    #pragma unroll
                    for (int s = 4 * kb; s < 4 * kb + 4; s++) ldsm4(a[s], lbase + slot_x(kb) + ((lx ^ (2 * (s & 3))) << 4));
                }
                if (kb == 0) continue;
                if (kb - 1 == NSQ) { p0 = cS[0][0] + cS[1][0]; p1 = cS[0][2] + cS[1][2]; }
                #pragma unroll
                for (int s = 4 * kb - 4; s < 4 * kb; s++) {
                    mma16816(cS[s & 1], a[s][0], a[s][1], a[s][2], a[s][3], 0x3F803F80u, 0x3F803F80u);
                    if (kb - 1 < NSQ) {
                        mma16816(cA, a[s][0], a[s][1], a[s][2], a[s][3], a[s][0], a[s][2]);
                        mma16816(cB, a[s][0], a[s][1], a[s][2], a[s][3], a[s][1], a[s][3]);
                    }
                }
            }
            const float m0 = (cS[0][0] + cS[1][0]) * (1.f / D_), m1 = (cS[0][2] + cS[1][2]) * (1.f / D_);
            const uint32_t mm0 = pack_bf16(m0, m0), mm1 = pack_bf16(m1, m1);
            if (lane == 0) mbar_arrive(bars + 8 * B_DONEX);
            auto center = [&](int kb) {
                #pragma unroll
                for (int s = 4 * kb; s < 4 * kb + 4; s++) { sub_bf16x2(a[s][0], mm0); sub_bf16x2(a[s][1], mm1); sub_bf16x2(a[s][2], mm0); sub_bf16x2(a[s][3], mm1); }
            };
            float q0, q1;
            auto sumsq = [&](int sa, int sb_) {
                if (sa == 4 * NSQ) {
                    const float c0 = bf_hi(mm0), c1 = bf_hi(mm1);
                    q0 = t == (g >> 1) ? fmaf(c0, fmaf(c0, 64.f * NSQ, -2.f * p0), (g & 1) ? cA[1] : cA[0]) - D_ * (m0 - c0) * (m0 - c0) : 0.f;
                    q1 = t == (g >> 1) ? fmaf(c1, fmaf(c1, 64.f * NSQ, -2.f * p1), (g & 1) ? cB[3] : cB[2]) - D_ * (m1 - c1) * (m1 - c1) : 0.f;
                }
                #pragma unroll
                for (int s = 0; s < 28; s++) {
                    if (s < sa || s >= sb_) continue;
                    #pragma unroll
                    for (int r = 0; r < 4; r++) {
                        const float lo = bf_lo(a[s][r]), hi = bf_hi(a[s][r]);
                        if (r & 1) q1 = fmaf(hi, hi, fmaf(lo, lo, q1)); else q0 = fmaf(hi, hi, fmaf(lo, lo, q0));
                    }
                }
                asm volatile("{\n.reg .pred p;\nsetp.ne.u32 p, %2, 0;\n@p st.shared.v2.f32 [%3], {%0,%1};\n}" :: "f"(q0), "f"(q1), "r"(never), "r"(sb) : "memory");
            };
            auto qsteps = [&](int sa, int sb_) {
                wg_fence();
                #pragma unroll
                for (int s = sa; s < sb_; s++) wgmma_rs56<1>(accQ, a[s], mkdesc(sb + SM_QO + s * 2048, 8192, 1024, 1) + wofs, s != 0);
                wg_commit();
                wg_wait<1>();
            };
            auto hand_over = [&](const uint32_t (&v)[7], int kv) {
                if (w < 3) {
                    uint4* hs = (uint4*)(smem_raw + (kv ? SM_HALOV : SM_HALOK)) + warp * 64 + lane;
                    hs[0] = make_uint4(v[0], v[1], v[2], v[3]); hs[32] = make_uint4(v[4], v[5], v[6], 0);
                } else if (tb < 15) {
                    uint4* hg = sc->halo + ((((tb + 1) * 8 + hp) * 2 + wg) * 2 + kv) * 96 + lane;
                    st_relaxed4(hg, v[0], v[1], v[2], ep); st_relaxed4(hg + 32, v[3], v[4], v[5], ep); st_relaxed4(hg + 64, v[6], ep, ep, ep);
                }
            };
            auto take_over = [&](uint32_t (&v)[7], int kv) {
                if (w == 0) mbar_wait(bars + 8 * (B_HALO + 2 * kv + wg), 0);
                const uint4* hs = (const uint4*)(smem_raw + (kv ? SM_HALOV : SM_HALOK)) + (w ? warp - 1 : warp + 3) * 64 + lane;
                const uint4 u0 = hs[0], u1 = hs[32];
                v[0] = u0.x; v[1] = u0.y; v[2] = u0.z; v[3] = u0.w; v[4] = u1.x; v[5] = u1.y; v[6] = u1.z;
            };
            uint32_t Ka[7], Kb[7], Kc[7], Va[7], Vb[7], Vc[7];
            float r0, r1;
            center(0);
            #pragma unroll
            for (int p = 0; p < 7; p++) {
                mbar_wait(bars + 8 * (B_FULLKV + p), 0);
                if (p == 0 && tid == 0) STAMP(26);
                if (p == 3 && tid == 0) STAMP(27);
                wg_fence();
                #pragma unroll
                for (int s = 8 * p; s < 8 * p + 8; s++) {
                    if (s == 4) { center(1); wg_fence(); }
                    const uint64_t desc = mkdesc(sb + slot_kv(p) + (s & 7) * 2048, 8192, 1024, 1) + wofs;
                    if (s < 28) wgmma_rs56<1>(accK, a[s], desc, s != 0); else wgmma_rs56<1>(accV, a[s - 28], desc, s != 28);
                }
                wg_commit();
                if (p > 0) {
                    wg_wait<1>();
                    if (leader) mbar_arrive(bars + 8 * (B_DONE1 + p - 1));
                }
                if (p < 3) center(2 * p + 2);
                if (p < 2) center(2 * p + 3);
                if (p > 0 && p < 6) sumsq(sq_cut(p), sq_cut(p + 1));
                if (p == 6) {
                    q0 = quad_sum(q0); q1 = quad_sum(q1);
                    r0 = rsqrt_approx(fmaxf(q0 * (1.f / D_), 0.f) + LN_EPS); r1 = rsqrt_approx(fmaxf(q1 * (1.f / D_), 0.f) + LN_EPS);
                    reg_fence(accK);
                    #pragma unroll
                    for (int j = 0; j < 7; j++) Kc[j] = pack_bf16(accK[4 * j + 2] * r1, accK[4 * j + 3] * r1);
                    hand_over(Kc, 0);
                }
            }
            if (tid == 0) STAMP(1);
            mbar_wait(bars + 8 * B_FQ, 0);
            qsteps(0, 7);
            reg_fence(accV);
            if (leader) mbar_arrive(bars + 8 * (B_DONE1 + 6));
            if (tid == 0) STAMP(2);
            #pragma unroll
            for (int j = 0; j < 7; j++) Vc[j] = movtrans(pack_bf16(accV[4 * j + 2] * r1, accV[4 * j + 3] * r1));
            if (w < 3) mbar_wait(bars + 8 * (B_DONE1 + 5), 0);
            hand_over(Vc, 1);
            if (tid == 96) STAMP(23);
            qsteps(7, 14);
            #pragma unroll
            for (int j = 0; j < 7; j++) {
                Kb[j] = pack_bf16(accK[4 * j] * r0, accK[4 * j + 1] * r0);
                Vb[j] = movtrans(pack_bf16(accV[4 * j] * r0, accV[4 * j + 1] * r0));
                asm volatile("" : "+r"(Kb[j]));
            }
            mbar_wait(bars + 8 * (B_FQ + 1), 0);
            qsteps(14, 21);
            qsteps(21, 28);
            named_sync(1 + wg, 128);
            take_over(Ka, 0);
            if (tid == 0) STAMP(3);
            wg_wait<0>();
            reg_fence(accQ);
            if (tid == 0) STAMP(4);
            uint32_t Q0[7], Q1[7];
            #pragma unroll
            for (int j = 0; j < 7; j++) { Q0[j] = pack_bf16(accQ[4 * j], accQ[4 * j + 1]); Q1[j] = pack_bf16(accQ[4 * j + 2], accQ[4 * j + 3]); }
            const bool first = (tb == 0 && w == 0);
            const float lsc = 0.1889822365046136f * 1.4426950408889634f;
            const float ls0 = lsc * r0, ls1 = lsc * r1;
            uint32_t pA[2], pB0[2], pB1[2], pC[2];
            #pragma unroll
            for (int h = 0; h < 2; h++) {
                const int j0 = 3 * h;
                const bool own3 = (t >= 2) == (h == 1);
                uint32_t qa[4], qb[4];
                #pragma unroll
                for (int j = 0; j < 4; j++) {
                    qa[j] = (j0 + j == 3 && !own3) ? 0u : Q0[j0 + j];
                    qb[j] = (j0 + j == 3 && !own3) ? 0u : Q1[j0 + j];
                }
                float sA[4] = {0.f, 0.f, 0.f, 0.f}, sB[4] = {0.f, 0.f, 0.f, 0.f}, sC[4] = {0.f, 0.f, 0.f, 0.f};
                #pragma unroll
                for (int k = 0; k < 2; k++) {
                    mma16816(sA, qa[2 * k], qb[2 * k], qa[2 * k + 1], qb[2 * k + 1], Ka[j0 + 2 * k], Ka[j0 + 2 * k + 1]);
                    mma16816(sB, qa[2 * k], qb[2 * k], qa[2 * k + 1], qb[2 * k + 1], Kb[j0 + 2 * k], Kb[j0 + 2 * k + 1]);
                    mma16816(sC, qa[2 * k], qb[2 * k], qa[2 * k + 1], qb[2 * k + 1], Kc[j0 + 2 * k], Kc[j0 + 2 * k + 1]);
                }
                const bool n0 = 2 * t <= g, n1 = 2 * t + 1 <= g;
                float l00 = n0 ? sB[0] : (first ? -INFINITY : sA[0]), l01 = n1 ? sB[1] : (first ? -INFINITY : sA[1]);
                float l10 = n0 ? sC[2] : sB[2], l11 = n1 ? sC[3] : sB[3];
                const float x0 = quad_max(fmaxf(l00, l01)), x1 = quad_max(fmaxf(l10, l11));
                const float e00 = ex2((l00 - x0) * ls0), e01 = ex2((l01 - x0) * ls0), e10 = ex2((l10 - x1) * ls1), e11 = ex2((l11 - x1) * ls1);
                const float i0 = rcp_approx(quad_sum(e00 + e01)), i1 = rcp_approx(quad_sum(e10 + e11));
                const float p00 = e00 * i0, p01 = e01 * i0, p10 = e10 * i1, p11 = e11 * i1;
                pA[h] = pack_bf16(n0 ? 0.f : p00, n1 ? 0.f : p01); pB0[h] = pack_bf16(n0 ? p00 : 0.f, n1 ? p01 : 0.f);
                pC[h] = pack_bf16(n0 ? p10 : 0.f, n1 ? p11 : 0.f); pB1[h] = pack_bf16(n0 ? 0.f : p10, n1 ? 0.f : p11);
            }
            float o[8][4];
            #pragma unroll
            for (int j = 0; j < 8; j++) {
                o[j][0] = o[j][1] = o[j][2] = o[j][3] = 0.f;
                mma16816(o[j], pB0[j >> 2], pB1[j >> 2], 0u, pC[j >> 2], Vb[j - (j >> 2)], Vc[j - (j >> 2)]);
            }
            if (tid == 0) STAMP(12);
            take_over(Va, 1);
            if (lane == 0) mbar_arrive(bars + 8 * B_DONEQ);
            if (tid == 0) STAMP(16);
            #pragma unroll
            for (int j = 0; j < 8; j++) mma1688(o[j], pA[j >> 2], 0u, Va[j - (j >> 2)]);
            const int tt = 2 * tb + (w >> 1);
            mbar_wait(bars + 8 * B_CLR, 0);
            uint32_t* od = sc->o + tt * 14336 + (7 * hp) * 256 + (2 * (2 * (w & 1) + wg)) * 32 + lane;
            #pragma unroll
            for (int j = 0; j < 7; j++) {
                float v[4];
                #pragma unroll
                for (int c = 0; c < 4; c++) v[c] = j < 3 ? o[j][c] : j > 3 ? o[j + 1][c] : (t < 2 ? o[3][c] : o[4][c]);
                od[j * 256] = pack_bf16(v[0], v[1]);
                od[j * 256 + 32] = pack_bf16(v[2], v[3]);
            }
            if (tid == 0) STAMP(5);
            post_hint(sc->hint_o + (tt * 32 + hp * 4 + (w & 1) * 2 + wg) * 2, ep, lane);
        }
        if (wg == 1) {
            uint32_t ph = 0;
            check_tiles(TSVAL 4, w, lane, ph, sb + SM_QO, sc->o + tt2 * 14336, B_FULLO);
            if (has_b1) check_tiles(TSVAL 32, w, lane, ph, sb + SM_BRING, sc->hn + q * 32 * 3584, B_FULLB);
            check_tiles(TSVAL 28, w, lane, ph, sb + SM_BRING, sc->u + q * 28 * 3584, B_FULLB);
        } else {
            const uint32_t rb10 = has_b1 ? __ldg((const unsigned short*)b1 + ft * 64 + 16 * w + g) : 0, rb11 = has_b1 ? __ldg((const unsigned short*)b1 + ft * 64 + 16 * w + g + 8) : 0;
            const uint32_t rb20 = __ldg((const unsigned short*)b2 + tt2 * 64 + 16 * w + g), rb21 = __ldg((const unsigned short*)b2 + tt2 * 64 + 16 * w + g + 8);
            {
                float acc[56];
                const int hrow = 32 * (w >> 1) + 2 * ((lane & 7) + (lane & 8)) + (w & 1);
                const uint32_t ha = sb + SM_H + hrow * 128 + (((lane >> 4) ^ (hrow & 7)) << 4);
                mbar_wait(bars + 8 * B_FULLWO, 0);
                #pragma unroll
                for (int jp = 0; jp < 7; jp++) {
                    uint32_t xx[4];
                    ldsm4(xx, hcol(ha, jp));
                    #pragma unroll
                    for (int r = 0; r < 4; r++) { acc[8 * jp + 2 * r] = bf_lo(xx[r]); acc[8 * jp + 2 * r + 1] = bf_hi(xx[r]); }
                }
                reg_fence(acc);
                #pragma unroll
                for (int i = 0; i < 4; i++) {
                    mbar_wait(bars + 8 * (B_FULLO + i), 0);
                    if (i == 0 && tid == 0) STAMP(7);
                    wg_fence();
                    #pragma unroll
                    for (int ss = 0; ss < 7; ss++) {
                        const int s = 7 * i + ss, kb = s >> 2;
                        wgmma_ss112<0, 1>(acc, mkdesc(sb + SM_QO + s * 2048, 1024, 128, 0),
                                          mkdesc(sb + slot_wo(kb) + (s & 3) * 2048, 8192, 1024, 1), 1);
                    }
                    wg_commit();
                    if (i > 0) {
                        wg_wait<1>();
                        if (leader) mbar_arrive(bars + 8 * (B_DONEO + i - 1));
                    }
                }
                wg_wait<0>();
                reg_fence(acc);
                if (leader) mbar_arrive(bars + 8 * (B_DONEO + 3));
                if (tid == 0) STAMP(8);
                float s0 = 0.f, s1 = 0.f, q0 = 0.f, q1 = 0.f, s2 = 0.f, s3 = 0.f, q2 = 0.f, q3 = 0.f;
                #pragma unroll
                for (int j = 0; j < 14; j++) {
                    s0 += acc[4 * j]; s2 += acc[4 * j + 1]; q0 = fmaf(acc[4 * j], acc[4 * j], q0); q2 = fmaf(acc[4 * j + 1], acc[4 * j + 1], q2);
                    s1 += acc[4 * j + 2]; s3 += acc[4 * j + 3]; q1 = fmaf(acc[4 * j + 2], acc[4 * j + 2], q1); q3 = fmaf(acc[4 * j + 3], acc[4 * j + 3], q3);
                }
                s0 = quad_sum(s0 + s2); s1 = quad_sum(s1 + s3); q0 = quad_sum(q0 + q2); q1 = quad_sum(q1 + q3);
                uint4* sp = sc->stats + tt2 * 256 + 16 * w + g;
                if (t < 2) st_relaxed4(sp + q * 64 + 8 * t, __float_as_uint(t ? s1 : s0), ep, __float_as_uint(t ? q1 : q0), ep);
                if (tid == 0) STAMP(9);
                #pragma unroll
                for (int jp = 0; jp < 7; jp++)
                    stsm4(hcol(ha, jp), pack_bf16(acc[8 * jp], acc[8 * jp + 1]), pack_bf16(acc[8 * jp + 2], acc[8 * jp + 3]),
                          pack_bf16(acc[8 * jp + 4], acc[8 * jp + 5]), pack_bf16(acc[8 * jp + 6], acc[8 * jp + 7]));
                {
                    uint4 v0, v1;
                    do {
                        v0 = ld_relaxed4(sp + t * 64); v1 = ld_relaxed4(sp + t * 64 + 8);
                    } while (__any_sync(0xffffffffu, t != q && (v0.y != ep || v0.w != ep || v1.y != ep || v1.w != ep)));
                    if (t != q) { s0 = __uint_as_float(v0.x); q0 = __uint_as_float(v0.z); s1 = __uint_as_float(v1.x); q1 = __uint_as_float(v1.z); }
                }
                if (tid == 0) STAMP(10);
                s0 = quad_sum(s0); s1 = quad_sum(s1); q0 = quad_sum(q0); q1 = quad_sum(q1);
                const float m0 = s0 * (1.f / D_), m1 = s1 * (1.f / D_);
                const float v0 = fmaxf(q0 * (1.f / D_) - m0 * m0, 0.f), v1 = fmaxf(q1 * (1.f / D_) - m1 * m1, 0.f);
                float r0 = rsqrt_approx(v0 + LN_EPS), r1 = rsqrt_approx(v1 + LN_EPS);
                r0 *= 0.5f * rsqrt_approx(fmaf(v0 * r0, r0, LN_EPS)); r1 *= 0.5f * rsqrt_approx(fmaf(v1 * r1, r1, LN_EPS));
                const float c0 = -m0 * r0, c1 = -m1 * r1;
                uint32_t* hd = sc->hn + (q * 32 + tt2) * 3584 + (2 * w) * 448 + lane;
                #pragma unroll
                for (int j = 0; j < 14; j++) {
                    if (j == HINT_H) post_hint_wg(sc->hint_h + (q * 32 + tt2) * 2, ep, w, lane);
                    hd[j * 32] = pack_bf16(fmaf(acc[4 * j], r0, c0), fmaf(acc[4 * j + 1], r0, c0));
                    hd[j * 32 + 448] = pack_bf16(fmaf(acc[4 * j + 2], r1, c1), fmaf(acc[4 * j + 3], r1, c1));
                }
                if (tid == 0) STAMP(11);
                if (HINT_H == 14) post_hint_wg(sc->hint_h + (q * 32 + tt2) * 2, ep, w, lane);
                if (tid == 96) STAMP(33);
            }
            if (has_b1) {
                float acc[56];
                #pragma unroll
                for (int j = 0; j < 56; j++) acc[j] = 0.5f * bf_lo((j & 2) ? rb11 : rb10);
                mix_mainloop<32, true>(acc, 0, leader);
                if (tid == 0) STAMP(14);
                mbar_wait(bars + 8 * B_CLR, 1);
                uint32_t* ud = sc->u + (q * 28 + ft) * 3584 + (2 * w) * 448 + lane;
                #pragma unroll
                for (int j = 0; j < 14; j++) {
                    if (j == HINT_U) post_hint_wg(sc->hint_u + (q * 32 + ft) * 2, ep, w, lane);
                    ud[j * 32] = pack_bf16(gelu_half(acc[4 * j]), gelu_half(acc[4 * j + 1]));
                    ud[j * 32 + 448] = pack_bf16(gelu_half(acc[4 * j + 2]), gelu_half(acc[4 * j + 3]));
                }
                if (tid == 0) STAMP(15);
                if (HINT_U == 14) post_hint_wg(sc->hint_u + (q * 32 + ft) * 2, ep, w, lane);
                if (tid == 96) STAMP(34);
            }
            {
                float acc[56];
                const float bb0 = bf_lo(rb20), bb1 = bf_lo(rb21);
                named_sync(1, 128);
                const uint32_t ad = sb + SM_H + (16 * w + (lane & 15)) * 128 + (((lane >> 4) ^ (lane & 7)) << 4);
                #pragma unroll
                for (int jp = 0; jp < 7; jp++) {
                    uint32_t hh[4];
                    ldsm4(hh, hcol(ad, jp));
                    #pragma unroll
                    for (int r = 0; r < 4; r++) { acc[8 * jp + 2 * r] = bf_lo(hh[r]) + ((r & 1) ? bb1 : bb0); acc[8 * jp + 2 * r + 1] = bf_hi(hh[r]) + ((r & 1) ? bb1 : bb0); }
                }
                mix_mainloop<28, false>(acc, has_b1, leader);
                if (leader) mbar_arrive(bars + 8 * B_END);
                if (tid == 0) STAMP(18);
                #pragma unroll
                for (int jp = 0; jp < 7; jp++)
                    stsm4(hcol(ad, jp), pack_bf16(acc[8 * jp], acc[8 * jp + 1]), pack_bf16(acc[8 * jp + 2], acc[8 * jp + 3]),
                          pack_bf16(acc[8 * jp + 4], acc[8 * jp + 5]), pack_bf16(acc[8 * jp + 6], acc[8 * jp + 7]));
                fence_async_smem();
                __syncwarp();
                if (elect()) {
                    tma2d_store(&tm_out64, c64, tt2 * 64 + 16 * w, sb + SM_H + w * 2048);
                    tma2d_store(&tm_out48, c48, tt2 * 64 + 16 * w, sb + SM_H + 8192 + w * 2048);
                    asm volatile("cp.async.bulk.commit_group;" ::: "memory");
                    asm volatile("cp.async.bulk.wait_group.read 0;" ::: "memory");
                }
                if (tid == 0) { sc->epoch[slot] = ep; STAMP(19); }
            }
        }
    } else {
        asm volatile("setmaxnreg.dec.sync.aligned.u32 40;");
        int warp2; asm("mov.u32 %0, %1;" : "=r"(warp2) : "r"(warp));
        if (warp2 > 8) {
            const int l0 = lane >> 1, wo_ = (l0 & 3) * 2 + (lane & 1);
            auto clear_o = [&]() {
                if (FULLCLR & 1) {
                    uint4* po = (uint4*)sc->o + 2 * tb * 3584 + hp * 448 + lane;
                    #pragma unroll 2
                    for (int i = 0; i < 14; i++) { st_relaxed4(po + i * 32, EMPTY, EMPTY, EMPTY, EMPTY); st_relaxed4(po + i * 32 + 3584, EMPTY, EMPTY, EMPTY, EMPTY); }
                } else {
                    uint4* po = (uint4*)sc->o + 2 * tb * 3584 + hp * 448 + wo_;
                    #pragma unroll
                    for (int i = 0; i < 7; i++) { const int l = l0 + 16 * i; st_relaxed4(po + (l < 56 ? l * 8 : l * 8 + 3584 - 448), EMPTY, EMPTY, EMPTY, EMPTY); }
                }
            };
            auto clear_h = [&]() {
                if (FULLCLR & 2) {
                    uint4* ph = (uint4*)sc->hn + (q * 32 + tt2) * 896 + lane;
                    #pragma unroll 4
                    for (int i = 0; i < 28; i++) st_relaxed4(ph + i * 32, EMPTY, EMPTY, EMPTY, EMPTY);
                } else {
                    uint4* ph = (uint4*)sc->hn + (q * 32 + tt2) * 896 + l0 * 8 + wo_;
                    #pragma unroll
                    for (int i = 0; i < 7; i++) st_relaxed4(ph + i * 128, EMPTY, EMPTY, EMPTY, EMPTY);
                }
            };
            if (warp == 11) { if (CLR_MODE == 0 || CLR_MODE == 3) clear_o(); if (CLR_MODE == 0) clear_h(); }
            if (elect()) {
                if (warp == 9) {
                    #pragma unroll
                    for (int i = B_DONE1; i < B_DONEO; i++) mbar_init(bars + 8 * i, i < B_DONEX ? 2 : 8);
                    mbar_init(bars + 8 * B_CLR, 1);
                }
                #pragma unroll
                for (int i = 0; i < 34; i++) mbar_init(bars + 8 * (B_DONEO + i) + (warp - 9) * 272, 1);
                asm volatile("fence.mbarrier_init.release.cluster;" ::: "memory");
            }
            named_sync(0, 384);
            if (warp == 9) named_arrive(4, 64);
            if (warp < 11) {
                const uint32_t ep = ld_volatile(&sc->epoch[slot]) + 1;
                mbar_wait(bars + 8 * (B_DONE1 + HALO_AT), 0);
                #pragma unroll 1
                for (int kv = 0; kv < 2; kv++) {
                    uint4 v0 = {}, v1 = {}, v2 = {};
                    if (tb > 0) {
                        const uint4* hg = sc->halo + (((tb * 8 + hp) * 2 + warp - 9) * 2 + kv) * 96 + lane;
                        do { v0 = ld_relaxed4(hg); v1 = ld_relaxed4(hg + 32); v2 = ld_relaxed4(hg + 64); } while (!__all_sync(0xffffffffu, v0.w == ep && v1.w == ep && v2.w == ep));
                    }
                    if (kv) mbar_wait(bars + 8 * (B_DONE1 + 5), 0);
                    uint4* hs = (uint4*)(smem_raw + (kv ? SM_HALOV : SM_HALOK)) + (4 * warp - 33) * 64 + lane;
                    hs[0] = make_uint4(v0.x, v0.y, v0.z, v1.x); hs[32] = make_uint4(v1.y, v1.z, v2.x, 0);
                    __syncwarp();
                    if (lane == 0) mbar_arrive(bars + 8 * (B_HALO + 2 * kv + warp - 9));
                }
                if (tid == 288) STAMP(21);
            }
            if (warp == 10) {
                if (!has_b1 && lane == 0) {
                    mbar_wait(bars + 8 * (B_DONEO + 3), 0);
                    uint32_t t = clock32() + PF_AT;
                    #pragma unroll 1
                    for (int i = 0; i < PF_N; i++) {
                        while ((int)(clock32() - t) < 0) __nanosleep(40);
                        bulk_prefetch((const char*)w2 + (i * 16 + mi) * 16384, 16384);
                        t += PF_PACE;
                    }
                }
            } else if (warp == 11) {
                if (CLR_MODE == 1) { clear_o(); clear_h(); }
                if (CLR_MODE == 2) { mbar_wait_wd(bars + 8 * (B_FULLKV + 2), 0); clear_o(); mbar_wait_wd(bars + 8 * (B_FULLKV + 4), 0); clear_h(); }
                if (CLR_MODE == 3) { mbar_wait_wd(bars + 8 * (B_FULLKV + 4), 0); clear_h(); }
                asm volatile("fence.acq_rel.gpu;" ::: "memory");
                __syncwarp();
                if (lane == 0) mbar_arrive(bars + 8 * B_CLR);
                if (lane == 0) STAMP(24);
                if (has_b1) {
                    uint4* pu = (uint4*)sc->u + (q * 28 + ft) * 896 + l0 * 8 + wo_;
                    if (FULLCLR & 4) {
                        pu = (uint4*)sc->u + (q * 28 + ft) * 896 + lane;
                        #pragma unroll 1
                        for (int i = 0; i < 14; i++) { mbar_wait_wd(bars + 8 * (B_DONE + 2 + i), 0); st_relaxed4(pu + i * 64, EMPTY, EMPTY, EMPTY, EMPTY); st_relaxed4(pu + i * 64 + 32, EMPTY, EMPTY, EMPTY, EMPTY); }
                    } else {
                        #pragma unroll 1
                        for (int i = 0; i < 7; i++) { mbar_wait_wd(bars + 8 * (B_DONE + 2 * i), 0); st_relaxed4(pu + i * 128, EMPTY, EMPTY, EMPTY, EMPTY); }
                    }
                    asm volatile("fence.acq_rel.gpu;" ::: "memory");
                    __syncwarp();
                    if (lane == 0) mbar_arrive(bars + 8 * B_CLR);
                }
                if (lane == 0) {
                    mbar_wait_wd(bars + 8 * B_END, 0);
                }
            } else {
                int aslot = 0;
                if (has_b1) {
                    #pragma unroll 1
                    for (int i = 0; i < 16; i++) {
                        mbar_wait(bars + 8 * (i < NA_SLOTS ? B_DONEQ + ((A_SCHED >> (4 * i)) & 15) : B_DONE + 1 + ((i - NA_SLOTS) * 22) / (15 - NA_SLOTS)), 0);
                        if (elect()) {
                            const uint32_t bar = bars + 8 * (B_FULLA + i), dst = sb + SM_ARING + aslot * 16384;
                            mbar_expect(bar, 16384);
                            tma3d(dst, &tm_w1, ft * 64, 0, i * 64, bar);
                            tma3d(dst + 8192, &tm_w1, ft * 64, 1, i * 64, bar);
                        }
                        aslot = aslot == NA_SLOTS - 1 ? 0 : aslot + 1;
                    }
                }
                aslot = 0;
                #pragma unroll 1
                for (int i = 0; i < 14; i++) {
                    if (i >= NA_SLOTS) mbar_wait(bars + 8 * (B_DONE + 1 + ((i - NA_SLOTS) * 18) / (13 - NA_SLOTS)), has_b1);
                    else if (has_b1) {
                        const int last = i + NA_SLOTS * ((15 - i) / NA_SLOTS);
                        mbar_wait(bars + 8 * (B_DONE + max(2 * last + 1, 32 - NB_SLOTS)), 0);
                    } else if (i == 0) { mbar_wait(bars + 8 * (B_DONEO + 3), 0); const uint32_t t = clock32() + PF_AT + 12 * PF_PACE; while ((int)(clock32() - t) < 0) __nanosleep(100); }
                    if (i == NA_SLOTS - 1 && has_b1) mbar_wait(bars + 8 * (B_DONE + 31), 0);
                    if (elect()) {
                        const uint32_t bar = bars + 8 * (B_FULLA + i);
                        mbar_expect(bar, 16384);
                        tma2d(sb + SM_ARING + aslot * 16384, &tm_w2, tt2 * 64, i * 128, bar);
                    }
                    aslot = aslot == NA_SLOTS - 1 ? 0 : aslot + 1;
                }
            }
        } else {
            auto krot = [&](int kb) { const int k = kb * 64 + (G & 1) * 192; return k < 448 ? k : k - 448; };
            if (elect()) {
                #pragma unroll
                for (int i = 0; i < 7; i++) mbar_init(bars + 8 * i, 1);
                asm volatile("fence.mbarrier_init.release.cluster;" ::: "memory");
                #pragma unroll 1
                for (int kb = 0; kb < 7; kb++) {
                    const uint32_t st = sb + slot_x(kb), bar = bars + 8 * (B_FULLX + kb);
                    mbar_expect(bar, 16384);
                    tma3d(st, &tm_x, krot(kb), 0, tb * 64, bar); tma3d(st + 8192, &tm_x, krot(kb), 1, tb * 64, bar);
                }
                #pragma unroll
                for (int i = 7; i < B_DONE1; i++) mbar_init(bars + 8 * i, 1);
                asm volatile("fence.mbarrier_init.release.cluster;" ::: "memory");
            }
            named_arrive(0, 384);
            #pragma unroll 1
            for (int kb = 0; kb < 7; kb++) {
                if (kb == 6) { named_sync(4, 64); mbar_wait(bars + 8 * B_DONEX, 0); }
                if (elect()) {
                    const uint32_t st = sb + slot_kv(kb), bar = bars + 8 * (B_FULLKV + kb);
                    mbar_expect(bar, 16384);
                    #pragma unroll
                    for (int i = 0; i < 2; i++) {
                        const int n = 2 * kb + i;
                        tma2d(st + i * 8192, &tm_wqkv, (n < 7 ? 448 : 896) + wcol, krot(n < 7 ? n : n - 7), bar);
                    }
                }
            }
            if (elect()) {
                mbar_expect(bars + 8 * B_FQ, 32768);
                mbar_expect(bars + 8 * (B_FQ + 1), 24576);
                #pragma unroll 1
                for (int i = 0; i < 7; i++) tma2d(sb + SM_QO + i * 8192, &tm_wqkv, wcol, krot(i), bars + 8 * (B_FQ + (i >> 2)));
                mbar_expect(bars + 8 * B_FULLWO, 512 * 112 * 2);
            }
            #pragma unroll 1
            for (int i = 0; i < 7; i++) {
                const int kb = ((q & 1 ? WO_ORD1 : WO_ORD0) >> (4 * i)) & 7;
                if (kb < 5) mbar_wait(bars + 8 * (B_DONE1 + kb), 0);
                if (i == WO_HOLD) { mbar_wait(bars + 8 * (B_HALO + 2), 0); mbar_wait(bars + 8 * (B_HALO + 3), 0); }
                if (elect()) {
                    tma2d(sb + slot_wo(kb), &tm_wo64, c64, kb * 64, bars + 8 * B_FULLWO);
                    tma2d(sb + slot_wo(kb) + 8192, &tm_wo48, c48, kb * 64, bars + 8 * B_FULLWO);
                }
            }
            if (XR_HOLD) { mbar_wait(bars + 8 * (B_HALO + 2), 0); mbar_wait(bars + 8 * (B_HALO + 3), 0); }
            if (elect()) {
                tma2d(sb + SM_H, &tm_xr64, c64, tt2 * 64, bars + 8 * B_FULLWO);
                tma2d(sb + SM_H + 8192, &tm_xr48, c48, tt2 * 64, bars + 8 * B_FULLWO);
            }
            if (smem_u32(smem_raw) != SB) __trap();
            const uint32_t ep = ld_volatile(&sc->epoch[slot]) + 1;
            mbar_wait(bars + 8 * B_DONEQ, 0);
            {
                uint32_t issued = 0;
                while (issued != 0x01010101u) {
                    uint32_t m = __ballot_sync(0xffffffffu, ld_relaxed(sc->hint_o + (tt2 * 32 + lane) * 2) == ep);
                    m &= m >> 4; m &= m >> 2; m &= m >> 1; m &= 0x01010101u & ~issued;
                    if ((m >> lane) & 1) {
                        const uint32_t bar = bars + 8 * B_RAW + lane;
                        mbar_expect(bar, 14336);
                        bulk_ld(sb + SM_QO + lane * 1792, sc->o + tt2 * 14336 + lane * 448, 14336, bar);
                    }
                    issued |= m;
                }
                __syncwarp();
            }
            if (lane == 0) STAMP(20);
            mbar_wait(bars + 8 * (B_DONEO + 3), 0);
            if (has_b1) {
                mix_producer_b<32>(TSVAL 0, sc->hint_h + q * 64, ep, sc->hn + q * 32 * 3584, lane);
                mbar_wait(bars + 8 * (B_DONE + 31), 0);
            }
            mix_producer_b<28>(TSVAL has_b1, sc->hint_u + q * 64, ep, sc->u + q * 28 * 3584, lane);
        }
    }
}

typedef CUresult (*EncodeFn)(CUtensorMap*, CUtensorMapDataType, cuuint32_t, void*, const cuuint64_t*, const cuuint64_t*, const cuuint32_t*,
                             const cuuint32_t*, CUtensorMapInterleave, CUtensorMapSwizzle, CUtensorMapL2promotion, CUtensorMapFloatOOBfill);

void make_map(EncodeFn fn, CUtensorMap* tm, const void* ptr, int rank, const cuuint64_t* dims, const cuuint64_t* strides, const cuuint32_t* box, CUtensorMapSwizzle sw) {
    cuuint32_t es[3] = {1, 1, 1};
    fn(tm, CU_TENSOR_MAP_DATA_TYPE_BFLOAT16, rank, const_cast<void*>(ptr), dims, strides, box, es, CU_TENSOR_MAP_INTERLEAVE_NONE, sw,
       CU_TENSOR_MAP_L2_PROMOTION_NONE, CU_TENSOR_MAP_FLOAT_OOB_FILL_NONE);
}

}

extern "C" void kernel_launch(void* const* d_in, const int* in_sizes, int n_in, void* d_out, int out_size) {
    const __nv_bfloat16* x = (const __nv_bfloat16*)d_in[0];
    const __nv_bfloat16* wqkv = (const __nv_bfloat16*)d_in[1];
    const __nv_bfloat16* wo = (const __nv_bfloat16*)d_in[2];
    const __nv_bfloat16* w1 = (const __nv_bfloat16*)d_in[4];
    const __nv_bfloat16* b1 = (const __nv_bfloat16*)d_in[5];
    const __nv_bfloat16* w2 = (const __nv_bfloat16*)d_in[6];
    const __nv_bfloat16* b2 = (const __nv_bfloat16*)d_in[7];

    void* fnp = nullptr; cudaDriverEntryPointQueryResult qr;
    cudaGetDriverEntryPoint("cuTensorMapEncodeTiled", &fnp, cudaEnableDefault, &qr);
    EncodeFn fn = (EncodeFn)fnp;
    CUtensorMap tx, twqkv, two64, two48, tw1, tw2, txr64, txr48, tout64, tout48;
    { cuuint64_t d[3] = {448, 2, 1024}, s[2] = {896, 1792}; cuuint32_t b[3] = {64, 1, 64}; make_map(fn, &tx, x, 3, d, s, b, CU_TENSOR_MAP_SWIZZLE_128B); }
    { cuuint64_t d[2] = {1344, 448}, s[1] = {2688}; cuuint32_t b[2] = {64, 64}; make_map(fn, &twqkv, wqkv, 2, d, s, b, CU_TENSOR_MAP_SWIZZLE_128B); }
    { cuuint64_t d[2] = {448, 448}, s[1] = {896}; cuuint32_t b[2] = {64, 64}; make_map(fn, &two64, wo, 2, d, s, b, CU_TENSOR_MAP_SWIZZLE_128B); }
    { cuuint64_t d[2] = {448, 448}, s[1] = {896}; cuuint32_t b[2] = {48, 64}; make_map(fn, &two48, wo, 2, d, s, b, CU_TENSOR_MAP_SWIZZLE_128B); }
    { cuuint64_t d[3] = {1792, 2, 1024}, s[2] = {3584, 7168}; cuuint32_t b[3] = {64, 1, 64}; make_map(fn, &tw1, w1, 3, d, s, b, CU_TENSOR_MAP_SWIZZLE_128B); }
    { cuuint64_t d[2] = {2048, 1792}, s[1] = {4096}; cuuint32_t b[2] = {64, 128}; make_map(fn, &tw2, w2, 2, d, s, b, CU_TENSOR_MAP_SWIZZLE_128B); }
    { cuuint64_t d[2] = {448, 2048}, s[1] = {896}; cuuint32_t b[2] = {64, 64}; make_map(fn, &txr64, x, 2, d, s, b, CU_TENSOR_MAP_SWIZZLE_128B); }
    { cuuint64_t d[2] = {448, 2048}, s[1] = {896}; cuuint32_t b[2] = {48, 64}; make_map(fn, &txr48, x, 2, d, s, b, CU_TENSOR_MAP_SWIZZLE_128B); }
    { cuuint64_t d[2] = {448, 2048}, s[1] = {896}; cuuint32_t b[2] = {64, 16}; make_map(fn, &tout64, d_out, 2, d, s, b, CU_TENSOR_MAP_SWIZZLE_128B); }
    { cuuint64_t d[2] = {448, 2048}, s[1] = {896}; cuuint32_t b[2] = {48, 16}; make_map(fn, &tout48, d_out, 2, d, s, b, CU_TENSOR_MAP_SWIZZLE_128B); }

    void* scv = nullptr;
    cudaGetSymbolAddress(&scv, g_scratch);
    Scratch* scp = (Scratch*)scv;
    int dev = 0, sms = 0;
    cudaGetDevice(&dev);
    cudaDeviceGetAttribute(&sms, cudaDevAttrMultiProcessorCount, dev);
    if (sms == 132) {
        cudaFuncSetAttribute(fused_kernel<true>, cudaFuncAttributeMaxDynamicSharedMemorySize, SM_TOTAL);
        fused_kernel<true><<<132, 384, SM_TOTAL>>>(scp, wo, w1, b1, w2, b2, tx, twqkv, two64, two48, tw1, tw2, txr64, txr48, tout64, tout48);
    } else {
        cudaFuncSetAttribute(fused_kernel<false>, cudaFuncAttributeMaxDynamicSharedMemorySize, SM_TOTAL);
        fused_kernel<false><<<132, 384, SM_TOTAL>>>(scp, wo, w1, b1, w2, b2, tx, twqkv, two64, two48, tw1, tw2, txr64, txr48, tout64, tout48);
    }
}
```

```cpp
#include <cuda_runtime.h>
#include <cuda_bf16.h>
#include <cuda.h>
#include <stdint.h>

namespace {

constexpr int D_ = 448;
constexpr float LN_EPS = 1e-5f;
constexpr float LOG2E_SCALE = 0.1889822365046136f * 1.4426950408889634f;

struct Tiles {
    uint32_t o[32 * 57344 / 4];
    uint32_t hn[4 * 32 * 14336 / 4];
    uint32_t u[4 * 28 * 14336 / 4];
};
struct Scratch {
    Tiles tiles[2];
    uint4 halo[128 * 2 * 2 * 3 * 32];
    uint4 stats[32 * 4 * 64];
    uint4 hint_kv[128 * 2 * 2 * 2];
    uint4 hint_o[32 * 32 * 2];
    uint4 hint_h[4 * 32 * 2];
    uint4 hint_u[4 * 32 * 2];
    uint32_t epoch[160];
    uint32_t clean[4];
};
__device__ __align__(1024) Scratch g_scratch;
#define STAMP(i) do {} while (0)
#define FST(i) do {} while (0)
#define TSARG
#define TSVAL

constexpr uint32_t SB = 1024;
constexpr int SM_SLOT = 16384;
__device__ __forceinline__ constexpr uint32_t slot_x(int kb) { return (kb ? 6 + kb : 0) * SM_SLOT; }
__device__ __forceinline__ constexpr uint32_t slot_kv(int kb) { return (kb < 5 ? 2 + kb : 6 - kb) * SM_SLOT; }
__device__ __forceinline__ constexpr uint32_t slot_wo(int kb) { return (kb < 6 ? 2 + kb : 12) * SM_SLOT; }
constexpr int SM_QO = 8 * SM_SLOT;
constexpr int SM_HALOK = SM_QO + 57344, SM_HALOV = 1 * SM_SLOT;
constexpr int NA_SLOTS = 6, NB_SLOTS = 8;
constexpr int SM_ARING = 0;
constexpr int SM_BRING = NA_SLOTS * 16384;
constexpr int SM_H = 212992;
constexpr int SM_MISC = 229376;
constexpr int SM_BAR = 231424;
constexpr int SM_TOTAL = 232448;
constexpr int B_FULLX = 0;
constexpr int B_FULLKV = 7;
constexpr int B_FQ = 14;
constexpr int B_DONE1 = 16;
constexpr int B_DONEX = 23;
constexpr int B_DONEQ = 24;
constexpr int B_DONEO = 25;
constexpr int B_FULLO = 29;
constexpr int B_FULLWO = 33;
constexpr int B_END = 34;
constexpr int B_HALO = 35;
constexpr int B_FULLA = 39;
constexpr int B_FULLB = 55;
constexpr int B_DONE = 87;
constexpr int B_RAW = 119;
constexpr int B_CLR = 127;

constexpr long long WD_CLKS = 2000000000ll;

template<int N> struct Int { static constexpr int value = N; };
template<int A, int B, class F> __device__ __forceinline__ void static_for(F&& f) { if constexpr (A < B) { f(Int<A>()); static_for<A + 1, B>(f); } }

__device__ __forceinline__ uint32_t smem_u32(const void* p) { return (uint32_t)__cvta_generic_to_shared(p); }
__device__ __forceinline__ void mbar_init(uint32_t bar, uint32_t cnt) { asm volatile("mbarrier.init.shared::cta.b64 [%0], %1;" :: "r"(bar), "r"(cnt) : "memory"); }
__device__ __forceinline__ void mbar_expect(uint32_t bar, uint32_t bytes) { asm volatile("mbarrier.arrive.expect_tx.shared::cta.b64 _, [%0], %1;" :: "r"(bar), "r"(bytes) : "memory"); }
__device__ __forceinline__ void mbar_arrive(uint32_t bar) { asm volatile("mbarrier.arrive.shared::cta.b64 _, [%0];" :: "r"(bar) : "memory"); }
__device__ __forceinline__ bool mbar_try(uint32_t bar, uint32_t parity) {
    uint32_t ok;
    asm volatile("{\n.reg .pred p;\nmbarrier.try_wait.parity.shared::cta.b64 p, [%1], %2;\nselp.u32 %0, 1, 0, p;\n}" : "=r"(ok) : "r"(bar), "r"(parity) : "memory");
    return ok;
}
__device__ __forceinline__ void mbar_wait(uint32_t bar, uint32_t parity) {
    asm volatile("{\n.reg .pred p;\n"
                 "WAIT_LOOP:\n"
                 "mbarrier.try_wait.parity.shared::cta.b64 p, [%0], %1;\n"
                 "@!p bra WAIT_LOOP;\n}" :: "r"(bar), "r"(parity) : "memory");
}
__device__ __forceinline__ void mbar_wait_wd(uint32_t bar, uint32_t parity) {
    const long long t0 = clock64();
    while (!mbar_try(bar, parity)) { if (clock64() - t0 > WD_CLKS) __trap(); }
}
__device__ __forceinline__ bool elect() { uint32_t p; asm volatile("{\n.reg .pred P;\nelect.sync _|P, 0xffffffff;\nselp.u32 %0, 1, 0, P;\n}" : "=r"(p)); return p; }
__device__ __forceinline__ void tma2d(uint32_t dst, const CUtensorMap* tm, int c0, int c1, uint32_t bar) {
    asm volatile("cp.async.bulk.tensor.2d.shared::cluster.global.mbarrier::complete_tx::bytes [%0], [%1, {%3, %4}], [%2];" :: "r"(dst), "l"(tm), "r"(bar), "r"(c0), "r"(c1) : "memory");
}
__device__ __forceinline__ void tma3d(uint32_t dst, const CUtensorMap* tm, int c0, int c1, int c2, uint32_t bar) {
    asm volatile("cp.async.bulk.tensor.3d.shared::cluster.global.mbarrier::complete_tx::bytes [%0], [%1, {%3, %4, %5}], [%2];" :: "r"(dst), "l"(tm), "r"(bar), "r"(c0), "r"(c1), "r"(c2) : "memory");
}
__device__ __forceinline__ void tma2d_store(const CUtensorMap* tm, int c0, int c1, uint32_t src) {
    asm volatile("cp.async.bulk.tensor.2d.global.shared::cta.bulk_group [%0, {%2, %3}], [%1];" :: "l"(tm), "r"(src), "r"(c0), "r"(c1) : "memory");
}
__device__ __forceinline__ void bulk_ld(uint32_t dst, const void* src, uint32_t bytes, uint32_t bar) {
    asm volatile("cp.async.bulk.shared::cluster.global.mbarrier::complete_tx::bytes [%0], [%1], %2, [%3];" :: "r"(dst), "l"(src), "r"(bytes), "r"(bar) : "memory");
}
__device__ __forceinline__ void bulk_prefetch(const void* src, uint32_t bytes) { asm volatile("cp.async.bulk.prefetch.L2.global [%0], %1;" :: "l"(src), "r"(bytes) : "memory"); }
__device__ __forceinline__ void fence_async_smem() { asm volatile("fence.proxy.async.shared::cta;" ::: "memory"); }
__device__ __forceinline__ uint32_t ld_acquire(const void* p) { uint32_t v; asm volatile("ld.acquire.gpu.global.u32 %0, [%1];" : "=r"(v) : "l"(p) : "memory"); return v; }
__device__ __forceinline__ void st_release(void* p, uint32_t v) { asm volatile("st.release.gpu.global.u32 [%0], %1;" :: "l"(p), "r"(v) : "memory"); }
__device__ __forceinline__ uint32_t ld_relaxed(const void* p) { uint32_t v; asm volatile("ld.relaxed.gpu.global.u32 %0, [%1];" : "=r"(v) : "l"(p) : "memory"); return v; }
__device__ __forceinline__ uint4 ld_relaxed4(const uint4* p) {
    uint4 v;
    asm volatile("{\n.reg .b128 t;\n.reg .b64 a, b;\nld.relaxed.gpu.global.b128 t, [%4];\nmov.b128 {a, b}, t;\nmov.b64 {%0, %1}, a;\nmov.b64 {%2, %3}, b;\n}" : "=r"(v.x), "=r"(v.y), "=r"(v.z), "=r"(v.w) : "l"(p) : "memory");
    return v;
}
__device__ __forceinline__ void st_relaxed4(uint4* p, uint32_t a, uint32_t b, uint32_t c, uint32_t d) {
    asm volatile("{\n.reg .b128 t;\n.reg .b64 a, b;\nmov.b64 a, {%1, %2};\nmov.b64 b, {%3, %4};\nmov.b128 t, {a, b};\nst.relaxed.gpu.global.b128 [%0], t;\n}" :: "l"(p), "r"(a), "r"(b), "r"(c), "r"(d) : "memory");
}
__device__ __forceinline__ uint32_t ld_volatile(const uint32_t* p) { uint32_t v; asm volatile("ld.volatile.global.u32 %0, [%1];" : "=r"(v) : "l"(p) : "memory"); return v; }
__device__ __forceinline__ void named_arrive(int id, int n) { asm volatile("bar.arrive %0, %1;" :: "r"(id), "r"(n) : "memory"); }
__device__ __forceinline__ void named_sync(int id, int n) { asm volatile("bar.sync %0, %1;" :: "r"(id), "r"(n) : "memory"); }
__device__ __forceinline__ void wg_fence() { asm volatile("wgmma.fence.sync.aligned;" ::: "memory"); }
__device__ __forceinline__ void wg_commit() { asm volatile("wgmma.commit_group.sync.aligned;" ::: "memory"); }
template<int N> __device__ __forceinline__ void wg_wait() { asm volatile("wgmma.wait_group.sync.aligned %0;" :: "n"(N) : "memory"); }
template<int N> __device__ __forceinline__ void reg_fence(float (&d)[N]) {
    #pragma unroll
    for (int i = 0; i < N; i++) asm volatile("" : "+f"(d[i]) :: "memory");
}
__device__ __forceinline__ constexpr uint64_t mkdesc(uint32_t addr, uint32_t lbo, uint32_t sbo, uint32_t sw) {
    return (uint64_t)((addr & 0x3FFFF) >> 4) | ((uint64_t)(lbo >> 4) << 16) | ((uint64_t)(sbo >> 4) << 32) | ((uint64_t)sw << 62);
}
__device__ __forceinline__ void ldsm4(uint32_t (&r)[4], uint32_t addr) {
    asm volatile("ldmatrix.sync.aligned.m8n8.x4.shared.b16 {%0,%1,%2,%3}, [%4];" : "=r"(r[0]), "=r"(r[1]), "=r"(r[2]), "=r"(r[3]) : "r"(addr) : "memory");
}
__device__ __forceinline__ void stsm4(uint32_t addr, uint32_t r0, uint32_t r1, uint32_t r2, uint32_t r3) {
    asm volatile("stmatrix.sync.aligned.m8n8.x4.shared.b16 [%0], {%1,%2,%3,%4};" :: "r"(addr), "r"(r0), "r"(r1), "r"(r2), "r"(r3) : "memory");
}
__device__ __forceinline__ uint32_t movtrans(uint32_t a) { uint32_t d; asm volatile("movmatrix.sync.aligned.m8n8.trans.b16 %0, %1;" : "=r"(d) : "r"(a)); return d; }
__device__ __forceinline__ uint32_t pack_bf16(float lo, float hi) { uint32_t r; asm("cvt.rn.bf16x2.f32 %0, %1, %2;" : "=r"(r) : "f"(hi), "f"(lo)); return r; }
__device__ __forceinline__ void sub_bf16x2(uint32_t& a, uint32_t b) { asm volatile("sub.rn.bf16x2 %0, %0, %1;" : "+r"(a) : "r"(b)); }
__device__ __forceinline__ float bf_lo(uint32_t v) { return __uint_as_float(v << 16); }
__device__ __forceinline__ float bf_hi(uint32_t v) { return __uint_as_float(v & 0xffff0000u); }
__device__ __forceinline__ void mma16816(float (&c)[4], uint32_t a0, uint32_t a1, uint32_t a2, uint32_t a3, uint32_t b0, uint32_t b1) {
    asm volatile("mma.sync.aligned.m16n8k16.row.col.f32.bf16.bf16.f32 {%0,%1,%2,%3}, {%4,%5,%6,%7}, {%8,%9}, {%0,%1,%2,%3};"
        : "+f"(c[0]), "+f"(c[1]), "+f"(c[2]), "+f"(c[3]) : "r"(a0), "r"(a1), "r"(a2), "r"(a3), "r"(b0), "r"(b1));
}
__device__ __forceinline__ void mma1688(float (&c)[4], uint32_t a0, uint32_t a1, uint32_t b0) {
    asm volatile("mma.sync.aligned.m16n8k8.row.col.f32.bf16.bf16.f32 {%0,%1,%2,%3}, {%4,%5}, {%6}, {%0,%1,%2,%3};"
        : "+f"(c[0]), "+f"(c[1]), "+f"(c[2]), "+f"(c[3]) : "r"(a0), "r"(a1), "r"(b0));
}
__device__ __forceinline__ float quad_sum(float v) { v += __shfl_xor_sync(0xffffffffu, v, 1); v += __shfl_xor_sync(0xffffffffu, v, 2); return v; }
__device__ __forceinline__ float quad_max(float v) { v = fmaxf(v, __shfl_xor_sync(0xffffffffu, v, 1)); v = fmaxf(v, __shfl_xor_sync(0xffffffffu, v, 2)); return v; }
__device__ __forceinline__ float ex2(float x) { float y; asm("ex2.approx.ftz.f32 %0, %1;" : "=f"(y) : "f"(x)); return y; }
__device__ __forceinline__ float rsqrt_approx(float x) { float y; asm("rsqrt.approx.ftz.f32 %0, %1;" : "=f"(y) : "f"(x)); return y; }
__device__ __forceinline__ float rcp_approx(float x) { float y; asm("rcp.approx.ftz.f32 %0, %1;" : "=f"(y) : "f"(x)); return y; }
__device__ __forceinline__ float gelu_half(float hx) {
    const float z = hx * fmaf(hx * hx, 8.f * 0.044715f * 0.7978845608028654f, 2.f * 0.7978845608028654f);
    float t; asm("tanh.approx.f32 %0, %1;" : "=f"(t) : "f"(z));
    return fmaf(hx, t, hx);
}
__device__ __forceinline__ uint32_t clock32() { uint32_t t; asm volatile("mov.u32 %0, %%clock;" : "=r"(t)); return t; }
#define PF_PACE 400

#define PF_AT 4000
#define NSQ 6
#define HALO_AT 3
#define PF_N 12
#define HINT_H 14
#define HINT_U 14
#define SP_AT 2000
#define SP_N 0
#define WO_HOLD 7
#define A_SCHED 0x322188
#define WO_ORD0 0x4321065
#define WO_ORD1 0x3465210
#define XR_HOLD 0
#define ROT 0
#define SQMIX 0
#define NPIPE 1
#define CL_SPLIT 1000
#define CL_AT 600
#define WARM 1
#define WARM_AT 300
#define HINT_O 0
template<int TB> __device__ __forceinline__ void wgmma_rs56(float (&d)[28], const uint32_t (&a)[4], uint64_t db, int sc) {
    asm volatile("{\n.reg .pred p;\nsetp.ne.b32 p, %33, 0;\n"
        "wgmma.mma_async.sync.aligned.m64n56k16.f32.bf16.bf16 {%0, %1, %2, %3, %4, %5, %6, %7, %8, %9, %10, %11, %12, %13, %14, %15, %16, %17, %18, %19, %20, %21, %22, %23, %24, %25, %26, %27}, {%28, %29, %30, %31}, %32, p, 1, 1, %34;\n}\n"
        : "+f"(d[0]), "+f"(d[1]), "+f"(d[2]), "+f"(d[3]), "+f"(d[4]), "+f"(d[5]), "+f"(d[6]), "+f"(d[7]), "+f"(d[8]), "+f"(d[9]), "+f"(d[10]), "+f"(d[11]), "+f"(d[12]), "+f"(d[13]), "+f"(d[14]), "+f"(d[15]), "+f"(d[16]), "+f"(d[17]), "+f"(d[18]), "+f"(d[19]), "+f"(d[20]), "+f"(d[21]), "+f"(d[22]), "+f"(d[23]), "+f"(d[24]), "+f"(d[25]), "+f"(d[26]), "+f"(d[27])
        : "r"(a[0]), "r"(a[1]), "r"(a[2]), "r"(a[3]), "l"(db), "r"(sc), "n"(TB));
}

template<int TA, int TB> __device__ __forceinline__ void wgmma_ss112(float (&d)[56], uint64_t da, uint64_t db, int sc) {
    asm volatile("{\n.reg .pred p;\nsetp.ne.b32 p, %58, 0;\n"
        "wgmma.mma_async.sync.aligned.m64n112k16.f32.bf16.bf16 {%0, %1, %2, %3, %4, %5, %6, %7, %8, %9, %10, %11, %12, %13, %14, %15, %16, %17, %18, %19, %20, %21, %22, %23, %24, %25, %26, %27, %28, %29, %30, %31, %32, %33, %34, %35, %36, %37, %38, %39, %40, %41, %42, %43, %44, %45, %46, %47, %48, %49, %50, %51, %52, %53, %54, %55}, %56, %57, p, 1, 1, %59, %60;\n}\n"
        : "+f"(d[0]), "+f"(d[1]), "+f"(d[2]), "+f"(d[3]), "+f"(d[4]), "+f"(d[5]), "+f"(d[6]), "+f"(d[7]), "+f"(d[8]), "+f"(d[9]), "+f"(d[10]), "+f"(d[11]), "+f"(d[12]), "+f"(d[13]), "+f"(d[14]), "+f"(d[15]), "+f"(d[16]), "+f"(d[17]), "+f"(d[18]), "+f"(d[19]), "+f"(d[20]), "+f"(d[21]), "+f"(d[22]), "+f"(d[23]), "+f"(d[24]), "+f"(d[25]), "+f"(d[26]), "+f"(d[27]), "+f"(d[28]), "+f"(d[29]), "+f"(d[30]), "+f"(d[31]), "+f"(d[32]), "+f"(d[33]), "+f"(d[34]), "+f"(d[35]), "+f"(d[36]), "+f"(d[37]), "+f"(d[38]), "+f"(d[39]), "+f"(d[40]), "+f"(d[41]), "+f"(d[42]), "+f"(d[43]), "+f"(d[44]), "+f"(d[45]), "+f"(d[46]), "+f"(d[47]), "+f"(d[48]), "+f"(d[49]), "+f"(d[50]), "+f"(d[51]), "+f"(d[52]), "+f"(d[53]), "+f"(d[54]), "+f"(d[55])
        : "l"(da), "l"(db), "r"(sc), "n"(TA), "n"(TB));
}

template<int NKB, bool PERM>
__device__ __forceinline__ void mix_mainloop(float (&acc)[56], uint32_t par, bool leader) {
    constexpr uint32_t sb = SB, bars = sb + SM_BAR;
    int bslot = 0, aslot = 0;
    reg_fence(acc);
    #pragma unroll 1
    for (int i = 0; i < NKB / 2; i++) {
        mbar_wait(bars + 8 * (B_FULLA + i), par);
        const uint64_t adesc = mkdesc(sb + SM_ARING, 8192, 1024, 1) + (uint32_t)(aslot * 1024);
        aslot = aslot == NA_SLOTS - 1 ? 0 : aslot + 1;
        #pragma unroll
        for (int jj = 0; jj < 2; jj++) {
            const int j = 2 * i + jj;
            mbar_wait(bars + 8 * (B_FULLB + j), par);
            const uint64_t bdesc = mkdesc(sb + SM_BRING, 1792, 128, 0) + (uint32_t)(bslot * 896);
            bslot = bslot == NB_SLOTS - 1 ? 0 : bslot + 1;
            wg_fence();
            #pragma unroll
            for (int s = 0; s < 4; s++) {
                const uint32_t aoff = PERM ? (s & 1) * 8192 + (jj * 32 + (s >> 1) * 16) * 128 : jj * 8192 + s * 2048;
                wgmma_ss112<1, 1>(acc, adesc + (aoff >> 4), bdesc + s * 224, 1);
            }
            wg_commit();
            wg_wait<1>();
            if (j > 0 && leader) mbar_arrive(bars + 8 * (B_DONE + j - 1));
        }
    }
    wg_wait<0>();
    reg_fence(acc);
    if (leader) mbar_arrive(bars + 8 * (B_DONE + NKB - 1));
}

constexpr uint32_t EMPTY = 0xFFFFFFFFu;
__device__ __forceinline__ void post_hint(uint4* p, uint32_t ep, int lane) { if (lane < 2) st_relaxed4(p + lane, ep, ep, ep, ep); }
__device__ __forceinline__ void post_hint_wg(uint4* p, uint32_t ep, int w, int lane) {
    if (w < 3) named_arrive(5, 128); else { named_sync(5, 128); post_hint(p, ep, lane); }
}

template<int NKB>
__device__ __forceinline__ void mix_producer_b(TSARG uint32_t par, const uint4* hints, uint32_t ep, const uint32_t* src, int lane) {
    constexpr uint32_t sb = SB, bars = sb + SM_BAR;
    uint32_t ready = 0;
    #pragma unroll 1
    for (int j = 0; j < NKB; j++) {
        while (!((ready >> j) & 1)) ready = __ballot_sync(0xffffffffu, ld_relaxed(hints + 2 * lane) == ep);
        if (j >= NB_SLOTS) mbar_wait(bars + 8 * (B_DONE + j - NB_SLOTS), par);
        if (j == 0 && lane == 0) STAMP(NKB == 32 ? 29 : 30);
        if (j == 7 && lane == 0) STAMP(NKB == 32 ? 35 : 36);
        if (elect()) {
            mbar_expect(bars + 8 * (B_RAW + (j & 7)), 14336);
            bulk_ld(sb + SM_BRING + (j & 7) * 14336, src + j * 3584, 14336, bars + 8 * (B_RAW + (j & 7)));
        }
    }
}
__device__ __forceinline__ void check_tiles(TSARG int n, int w, int lane, uint32_t& ph, uint32_t dst, const uint32_t* src, int full) {
    constexpr uint32_t bars = SB + SM_BAR;
    #pragma unroll 1
    for (int j = w; j < n; j += 4) {
        const uint32_t raw = bars + 8 * (B_RAW + (j & 7)), d = dst + (j & 7) * 14336, a = d + lane * 128 + (lane & 3) * 32 + (lane >> 2) * 4;
        bool bad;
        do {
            mbar_wait(raw, (ph >> (j & 4)) & 1);
            ph ^= 1u << (j & 4);
            if (j == 0 && lane == 0) STAMP(n == 4 ? 6 : n == 32 ? 31 : 32);
            uint32_t v0, v1, v2, v3;
            asm volatile("ld.shared.u32 %0, [%4];\nld.shared.u32 %1, [%4+4096];\nld.shared.u32 %2, [%4+8192];\nld.shared.u32 %3, [%4+10240];"
                         : "=r"(v0), "=r"(v1), "=r"(v2), "=r"(v3) : "r"(a) : "memory");
            bad = __any_sync(0xffffffffu, max(max(v0, v1), max(v2, v3)) == EMPTY);
            if (elect() && bad) {
                mbar_expect(raw, 14336); bulk_ld(d, src + j * 3584, 14336, raw);
            }
        } while (bad);
        if (lane == 0) mbar_arrive(bars + 8 * (full + j));
    }
}

__device__ __forceinline__ uint32_t hcol(uint32_t a, int jp) { return (a ^ ((jp & 3) << 5)) + (jp >> 2) * 8192; }

template<bool USE_SMID>
__global__ void __launch_bounds__(384, 1)
fused_kernel(Scratch* __restrict__ sc, const __nv_bfloat16* __restrict__ wo,
             const __nv_bfloat16* __restrict__ w1, const __nv_bfloat16* __restrict__ b1,
             const __nv_bfloat16* __restrict__ w2, const __nv_bfloat16* __restrict__ b2,
             const __grid_constant__ CUtensorMap tm_x, const __grid_constant__ CUtensorMap tm_wqkv,
             const __grid_constant__ CUtensorMap tm_wo64, const __grid_constant__ CUtensorMap tm_wo48,
             const __grid_constant__ CUtensorMap tm_w1, const __grid_constant__ CUtensorMap tm_w2,
             const __grid_constant__ CUtensorMap tm_xr64, const __grid_constant__ CUtensorMap tm_xr48,
             const __grid_constant__ CUtensorMap tm_out64, const __grid_constant__ CUtensorMap tm_out48) {
    extern __shared__ __align__(1024) uint8_t smem_raw[];
    constexpr uint32_t sb = SB;
    constexpr uint32_t bars = sb + SM_BAR;
    const int tid = threadIdx.x, lane = tid & 31;
    const int warp = __shfl_sync(0xffffffffu, tid >> 5, 0);
    int slot;
    if (USE_SMID) {
        asm("{\n.reg .u32 s, t, u, d, a, b, c;\n.reg .pred p, r;\n"
            "mov.u32 s, %%smid;\nshr.u32 t, s, 1;\nsub.u32 u, t, 32;\nmul.lo.u32 d, u, 37;\nshr.u32 d, d, 8;\n"
            "and.b32 a, t, 7;\nshl.b32 a, a, 3;\nshr.u32 c, t, 3;\nadd.u32 a, a, c;\n"
            "mad.lo.u32 b, d, -55, 12;\nshl.b32 c, u, 3;\nadd.u32 b, b, c;\n"
            "setp.lt.u32 p, t, 32;\nselp.u32 a, a, b, p;\n"
            "setp.lt.u32 r, t, 64;\nselp.u32 c, 56, 0, r;\nsub.u32 c, t, c;\nsetp.lt.u32 p, t, 60;\nselp.u32 a, a, c, p;\n"
            "and.b32 s, s, 1;\nshl.b32 a, a, 1;\nadd.u32 %0, a, s;\n}" : "=r"(slot));
    } else slot = blockIdx.x;
    const int G = slot >> 4, mi = slot & 15;
    const int tb = 4 * (G >> 1) + (mi >> 2), hp = 2 * (mi & 3) + (G & 1);
    const int wcol = (hp * 56) & ~15;
    if (slot >= 128) {
        const uint32_t ep = ld_volatile(&sc->epoch[slot]) + 1;
        if (warp < 4) {
            #pragma unroll 1
            for (uint32_t e = ld_volatile(&sc->clean[mi]) == ep ? ep + 1 : ep; e != ep + 2; e++) {
                constexpr int NL = sizeof(Tiles) / 512;
                uint4* p = (uint4*)&sc->tiles[e & 1] + (mi * NL + (lane >> 1)) * 8 + (lane & 7);
                if (e != ep) {
                    while (ld_relaxed(sc->hint_h) != ep) __nanosleep(200);
                    __nanosleep(CL_AT);
                }
                #pragma unroll 7
                for (int i = warp; i < NL / 16; i += 4) st_relaxed4(p + i * 128, EMPTY, EMPTY, EMPTY, EMPTY);
                named_sync(1, 128);
                if (tid == 0) st_release(&sc->clean[mi], e);
            }
        }
        if (tid == 128) {
            const long long t0 = clock64();
            while (clock64() - t0 < SP_AT) {}
            #pragma unroll 1
            for (int i = 0; i < 7; i++) bulk_prefetch((const char*)wo + (i * 4 + mi) * 14336, 14336);
            #pragma unroll 1
            for (int i = 0; i < SP_N; i++) bulk_prefetch((const char*)w1 + (i * 4 + mi) * 14336, 14336);
            while (ld_relaxed(sc->hint_u) != ep) { __nanosleep(500); if (clock64() - t0 > WD_CLKS) __trap(); }
            sc->epoch[slot] = ep;
        }
        return;
    }
    const int q = mi & 3, tt2 = 4 * G + (mi >> 2), ft = 4 * (G - 1) + (mi >> 2);
    const bool has_b1 = G > 0;
    const int c64 = 64 * q, c48 = 256 + 48 * q;

    if (warp < 8) {
        if (WARM) {
            const int w = warp & 3, wg = warp >> 2, g = lane >> 2, t = lane & 3;
            if (WARM_AT) { const uint32_t t0 = clock32(); while (clock32() - t0 < WARM_AT) {} __syncwarp(); }
            if (w == 3 && lane < 4) st_relaxed4(sc->hint_kv + ((tb * 8 + hp) * 2 + wg) * 4 + lane, 0, 0, 0, 0);
            post_hint(sc->hint_o + ((2 * tb + (w >> 1)) * 32 + hp * 4 + (w & 1) * 2 + wg) * 2, 0, lane);
            if (wg == 0) {
                if (t < 2) st_relaxed4(sc->stats + tt2 * 256 + q * 64 + 16 * w + g + 8 * t, 0, 0, 0, 0);
                if (w == 3) { post_hint(sc->hint_h + (q * 32 + tt2) * 2, 0, lane); post_hint(sc->hint_u + (q * 32 + (ft & 31)) * 2, 0, lane); }
            }
        }
        named_sync(0, 384);
        asm volatile("setmaxnreg.inc.sync.aligned.u32 232;");
        int tid; asm volatile("mov.u32 %0, %%tid.x;" : "=r"(tid));
        const int lane = tid & 31, warp = __shfl_sync(0xffffffffu, tid >> 5, 0), wg = warp >> 2;
        const uint32_t ep = ld_volatile(&sc->epoch[slot]) + 1;
        Tiles* const tl = &sc->tiles[ep & 1];
        const int w = warp & 3, g = lane >> 2, t = lane & 3;
        const bool leader = (tid & 127) == 0;
        {
            uint32_t a[28][4];
            float accK[28], accV[28], accQ[28];
            const int lrow = 16 * w + (lane & 7) + (lane & 8);
            const uint32_t lbase = sb + wg * 8192 + lrow * 128;
            const uint32_t lx = (lane >> 4) ^ (lane & 7);
            const uint32_t never = gridDim.y - 1;
            const uint32_t wofs = hp & 1;
            auto pin2 = [&](uint32_t x0, uint32_t x1) {
                asm volatile("{\n.reg .pred p;\nsetp.ne.u32 p, %2, 0;\n@p st.shared.v2.b32 [%0], {%0,%1};\n}" :: "r"(x0), "r"(x1), "r"(never) : "memory");
            };
            float cS[2][4] = {}, cA[2][4] = {}, cB[2][4] = {}, q0 = 0.f, q1 = 0.f;
            auto sq = [&](float& acc, uint32_t v) { const float lo = bf_lo(v), hi = bf_hi(v); acc = fmaf(hi, hi, fmaf(lo, lo, acc)); };
            #pragma unroll
            for (int kb = 0; kb < 8; kb++) {
                if (kb < 7) {
                    mbar_wait(bars + 8 * (B_FULLX + kb), 0);
                    if (kb == 0 && tid == 0) STAMP(0);
                    if (kb == 6 && tid == 0) STAMP(25);
                    if (kb == 0) FST(0); if (kb == 2) FST(1); if (kb == 4) FST(2); if (kb == 6) FST(3);
                    #pragma unroll
                    for (int s = 4 * kb; s < 4 * kb + 4; s++) ldsm4(a[s], lbase + slot_x(kb) + ((lx ^ (2 * (s & 3))) << 4));
                }
                if (kb == NPIPE) continue;
                const int kc = kb < NPIPE ? kb : kb - 1;
                #pragma unroll
                for (int s = 4 * kc; s < 4 * kc + 4; s++) {
                    mma16816(cS[s & 1], a[s][0], a[s][1], a[s][2], a[s][3], 0x3F803F80u, 0x3F803F80u);
                    if (kc < NSQ) {
                        mma1688(cA[0], a[s][0], a[s][1], a[s][0]); mma1688(cA[1], a[s][2], a[s][3], a[s][2]);
                        if (SQMIX) { sq(q1, a[s][1]); sq(q1, a[s][3]); }
                        else { mma1688(cB[0], a[s][0], a[s][1], a[s][1]); mma1688(cB[1], a[s][2], a[s][3], a[s][3]); }
                    }
                }
                if (SQMIX && kc < NSQ) pin2(__float_as_uint(q1), 0);
            }
            const float m0 = (cS[0][0] + cS[1][0]) * (1.f / D_), m1 = (cS[0][2] + cS[1][2]) * (1.f / D_);
            const uint32_t mm0 = pack_bf16(m0, m0), mm1 = pack_bf16(m1, m1);
            if (lane == 0) mbar_arrive(bars + 8 * B_DONEX);
            auto center = [&](int s) { sub_bf16x2(a[s][0], mm0); sub_bf16x2(a[s][1], mm1); sub_bf16x2(a[s][2], mm0); sub_bf16x2(a[s][3], mm1); };
            uint32_t Ka[8], Kb[8], Kc[8], Va[8], Vb[7], Vc[8];
            float r0, r1, ls0, ls1;
            uint32_t pm, zero;
            uint32_t* od;
            uint4* oh;
            auto kpack = [&](uint32_t (&k)[8], int j, int c, float r) {
                const uint32_t v = pack_bf16(accK[4 * j + c] * r, accK[4 * j + c + 1] * r);
                if (j == 3) { k[3] = t < 2 ? v : 0u; k[4] = t < 2 ? 0u : v; } else k[j + (j > 3)] = v;
            };
            auto batch = [&](auto c0, auto c1) {
                constexpr int n0 = c0.value, n1 = c1.value;
                wg_fence();
                static_for<n0, n1>([&](auto nc) {
                    constexpr int n = nc.value;
                    if (n == 4) { center(4); center(5); center(6); center(7); wg_fence(); }
                    const uint64_t desc = mkdesc(sb + (n < 56 ? slot_kv(n >> 3) + (n & 7) * 2048 : SM_QO + (n - 56) * 2048), 8192, 1024, 1) + wofs;
                    wgmma_rs56<1>(n < 28 ? accK : n < 56 ? accV : accQ, a[n % 28], desc, n % 28 != 0);
                });
                wg_commit();
                if (n0 > 0) wg_wait<1>();
            };
            auto hand_over = [&](const uint32_t (&v)[8], int kv) {
                if (w < 3) {
                    mbar_wait(bars + 8 * (kv ? B_DONE1 + 5 : B_DONEX), 0);
                    uint4* hs = (uint4*)(smem_raw + (kv ? SM_HALOV : SM_HALOK)) + warp * 64 + lane;
                    hs[0] = make_uint4(v[0], v[1], v[2], v[3]); hs[32] = make_uint4(v[4], v[5], v[6], v[7]);
                } else if (tb < 15) {
                    uint4* hg = sc->halo + ((((tb + 1) * 8 + hp) * 2 + wg) * 2 + kv) * 96 + lane;
                    st_relaxed4(hg, v[0], v[1], v[2], ep); st_relaxed4(hg + 32, v[3], v[4], v[5], ep); st_relaxed4(hg + 64, v[6], v[7], ep, ep);
                    post_hint(sc->hint_kv + ((tb * 8 + hp) * 2 + wg) * 4 + kv * 2, ep, lane);
                }
            };
            auto take_over = [&](uint32_t (&v)[8], int kv) {
                if (w == 0) mbar_wait(bars + 8 * (B_HALO + 2 * kv + wg), 0);
                const uint4* hs = (const uint4*)(smem_raw + (kv ? SM_HALOV : SM_HALOK)) + (w ? warp - 1 : warp + 3) * 64 + lane;
                const uint4 u0 = hs[0], u1 = hs[32];
                v[0] = u0.x; v[1] = u0.y; v[2] = u0.z; v[3] = u0.w; v[4] = u1.x; v[5] = u1.y; v[6] = u1.z; v[7] = u1.w;
            };
            center(0); center(1); center(2); center(3);
            static_for<0, 7>([&](auto pc) {
                constexpr int p = pc.value;
                mbar_wait(bars + 8 * (B_FULLKV + p), 0);
                if (p == 0 && tid == 0) STAMP(26);
                if (p == 3 && tid == 0) STAMP(27);
                FST(4 + p);
                batch(Int<8 * p>(), Int<8 * p + 8>());
                if (p > 0 && leader) mbar_arrive(bars + 8 * (B_DONE1 + p - 1));
                #pragma unroll
                for (int s = 8 * p + 8; s < 8 * p + 16 && s < 28; s++) {
                    if (s >= 4 * NSQ) { sq(q0, a[s][0]); sq(q1, a[s][1]); sq(q0, a[s][2]); sq(q1, a[s][3]); }
                    center(s);
                }
                if (p == 3) {
                    if (t == (g >> 1)) { q0 += (g & 1) ? cA[0][1] + cA[1][1] : cA[0][0] + cA[1][0]; if (!SQMIX) q1 += (g & 1) ? cB[0][3] + cB[1][3] : cB[0][2] + cB[1][2]; }
                    q0 = quad_sum(q0); q1 = quad_sum(q1);
                    r0 = rsqrt_approx(fmaxf(q0 * (1.f / D_) - m0 * m0, 0.f) + LN_EPS); r1 = rsqrt_approx(fmaxf(q1 * (1.f / D_) - m1 * m1, 0.f) + LN_EPS);
                    pin2(__float_as_uint(r0), __float_as_uint(r1));
                }
                if (p == 4) {
                    reg_fence(accK);
                    #pragma unroll
                    for (int j = 0; j < 7; j++) kpack(Kc, j, 2, r1);
                    hand_over(Kc, 0);
                }
                if (p == 5) {
                    #pragma unroll
                    for (int j = 0; j < 7; j++) kpack(Kb, j, 0, r0);
                    #pragma unroll
                    for (int j = 0; j < 8; j += 2) pin2(Kb[j], Kb[j + 1]);
                    ls0 = LOG2E_SCALE * r0; ls1 = LOG2E_SCALE * r1;
                    pm = (2 * t <= g ? 0xFFFFu : 0u) | (2 * t + 1 <= g ? 0xFFFF0000u : 0u);
                    zero = never; asm volatile("" : "+r"(zero));
                    pin2(__float_as_uint(ls0), __float_as_uint(ls1)); pin2(pm, zero);
                }
                if (p == 6) {
                    const int tt = 2 * tb + (w >> 1);
                    od = tl->o + tt * 14336 + (7 * hp) * 256 + (2 * (2 * (w & 1) + wg)) * 32 + lane;
                    oh = sc->hint_o + (tt * 32 + hp * 4 + (w & 1) * 2 + wg) * 2 + (lane & 1);
                    pin2((uint32_t)(uint64_t)od, (uint32_t)((uint64_t)od >> 32));
                    pin2((uint32_t)(uint64_t)oh, (uint32_t)((uint64_t)oh >> 32));
                }
            });
            if (tid == 0) STAMP(1);
            FST(11);
            mbar_wait(bars + 8 * B_FQ, 0);
            batch(Int<56>(), Int<60>());
            reg_fence(accV);
            if (leader) mbar_arrive(bars + 8 * (B_DONE1 + 6));
            if (tid == 0) STAMP(2);
            FST(12);
            #pragma unroll
            for (int j = 0; j < 7; j++) Vc[j] = movtrans(pack_bf16(accV[4 * j + 2] * r1, accV[4 * j + 3] * r1));
            Vc[7] = ep;
            hand_over(Vc, 1);
            if (tid == 96) STAMP(23);
            batch(Int<60>(), Int<66>());
            #pragma unroll
            for (int j = 0; j < 7; j++) {
                Vb[j] = movtrans(pack_bf16(accV[4 * j] * r0, accV[4 * j + 1] * r0));
                Vc[j] |= zero;
            }
            batch(Int<66>(), Int<72>());
            #pragma unroll
            for (int j = 0; j < 7; j++) pin2(Vb[j], Vc[j]);
            mbar_wait(bars + 8 * (B_FQ + 1), 0);
            mbar_wait(bars + 8 * B_CLR, 0);
            FST(13);
            batch(Int<72>(), Int<84>());
            FST(14);
            named_sync(1 + wg, 128);
            take_over(Ka, 0);
            if (tid == 0) STAMP(3);
            wg_wait<0>();
            reg_fence(accQ);
            if (tid == 0) STAMP(4);
            FST(15);
            const bool first = (tb == 0 && w == 0);
            uint32_t pA[2], pB0[2], pB1[2], pC[2], z0[2], z1[2];
            #pragma unroll
            for (int h = 0; h < 2; h++) {
                float sA[4] = {0.f, 0.f, 0.f, 0.f}, sB[4] = {0.f, 0.f, 0.f, 0.f}, sC[4] = {0.f, 0.f, 0.f, 0.f};
                #pragma unroll
                for (int k = 0; k < 2; k++) {
                    const float* qq = accQ + 12 * h + 8 * k;
                    uint32_t a0 = pack_bf16(qq[0], qq[1]), a1 = pack_bf16(qq[2], qq[3]);
                    if (h == 1 && k == 0) { a0 |= zero; a1 |= zero; }
                    const uint32_t a2 = pack_bf16(qq[4], qq[5]), a3 = pack_bf16(qq[6], qq[7]);
                    mma16816(sB, a0, a1, a2, a3, Kb[4 * h + 2 * k], Kb[4 * h + 2 * k + 1]);
                    mma16816(sA, a0, a1, a2, a3, Ka[4 * h + 2 * k], Ka[4 * h + 2 * k + 1]);
                    mma16816(sC, a0, a1, a2, a3, Kc[4 * h + 2 * k], Kc[4 * h + 2 * k + 1]);
                }
                const bool n0 = pm & 1, n1 = (int)pm < 0;
                const float l00 = n0 ? sB[0] : (first ? -INFINITY : sA[0]), l01 = n1 ? sB[1] : (first ? -INFINITY : sA[1]);
                const float l10 = n0 ? sC[2] : sB[2], l11 = n1 ? sC[3] : sB[3];
                const float x0 = -ls0 * quad_max(fmaxf(l00, l01)), x1 = -ls1 * quad_max(fmaxf(l10, l11));
                const float e00 = ex2(fmaf(l00, ls0, x0)), e01 = ex2(fmaf(l01, ls0, x0)), e10 = ex2(fmaf(l10, ls1, x1)), e11 = ex2(fmaf(l11, ls1, x1));
                const float i0 = rcp_approx(quad_sum(e00 + e01)), i1 = rcp_approx(quad_sum(e10 + e11));
                const uint32_t P0 = pack_bf16(e00 * i0, e01 * i0), P1 = pack_bf16(e10 * i1, e11 * i1);
                pB0[h] = P0 & pm; pA[h] = P0 & ~pm; pC[h] = P1 & pm; pB1[h] = P1 & ~pm; z0[h] = P0 & zero; z1[h] = P1 & zero;
            }
            float o[8][4];
            #pragma unroll
            for (int j = 0; j < 8; j++) {
                o[j][0] = o[j][1] = o[j][2] = o[j][3] = 0.f;
                mma16816(o[j], pB0[j >> 2], pB1[j >> 2], z0[j >> 2], pC[j >> 2], Vb[j - (j >> 2)], Vc[j - (j >> 2)]);
            }
            if (tid == 0) STAMP(12);
            FST(16);
            take_over(Va, 1);
            if (HINT_O == 1 && lane < 2) st_relaxed4(oh, ep, ep, ep, ep);
            if (lane == 0) mbar_arrive(bars + 8 * B_DONEQ);
            if (tid == 0) STAMP(16);
            #pragma unroll
            for (int j = 0; j < 8; j++) mma1688(o[j], pA[j >> 2], z1[j >> 2], Va[j - (j >> 2)]);
            #pragma unroll
            for (int j = 0; j < 7; j++) {
                float v[4];
                #pragma unroll
                for (int c = 0; c < 4; c++) v[c] = j < 3 ? o[j][c] : j > 3 ? o[j + 1][c] : (t < 2 ? o[3][c] : o[4][c]);
                od[j * 256] = pack_bf16(v[0], v[1]);
                od[j * 256 + 32] = pack_bf16(v[2], v[3]);
            }
            if (tid == 0) STAMP(5);
            FST(17);
            if (HINT_O == 0 && lane < 2) st_relaxed4(oh, ep, ep, ep, ep);
        }
        if (wg == 1) {
            uint32_t ph = 0;
            check_tiles(TSVAL 4, w, lane, ph, sb + SM_QO, tl->o + tt2 * 14336, B_FULLO);
            if (has_b1) check_tiles(TSVAL 32, w, lane, ph, sb + SM_BRING, tl->hn + q * 32 * 3584, B_FULLB);
            check_tiles(TSVAL 28, w, lane, ph, sb + SM_BRING, tl->u + q * 28 * 3584, B_FULLB);
        } else {
            const uint32_t rb10 = has_b1 ? __ldg((const unsigned short*)b1 + ft * 64 + 16 * w + g) : 0, rb11 = has_b1 ? __ldg((const unsigned short*)b1 + ft * 64 + 16 * w + g + 8) : 0;
            const uint32_t rb20 = __ldg((const unsigned short*)b2 + tt2 * 64 + 16 * w + g), rb21 = __ldg((const unsigned short*)b2 + tt2 * 64 + 16 * w + g + 8);
            {
                float acc[56];
                const int hrow = 32 * (w >> 1) + 2 * ((lane & 7) + (lane & 8)) + (w & 1);
                const uint32_t ha = sb + SM_H + hrow * 128 + (((lane >> 4) ^ (hrow & 7)) << 4);
                mbar_wait(bars + 8 * B_FULLWO, 0);
                #pragma unroll
                for (int jp = 0; jp < 7; jp++) {
                    uint32_t xx[4];
                    ldsm4(xx, hcol(ha, jp));
                    #pragma unroll
                    for (int r = 0; r < 4; r++) { acc[8 * jp + 2 * r] = bf_lo(xx[r]); acc[8 * jp + 2 * r + 1] = bf_hi(xx[r]); }
                }
                reg_fence(acc);
                #pragma unroll
                for (int i = 0; i < 4; i++) {
                    mbar_wait(bars + 8 * (B_FULLO + i), 0);
                    if (i == 0 && tid == 0) STAMP(7);
                    wg_fence();
                    #pragma unroll
                    for (int ss = 0; ss < 7; ss++) {
                        const int s = 7 * i + ss, kb = s >> 2;
                        wgmma_ss112<0, 1>(acc, mkdesc(sb + SM_QO + s * 2048, 1024, 128, 0),
                                          mkdesc(sb + slot_wo(kb) + (s & 3) * 2048, 8192, 1024, 1), 1);
                    }
                    wg_commit();
                    if (i > 0) {
                        wg_wait<1>();
                        if (leader) mbar_arrive(bars + 8 * (B_DONEO + i - 1));
                    }
                }
                wg_wait<0>();
                reg_fence(acc);
                if (leader) mbar_arrive(bars + 8 * (B_DONEO + 3));
                if (tid == 0) STAMP(8);
                float s0 = 0.f, s1 = 0.f, q0 = 0.f, q1 = 0.f, s2 = 0.f, s3 = 0.f, q2 = 0.f, q3 = 0.f;
                #pragma unroll
                for (int j = 0; j < 14; j++) {
                    s0 += acc[4 * j]; s2 += acc[4 * j + 1]; q0 = fmaf(acc[4 * j], acc[4 * j], q0); q2 = fmaf(acc[4 * j + 1], acc[4 * j + 1], q2);
                    s1 += acc[4 * j + 2]; s3 += acc[4 * j + 3]; q1 = fmaf(acc[4 * j + 2], acc[4 * j + 2], q1); q3 = fmaf(acc[4 * j + 3], acc[4 * j + 3], q3);
                }
                s0 = quad_sum(s0 + s2); s1 = quad_sum(s1 + s3); q0 = quad_sum(q0 + q2); q1 = quad_sum(q1 + q3);
                uint4* sp = sc->stats + tt2 * 256 + 16 * w + g;
                if (t < 2) st_relaxed4(sp + q * 64 + 8 * t, __float_as_uint(t ? s1 : s0), ep, __float_as_uint(t ? q1 : q0), ep);
                if (tid == 0) STAMP(9);
                #pragma unroll
                for (int jp = 0; jp < 7; jp++)
                    stsm4(hcol(ha, jp), pack_bf16(acc[8 * jp], acc[8 * jp + 1]), pack_bf16(acc[8 * jp + 2], acc[8 * jp + 3]),
                          pack_bf16(acc[8 * jp + 4], acc[8 * jp + 5]), pack_bf16(acc[8 * jp + 6], acc[8 * jp + 7]));
                {
                    uint4 v0, v1;
                    do {
                        v0 = ld_relaxed4(sp + t * 64); v1 = ld_relaxed4(sp + t * 64 + 8);
                    } while (__any_sync(0xffffffffu, t != q && (v0.y != ep || v0.w != ep || v1.y != ep || v1.w != ep)));
                    if (t != q) { s0 = __uint_as_float(v0.x); q0 = __uint_as_float(v0.z); s1 = __uint_as_float(v1.x); q1 = __uint_as_float(v1.z); }
                }
                if (tid == 0) STAMP(10);
                s0 = quad_sum(s0); s1 = quad_sum(s1); q0 = quad_sum(q0); q1 = quad_sum(q1);
                const float m0 = s0 * (1.f / D_), m1 = s1 * (1.f / D_);
                const float v0 = fmaxf(q0 * (1.f / D_) - m0 * m0, 0.f), v1 = fmaxf(q1 * (1.f / D_) - m1 * m1, 0.f);
                float r0 = rsqrt_approx(v0 + LN_EPS), r1 = rsqrt_approx(v1 + LN_EPS);
                r0 *= 0.5f * rsqrt_approx(fmaf(v0 * r0, r0, LN_EPS)); r1 *= 0.5f * rsqrt_approx(fmaf(v1 * r1, r1, LN_EPS));
                const float c0 = -m0 * r0, c1 = -m1 * r1;
                uint32_t* hd = tl->hn + (q * 32 + tt2) * 3584 + (2 * w) * 448 + lane;
                #pragma unroll
                for (int j = 0; j < 14; j++) {
                    if (j == HINT_H) post_hint_wg(sc->hint_h + (q * 32 + tt2) * 2, ep, w, lane);
                    hd[j * 32] = pack_bf16(fmaf(acc[4 * j], r0, c0), fmaf(acc[4 * j + 1], r0, c0));
                    hd[j * 32 + 448] = pack_bf16(fmaf(acc[4 * j + 2], r1, c1), fmaf(acc[4 * j + 3], r1, c1));
                }
                if (tid == 0) STAMP(11);
                if (HINT_H == 14) post_hint_wg(sc->hint_h + (q * 32 + tt2) * 2, ep, w, lane);
                if (tid == 96) STAMP(33);
            }
            if (has_b1) {
                float acc[56];
                #pragma unroll
                for (int j = 0; j < 56; j++) acc[j] = 0.5f * bf_lo((j & 2) ? rb11 : rb10);
                mix_mainloop<32, true>(acc, 0, leader);
                if (tid == 0) STAMP(14);
                uint32_t* ud = tl->u + (q * 28 + ft) * 3584 + (2 * w) * 448 + lane;
                #pragma unroll
                for (int j = 0; j < 14; j++) {
                    if (j == HINT_U) post_hint_wg(sc->hint_u + (q * 32 + ft) * 2, ep, w, lane);
                    ud[j * 32] = pack_bf16(gelu_half(acc[4 * j]), gelu_half(acc[4 * j + 1]));
                    ud[j * 32 + 448] = pack_bf16(gelu_half(acc[4 * j + 2]), gelu_half(acc[4 * j + 3]));
                }
                if (tid == 0) STAMP(15);
                if (HINT_U == 14) post_hint_wg(sc->hint_u + (q * 32 + ft) * 2, ep, w, lane);
                if (tid == 96) STAMP(34);
            }
            {
                float acc[56];
                const float bb0 = bf_lo(rb20), bb1 = bf_lo(rb21);
                named_sync(1, 128);
                const uint32_t ad = sb + SM_H + (16 * w + (lane & 15)) * 128 + (((lane >> 4) ^ (lane & 7)) << 4);
                #pragma unroll
                for (int jp = 0; jp < 7; jp++) {
                    uint32_t hh[4];
                    ldsm4(hh, hcol(ad, jp));
                    #pragma unroll
                    for (int r = 0; r < 4; r++) { acc[8 * jp + 2 * r] = bf_lo(hh[r]) + ((r & 1) ? bb1 : bb0); acc[8 * jp + 2 * r + 1] = bf_hi(hh[r]) + ((r & 1) ? bb1 : bb0); }
                }
                mix_mainloop<28, false>(acc, has_b1, leader);
                if (leader) mbar_arrive(bars + 8 * B_END);
                if (tid == 0) STAMP(18);
                #pragma unroll
                for (int jp = 0; jp < 7; jp++)
                    stsm4(hcol(ad, jp), pack_bf16(acc[8 * jp], acc[8 * jp + 1]), pack_bf16(acc[8 * jp + 2], acc[8 * jp + 3]),
                          pack_bf16(acc[8 * jp + 4], acc[8 * jp + 5]), pack_bf16(acc[8 * jp + 6], acc[8 * jp + 7]));
                fence_async_smem();
                __syncwarp();
                if (elect()) {
                    tma2d_store(&tm_out64, c64, tt2 * 64 + 16 * w, sb + SM_H + w * 2048);
                    tma2d_store(&tm_out48, c48, tt2 * 64 + 16 * w, sb + SM_H + 8192 + w * 2048);
                    asm volatile("cp.async.bulk.commit_group;" ::: "memory");
                    asm volatile("cp.async.bulk.wait_group.read 0;" ::: "memory");
                }
                if (tid == 0) { sc->epoch[slot] = ep; STAMP(19); }
            }
        }
    } else {
        asm volatile("setmaxnreg.dec.sync.aligned.u32 40;");
        int warp2; asm("mov.u32 %0, %1;" : "=r"(warp2) : "r"(warp));
        if (warp2 > 8) {
            if (elect()) {
                if (warp == 9) {
                    #pragma unroll
                    for (int i = B_DONE1; i < B_DONEO; i++) mbar_init(bars + 8 * i, i < B_DONEX ? 2 : 8);
                    mbar_init(bars + 8 * B_CLR, 1);
                }
                #pragma unroll
                for (int i = 0; i < 34; i++) mbar_init(bars + 8 * (B_DONEO + i) + (warp - 9) * 272, 1);
                asm volatile("fence.mbarrier_init.release.cluster;" ::: "memory");
            }
            named_sync(0, 384);
            if (warp == 9) named_arrive(4, 64);
            if (warp < 11) {
                const uint32_t ep = ld_volatile(&sc->epoch[slot]) + 1;
                mbar_wait(bars + 8 * (B_DONE1 + HALO_AT), 0);
                #pragma unroll 1
                for (int kv = 0; kv < 2; kv++) {
                    uint4 v0 = {}, v1 = {}, v2 = {};
                    if (tb > 0) {
                        const uint4* hg = sc->halo + (((tb * 8 + hp) * 2 + warp - 9) * 2 + kv) * 96 + lane;
                        while (ld_relaxed(sc->hint_kv + (((tb - 1) * 8 + hp) * 2 + warp - 9) * 4 + kv * 2) != ep) {}
                        do { v0 = ld_relaxed4(hg); v1 = ld_relaxed4(hg + 32); v2 = ld_relaxed4(hg + 64); } while (!__all_sync(0xffffffffu, v0.w == ep && v1.w == ep && v2.w == ep));
                    }
                    if (kv) mbar_wait(bars + 8 * (B_DONE1 + 5), 0);
                    uint4* hs = (uint4*)(smem_raw + (kv ? SM_HALOV : SM_HALOK)) + (4 * warp - 33) * 64 + lane;
                    hs[0] = make_uint4(v0.x, v0.y, v0.z, v1.x); hs[32] = make_uint4(v1.y, v1.z, v2.x, v2.y);
                    __syncwarp();
                    if (lane == 0) mbar_arrive(bars + 8 * (B_HALO + 2 * kv + warp - 9));
                }
                if (tid == 288) STAMP(21);
            }
            if (warp == 10) {
                if (!has_b1 && lane == 0) {
                    mbar_wait(bars + 8 * (B_DONEO + 3), 0);
                    uint32_t t = clock32() + PF_AT;
                    #pragma unroll 1
                    for (int i = 0; i < PF_N; i++) {
                        while ((int)(clock32() - t) < 0) __nanosleep(40);
                        bulk_prefetch((const char*)w2 + (i * 16 + mi) * 16384, 16384);
                        t += PF_PACE;
                    }
                }
            } else if (warp == 11) {
                const uint32_t ep = ld_volatile(&sc->epoch[slot]) + 1;
                const long long t0 = clock64();
                while (__any_sync(0xffffffffu, (int)(ld_acquire(&sc->clean[lane & 3]) - ep) < 0)) if (clock64() - t0 > WD_CLKS) __trap();
                if (lane == 0) mbar_arrive(bars + 8 * B_CLR);
                if (lane == 0) {
                    mbar_wait_wd(bars + 8 * B_END, 0);
                }
            } else {
                int aslot = 0;
                if (has_b1) {
                    #pragma unroll 1
                    for (int i = 0; i < 16; i++) {
                        mbar_wait(bars + 8 * (i < NA_SLOTS ? B_DONEQ + ((A_SCHED >> (4 * i)) & 15) : B_DONE + 1 + ((i - NA_SLOTS) * 22) / (15 - NA_SLOTS)), 0);
                        if (elect()) {
                            const uint32_t bar = bars + 8 * (B_FULLA + i), dst = sb + SM_ARING + aslot * 16384;
                            mbar_expect(bar, 16384);
                            tma3d(dst, &tm_w1, ft * 64, 0, i * 64, bar);
                            tma3d(dst + 8192, &tm_w1, ft * 64, 1, i * 64, bar);
                        }
                        aslot = aslot == NA_SLOTS - 1 ? 0 : aslot + 1;
                    }
                }
                aslot = 0;
                #pragma unroll 1
                for (int i = 0; i < 14; i++) {
                    if (i >= NA_SLOTS) mbar_wait(bars + 8 * (B_DONE + 1 + ((i - NA_SLOTS) * 18) / (13 - NA_SLOTS)), has_b1);
                    else if (has_b1) {
                        const int last = i + NA_SLOTS * ((15 - i) / NA_SLOTS);
                        mbar_wait(bars + 8 * (B_DONE + max(2 * last + 1, 32 - NB_SLOTS)), 0);
                    } else if (i == 0) { mbar_wait(bars + 8 * (B_DONEO + 3), 0); const uint32_t t = clock32() + PF_AT + 12 * PF_PACE; while ((int)(clock32() - t) < 0) __nanosleep(100); }
                    if (i == NA_SLOTS - 1 && has_b1) mbar_wait(bars + 8 * (B_DONE + 31), 0);
                    if (elect()) {
                        const uint32_t bar = bars + 8 * (B_FULLA + i);
                        mbar_expect(bar, 16384);
                        tma2d(sb + SM_ARING + aslot * 16384, &tm_w2, tt2 * 64, i * 128, bar);
                    }
                    aslot = aslot == NA_SLOTS - 1 ? 0 : aslot + 1;
                }
            }
        } else {
            auto krot = [&](int kb) { const int k = kb * 64 + (G & 1) * 64 * ROT; return k < 448 ? k : k - 448; };
            if (elect()) {
                #pragma unroll
                for (int i = 0; i < 7; i++) mbar_init(bars + 8 * i, 1);
                asm volatile("fence.mbarrier_init.release.cluster;" ::: "memory");
                #pragma unroll 1
                for (int kb = 0; kb < 7; kb++) {
                    const uint32_t st = sb + slot_x(kb), bar = bars + 8 * (B_FULLX + kb);
                    mbar_expect(bar, 16384);
                    tma3d(st, &tm_x, krot(kb), 0, tb * 64, bar); tma3d(st + 8192, &tm_x, krot(kb), 1, tb * 64, bar);
                }
                #pragma unroll
                for (int i = 7; i < B_DONE1; i++) mbar_init(bars + 8 * i, 1);
                asm volatile("fence.mbarrier_init.release.cluster;" ::: "memory");
            }
            named_arrive(0, 384);
            #pragma unroll 1
            for (int kb = 0; kb < 7; kb++) {
                if (kb == 6) { named_sync(4, 64); mbar_wait(bars + 8 * B_DONEX, 0); }
                if (elect()) {
                    const uint32_t st = sb + slot_kv(kb), bar = bars + 8 * (B_FULLKV + kb);
                    mbar_expect(bar, 16384);
                    #pragma unroll
                    for (int i = 0; i < 2; i++) {
                        const int n = 2 * kb + (ROT ? i : i ^ (G & 1));
                        tma2d(st + (n & 1) * 8192, &tm_wqkv, (n < 7 ? 448 : 896) + wcol, krot(n < 7 ? n : n - 7), bar);
                    }
                }
            }
            if (elect()) {
                mbar_expect(bars + 8 * B_FQ, 32768);
                mbar_expect(bars + 8 * (B_FQ + 1), 24576);
                #pragma unroll 1
                for (int i = 0; i < 7; i++) { const int j = ROT || i == 6 ? i : i ^ (G & 1); tma2d(sb + SM_QO + j * 8192, &tm_wqkv, wcol, krot(j), bars + 8 * (B_FQ + (i >> 2))); }
                mbar_expect(bars + 8 * B_FULLWO, 512 * 112 * 2);
            }
            #pragma unroll 1
            for (int i = 0; i < 7; i++) {
                const int kb = ((q & 1 ? WO_ORD1 : WO_ORD0) >> (4 * i)) & 7;
                if (kb < 5) mbar_wait(bars + 8 * (B_DONE1 + kb), 0);
                if (i == WO_HOLD) { mbar_wait(bars + 8 * (B_HALO + 2), 0); mbar_wait(bars + 8 * (B_HALO + 3), 0); }
                if (elect()) {
                    tma2d(sb + slot_wo(kb), &tm_wo64, c64, kb * 64, bars + 8 * B_FULLWO);
                    tma2d(sb + slot_wo(kb) + 8192, &tm_wo48, c48, kb * 64, bars + 8 * B_FULLWO);
                }
            }
            if (XR_HOLD) { mbar_wait(bars + 8 * (B_HALO + 2), 0); mbar_wait(bars + 8 * (B_HALO + 3), 0); }
            if (elect()) {
                tma2d(sb + SM_H, &tm_xr64, c64, tt2 * 64, bars + 8 * B_FULLWO);
                tma2d(sb + SM_H + 8192, &tm_xr48, c48, tt2 * 64, bars + 8 * B_FULLWO);
            }
            if (smem_u32(smem_raw) != SB) __trap();
            const uint32_t ep = ld_volatile(&sc->epoch[slot]) + 1;
            const Tiles* const tl = &sc->tiles[ep & 1];
            mbar_wait(bars + 8 * B_DONEQ, 0);
            {
                uint32_t issued = 0;
                while (issued != 0x01010101u) {
                    uint32_t m = __ballot_sync(0xffffffffu, ld_relaxed(sc->hint_o + (tt2 * 32 + lane) * 2) == ep);
                    m &= m >> 4; m &= m >> 2; m &= m >> 1; m &= 0x01010101u & ~issued;
                    if ((m >> lane) & 1) {
                        const uint32_t bar = bars + 8 * B_RAW + lane;
                        mbar_expect(bar, 14336);
                        bulk_ld(sb + SM_QO + lane * 1792, tl->o + tt2 * 14336 + lane * 448, 14336, bar);
                    }
                    issued |= m;
                }
                __syncwarp();
            }
            if (lane == 0) STAMP(20);
            mbar_wait(bars + 8 * (B_DONEO + 3), 0);
            if (has_b1) {
                mix_producer_b<32>(TSVAL 0, sc->hint_h + q * 64, ep, tl->hn + q * 32 * 3584, lane);
                mbar_wait(bars + 8 * (B_DONE + 31), 0);
            }
            mix_producer_b<28>(TSVAL has_b1, sc->hint_u + q * 64, ep, tl->u + q * 28 * 3584, lane);
        }
    }
}

typedef CUresult (*EncodeFn)(CUtensorMap*, CUtensorMapDataType, cuuint32_t, void*, const cuuint64_t*, const cuuint64_t*, const cuuint32_t*,
                             const cuuint32_t*, CUtensorMapInterleave, CUtensorMapSwizzle, CUtensorMapL2promotion, CUtensorMapFloatOOBfill);

void make_map(EncodeFn fn, CUtensorMap* tm, const void* ptr, int rank, const cuuint64_t* dims, const cuuint64_t* strides, const cuuint32_t* box, CUtensorMapSwizzle sw) {
    cuuint32_t es[3] = {1, 1, 1};
    fn(tm, CU_TENSOR_MAP_DATA_TYPE_BFLOAT16, rank, const_cast<void*>(ptr), dims, strides, box, es, CU_TENSOR_MAP_INTERLEAVE_NONE, sw,
       CU_TENSOR_MAP_L2_PROMOTION_NONE, CU_TENSOR_MAP_FLOAT_OOB_FILL_NONE);
}

}

extern "C" void kernel_launch(void* const* d_in, const int* in_sizes, int n_in, void* d_out, int out_size) {
    const __nv_bfloat16* x = (const __nv_bfloat16*)d_in[0];
    const __nv_bfloat16* wqkv = (const __nv_bfloat16*)d_in[1];
    const __nv_bfloat16* wo = (const __nv_bfloat16*)d_in[2];
    const __nv_bfloat16* w1 = (const __nv_bfloat16*)d_in[4];
    const __nv_bfloat16* b1 = (const __nv_bfloat16*)d_in[5];
    const __nv_bfloat16* w2 = (const __nv_bfloat16*)d_in[6];
    const __nv_bfloat16* b2 = (const __nv_bfloat16*)d_in[7];

    void* fnp = nullptr; cudaDriverEntryPointQueryResult qr;
    cudaGetDriverEntryPoint("cuTensorMapEncodeTiled", &fnp, cudaEnableDefault, &qr);
    EncodeFn fn = (EncodeFn)fnp;
    CUtensorMap tx, twqkv, two64, two48, tw1, tw2, txr64, txr48, tout64, tout48;
    { cuuint64_t d[3] = {448, 2, 1024}, s[2] = {896, 1792}; cuuint32_t b[3] = {64, 1, 64}; make_map(fn, &tx, x, 3, d, s, b, CU_TENSOR_MAP_SWIZZLE_128B); }
    { cuuint64_t d[2] = {1344, 448}, s[1] = {2688}; cuuint32_t b[2] = {64, 64}; make_map(fn, &twqkv, wqkv, 2, d, s, b, CU_TENSOR_MAP_SWIZZLE_128B); }
    { cuuint64_t d[2] = {448, 448}, s[1] = {896}; cuuint32_t b[2] = {64, 64}; make_map(fn, &two64, wo, 2, d, s, b, CU_TENSOR_MAP_SWIZZLE_128B); }
    { cuuint64_t d[2] = {448, 448}, s[1] = {896}; cuuint32_t b[2] = {48, 64}; make_map(fn, &two48, wo, 2, d, s, b, CU_TENSOR_MAP_SWIZZLE_128B); }
    { cuuint64_t d[3] = {1792, 2, 1024}, s[2] = {3584, 7168}; cuuint32_t b[3] = {64, 1, 64}; make_map(fn, &tw1, w1, 3, d, s, b, CU_TENSOR_MAP_SWIZZLE_128B); }
    { cuuint64_t d[2] = {2048, 1792}, s[1] = {4096}; cuuint32_t b[2] = {64, 128}; make_map(fn, &tw2, w2, 2, d, s, b, CU_TENSOR_MAP_SWIZZLE_128B); }
    { cuuint64_t d[2] = {448, 2048}, s[1] = {896}; cuuint32_t b[2] = {64, 64}; make_map(fn, &txr64, x, 2, d, s, b, CU_TENSOR_MAP_SWIZZLE_128B); }
    { cuuint64_t d[2] = {448, 2048}, s[1] = {896}; cuuint32_t b[2] = {48, 64}; make_map(fn, &txr48, x, 2, d, s, b, CU_TENSOR_MAP_SWIZZLE_128B); }
    { cuuint64_t d[2] = {448, 2048}, s[1] = {896}; cuuint32_t b[2] = {64, 16}; make_map(fn, &tout64, d_out, 2, d, s, b, CU_TENSOR_MAP_SWIZZLE_128B); }
    { cuuint64_t d[2] = {448, 2048}, s[1] = {896}; cuuint32_t b[2] = {48, 16}; make_map(fn, &tout48, d_out, 2, d, s, b, CU_TENSOR_MAP_SWIZZLE_128B); }

    void* scv = nullptr;
    cudaGetSymbolAddress(&scv, g_scratch);
    Scratch* scp = (Scratch*)scv;
    int dev = 0, sms = 0;
    cudaGetDevice(&dev);
    cudaDeviceGetAttribute(&sms, cudaDevAttrMultiProcessorCount, dev);
    if (sms == 132) {
        cudaFuncSetAttribute(fused_kernel<true>, cudaFuncAttributeMaxDynamicSharedMemorySize, SM_TOTAL);
        fused_kernel<true><<<132, 384, SM_TOTAL>>>(scp, wo, w1, b1, w2, b2, tx, twqkv, two64, two48, tw1, tw2, txr64, txr48, tout64, tout48);
    } else {
        cudaFuncSetAttribute(fused_kernel<false>, cudaFuncAttributeMaxDynamicSharedMemorySize, SM_TOTAL);
        fused_kernel<false><<<132, 384, SM_TOTAL>>>(scp, wo, w1, b1, w2, b2, tx, twqkv, two64, two48, tw1, tw2, txr64, txr48, tout64, tout48);
    }
}
```

```cpp
#include <cuda_runtime.h>
#include <cuda_bf16.h>
#include <cuda.h>
#include <stdint.h>

namespace {

constexpr int D_ = 448;
constexpr float LN_EPS = 1e-5f;
constexpr float LOG2E_SCALE = 0.1889822365046136f * 1.4426950408889634f;

struct Tiles {
    uint32_t o[32 * 57344 / 4];
    uint32_t hn[4 * 32 * 14336 / 4];
    uint32_t u[4 * 28 * 14336 / 4];
};
struct Scratch {
    Tiles tiles[2];
    uint4 halo[128 * 2 * 2 * 3 * 32];
    uint4 stats[32 * 4 * 64];
    uint4 hint_kv[128 * 2 * 2 * 2];
    uint4 hint_o[32 * 32 * 2];
    uint4 hint_h[4 * 32 * 2];
    uint4 hint_u[4 * 32 * 2];
    uint32_t epoch[160];
    uint32_t clean[4];
};
__device__ __align__(1024) Scratch g_scratch;
#define STAMP(i) do {} while (0)
#define FST(i) do {} while (0)
#define TSARG
#define TSVAL

constexpr uint32_t SB = 1024;
constexpr int SM_SLOT = 16384;
__device__ __forceinline__ constexpr uint32_t slot_x(int kb) { return (kb ? 6 + kb : 0) * SM_SLOT; }
__device__ __forceinline__ constexpr uint32_t slot_kv(int kb) { return (kb < 5 ? 2 + kb : 6 - kb) * SM_SLOT; }
__device__ __forceinline__ constexpr uint32_t slot_wo(int kb) { return (kb < 6 ? 2 + kb : 12) * SM_SLOT; }
constexpr int SM_QO = 8 * SM_SLOT;
constexpr int SM_HALOK = SM_QO + 57344, SM_HALOV = 1 * SM_SLOT;
constexpr int NA_SLOTS = 6, NB_SLOTS = 8;
constexpr int SM_ARING = 0;
constexpr int SM_BRING = NA_SLOTS * 16384;
constexpr int SM_H = 212992;
constexpr int SM_MISC = 229376;
constexpr int SM_BAR = 231424;
constexpr int SM_TOTAL = 232448;
constexpr int B_FULLX = 0;
constexpr int B_FULLKV = 7;
constexpr int B_FQ = 14;
constexpr int B_DONE1 = 16;
constexpr int B_DONEX = 23;
constexpr int B_DONEQ = 24;
constexpr int B_DONEO = 25;
constexpr int B_FULLO = 29;
constexpr int B_FULLWO = 33;
constexpr int B_END = 34;
constexpr int B_HALO = 35;
constexpr int B_FULLA = 39;
constexpr int B_FULLB = 55;
constexpr int B_DONE = 87;
constexpr int B_RAW = 119;
constexpr int B_CLR = 127;

constexpr long long WD_CLKS = 2000000000ll;

template<int N> struct Int { static constexpr int value = N; };
template<int A, int B, class F> __device__ __forceinline__ void static_for(F&& f) { if constexpr (A < B) { f(Int<A>()); static_for<A + 1, B>(f); } }

__device__ __forceinline__ uint32_t smem_u32(const void* p) { return (uint32_t)__cvta_generic_to_shared(p); }
__device__ __forceinline__ void mbar_init(uint32_t bar, uint32_t cnt) { asm volatile("mbarrier.init.shared::cta.b64 [%0], %1;" :: "r"(bar), "r"(cnt) : "memory"); }
__device__ __forceinline__ void mbar_expect(uint32_t bar, uint32_t bytes) { asm volatile("mbarrier.arrive.expect_tx.shared::cta.b64 _, [%0], %1;" :: "r"(bar), "r"(bytes) : "memory"); }
__device__ __forceinline__ void mbar_arrive(uint32_t bar) { asm volatile("mbarrier.arrive.shared::cta.b64 _, [%0];" :: "r"(bar) : "memory"); }
__device__ __forceinline__ bool mbar_try(uint32_t bar, uint32_t parity) {
    uint32_t ok;
    asm volatile("{\n.reg .pred p;\nmbarrier.try_wait.parity.shared::cta.b64 p, [%1], %2;\nselp.u32 %0, 1, 0, p;\n}" : "=r"(ok) : "r"(bar), "r"(parity) : "memory");
    return ok;
}
__device__ __forceinline__ void mbar_wait(uint32_t bar, uint32_t parity) {
    asm volatile("{\n.reg .pred p;\n"
                 "WAIT_LOOP:\n"
                 "mbarrier.try_wait.parity.shared::cta.b64 p, [%0], %1;\n"
                 "@!p bra WAIT_LOOP;\n}" :: "r"(bar), "r"(parity) : "memory");
}
__device__ __forceinline__ void mbar_wait_wd(uint32_t bar, uint32_t parity) {
    const long long t0 = clock64();
    while (!mbar_try(bar, parity)) { if (clock64() - t0 > WD_CLKS) __trap(); }
}
__device__ __forceinline__ bool elect() { uint32_t p; asm volatile("{\n.reg .pred P;\nelect.sync _|P, 0xffffffff;\nselp.u32 %0, 1, 0, P;\n}" : "=r"(p)); return p; }
__device__ __forceinline__ void tma2d(uint32_t dst, const CUtensorMap* tm, int c0, int c1, uint32_t bar) {
    asm volatile("cp.async.bulk.tensor.2d.shared::cluster.global.mbarrier::complete_tx::bytes [%0], [%1, {%3, %4}], [%2];" :: "r"(dst), "l"(tm), "r"(bar), "r"(c0), "r"(c1) : "memory");
}
__device__ __forceinline__ void tma3d(uint32_t dst, const CUtensorMap* tm, int c0, int c1, int c2, uint32_t bar) {
    asm volatile("cp.async.bulk.tensor.3d.shared::cluster.global.mbarrier::complete_tx::bytes [%0], [%1, {%3, %4, %5}], [%2];" :: "r"(dst), "l"(tm), "r"(bar), "r"(c0), "r"(c1), "r"(c2) : "memory");
}
__device__ __forceinline__ void tma2d_store(const CUtensorMap* tm, int c0, int c1, uint32_t src) {
    asm volatile("cp.async.bulk.tensor.2d.global.shared::cta.bulk_group [%0, {%2, %3}], [%1];" :: "l"(tm), "r"(src), "r"(c0), "r"(c1) : "memory");
}
__device__ __forceinline__ void bulk_ld(uint32_t dst, const void* src, uint32_t bytes, uint32_t bar) {
    asm volatile("cp.async.bulk.shared::cluster.global.mbarrier::complete_tx::bytes [%0], [%1], %2, [%3];" :: "r"(dst), "l"(src), "r"(bytes), "r"(bar) : "memory");
}
__device__ __forceinline__ void bulk_prefetch(const void* src, uint32_t bytes) { asm volatile("cp.async.bulk.prefetch.L2.global [%0], %1;" :: "l"(src), "r"(bytes) : "memory"); }
__device__ __forceinline__ void prefetch_map(const CUtensorMap* tm) { asm volatile("prefetch.tensormap [%0];" :: "l"(tm) : "memory"); }
__device__ __forceinline__ void st_global(uint32_t* p, uint32_t v) { asm volatile("st.global.u32 [%0], %1;" :: "l"(p), "r"(v) : "memory"); }
__device__ __forceinline__ void pin4(uint32_t never, float a, float b, float c, float d) {
    asm volatile("{\n.reg .pred p;\nsetp.ne.u32 p, %4, 0;\n@p st.shared.v4.f32 [%4], {%0,%1,%2,%3};\n}" :: "f"(a), "f"(b), "f"(c), "f"(d), "r"(never) : "memory");
}
__device__ __forceinline__ void fence_async_smem() { asm volatile("fence.proxy.async.shared::cta;" ::: "memory"); }
__device__ __forceinline__ uint32_t ld_acquire(const void* p) { uint32_t v; asm volatile("ld.acquire.gpu.global.u32 %0, [%1];" : "=r"(v) : "l"(p) : "memory"); return v; }
__device__ __forceinline__ void st_release(void* p, uint32_t v) { asm volatile("st.release.gpu.global.u32 [%0], %1;" :: "l"(p), "r"(v) : "memory"); }
__device__ __forceinline__ uint32_t ld_relaxed(const void* p) { uint32_t v; asm volatile("ld.relaxed.gpu.global.u32 %0, [%1];" : "=r"(v) : "l"(p) : "memory"); return v; }
__device__ __forceinline__ uint4 ld_relaxed4(const uint4* p) {
    uint4 v;
    asm volatile("{\n.reg .b128 t;\n.reg .b64 a, b;\nld.relaxed.gpu.global.b128 t, [%4];\nmov.b128 {a, b}, t;\nmov.b64 {%0, %1}, a;\nmov.b64 {%2, %3}, b;\n}" : "=r"(v.x), "=r"(v.y), "=r"(v.z), "=r"(v.w) : "l"(p) : "memory");
    return v;
}
__device__ __forceinline__ void st_relaxed4(uint4* p, uint32_t a, uint32_t b, uint32_t c, uint32_t d) {
    asm volatile("{\n.reg .b128 t;\n.reg .b64 a, b;\nmov.b64 a, {%1, %2};\nmov.b64 b, {%3, %4};\nmov.b128 t, {a, b};\nst.relaxed.gpu.global.b128 [%0], t;\n}" :: "l"(p), "r"(a), "r"(b), "r"(c), "r"(d) : "memory");
}
__device__ __forceinline__ uint32_t ld_volatile(const uint32_t* p) { uint32_t v; asm volatile("ld.volatile.global.u32 %0, [%1];" : "=r"(v) : "l"(p) : "memory"); return v; }
__device__ __forceinline__ void named_arrive(int id, int n) { asm volatile("bar.arrive %0, %1;" :: "r"(id), "r"(n) : "memory"); }
__device__ __forceinline__ void named_sync(int id, int n) { asm volatile("bar.sync %0, %1;" :: "r"(id), "r"(n) : "memory"); }
__device__ __forceinline__ void wg_fence() { asm volatile("wgmma.fence.sync.aligned;" ::: "memory"); }
__device__ __forceinline__ void wg_commit() { asm volatile("wgmma.commit_group.sync.aligned;" ::: "memory"); }
template<int N> __device__ __forceinline__ void wg_wait() { asm volatile("wgmma.wait_group.sync.aligned %0;" :: "n"(N) : "memory"); }
template<int N> __device__ __forceinline__ void reg_fence(float (&d)[N]) {
    #pragma unroll
    for (int i = 0; i < N; i++) asm volatile("" : "+f"(d[i]) :: "memory");
}
__device__ __forceinline__ constexpr uint64_t mkdesc(uint32_t addr, uint32_t lbo, uint32_t sbo, uint32_t sw) {
    return (uint64_t)((addr & 0x3FFFF) >> 4) | ((uint64_t)(lbo >> 4) << 16) | ((uint64_t)(sbo >> 4) << 32) | ((uint64_t)sw << 62);
}
__device__ __forceinline__ void ldsm4(uint32_t (&r)[4], uint32_t addr) {
    asm volatile("ldmatrix.sync.aligned.m8n8.x4.shared.b16 {%0,%1,%2,%3}, [%4];" : "=r"(r[0]), "=r"(r[1]), "=r"(r[2]), "=r"(r[3]) : "r"(addr) : "memory");
}
__device__ __forceinline__ void stsm4(uint32_t addr, uint32_t r0, uint32_t r1, uint32_t r2, uint32_t r3) {
    asm volatile("stmatrix.sync.aligned.m8n8.x4.shared.b16 [%0], {%1,%2,%3,%4};" :: "r"(addr), "r"(r0), "r"(r1), "r"(r2), "r"(r3) : "memory");
}
__device__ __forceinline__ uint32_t movtrans(uint32_t a) { uint32_t d; asm volatile("movmatrix.sync.aligned.m8n8.trans.b16 %0, %1;" : "=r"(d) : "r"(a)); return d; }
__device__ __forceinline__ uint32_t pack_bf16(float lo, float hi) { uint32_t r; asm("cvt.rn.bf16x2.f32 %0, %1, %2;" : "=r"(r) : "f"(hi), "f"(lo)); return r; }
__device__ __forceinline__ void sub_bf16x2(uint32_t& a, uint32_t b) { asm volatile("sub.rn.bf16x2 %0, %0, %1;" : "+r"(a) : "r"(b)); }
__device__ __forceinline__ float bf_lo(uint32_t v) { return __uint_as_float(v << 16); }
__device__ __forceinline__ float bf_hi(uint32_t v) { return __uint_as_float(v & 0xffff0000u); }
__device__ __forceinline__ void mma16816(float (&c)[4], uint32_t a0, uint32_t a1, uint32_t a2, uint32_t a3, uint32_t b0, uint32_t b1) {
    asm volatile("mma.sync.aligned.m16n8k16.row.col.f32.bf16.bf16.f32 {%0,%1,%2,%3}, {%4,%5,%6,%7}, {%8,%9}, {%0,%1,%2,%3};"
        : "+f"(c[0]), "+f"(c[1]), "+f"(c[2]), "+f"(c[3]) : "r"(a0), "r"(a1), "r"(a2), "r"(a3), "r"(b0), "r"(b1));
}
__device__ __forceinline__ void mma1688(float (&c)[4], uint32_t a0, uint32_t a1, uint32_t b0) {
    asm volatile("mma.sync.aligned.m16n8k8.row.col.f32.bf16.bf16.f32 {%0,%1,%2,%3}, {%4,%5}, {%6}, {%0,%1,%2,%3};"
        : "+f"(c[0]), "+f"(c[1]), "+f"(c[2]), "+f"(c[3]) : "r"(a0), "r"(a1), "r"(b0));
}
__device__ __forceinline__ float quad_sum(float v) { v += __shfl_xor_sync(0xffffffffu, v, 1); v += __shfl_xor_sync(0xffffffffu, v, 2); return v; }
__device__ __forceinline__ float quad_max(float v) { v = fmaxf(v, __shfl_xor_sync(0xffffffffu, v, 1)); v = fmaxf(v, __shfl_xor_sync(0xffffffffu, v, 2)); return v; }
__device__ __forceinline__ float ex2(float x) { float y; asm("ex2.approx.ftz.f32 %0, %1;" : "=f"(y) : "f"(x)); return y; }
__device__ __forceinline__ float rsqrt_approx(float x) { float y; asm("rsqrt.approx.ftz.f32 %0, %1;" : "=f"(y) : "f"(x)); return y; }
__device__ __forceinline__ float rcp_approx(float x) { float y; asm("rcp.approx.ftz.f32 %0, %1;" : "=f"(y) : "f"(x)); return y; }
__device__ __forceinline__ float gelu_half(float hx) {
    const float z = hx * fmaf(hx * hx, 8.f * 0.044715f * 0.7978845608028654f, 2.f * 0.7978845608028654f);
    float t; asm("tanh.approx.f32 %0, %1;" : "=f"(t) : "f"(z));
    return fmaf(hx, t, hx);
}
__device__ __forceinline__ uint32_t clock32() { uint32_t t; asm volatile("mov.u32 %0, %%clock;" : "=r"(t)); return t; }
#define PF_PACE 400

#define PF_AT 4000
#define NSQ 6
#define HALO_AT 3
#define PF_N 12
#define HINT_H 7
#define HINT_U 8
#define SP_AT 2000
#define SP_N 0
#define WO_HOLD 7
#define A_SCHED 0x322188
#define WO_ORD0 0x4321065
#define WO_ORD1 0x3465210
#define XR_HOLD 0
#define ROT 0
#define SQMIX 0
#define NPIPE 1
#define CL_SPLIT 1000
#define CL_AT 600
#define WARM 1
#define WARM_AT 300
#define HINT_O 0
#define W2_AT 23
#define W2_HOLD 5
#define START_N 8
#define NOCHECK 1
#define A3_END 20
#define A4_END 16
#define TAIL3 0
#define TAIL4 0
template<int TB> __device__ __forceinline__ void wgmma_rs56(float (&d)[28], const uint32_t (&a)[4], uint64_t db, int sc) {
    asm volatile("{\n.reg .pred p;\nsetp.ne.b32 p, %33, 0;\n"
        "wgmma.mma_async.sync.aligned.m64n56k16.f32.bf16.bf16 {%0, %1, %2, %3, %4, %5, %6, %7, %8, %9, %10, %11, %12, %13, %14, %15, %16, %17, %18, %19, %20, %21, %22, %23, %24, %25, %26, %27}, {%28, %29, %30, %31}, %32, p, 1, 1, %34;\n}\n"
        : "+f"(d[0]), "+f"(d[1]), "+f"(d[2]), "+f"(d[3]), "+f"(d[4]), "+f"(d[5]), "+f"(d[6]), "+f"(d[7]), "+f"(d[8]), "+f"(d[9]), "+f"(d[10]), "+f"(d[11]), "+f"(d[12]), "+f"(d[13]), "+f"(d[14]), "+f"(d[15]), "+f"(d[16]), "+f"(d[17]), "+f"(d[18]), "+f"(d[19]), "+f"(d[20]), "+f"(d[21]), "+f"(d[22]), "+f"(d[23]), "+f"(d[24]), "+f"(d[25]), "+f"(d[26]), "+f"(d[27])
        : "r"(a[0]), "r"(a[1]), "r"(a[2]), "r"(a[3]), "l"(db), "r"(sc), "n"(TB));
}

template<int TA, int TB, int SC = 1> __device__ __forceinline__ void wgmma_ss112(float (&d)[56], uint64_t da, uint64_t db) {
    asm volatile("wgmma.mma_async.sync.aligned.m64n112k16.f32.bf16.bf16 {%0, %1, %2, %3, %4, %5, %6, %7, %8, %9, %10, %11, %12, %13, %14, %15, %16, %17, %18, %19, %20, %21, %22, %23, %24, %25, %26, %27, %28, %29, %30, %31, %32, %33, %34, %35, %36, %37, %38, %39, %40, %41, %42, %43, %44, %45, %46, %47, %48, %49, %50, %51, %52, %53, %54, %55}, %56, %57, %60, 1, 1, %58, %59;\n"
        : "+f"(d[0]), "+f"(d[1]), "+f"(d[2]), "+f"(d[3]), "+f"(d[4]), "+f"(d[5]), "+f"(d[6]), "+f"(d[7]), "+f"(d[8]), "+f"(d[9]), "+f"(d[10]), "+f"(d[11]), "+f"(d[12]), "+f"(d[13]), "+f"(d[14]), "+f"(d[15]), "+f"(d[16]), "+f"(d[17]), "+f"(d[18]), "+f"(d[19]), "+f"(d[20]), "+f"(d[21]), "+f"(d[22]), "+f"(d[23]), "+f"(d[24]), "+f"(d[25]), "+f"(d[26]), "+f"(d[27]), "+f"(d[28]), "+f"(d[29]), "+f"(d[30]), "+f"(d[31]), "+f"(d[32]), "+f"(d[33]), "+f"(d[34]), "+f"(d[35]), "+f"(d[36]), "+f"(d[37]), "+f"(d[38]), "+f"(d[39]), "+f"(d[40]), "+f"(d[41]), "+f"(d[42]), "+f"(d[43]), "+f"(d[44]), "+f"(d[45]), "+f"(d[46]), "+f"(d[47]), "+f"(d[48]), "+f"(d[49]), "+f"(d[50]), "+f"(d[51]), "+f"(d[52]), "+f"(d[53]), "+f"(d[54]), "+f"(d[55])
        : "l"(da), "l"(db), "n"(TA), "n"(TB), "n"(SC));
}

template<int TA, int TB, int SC = 1> __device__ __forceinline__ void wgmma_ss64(float (&d)[32], uint64_t da, uint64_t db) {
    asm volatile("wgmma.mma_async.sync.aligned.m64n64k16.f32.bf16.bf16 {%0, %1, %2, %3, %4, %5, %6, %7, %8, %9, %10, %11, %12, %13, %14, %15, %16, %17, %18, %19, %20, %21, %22, %23, %24, %25, %26, %27, %28, %29, %30, %31}, %32, %33, %36, 1, 1, %34, %35;\n"
        : "+f"(d[0]), "+f"(d[1]), "+f"(d[2]), "+f"(d[3]), "+f"(d[4]), "+f"(d[5]), "+f"(d[6]), "+f"(d[7]), "+f"(d[8]), "+f"(d[9]), "+f"(d[10]), "+f"(d[11]), "+f"(d[12]), "+f"(d[13]), "+f"(d[14]), "+f"(d[15]), "+f"(d[16]), "+f"(d[17]), "+f"(d[18]), "+f"(d[19]), "+f"(d[20]), "+f"(d[21]), "+f"(d[22]), "+f"(d[23]), "+f"(d[24]), "+f"(d[25]), "+f"(d[26]), "+f"(d[27]), "+f"(d[28]), "+f"(d[29]), "+f"(d[30]), "+f"(d[31])
        : "l"(da), "l"(db), "n"(TA), "n"(TB), "n"(SC));
}

template<int TA, int TB, int SC = 1> __device__ __forceinline__ void wgmma_ss48(float (&d)[24], uint64_t da, uint64_t db) {
    asm volatile("wgmma.mma_async.sync.aligned.m64n48k16.f32.bf16.bf16 {%0, %1, %2, %3, %4, %5, %6, %7, %8, %9, %10, %11, %12, %13, %14, %15, %16, %17, %18, %19, %20, %21, %22, %23}, %24, %25, %28, 1, 1, %26, %27;\n"
        : "+f"(d[0]), "+f"(d[1]), "+f"(d[2]), "+f"(d[3]), "+f"(d[4]), "+f"(d[5]), "+f"(d[6]), "+f"(d[7]), "+f"(d[8]), "+f"(d[9]), "+f"(d[10]), "+f"(d[11]), "+f"(d[12]), "+f"(d[13]), "+f"(d[14]), "+f"(d[15]), "+f"(d[16]), "+f"(d[17]), "+f"(d[18]), "+f"(d[19]), "+f"(d[20]), "+f"(d[21]), "+f"(d[22]), "+f"(d[23])
        : "l"(da), "l"(db), "n"(TA), "n"(TB), "n"(SC));
}

template<int NKB, int TAIL, bool PERM, class F>
__device__ __forceinline__ void mix_mainloop(TSARG float (&acc)[56], uint32_t par, bool leader, uint32_t never, F&& left) {
    constexpr uint32_t sb = SB, bars = sb + SM_BAR;
    constexpr int A0 = PERM ? 0 : 16 % NA_SLOTS;
    auto aoff = [](int jj, int s) { return (PERM ? (s & 1) * 8192 + (jj * 32 + (s >> 1) * 16) * 128 : jj * 8192 + s * 2048) >> 4; };
    int bslot = 0, aslot = A0;
    reg_fence(acc);
    #pragma unroll 1
    for (int i = 0; i < (NKB - TAIL) / 2; i++) {
        mbar_wait(bars + 8 * (B_FULLA + i), par);
        const uint64_t adesc = mkdesc(sb + SM_ARING, 8192, 1024, 1) + (uint32_t)(aslot * 1024);
        aslot = aslot == NA_SLOTS - 1 ? 0 : aslot + 1;
        #pragma unroll
        for (int jj = 0; jj < 2; jj++) {
            const int j = 2 * i + jj;
            mbar_wait(bars + 8 * (B_FULLB + j), par);
            const uint64_t bdesc = mkdesc(sb + SM_BRING, 1792, 128, 0) + (uint32_t)(bslot * 896);
            bslot = bslot == NB_SLOTS - 1 ? 0 : bslot + 1;
            wg_fence();
            #pragma unroll
            for (int s = 0; s < 4; s++) wgmma_ss112<1, 1>(acc, adesc + aoff(jj, s), bdesc + s * 224);
            wg_commit();
            wg_wait<1>();
            if (j > 0 && leader) mbar_arrive(bars + 8 * (B_DONE + j - 1));
        }
    }
    auto ad = [&](int j, int s) { return mkdesc(sb + SM_ARING + (A0 + j / 2) % NA_SLOTS * 16384, 8192, 1024, 1) + aoff(j & 1, s); };
    auto bd = [&](int j, int s) { return mkdesc(sb + SM_BRING + j % NB_SLOTS * 14336, 1792, 128, 0) + s * 224; };
    float accl[32], accr[24];
    #pragma unroll
    for (int j = NKB - TAIL; j < NKB; j++) {
        if (!(j & 1)) mbar_wait(bars + 8 * (B_FULLA + j / 2), par);
        mbar_wait(bars + 8 * (B_FULLB + j), par);
        wg_fence();
        #pragma unroll
        for (int s = 0; s < 4; s++) {
            if (j == NKB - TAIL && s == 0) wgmma_ss64<1, 1, 0>(accl, ad(j, s), bd(j, s)); else wgmma_ss64<1, 1>(accl, ad(j, s), bd(j, s));
        }
        wg_commit();
        wg_wait<1>();
        if (j == NKB - TAIL) {
            reg_fence(acc);
            if (leader) mbar_arrive(bars + 8 * (B_DONE + j - 1));
            #pragma unroll
            for (int c = 0; c < 24; c++) accr[c] = __uint_as_float(__float_as_uint(acc[32 + c]) | never);
            reg_fence(accr);
        }
    }
    static_for<NKB - TAIL, NKB>([&](auto jc) {
        constexpr int j = jc.value;
        if (j != NKB - TAIL + 1) wg_fence();
        #pragma unroll
        for (int s = 0; s < 4; s++) wgmma_ss48<1, 1>(accr, ad(j, s), bd(j, s) + 64);
        if constexpr (j > NKB - TAIL) {
            wg_commit();
            if (j == NKB - TAIL + 1) {
                wg_wait<1>(); reg_fence(accl);
                #pragma unroll
                for (int c = 0; c < 32; c++) accl[c] += acc[c];
            }
            else mbar_wait(bars + 8 * (B_FULLB + j), par);
            left(Int<j - (NKB - TAIL + 1)>(), accl);
            if (never) mbar_arrive(bars);
        }
    });
    wg_wait<0>();
    if (TAIL) {
        reg_fence(accr);
        #pragma unroll
        for (int c = 0; c < 24; c++) acc[32 + c] = accr[c];
    } else reg_fence(acc);
    if (leader) mbar_arrive(bars + 8 * (B_DONE + NKB - 1));
}

constexpr uint32_t EMPTY = 0xFFFFFFFFu;
__device__ __forceinline__ void post_hint(uint4* p, uint32_t ep, int lane) { if (lane < 2) st_relaxed4(p + lane, ep, ep, ep, ep); }
__device__ __forceinline__ void post_hint_wg(uint4* p, uint32_t ep, int w, int lane) {
    if (w < 3) named_arrive(5, 128); else { named_sync(5, 128); post_hint(p, ep, lane); }
}

template<int NKB>
__device__ __forceinline__ void mix_producer_b(TSARG uint32_t par, const uint4* hints, uint32_t ep, const uint32_t* src, int lane) {
    constexpr uint32_t sb = SB, bars = sb + SM_BAR;
    uint32_t ready = 0;
    constexpr uint32_t first = START_N >= NKB ? 0xffffffffu >> (32 - NKB) : (1u << START_N) - 1;
    while ((ready & first) != first) ready = __ballot_sync(0xffffffffu, ld_relaxed(hints + 2 * lane) == ep);
    #pragma unroll 1
    for (int j = 0; j < NKB; j++) {
        if (!NOCHECK) while (!((ready >> j) & 1)) ready = __ballot_sync(0xffffffffu, ld_relaxed(hints + 2 * lane) == ep);
        if (j >= NB_SLOTS) mbar_wait(bars + 8 * (B_DONE + j - NB_SLOTS), par);
        if (j == 0 && lane == 0) STAMP(NKB == 32 ? 29 : 30);
        if (j == 7 && lane == 0) STAMP(NKB == 32 ? 35 : 36);
        if (elect()) {
            mbar_expect(bars + 8 * (B_RAW + (j & 7)), 14336);
            bulk_ld(sb + SM_BRING + (j & 7) * 14336, src + j * 3584, 14336, bars + 8 * (B_RAW + (j & 7)));
        }
    }
}
__device__ __forceinline__ void check_tiles(TSARG int n, int w, int lane, uint32_t& ph, uint32_t dst, const uint32_t* src, int full) {
    constexpr uint32_t bars = SB + SM_BAR;
    #pragma unroll 1
    for (int j = w; j < n; j += 4) {
        const uint32_t raw = bars + 8 * (B_RAW + (j & 7)), d = dst + (j & 7) * 14336, a = d + lane * 128 + (lane & 3) * 32 + (lane >> 2) * 4;
        bool bad;
        do {
            mbar_wait(raw, (ph >> (j & 4)) & 1);
            ph ^= 1u << (j & 4);
            if (j == 0 && lane == 0) STAMP(n == 4 ? 6 : n == 32 ? 31 : 32);
            uint32_t v0, v1, v2, v3;
            asm volatile("ld.shared.u32 %0, [%4];\nld.shared.u32 %1, [%4+4096];\nld.shared.u32 %2, [%4+8192];\nld.shared.u32 %3, [%4+10240];"
                         : "=r"(v0), "=r"(v1), "=r"(v2), "=r"(v3) : "r"(a) : "memory");
            bad = __any_sync(0xffffffffu, max(max(v0, v1), max(v2, v3)) == EMPTY);
            if (elect() && bad) {
                mbar_expect(raw, 14336); bulk_ld(d, src + j * 3584, 14336, raw);
            }
        } while (bad);
        if (lane == 0) mbar_arrive(bars + 8 * (full + j));
    }
}

__device__ __forceinline__ uint32_t hcol(uint32_t a, int jp) { return (a ^ ((jp & 3) << 5)) + (jp >> 2) * 8192; }

template<bool USE_SMID>
__global__ void __launch_bounds__(384, 1)
fused_kernel(Scratch* __restrict__ sc, const __nv_bfloat16* __restrict__ wo,
             const __nv_bfloat16* __restrict__ w1, const __nv_bfloat16* __restrict__ b1,
             const __nv_bfloat16* __restrict__ w2, const __nv_bfloat16* __restrict__ b2,
             const __grid_constant__ CUtensorMap tm_x, const __grid_constant__ CUtensorMap tm_wqkv,
             const __grid_constant__ CUtensorMap tm_wo64, const __grid_constant__ CUtensorMap tm_wo48,
             const __grid_constant__ CUtensorMap tm_w1, const __grid_constant__ CUtensorMap tm_w2,
             const __grid_constant__ CUtensorMap tm_xr64, const __grid_constant__ CUtensorMap tm_xr48,
             const __grid_constant__ CUtensorMap tm_out64, const __grid_constant__ CUtensorMap tm_out48) {
    extern __shared__ __align__(1024) uint8_t smem_raw[];
    constexpr uint32_t sb = SB;
    constexpr uint32_t bars = sb + SM_BAR;
    const int tid = threadIdx.x, lane = tid & 31;
    const int warp = __shfl_sync(0xffffffffu, tid >> 5, 0);
    int slot;
    if (USE_SMID) {
        asm("{\n.reg .u32 s, t, u, d, a, b, c;\n.reg .pred p, r;\n"
            "mov.u32 s, %%smid;\nshr.u32 t, s, 1;\nsub.u32 u, t, 32;\nmul.lo.u32 d, u, 37;\nshr.u32 d, d, 8;\n"
            "and.b32 a, t, 7;\nshl.b32 a, a, 3;\nshr.u32 c, t, 3;\nadd.u32 a, a, c;\n"
            "mad.lo.u32 b, d, -55, 12;\nshl.b32 c, u, 3;\nadd.u32 b, b, c;\n"
            "setp.lt.u32 p, t, 32;\nselp.u32 a, a, b, p;\n"
            "setp.lt.u32 r, t, 64;\nselp.u32 c, 56, 0, r;\nsub.u32 c, t, c;\nsetp.lt.u32 p, t, 60;\nselp.u32 a, a, c, p;\n"
            "and.b32 s, s, 1;\nshl.b32 a, a, 1;\nadd.u32 %0, a, s;\n}" : "=r"(slot));
    } else slot = blockIdx.x;
    const int G = slot >> 4, mi = slot & 15;
    const int tb = 4 * (G >> 1) + (mi >> 2), hp = 2 * (mi & 3) + (G & 1);
    const int wcol = (hp * 56) & ~15;
    if (slot >= 128) {
        const uint32_t ep = ld_volatile(&sc->epoch[slot]) + 1;
        if (warp < 4) {
            #pragma unroll 1
            for (uint32_t e = ld_volatile(&sc->clean[mi]) == ep ? ep + 1 : ep; e != ep + 2; e++) {
                constexpr int NL = sizeof(Tiles) / 512;
                uint4* p = (uint4*)&sc->tiles[e & 1] + (mi * NL + (lane >> 1)) * 8 + (lane & 7);
                if (e != ep) {
                    while (ld_relaxed(sc->hint_h) != ep) __nanosleep(200);
                    __nanosleep(CL_AT);
                }
                #pragma unroll 7
                for (int i = warp; i < NL / 16; i += 4) st_relaxed4(p + i * 128, EMPTY, EMPTY, EMPTY, EMPTY);
                named_sync(1, 128);
                if (tid == 0) st_release(&sc->clean[mi], e);
            }
        }
        if (tid == 128) {
            const long long t0 = clock64();
            while (clock64() - t0 < SP_AT) {}
            #pragma unroll 1
            for (int i = 0; i < 7; i++) bulk_prefetch((const char*)wo + (i * 4 + mi) * 14336, 14336);
            #pragma unroll 1
            for (int i = 0; i < SP_N; i++) bulk_prefetch((const char*)w1 + (i * 4 + mi) * 14336, 14336);
            while (ld_relaxed(sc->hint_u) != ep) { __nanosleep(500); if (clock64() - t0 > WD_CLKS) __trap(); }
            sc->epoch[slot] = ep;
        }
        return;
    }
    const int q = mi & 3, tt2 = 4 * G + (mi >> 2), ft = 4 * (G - 1) + (mi >> 2);
    const bool has_b1 = G > 0;
    const int c64 = 64 * q, c48 = 256 + 48 * q;

    if (warp < 8) {
        if (WARM) {
            const int w = warp & 3, wg = warp >> 2, g = lane >> 2, t = lane & 3;
            if (WARM_AT) { const uint32_t t0 = clock32(); while (clock32() - t0 < WARM_AT) {} __syncwarp(); }
            if (w == 3 && lane < 4) st_relaxed4(sc->hint_kv + ((tb * 8 + hp) * 2 + wg) * 4 + lane, 0, 0, 0, 0);
            post_hint(sc->hint_o + ((2 * tb + (w >> 1)) * 32 + hp * 4 + (w & 1) * 2 + wg) * 2, 0, lane);
            if (wg == 0) {
                if (t < 2) st_relaxed4(sc->stats + tt2 * 256 + q * 64 + 16 * w + g + 8 * t, 0, 0, 0, 0);
                if (w == 3) { post_hint(sc->hint_h + (q * 32 + tt2) * 2, 0, lane); post_hint(sc->hint_u + (q * 32 + (ft & 31)) * 2, 0, lane); }
            }
        }
        named_sync(0, 384);
        asm volatile("setmaxnreg.inc.sync.aligned.u32 232;");
        int tid; asm volatile("mov.u32 %0, %%tid.x;" : "=r"(tid));
        const int lane = tid & 31, warp = __shfl_sync(0xffffffffu, tid >> 5, 0), wg = warp >> 2;
        const uint32_t ep = ld_volatile(&sc->epoch[slot]) + 1;
        Tiles* const tl = &sc->tiles[ep & 1];
        const int w = warp & 3, g = lane >> 2, t = lane & 3;
        const bool leader = (tid & 127) == 0;
        const uint32_t never = gridDim.y - 1;
        {
            uint32_t a[28][4];
            float accK[28], accV[28], accQ[28];
            const int lrow = 16 * w + (lane & 7) + (lane & 8);
            const uint32_t lbase = sb + wg * 8192 + lrow * 128;
            const uint32_t lx = (lane >> 4) ^ (lane & 7);
            const uint32_t wofs = hp & 1;
            auto pin2 = [&](uint32_t x0, uint32_t x1) {
                asm volatile("{\n.reg .pred p;\nsetp.ne.u32 p, %2, 0;\n@p st.shared.v2.b32 [%0], {%0,%1};\n}" :: "r"(x0), "r"(x1), "r"(never) : "memory");
            };
            float cS[2][4] = {}, cA[2][4] = {}, cB[2][4] = {}, q0 = 0.f, q1 = 0.f;
            auto sq = [&](float& acc, uint32_t v) { const float lo = bf_lo(v), hi = bf_hi(v); acc = fmaf(hi, hi, fmaf(lo, lo, acc)); };
            #pragma unroll
            for (int kb = 0; kb < 8; kb++) {
                if (kb < 7) {
                    mbar_wait(bars + 8 * (B_FULLX + kb), 0);
                    if (kb == 0 && tid == 0) STAMP(0);
                    if (kb == 6 && tid == 0) STAMP(25);
                    if (kb == 0) FST(0); if (kb == 2) FST(1); if (kb == 4) FST(2); if (kb == 6) FST(3);
                    #pragma unroll
                    for (int s = 4 * kb; s < 4 * kb + 4; s++) ldsm4(a[s], lbase + slot_x(kb) + ((lx ^ (2 * (s & 3))) << 4));
                }
                if (kb == NPIPE) continue;
                const int kc = kb < NPIPE ? kb : kb - 1;
                #pragma unroll
                for (int s = 4 * kc; s < 4 * kc + 4; s++) {
                    mma16816(cS[s & 1], a[s][0], a[s][1], a[s][2], a[s][3], 0x3F803F80u, 0x3F803F80u);
                    if (kc < NSQ) {
                        mma1688(cA[0], a[s][0], a[s][1], a[s][0]); mma1688(cA[1], a[s][2], a[s][3], a[s][2]);
                        if (SQMIX) { sq(q1, a[s][1]); sq(q1, a[s][3]); }
                        else { mma1688(cB[0], a[s][0], a[s][1], a[s][1]); mma1688(cB[1], a[s][2], a[s][3], a[s][3]); }
                    }
                }
                if (SQMIX && kc < NSQ) pin2(__float_as_uint(q1), 0);
            }
            const float m0 = (cS[0][0] + cS[1][0]) * (1.f / D_), m1 = (cS[0][2] + cS[1][2]) * (1.f / D_);
            const uint32_t mm0 = pack_bf16(m0, m0), mm1 = pack_bf16(m1, m1);
            if (lane == 0) mbar_arrive(bars + 8 * B_DONEX);
            auto center = [&](int s) { sub_bf16x2(a[s][0], mm0); sub_bf16x2(a[s][1], mm1); sub_bf16x2(a[s][2], mm0); sub_bf16x2(a[s][3], mm1); };
            uint32_t Ka[8], Kb[8], Kc[8], Va[8], Vb[7], Vc[8];
            float r0, r1, ls0, ls1;
            uint32_t pm, zero;
            uint32_t* od;
            uint4* oh;
            auto kpack = [&](uint32_t (&k)[8], int j, int c, float r) {
                const uint32_t v = pack_bf16(accK[4 * j + c] * r, accK[4 * j + c + 1] * r);
                if (j == 3) { k[3] = t < 2 ? v : 0u; k[4] = t < 2 ? 0u : v; } else k[j + (j > 3)] = v;
            };
            auto batch = [&](auto c0, auto c1) {
                constexpr int n0 = c0.value, n1 = c1.value;
                wg_fence();
                static_for<n0, n1>([&](auto nc) {
                    constexpr int n = nc.value;
                    if (n == 4) { center(4); center(5); center(6); center(7); wg_fence(); }
                    const uint64_t desc = mkdesc(sb + (n < 56 ? slot_kv(n >> 3) + (n & 7) * 2048 : SM_QO + (n - 56) * 2048), 8192, 1024, 1) + wofs;
                    wgmma_rs56<1>(n < 28 ? accK : n < 56 ? accV : accQ, a[n % 28], desc, n % 28 != 0);
                });
                wg_commit();
                if (n0 > 0) wg_wait<1>();
            };
            auto hand_over = [&](const uint32_t (&v)[8], int kv) {
                if (w < 3) {
                    mbar_wait(bars + 8 * (kv ? B_DONE1 + 5 : B_DONEX), 0);
                    uint4* hs = (uint4*)(smem_raw + (kv ? SM_HALOV : SM_HALOK)) + warp * 64 + lane;
                    hs[0] = make_uint4(v[0], v[1], v[2], v[3]); hs[32] = make_uint4(v[4], v[5], v[6], v[7]);
                } else if (tb < 15) {
                    uint4* hg = sc->halo + ((((tb + 1) * 8 + hp) * 2 + wg) * 2 + kv) * 96 + lane;
                    st_relaxed4(hg, v[0], v[1], v[2], ep); st_relaxed4(hg + 32, v[3], v[4], v[5], ep); st_relaxed4(hg + 64, v[6], v[7], ep, ep);
                    post_hint(sc->hint_kv + ((tb * 8 + hp) * 2 + wg) * 4 + kv * 2, ep, lane);
                }
            };
            auto take_over = [&](uint32_t (&v)[8], int kv) {
                if (w == 0) mbar_wait(bars + 8 * (B_HALO + 2 * kv + wg), 0);
                const uint4* hs = (const uint4*)(smem_raw + (kv ? SM_HALOV : SM_HALOK)) + (w ? warp - 1 : warp + 3) * 64 + lane;
                const uint4 u0 = hs[0], u1 = hs[32];
                v[0] = u0.x; v[1] = u0.y; v[2] = u0.z; v[3] = u0.w; v[4] = u1.x; v[5] = u1.y; v[6] = u1.z; v[7] = u1.w;
            };
            center(0); center(1); center(2); center(3);
            static_for<0, 7>([&](auto pc) {
                constexpr int p = pc.value;
                mbar_wait(bars + 8 * (B_FULLKV + p), 0);
                if (p == 0 && tid == 0) STAMP(26);
                if (p == 3 && tid == 0) STAMP(27);
                FST(4 + p);
                batch(Int<8 * p>(), Int<8 * p + 8>());
                if (p > 0 && leader) mbar_arrive(bars + 8 * (B_DONE1 + p - 1));
                #pragma unroll
                for (int s = 8 * p + 8; s < 8 * p + 16 && s < 28; s++) {
                    if (s >= 4 * NSQ) { sq(q0, a[s][0]); sq(q1, a[s][1]); sq(q0, a[s][2]); sq(q1, a[s][3]); }
                    center(s);
                }
                if (p == 3) {
                    if (t == (g >> 1)) { q0 += (g & 1) ? cA[0][1] + cA[1][1] : cA[0][0] + cA[1][0]; if (!SQMIX) q1 += (g & 1) ? cB[0][3] + cB[1][3] : cB[0][2] + cB[1][2]; }
                    q0 = quad_sum(q0); q1 = quad_sum(q1);
                    r0 = rsqrt_approx(fmaxf(q0 * (1.f / D_) - m0 * m0, 0.f) + LN_EPS); r1 = rsqrt_approx(fmaxf(q1 * (1.f / D_) - m1 * m1, 0.f) + LN_EPS);
                    pin2(__float_as_uint(r0), __float_as_uint(r1));
                }
                if (p == 4) {
                    reg_fence(accK);
                    #pragma unroll
                    for (int j = 0; j < 7; j++) kpack(Kc, j, 2, r1);
                    hand_over(Kc, 0);
                }
                if (p == 5) {
                    #pragma unroll
                    for (int j = 0; j < 7; j++) kpack(Kb, j, 0, r0);
                    #pragma unroll
                    for (int j = 0; j < 8; j += 2) pin2(Kb[j], Kb[j + 1]);
                    ls0 = LOG2E_SCALE * r0; ls1 = LOG2E_SCALE * r1;
                    pm = (2 * t <= g ? 0xFFFFu : 0u) | (2 * t + 1 <= g ? 0xFFFF0000u : 0u);
                    zero = never; asm volatile("" : "+r"(zero));
                    pin2(__float_as_uint(ls0), __float_as_uint(ls1)); pin2(pm, zero);
                }
                if (p == 6) {
                    const int tt = 2 * tb + (w >> 1);
                    od = tl->o + tt * 14336 + (7 * hp) * 256 + (2 * (2 * (w & 1) + wg)) * 32 + lane;
                    oh = sc->hint_o + (tt * 32 + hp * 4 + (w & 1) * 2 + wg) * 2 + (lane & 1);
                    pin2((uint32_t)(uint64_t)od, (uint32_t)((uint64_t)od >> 32));
                    pin2((uint32_t)(uint64_t)oh, (uint32_t)((uint64_t)oh >> 32));
                }
            });
            if (tid == 0) STAMP(1);
            FST(11);
            mbar_wait(bars + 8 * B_FQ, 0);
            batch(Int<56>(), Int<60>());
            reg_fence(accV);
            if (leader) mbar_arrive(bars + 8 * (B_DONE1 + 6));
            if (tid == 0) STAMP(2);
            FST(12);
            #pragma unroll
            for (int j = 0; j < 7; j++) Vc[j] = movtrans(pack_bf16(accV[4 * j + 2] * r1, accV[4 * j + 3] * r1));
            Vc[7] = ep;
            hand_over(Vc, 1);
            if (tid == 96) STAMP(23);
            batch(Int<60>(), Int<66>());
            #pragma unroll
            for (int j = 0; j < 7; j++) {
                Vb[j] = movtrans(pack_bf16(accV[4 * j] * r0, accV[4 * j + 1] * r0));
                Vc[j] |= zero;
            }
            batch(Int<66>(), Int<72>());
            #pragma unroll
            for (int j = 0; j < 7; j++) pin2(Vb[j], Vc[j]);
            mbar_wait(bars + 8 * (B_FQ + 1), 0);
            mbar_wait(bars + 8 * B_CLR, 0);
            FST(13);
            batch(Int<72>(), Int<84>());
            FST(14);
            named_sync(1 + wg, 128);
            take_over(Ka, 0);
            if (tid == 0) STAMP(3);
            wg_wait<0>();
            reg_fence(accQ);
            if (tid == 0) STAMP(4);
            FST(15);
            const bool first = (tb == 0 && w == 0);
            uint32_t pA[2], pB0[2], pB1[2], pC[2], z0[2], z1[2];
            #pragma unroll
            for (int h = 0; h < 2; h++) {
                float sA[4] = {0.f, 0.f, 0.f, 0.f}, sB[4] = {0.f, 0.f, 0.f, 0.f}, sC[4] = {0.f, 0.f, 0.f, 0.f};
                #pragma unroll
                for (int k = 0; k < 2; k++) {
                    const float* qq = accQ + 12 * h + 8 * k;
                    uint32_t a0 = pack_bf16(qq[0], qq[1]), a1 = pack_bf16(qq[2], qq[3]);
                    if (h == 1 && k == 0) { a0 |= zero; a1 |= zero; }
                    const uint32_t a2 = pack_bf16(qq[4], qq[5]), a3 = pack_bf16(qq[6], qq[7]);
                    mma16816(sB, a0, a1, a2, a3, Kb[4 * h + 2 * k], Kb[4 * h + 2 * k + 1]);
                    mma16816(sA, a0, a1, a2, a3, Ka[4 * h + 2 * k], Ka[4 * h + 2 * k + 1]);
                    mma16816(sC, a0, a1, a2, a3, Kc[4 * h + 2 * k], Kc[4 * h + 2 * k + 1]);
                }
                const bool n0 = pm & 1, n1 = (int)pm < 0;
                const float l00 = n0 ? sB[0] : (first ? -INFINITY : sA[0]), l01 = n1 ? sB[1] : (first ? -INFINITY : sA[1]);
                const float l10 = n0 ? sC[2] : sB[2], l11 = n1 ? sC[3] : sB[3];
                const float x0 = -ls0 * quad_max(fmaxf(l00, l01)), x1 = -ls1 * quad_max(fmaxf(l10, l11));
                const float e00 = ex2(fmaf(l00, ls0, x0)), e01 = ex2(fmaf(l01, ls0, x0)), e10 = ex2(fmaf(l10, ls1, x1)), e11 = ex2(fmaf(l11, ls1, x1));
                const float i0 = rcp_approx(quad_sum(e00 + e01)), i1 = rcp_approx(quad_sum(e10 + e11));
                const uint32_t P0 = pack_bf16(e00 * i0, e01 * i0), P1 = pack_bf16(e10 * i1, e11 * i1);
                pB0[h] = P0 & pm; pA[h] = P0 & ~pm; pC[h] = P1 & pm; pB1[h] = P1 & ~pm; z0[h] = P0 & zero; z1[h] = P1 & zero;
            }
            float o[8][4];
            #pragma unroll
            for (int j = 0; j < 8; j++) {
                o[j][0] = o[j][1] = o[j][2] = o[j][3] = 0.f;
                mma16816(o[j], pB0[j >> 2], pB1[j >> 2], z0[j >> 2], pC[j >> 2], Vb[j - (j >> 2)], Vc[j - (j >> 2)]);
            }
            if (tid == 0) STAMP(12);
            FST(16);
            take_over(Va, 1);
            if (HINT_O == 1 && lane < 2) st_relaxed4(oh, ep, ep, ep, ep);
            if (lane == 0) mbar_arrive(bars + 8 * B_DONEQ);
            if (tid == 0) STAMP(16);
            #pragma unroll
            for (int j = 0; j < 8; j++) mma1688(o[j], pA[j >> 2], z1[j >> 2], Va[j - (j >> 2)]);
            #pragma unroll
            for (int j = 0; j < 7; j++) {
                float v[4];
                #pragma unroll
                for (int c = 0; c < 4; c++) v[c] = j < 3 ? o[j][c] : j > 3 ? o[j + 1][c] : (t < 2 ? o[3][c] : o[4][c]);
                od[j * 256] = pack_bf16(v[0], v[1]);
                od[j * 256 + 32] = pack_bf16(v[2], v[3]);
            }
            if (tid == 0) STAMP(5);
            FST(17);
            if (HINT_O == 0 && lane < 2) st_relaxed4(oh, ep, ep, ep, ep);
        }
        if (wg == 1) {
            uint32_t ph = 0;
            check_tiles(TSVAL 4, w, lane, ph, sb + SM_QO, tl->o + tt2 * 14336, B_FULLO);
            if (has_b1) check_tiles(TSVAL 32, w, lane, ph, sb + SM_BRING, tl->hn + q * 32 * 3584, B_FULLB);
            check_tiles(TSVAL 28, w, lane, ph, sb + SM_BRING, tl->u + q * 28 * 3584, B_FULLB);
        } else {
            const uint32_t rb10 = has_b1 ? __ldg((const unsigned short*)b1 + ft * 64 + 16 * w + g) : 0, rb11 = has_b1 ? __ldg((const unsigned short*)b1 + ft * 64 + 16 * w + g + 8) : 0;
            const uint32_t rb20 = __ldg((const unsigned short*)b2 + tt2 * 64 + 16 * w + g), rb21 = __ldg((const unsigned short*)b2 + tt2 * 64 + 16 * w + g + 8);
            {
                float acc[56];
                const int hrow = 32 * (w >> 1) + 2 * ((lane & 7) + (lane & 8)) + (w & 1);
                const uint32_t ha = sb + SM_H + hrow * 128 + (((lane >> 4) ^ (hrow & 7)) << 4);
                mbar_wait(bars + 8 * B_FULLWO, 0);
                #pragma unroll
                for (int jp = 0; jp < 7; jp++) {
                    uint32_t xx[4];
                    ldsm4(xx, hcol(ha, jp));
                    #pragma unroll
                    for (int r = 0; r < 4; r++) { acc[8 * jp + 2 * r] = bf_lo(xx[r]); acc[8 * jp + 2 * r + 1] = bf_hi(xx[r]); }
                }
                reg_fence(acc);
                float accl[32], accr[24];
                auto od_ = [&](int s) { return mkdesc(sb + SM_QO + s * 2048, 1024, 128, 0); };
                auto wd_ = [&](int s) { return mkdesc(sb + slot_wo(s >> 2) + (s & 3) * 2048, 8192, 1024, 1); };
                #pragma unroll
                for (int i = 0; i < 5; i++) {
                    if (i < 4) mbar_wait(bars + 8 * (B_FULLO + i), 0);
                    if (i == 0 && tid == 0) STAMP(7);
                    wg_fence();
                    #pragma unroll
                    for (int ss = 0; ss < 7; ss++) {
                        if (i < 3) wgmma_ss112<0, 1>(acc, od_(7 * i + ss), wd_(7 * i + ss));
                        else if (i == 3) { if (ss == 0) wgmma_ss64<0, 1, 0>(accl, od_(21), wd_(21)); else wgmma_ss64<0, 1>(accl, od_(21 + ss), wd_(21 + ss)); }
                        else wgmma_ss48<0, 1>(accr, od_(21 + ss), wd_(21 + ss) + 512);
                    }
                    wg_commit();
                    if (i > 0) {
                        wg_wait<1>();
                        if (i == 3) {
                            reg_fence(acc);
                            #pragma unroll
                            for (int c = 0; c < 24; c++) accr[c] = __uint_as_float(__float_as_uint(acc[32 + c]) | never);
                            reg_fence(accr);
                        }
                        if (i < 4 && leader) mbar_arrive(bars + 8 * (B_DONEO + i - 1));
                    }
                }
                float s0 = 0.f, s1 = 0.f, q0 = 0.f, q1 = 0.f, s2 = 0.f, s3 = 0.f, q2 = 0.f, q3 = 0.f;
                reg_fence(accl);
                #pragma unroll
                for (int c = 0; c < 32; c++) acc[c] += accl[c];
                #pragma unroll
                for (int j = 0; j < 14; j++) {
                    if (j == 8) {
                        pin4(never, s0, s1, s2, s3); pin4(never, q0, q1, q2, q3);
                        wg_wait<0>();
                        reg_fence(accr);
                        #pragma unroll
                        for (int c = 0; c < 24; c++) acc[32 + c] = accr[c];
                        if (leader) mbar_arrive(bars + 8 * (B_DONEO + 3));
                        if (tid == 0) STAMP(8);
                    }
                    s0 += acc[4 * j]; s2 += acc[4 * j + 1]; q0 = fmaf(acc[4 * j], acc[4 * j], q0); q2 = fmaf(acc[4 * j + 1], acc[4 * j + 1], q2);
                    s1 += acc[4 * j + 2]; s3 += acc[4 * j + 3]; q1 = fmaf(acc[4 * j + 2], acc[4 * j + 2], q1); q3 = fmaf(acc[4 * j + 3], acc[4 * j + 3], q3);
                }
                s0 = quad_sum(s0 + s2); s1 = quad_sum(s1 + s3); q0 = quad_sum(q0 + q2); q1 = quad_sum(q1 + q3);
                uint4* sp = sc->stats + tt2 * 256 + 16 * w + g;
                if (t < 2) st_relaxed4(sp + q * 64 + 8 * t, __float_as_uint(t ? s1 : s0), ep, __float_as_uint(t ? q1 : q0), ep);
                if (tid == 0) STAMP(9);
                #pragma unroll
                for (int jp = 0; jp < 7; jp++)
                    stsm4(hcol(ha, jp), pack_bf16(acc[8 * jp], acc[8 * jp + 1]), pack_bf16(acc[8 * jp + 2], acc[8 * jp + 3]),
                          pack_bf16(acc[8 * jp + 4], acc[8 * jp + 5]), pack_bf16(acc[8 * jp + 6], acc[8 * jp + 7]));
                {
                    uint4 v0, v1;
                    do {
                        v0 = ld_relaxed4(sp + t * 64); v1 = ld_relaxed4(sp + t * 64 + 8);
                    } while (__any_sync(0xffffffffu, t != q && (v0.y != ep || v0.w != ep || v1.y != ep || v1.w != ep)));
                    if (t != q) { s0 = __uint_as_float(v0.x); q0 = __uint_as_float(v0.z); s1 = __uint_as_float(v1.x); q1 = __uint_as_float(v1.z); }
                }
                if (tid == 0) STAMP(10);
                s0 = quad_sum(s0); s1 = quad_sum(s1); q0 = quad_sum(q0); q1 = quad_sum(q1);
                const float m0 = s0 * (1.f / D_), m1 = s1 * (1.f / D_);
                const float v0 = fmaxf(q0 * (1.f / D_) - m0 * m0, 0.f), v1 = fmaxf(q1 * (1.f / D_) - m1 * m1, 0.f);
                const float r0 = rsqrt_approx(fmaf(v0, 4.f + 4.f * LN_EPS, 4.f * LN_EPS * LN_EPS)), r1 = rsqrt_approx(fmaf(v1, 4.f + 4.f * LN_EPS, 4.f * LN_EPS * LN_EPS));
                const float c0 = -m0 * r0, c1 = -m1 * r1;
                uint32_t* hd = tl->hn + (q * 32 + tt2) * 3584 + (2 * w) * 448 + lane;
                #pragma unroll
                for (int j = 0; j < 14; j++) {
                    if (j == HINT_H) post_hint_wg(sc->hint_h + (q * 32 + tt2) * 2, ep, w, lane);
                    hd[j * 32] = pack_bf16(fmaf(acc[4 * j], r0, c0), fmaf(acc[4 * j + 1], r0, c0));
                    hd[j * 32 + 448] = pack_bf16(fmaf(acc[4 * j + 2], r1, c1), fmaf(acc[4 * j + 3], r1, c1));
                }
                if (tid == 0) STAMP(11);
                if (HINT_H == 14) post_hint_wg(sc->hint_h + (q * 32 + tt2) * 2, ep, w, lane);
                if (tid == 96) STAMP(33);
            }
            if (has_b1) {
                float acc[56];
                #pragma unroll
                for (int j = 0; j < 56; j++) acc[j] = 0.5f * bf_lo((j & 2) ? rb11 : rb10);
                uint32_t* ud = tl->u + (q * 28 + ft) * 3584 + (2 * w) * 448 + lane;
                auto ustore = [&](auto& acc, int j0, int j1) {
                    #pragma unroll
                    for (int j = j0; j < j1; j++) {
                        if (j == HINT_U) post_hint_wg(sc->hint_u + (q * 32 + ft) * 2, ep, w, lane);
                        st_global(ud + j * 32, pack_bf16(gelu_half(acc[4 * j]), gelu_half(acc[4 * j + 1])));
                        st_global(ud + j * 32 + 448, pack_bf16(gelu_half(acc[4 * j + 2]), gelu_half(acc[4 * j + 3])));
                    }
                };
                mix_mainloop<32, TAIL3, true>(TSVAL acc, 0, leader, never, [&](auto ic, auto& al) { constexpr int i = ic.value; ustore(al, 8 * i / (TAIL3 - 1), 8 * (i + 1) / (TAIL3 - 1)); });
                if (tid == 0) STAMP(14);
                ustore(acc, TAIL3 ? 8 : 0, 14);
                if (tid == 0) STAMP(15);
                if (HINT_U == 14) post_hint_wg(sc->hint_u + (q * 32 + ft) * 2, ep, w, lane);
                if (tid == 96) STAMP(34);
            }
            {
                float acc[56];
                const float bb0 = bf_lo(rb20), bb1 = bf_lo(rb21);
                named_sync(1, 128);
                const uint32_t ad = sb + SM_H + (16 * w + (lane & 15)) * 128 + (((lane >> 4) ^ (lane & 7)) << 4);
                #pragma unroll
                for (int jp = 0; jp < 7; jp++) {
                    uint32_t hh[4];
                    ldsm4(hh, hcol(ad, jp));
                    #pragma unroll
                    for (int r = 0; r < 4; r++) { acc[8 * jp + 2 * r] = bf_lo(hh[r]) + ((r & 1) ? bb1 : bb0); acc[8 * jp + 2 * r + 1] = bf_hi(hh[r]) + ((r & 1) ? bb1 : bb0); }
                }
                auto ostore = [&](auto& acc, int half) {
                    #pragma unroll
                    for (int jp = 4 * half; jp < 4 + 3 * half; jp++)
                        stsm4(hcol(ad, jp), pack_bf16(acc[8 * jp], acc[8 * jp + 1]), pack_bf16(acc[8 * jp + 2], acc[8 * jp + 3]),
                              pack_bf16(acc[8 * jp + 4], acc[8 * jp + 5]), pack_bf16(acc[8 * jp + 6], acc[8 * jp + 7]));
                    if (!TAIL4 && !half) return;
                    fence_async_smem();
                    __syncwarp();
                    if (!TAIL4 && elect()) tma2d_store(&tm_out64, c64, tt2 * 64 + 16 * w, sb + SM_H + w * 2048);
                    if (elect()) tma2d_store(half ? &tm_out48 : &tm_out64, half ? c48 : c64, tt2 * 64 + 16 * w, sb + SM_H + half * 8192 + w * 2048);
                };
                mix_mainloop<28, TAIL4, false>(TSVAL acc, has_b1, leader, never, [&](auto ic, auto& al) { if (ic.value == 0) ostore(al, 0); });
                if (leader) mbar_arrive(bars + 8 * B_END);
                if (tid == 0) STAMP(18);
                if (!TAIL4) ostore(acc, 0);
                ostore(acc, 1);
                asm volatile("cp.async.bulk.commit_group;" ::: "memory");
                asm volatile("cp.async.bulk.wait_group.read 0;" ::: "memory");
                if (tid == 0) { sc->epoch[slot] = ep; STAMP(19); }
            }
        }
    } else {
        asm volatile("setmaxnreg.dec.sync.aligned.u32 40;");
        int warp2; asm("mov.u32 %0, %1;" : "=r"(warp2) : "r"(warp));
        if (warp2 > 8) {
            if (elect()) {
                if (warp == 9) {
                    #pragma unroll
                    for (int i = B_DONE1; i < B_DONEO; i++) mbar_init(bars + 8 * i, i < B_DONEX ? 2 : 8);
                    mbar_init(bars + 8 * B_CLR, 1);
                }
                #pragma unroll
                for (int i = 0; i < 34; i++) mbar_init(bars + 8 * (B_DONEO + i) + (warp - 9) * 272, 1);
                asm volatile("fence.mbarrier_init.release.cluster;" ::: "memory");
            }
            named_sync(0, 384);
            if (warp == 9) named_arrive(4, 64);
            if (warp < 11) {
                const uint32_t ep = ld_volatile(&sc->epoch[slot]) + 1;
                mbar_wait(bars + 8 * (B_DONE1 + HALO_AT), 0);
                #pragma unroll 1
                for (int kv = 0; kv < 2; kv++) {
                    uint4 v0 = {}, v1 = {}, v2 = {};
                    if (tb > 0) {
                        const uint4* hg = sc->halo + (((tb * 8 + hp) * 2 + warp - 9) * 2 + kv) * 96 + lane;
                        while (ld_relaxed(sc->hint_kv + (((tb - 1) * 8 + hp) * 2 + warp - 9) * 4 + kv * 2) != ep) {}
                        do { v0 = ld_relaxed4(hg); v1 = ld_relaxed4(hg + 32); v2 = ld_relaxed4(hg + 64); } while (!__all_sync(0xffffffffu, v0.w == ep && v1.w == ep && v2.w == ep));
                    }
                    if (kv) mbar_wait(bars + 8 * (B_DONE1 + 5), 0);
                    uint4* hs = (uint4*)(smem_raw + (kv ? SM_HALOV : SM_HALOK)) + (4 * warp - 33) * 64 + lane;
                    hs[0] = make_uint4(v0.x, v0.y, v0.z, v1.x); hs[32] = make_uint4(v1.y, v1.z, v2.x, v2.y);
                    __syncwarp();
                    if (lane == 0) mbar_arrive(bars + 8 * (B_HALO + 2 * kv + warp - 9));
                }
                if (tid == 288) STAMP(21);
            }
            if (warp == 10) {
                if (!has_b1 && lane == 0) {
                    mbar_wait(bars + 8 * (B_DONEO + 3), 0);
                    uint32_t t = clock32() + PF_AT;
                    #pragma unroll 1
                    for (int i = 0; i < PF_N; i++) {
                        while ((int)(clock32() - t) < 0) __nanosleep(40);
                        bulk_prefetch((const char*)w2 + (i * 16 + mi) * 16384, 16384);
                        t += PF_PACE;
                    }
                }
            } else if (warp == 11) {
                const uint32_t ep = ld_volatile(&sc->epoch[slot]) + 1;
                const long long t0 = clock64();
                while (__any_sync(0xffffffffu, (int)(ld_acquire(&sc->clean[lane & 3]) - ep) < 0)) if (clock64() - t0 > WD_CLKS) __trap();
                if (lane == 0) mbar_arrive(bars + 8 * B_CLR);
                if (lane == 0) {
                    mbar_wait_wd(bars + 8 * B_END, 0);
                }
            } else {
                int aslot = 0;
                if (lane == 0) { prefetch_map(&tm_out64); prefetch_map(&tm_out48); }
                if (has_b1) {
                    #pragma unroll 1
                    for (int i = 0; i < 16; i++) {
                        mbar_wait(bars + 8 * (i < NA_SLOTS ? B_DONEQ + ((A_SCHED >> (4 * i)) & 15) : B_DONE + 1 + ((i - NA_SLOTS) * A3_END) / (15 - NA_SLOTS)), 0);
                        if (elect()) {
                            const uint32_t bar = bars + 8 * (B_FULLA + i), dst = sb + SM_ARING + aslot * 16384;
                            mbar_expect(bar, 16384);
                            tma3d(dst, &tm_w1, ft * 64, 0, i * 64, bar);
                            tma3d(dst + 8192, &tm_w1, ft * 64, 1, i * 64, bar);
                        }
                        aslot = aslot == NA_SLOTS - 1 ? 0 : aslot + 1;
                    }
                }
                aslot = 16 % NA_SLOTS;
                #pragma unroll 1
                for (int i = 0; i < 14; i++) {
                    if (i >= NA_SLOTS) mbar_wait(bars + 8 * (B_DONE + 1 + ((i - NA_SLOTS) * A4_END) / (13 - NA_SLOTS)), has_b1);
                    else if (has_b1) {
                        mbar_wait(bars + 8 * (B_DONE + (i < (TAIL3 > 2 ? 6 - TAIL3 / 2 : 5) ? max(33 - 2 * NA_SLOTS + 2 * i, W2_AT) : 31)), 0);
                        if (i >= W2_HOLD) mbar_wait(bars + 8 * B_FULLB, 1);
                    } else if (i == 0) { mbar_wait(bars + 8 * (B_DONEO + 3), 0); const uint32_t t = clock32() + PF_AT + 12 * PF_PACE; while ((int)(clock32() - t) < 0) __nanosleep(100); }
                    if (elect()) {
                        const uint32_t bar = bars + 8 * (B_FULLA + i);
                        mbar_expect(bar, 16384);
                        tma2d(sb + SM_ARING + aslot * 16384, &tm_w2, tt2 * 64, i * 128, bar);
                    }
                    aslot = aslot == NA_SLOTS - 1 ? 0 : aslot + 1;
                }
            }
        } else {
            auto krot = [&](int kb) { const int k = kb * 64 + (G & 1) * 64 * ROT; return k < 448 ? k : k - 448; };
            if (elect()) {
                #pragma unroll
                for (int i = 0; i < 7; i++) mbar_init(bars + 8 * i, 1);
                asm volatile("fence.mbarrier_init.release.cluster;" ::: "memory");
                #pragma unroll 1
                for (int kb = 0; kb < 7; kb++) {
                    const uint32_t st = sb + slot_x(kb), bar = bars + 8 * (B_FULLX + kb);
                    mbar_expect(bar, 16384);
                    tma3d(st, &tm_x, krot(kb), 0, tb * 64, bar); tma3d(st + 8192, &tm_x, krot(kb), 1, tb * 64, bar);
                }
                #pragma unroll
                for (int i = 7; i < B_DONE1; i++) mbar_init(bars + 8 * i, 1);
                asm volatile("fence.mbarrier_init.release.cluster;" ::: "memory");
            }
            named_arrive(0, 384);
            #pragma unroll 1
            for (int kb = 0; kb < 7; kb++) {
                if (kb == 6) { named_sync(4, 64); mbar_wait(bars + 8 * B_DONEX, 0); }
                if (elect()) {
                    const uint32_t st = sb + slot_kv(kb), bar = bars + 8 * (B_FULLKV + kb);
                    mbar_expect(bar, 16384);
                    #pragma unroll
                    for (int i = 0; i < 2; i++) {
                        const int n = 2 * kb + (ROT ? i : i ^ (G & 1));
                        tma2d(st + (n & 1) * 8192, &tm_wqkv, (n < 7 ? 448 : 896) + wcol, krot(n < 7 ? n : n - 7), bar);
                    }
                }
            }
            if (elect()) {
                mbar_expect(bars + 8 * B_FQ, 32768);
                mbar_expect(bars + 8 * (B_FQ + 1), 24576);
                #pragma unroll 1
                for (int i = 0; i < 7; i++) { const int j = ROT || i == 6 ? i : i ^ (G & 1); tma2d(sb + SM_QO + j * 8192, &tm_wqkv, wcol, krot(j), bars + 8 * (B_FQ + (i >> 2))); }
                mbar_expect(bars + 8 * B_FULLWO, 512 * 112 * 2);
            }
            #pragma unroll 1
            for (int i = 0; i < 7; i++) {
                const int kb = ((q & 1 ? WO_ORD1 : WO_ORD0) >> (4 * i)) & 7;
                if (kb < 5) mbar_wait(bars + 8 * (B_DONE1 + kb), 0);
                if (i == WO_HOLD) { mbar_wait(bars + 8 * (B_HALO + 2), 0); mbar_wait(bars + 8 * (B_HALO + 3), 0); }
                if (elect()) {
                    tma2d(sb + slot_wo(kb), &tm_wo64, c64, kb * 64, bars + 8 * B_FULLWO);
                    tma2d(sb + slot_wo(kb) + 8192, &tm_wo48, c48, kb * 64, bars + 8 * B_FULLWO);
                }
            }
            if (XR_HOLD) { mbar_wait(bars + 8 * (B_HALO + 2), 0); mbar_wait(bars + 8 * (B_HALO + 3), 0); }
            if (elect()) {
                tma2d(sb + SM_H, &tm_xr64, c64, tt2 * 64, bars + 8 * B_FULLWO);
                tma2d(sb + SM_H + 8192, &tm_xr48, c48, tt2 * 64, bars + 8 * B_FULLWO);
            }
            if (smem_u32(smem_raw) != SB) __trap();
            const uint32_t ep = ld_volatile(&sc->epoch[slot]) + 1;
            const Tiles* const tl = &sc->tiles[ep & 1];
            mbar_wait(bars + 8 * B_DONEQ, 0);
            {
                uint32_t issued = 0;
                while (issued != 0x01010101u) {
                    uint32_t m = __ballot_sync(0xffffffffu, ld_relaxed(sc->hint_o + (tt2 * 32 + lane) * 2) == ep);
                    m &= m >> 4; m &= m >> 2; m &= m >> 1; m &= 0x01010101u & ~issued;
                    if ((m >> lane) & 1) {
                        const uint32_t bar = bars + 8 * B_RAW + lane;
                        mbar_expect(bar, 14336);
                        bulk_ld(sb + SM_QO + lane * 1792, tl->o + tt2 * 14336 + lane * 448, 14336, bar);
                    }
                    issued |= m;
                }
                __syncwarp();
            }
            if (lane == 0) STAMP(20);
            mbar_wait(bars + 8 * (B_DONEO + 3), 0);
            if (has_b1) {
                mix_producer_b<32>(TSVAL 0, sc->hint_h + q * 64, ep, tl->hn + q * 32 * 3584, lane);
                mbar_wait(bars + 8 * (B_DONE + 31), 0);
            }
            mix_producer_b<28>(TSVAL has_b1, sc->hint_u + q * 64, ep, tl->u + q * 28 * 3584, lane);
        }
    }
}

typedef CUresult (*EncodeFn)(CUtensorMap*, CUtensorMapDataType, cuuint32_t, void*, const cuuint64_t*, const cuuint64_t*, const cuuint32_t*,
                             const cuuint32_t*, CUtensorMapInterleave, CUtensorMapSwizzle, CUtensorMapL2promotion, CUtensorMapFloatOOBfill);

void make_map(EncodeFn fn, CUtensorMap* tm, const void* ptr, int rank, const cuuint64_t* dims, const cuuint64_t* strides, const cuuint32_t* box, CUtensorMapSwizzle sw) {
    cuuint32_t es[3] = {1, 1, 1};
    fn(tm, CU_TENSOR_MAP_DATA_TYPE_BFLOAT16, rank, const_cast<void*>(ptr), dims, strides, box, es, CU_TENSOR_MAP_INTERLEAVE_NONE, sw,
       CU_TENSOR_MAP_L2_PROMOTION_NONE, CU_TENSOR_MAP_FLOAT_OOB_FILL_NONE);
}

}

extern "C" void kernel_launch(void* const* d_in, const int* in_sizes, int n_in, void* d_out, int out_size) {
    const __nv_bfloat16* x = (const __nv_bfloat16*)d_in[0];
    const __nv_bfloat16* wqkv = (const __nv_bfloat16*)d_in[1];
    const __nv_bfloat16* wo = (const __nv_bfloat16*)d_in[2];
    const __nv_bfloat16* w1 = (const __nv_bfloat16*)d_in[4];
    const __nv_bfloat16* b1 = (const __nv_bfloat16*)d_in[5];
    const __nv_bfloat16* w2 = (const __nv_bfloat16*)d_in[6];
    const __nv_bfloat16* b2 = (const __nv_bfloat16*)d_in[7];

    void* fnp = nullptr; cudaDriverEntryPointQueryResult qr;
    cudaGetDriverEntryPoint("cuTensorMapEncodeTiled", &fnp, cudaEnableDefault, &qr);
    EncodeFn fn = (EncodeFn)fnp;
    CUtensorMap tx, twqkv, two64, two48, tw1, tw2, txr64, txr48, tout64, tout48;
    { cuuint64_t d[3] = {448, 2, 1024}, s[2] = {896, 1792}; cuuint32_t b[3] = {64, 1, 64}; make_map(fn, &tx, x, 3, d, s, b, CU_TENSOR_MAP_SWIZZLE_128B); }
    { cuuint64_t d[2] = {1344, 448}, s[1] = {2688}; cuuint32_t b[2] = {64, 64}; make_map(fn, &twqkv, wqkv, 2, d, s, b, CU_TENSOR_MAP_SWIZZLE_128B); }
    { cuuint64_t d[2] = {448, 448}, s[1] = {896}; cuuint32_t b[2] = {64, 64}; make_map(fn, &two64, wo, 2, d, s, b, CU_TENSOR_MAP_SWIZZLE_128B); }
    { cuuint64_t d[2] = {448, 448}, s[1] = {896}; cuuint32_t b[2] = {48, 64}; make_map(fn, &two48, wo, 2, d, s, b, CU_TENSOR_MAP_SWIZZLE_128B); }
    { cuuint64_t d[3] = {1792, 2, 1024}, s[2] = {3584, 7168}; cuuint32_t b[3] = {64, 1, 64}; make_map(fn, &tw1, w1, 3, d, s, b, CU_TENSOR_MAP_SWIZZLE_128B); }
    { cuuint64_t d[2] = {2048, 1792}, s[1] = {4096}; cuuint32_t b[2] = {64, 128}; make_map(fn, &tw2, w2, 2, d, s, b, CU_TENSOR_MAP_SWIZZLE_128B); }
    { cuuint64_t d[2] = {448, 2048}, s[1] = {896}; cuuint32_t b[2] = {64, 64}; make_map(fn, &txr64, x, 2, d, s, b, CU_TENSOR_MAP_SWIZZLE_128B); }
    { cuuint64_t d[2] = {448, 2048}, s[1] = {896}; cuuint32_t b[2] = {48, 64}; make_map(fn, &txr48, x, 2, d, s, b, CU_TENSOR_MAP_SWIZZLE_128B); }
    { cuuint64_t d[2] = {448, 2048}, s[1] = {896}; cuuint32_t b[2] = {64, 16}; make_map(fn, &tout64, d_out, 2, d, s, b, CU_TENSOR_MAP_SWIZZLE_128B); }
    { cuuint64_t d[2] = {448, 2048}, s[1] = {896}; cuuint32_t b[2] = {48, 16}; make_map(fn, &tout48, d_out, 2, d, s, b, CU_TENSOR_MAP_SWIZZLE_128B); }

    void* scv = nullptr;
    cudaGetSymbolAddress(&scv, g_scratch);
    Scratch* scp = (Scratch*)scv;
    int dev = 0, sms = 0;
    cudaGetDevice(&dev);
    cudaDeviceGetAttribute(&sms, cudaDevAttrMultiProcessorCount, dev);
    if (sms == 132) {
        cudaFuncSetAttribute(fused_kernel<true>, cudaFuncAttributeMaxDynamicSharedMemorySize, SM_TOTAL);
        fused_kernel<true><<<132, 384, SM_TOTAL>>>(scp, wo, w1, b1, w2, b2, tx, twqkv, two64, two48, tw1, tw2, txr64, txr48, tout64, tout48);
    } else {
        cudaFuncSetAttribute(fused_kernel<false>, cudaFuncAttributeMaxDynamicSharedMemorySize, SM_TOTAL);
        fused_kernel<false><<<132, 384, SM_TOTAL>>>(scp, wo, w1, b1, w2, b2, tx, twqkv, two64, two48, tw1, tw2, txr64, txr48, tout64, tout48);
    }
}
```

```cpp
#include <cuda_runtime.h>
#include <cuda_bf16.h>
#include <cuda.h>
#include <stdint.h>

namespace {

constexpr int D_ = 448;
constexpr float LN_EPS = 1e-5f;
constexpr float LOG2E_SCALE = 0.1889822365046136f * 1.4426950408889634f;

struct Tiles {
    uint32_t o[32 * 57344 / 4];
    uint32_t hn[4 * 32 * 14336 / 4];
    uint32_t u[4 * 28 * 14336 / 4];
};
struct Scratch {
    Tiles tiles[2];
    uint4 halo[128 * 2 * 2 * 3 * 32];
    uint4 stats[32 * 4 * 64];
    uint4 hint_kv[128 * 2 * 2 * 2];
    uint4 hint_o[32 * 32 * 2];
    uint4 hint_h[4 * 32 * 2];
    uint4 hint_u[4 * 32 * 2];
    uint32_t epoch[160];
    uint32_t clean[4];
};
__device__ __align__(1024) Scratch g_scratch;
#define STAMP(i) do {} while (0)
#define FST(i) do {} while (0)
#define TSARG
#define TSVAL

constexpr uint32_t SB = 1024;
constexpr int SM_SLOT = 16384;
__device__ __forceinline__ constexpr uint32_t slot_x(int kb) { return (kb ? 6 + kb : 0) * SM_SLOT; }
__device__ __forceinline__ constexpr uint32_t slot_kv(int kb) { return (kb < 5 ? 2 + kb : 6 - kb) * SM_SLOT; }
__device__ __forceinline__ constexpr uint32_t slot_wo(int kb) { return (kb < 6 ? 2 + kb : 12) * SM_SLOT; }
constexpr int SM_QO = 8 * SM_SLOT;
constexpr int SM_HALOK = SM_QO + 57344, SM_HALOV = 1 * SM_SLOT;
constexpr int NA_SLOTS = 6, NB_SLOTS = 8;
constexpr int SM_ARING = 0;
constexpr int SM_BRING = NA_SLOTS * 16384;
constexpr int SM_H = 212992;
constexpr int SM_MISC = 229376;
constexpr int SM_BAR = 231424;
constexpr int SM_TOTAL = 232448;
constexpr int B_FULLX = 0;
constexpr int B_FULLKV = 7;
constexpr int B_FQ = 14;
constexpr int B_DONE1 = 16;
constexpr int B_DONEX = 23;
constexpr int B_DONEQ = 24;
constexpr int B_DONEO = 25;
constexpr int B_FULLO = 29;
constexpr int B_FULLWO = 33;
constexpr int B_END = 34;
constexpr int B_HALO = 35;
constexpr int B_FULLA = 39;
constexpr int B_FULLB = 55;
constexpr int B_DONE = 87;
constexpr int B_RAW = 119;
constexpr int B_CLR = 127;

constexpr long long WD_CLKS = 2000000000ll;

template<int N> struct Int { static constexpr int value = N; };
template<int A, int B, class F> __device__ __forceinline__ void static_for(F&& f) { if constexpr (A < B) { f(Int<A>()); static_for<A + 1, B>(f); } }

__device__ __forceinline__ uint32_t smem_u32(const void* p) { return (uint32_t)__cvta_generic_to_shared(p); }
__device__ __forceinline__ void mbar_init(uint32_t bar, uint32_t cnt) { asm volatile("mbarrier.init.shared::cta.b64 [%0], %1;" :: "r"(bar), "r"(cnt) : "memory"); }
__device__ __forceinline__ void mbar_expect(uint32_t bar, uint32_t bytes) { asm volatile("mbarrier.arrive.expect_tx.shared::cta.b64 _, [%0], %1;" :: "r"(bar), "r"(bytes) : "memory"); }
__device__ __forceinline__ void mbar_arrive(uint32_t bar) { asm volatile("mbarrier.arrive.shared::cta.b64 _, [%0];" :: "r"(bar) : "memory"); }
__device__ __forceinline__ bool mbar_try(uint32_t bar, uint32_t parity) {
    uint32_t ok;
    asm volatile("{\n.reg .pred p;\nmbarrier.try_wait.parity.shared::cta.b64 p, [%1], %2;\nselp.u32 %0, 1, 0, p;\n}" : "=r"(ok) : "r"(bar), "r"(parity) : "memory");
    return ok;
}
__device__ __forceinline__ void mbar_wait(uint32_t bar, uint32_t parity) {
    asm volatile("{\n.reg .pred p;\n"
                 "WAIT_LOOP:\n"
                 "mbarrier.try_wait.parity.shared::cta.b64 p, [%0], %1;\n"
                 "@!p bra WAIT_LOOP;\n}" :: "r"(bar), "r"(parity) : "memory");
}
__device__ __forceinline__ void mbar_wait_wd(uint32_t bar, uint32_t parity) {
    const long long t0 = clock64();
    while (!mbar_try(bar, parity)) { if (clock64() - t0 > WD_CLKS) __trap(); }
}
__device__ __forceinline__ bool elect() { uint32_t p; asm volatile("{\n.reg .pred P;\nelect.sync _|P, 0xffffffff;\nselp.u32 %0, 1, 0, P;\n}" : "=r"(p)); return p; }
__device__ __forceinline__ void tma2d(uint32_t dst, const CUtensorMap* tm, int c0, int c1, uint32_t bar) {
    asm volatile("cp.async.bulk.tensor.2d.shared::cluster.global.mbarrier::complete_tx::bytes [%0], [%1, {%3, %4}], [%2];" :: "r"(dst), "l"(tm), "r"(bar), "r"(c0), "r"(c1) : "memory");
}
__device__ __forceinline__ void tma3d(uint32_t dst, const CUtensorMap* tm, int c0, int c1, int c2, uint32_t bar) {
    asm volatile("cp.async.bulk.tensor.3d.shared::cluster.global.mbarrier::complete_tx::bytes [%0], [%1, {%3, %4, %5}], [%2];" :: "r"(dst), "l"(tm), "r"(bar), "r"(c0), "r"(c1), "r"(c2) : "memory");
}
__device__ __forceinline__ void tma2d_store(const CUtensorMap* tm, int c0, int c1, uint32_t src) {
    asm volatile("cp.async.bulk.tensor.2d.global.shared::cta.bulk_group [%0, {%2, %3}], [%1];" :: "l"(tm), "r"(src), "r"(c0), "r"(c1) : "memory");
}
__device__ __forceinline__ void bulk_ld(uint32_t dst, const void* src, uint32_t bytes, uint32_t bar) {
    asm volatile("cp.async.bulk.shared::cluster.global.mbarrier::complete_tx::bytes [%0], [%1], %2, [%3];" :: "r"(dst), "l"(src), "r"(bytes), "r"(bar) : "memory");
}
__device__ __forceinline__ void bulk_prefetch(const void* src, uint32_t bytes) { asm volatile("cp.async.bulk.prefetch.L2.global [%0], %1;" :: "l"(src), "r"(bytes) : "memory"); }
__device__ __forceinline__ void prefetch_map(const CUtensorMap* tm) { asm volatile("prefetch.tensormap [%0];" :: "l"(tm) : "memory"); }
__device__ __forceinline__ void st_global_if(uint32_t c, uint32_t* p, uint32_t v) {
    asm volatile("{\n.reg .pred p;\nsetp.ne.u32 p, %2, 0;\n@p st.global.u32 [%0], %1;\n}" :: "l"(p), "r"(v), "r"(c) : "memory");
}
__device__ __forceinline__ void pin4(uint32_t never, float a, float b, float c, float d) {
    asm volatile("{\n.reg .pred p;\nsetp.ne.u32 p, %4, 0;\n@p st.shared.v4.f32 [%4], {%0,%1,%2,%3};\n}" :: "f"(a), "f"(b), "f"(c), "f"(d), "r"(never) : "memory");
}
__device__ __forceinline__ void fence_async_smem() { asm volatile("fence.proxy.async.shared::cta;" ::: "memory"); }
__device__ __forceinline__ uint32_t ld_acquire(const void* p) { uint32_t v; asm volatile("ld.acquire.gpu.global.u32 %0, [%1];" : "=r"(v) : "l"(p) : "memory"); return v; }
__device__ __forceinline__ void st_release(void* p, uint32_t v) { asm volatile("st.release.gpu.global.u32 [%0], %1;" :: "l"(p), "r"(v) : "memory"); }
__device__ __forceinline__ uint32_t ld_relaxed(const void* p) { uint32_t v; asm volatile("ld.relaxed.gpu.global.u32 %0, [%1];" : "=r"(v) : "l"(p) : "memory"); return v; }
__device__ __forceinline__ uint2 ld_relaxed2(const void* p) {
    uint2 v; asm volatile("{\n.reg .b64 a;\nld.relaxed.gpu.global.b64 a, [%2];\nmov.b64 {%0, %1}, a;\n}" : "=r"(v.x), "=r"(v.y) : "l"(p) : "memory"); return v;
}
__device__ __forceinline__ uint4 ld_relaxed4(const uint4* p) {
    uint4 v;
    asm volatile("{\n.reg .b128 t;\n.reg .b64 a, b;\nld.relaxed.gpu.global.b128 t, [%4];\nmov.b128 {a, b}, t;\nmov.b64 {%0, %1}, a;\nmov.b64 {%2, %3}, b;\n}" : "=r"(v.x), "=r"(v.y), "=r"(v.z), "=r"(v.w) : "l"(p) : "memory");
    return v;
}
__device__ __forceinline__ void st_relaxed4(uint4* p, uint32_t a, uint32_t b, uint32_t c, uint32_t d) {
    asm volatile("{\n.reg .b128 t;\n.reg .b64 a, b;\nmov.b64 a, {%1, %2};\nmov.b64 b, {%3, %4};\nmov.b128 t, {a, b};\nst.relaxed.gpu.global.b128 [%0], t;\n}" :: "l"(p), "r"(a), "r"(b), "r"(c), "r"(d) : "memory");
}
__device__ __forceinline__ uint32_t ld_volatile(const uint32_t* p) { uint32_t v; asm volatile("ld.volatile.global.u32 %0, [%1];" : "=r"(v) : "l"(p) : "memory"); return v; }
__device__ __forceinline__ void named_arrive(int id, int n) { asm volatile("bar.arrive %0, %1;" :: "r"(id), "r"(n) : "memory"); }
__device__ __forceinline__ void named_sync(int id, int n) { asm volatile("bar.sync %0, %1;" :: "r"(id), "r"(n) : "memory"); }
__device__ __forceinline__ void wg_fence() { asm volatile("wgmma.fence.sync.aligned;" ::: "memory"); }
__device__ __forceinline__ void wg_commit() { asm volatile("wgmma.commit_group.sync.aligned;" ::: "memory"); }
template<int N> __device__ __forceinline__ void wg_wait() { asm volatile("wgmma.wait_group.sync.aligned %0;" :: "n"(N) : "memory"); }
template<int N> __device__ __forceinline__ void reg_fence(float (&d)[N]) {
    #pragma unroll
    for (int i = 0; i < N; i++) asm volatile("" : "+f"(d[i]) :: "memory");
}
__device__ __forceinline__ constexpr uint64_t mkdesc(uint32_t addr, uint32_t lbo, uint32_t sbo, uint32_t sw) {
    return (uint64_t)((addr & 0x3FFFF) >> 4) | ((uint64_t)(lbo >> 4) << 16) | ((uint64_t)(sbo >> 4) << 32) | ((uint64_t)sw << 62);
}
__device__ __forceinline__ void ldsm4(uint32_t (&r)[4], uint32_t addr) {
    asm volatile("ldmatrix.sync.aligned.m8n8.x4.shared.b16 {%0,%1,%2,%3}, [%4];" : "=r"(r[0]), "=r"(r[1]), "=r"(r[2]), "=r"(r[3]) : "r"(addr) : "memory");
}
__device__ __forceinline__ void stsm4(uint32_t addr, uint32_t r0, uint32_t r1, uint32_t r2, uint32_t r3) {
    asm volatile("stmatrix.sync.aligned.m8n8.x4.shared.b16 [%0], {%1,%2,%3,%4};" :: "r"(addr), "r"(r0), "r"(r1), "r"(r2), "r"(r3) : "memory");
}
__device__ __forceinline__ uint32_t movtrans(uint32_t a) { uint32_t d; asm volatile("movmatrix.sync.aligned.m8n8.trans.b16 %0, %1;" : "=r"(d) : "r"(a)); return d; }
__device__ __forceinline__ uint32_t pack_bf16(float lo, float hi) { uint32_t r; asm("cvt.rn.bf16x2.f32 %0, %1, %2;" : "=r"(r) : "f"(hi), "f"(lo)); return r; }
__device__ __forceinline__ void sub_bf16x2(uint32_t& a, uint32_t b) { asm volatile("sub.rn.bf16x2 %0, %0, %1;" : "+r"(a) : "r"(b)); }
__device__ __forceinline__ float bf_lo(uint32_t v) { return __uint_as_float(v << 16); }
__device__ __forceinline__ float bf_hi(uint32_t v) { return __uint_as_float(v & 0xffff0000u); }
__device__ __forceinline__ void mma16816(float (&c)[4], uint32_t a0, uint32_t a1, uint32_t a2, uint32_t a3, uint32_t b0, uint32_t b1) {
    asm volatile("mma.sync.aligned.m16n8k16.row.col.f32.bf16.bf16.f32 {%0,%1,%2,%3}, {%4,%5,%6,%7}, {%8,%9}, {%0,%1,%2,%3};"
        : "+f"(c[0]), "+f"(c[1]), "+f"(c[2]), "+f"(c[3]) : "r"(a0), "r"(a1), "r"(a2), "r"(a3), "r"(b0), "r"(b1));
}
__device__ __forceinline__ void mma1688(float (&c)[4], uint32_t a0, uint32_t a1, uint32_t b0) {
    asm volatile("mma.sync.aligned.m16n8k8.row.col.f32.bf16.bf16.f32 {%0,%1,%2,%3}, {%4,%5}, {%6}, {%0,%1,%2,%3};"
        : "+f"(c[0]), "+f"(c[1]), "+f"(c[2]), "+f"(c[3]) : "r"(a0), "r"(a1), "r"(b0));
}
__device__ __forceinline__ float quad_sum(float v) { v += __shfl_xor_sync(0xffffffffu, v, 1); v += __shfl_xor_sync(0xffffffffu, v, 2); return v; }
__device__ __forceinline__ float quad_max(float v) { v = fmaxf(v, __shfl_xor_sync(0xffffffffu, v, 1)); v = fmaxf(v, __shfl_xor_sync(0xffffffffu, v, 2)); return v; }
__device__ __forceinline__ float ex2(float x) { float y; asm("ex2.approx.ftz.f32 %0, %1;" : "=f"(y) : "f"(x)); return y; }
__device__ __forceinline__ float rsqrt_approx(float x) { float y; asm("rsqrt.approx.ftz.f32 %0, %1;" : "=f"(y) : "f"(x)); return y; }
__device__ __forceinline__ float rcp_approx(float x) { float y; asm("rcp.approx.ftz.f32 %0, %1;" : "=f"(y) : "f"(x)); return y; }
__device__ __forceinline__ float gelu_half(float hx) {
    const float z = hx * fmaf(hx * hx, 8.f * 0.044715f * 0.7978845608028654f, 2.f * 0.7978845608028654f);
    float t; asm("tanh.approx.f32 %0, %1;" : "=f"(t) : "f"(z));
    return fmaf(hx, t, hx);
}
__device__ __forceinline__ uint32_t gtime32() { uint32_t t; asm volatile("mov.u32 %0, %%globaltimer_lo;" : "=r"(t)); return t; }
__device__ __forceinline__ uint32_t clock32() { uint32_t t; asm volatile("mov.u32 %0, %%clock;" : "=r"(t)); return t; }
#define PF_PACE 400

#define PF_AT 4000
#define NSQ 6
#define HALO_AT 3
#define PF_N 12
#define HINT_H 0
#define HINT_U 0
#define SP_AT 2000
#define SP_N 0
#define WO_HOLD 7
#define A_SCHED 0x322188
#define WO_ORD0 0x4321065
#define WO_ORD1 0x3465210
#define XR_HOLD 0
#define ROT 0
#define SQMIX 0
#define NPIPE 1
#define CL_SPLIT 1000
#define CL_AT 600
#define WARM 1
#define WARM_AT 300
#define HINT_O 0
#define W2_AT 23
#define W2_HOLD 5
#define A3_END 20
#define A4_END 16
#define DRY 7
#define GO_H 640
#define GO_U 640
template<int TB> __device__ __forceinline__ void wgmma_rs56(float (&d)[28], const uint32_t (&a)[4], uint64_t db, int sc) {
    asm volatile("{\n.reg .pred p;\nsetp.ne.b32 p, %33, 0;\n"
        "wgmma.mma_async.sync.aligned.m64n56k16.f32.bf16.bf16 {%0, %1, %2, %3, %4, %5, %6, %7, %8, %9, %10, %11, %12, %13, %14, %15, %16, %17, %18, %19, %20, %21, %22, %23, %24, %25, %26, %27}, {%28, %29, %30, %31}, %32, p, 1, 1, %34;\n}\n"
        : "+f"(d[0]), "+f"(d[1]), "+f"(d[2]), "+f"(d[3]), "+f"(d[4]), "+f"(d[5]), "+f"(d[6]), "+f"(d[7]), "+f"(d[8]), "+f"(d[9]), "+f"(d[10]), "+f"(d[11]), "+f"(d[12]), "+f"(d[13]), "+f"(d[14]), "+f"(d[15]), "+f"(d[16]), "+f"(d[17]), "+f"(d[18]), "+f"(d[19]), "+f"(d[20]), "+f"(d[21]), "+f"(d[22]), "+f"(d[23]), "+f"(d[24]), "+f"(d[25]), "+f"(d[26]), "+f"(d[27])
        : "r"(a[0]), "r"(a[1]), "r"(a[2]), "r"(a[3]), "l"(db), "r"(sc), "n"(TB));
}

template<int TA, int TB, int SC = 1> __device__ __forceinline__ void wgmma_ss112(float (&d)[56], uint64_t da, uint64_t db) {
    asm volatile("wgmma.mma_async.sync.aligned.m64n112k16.f32.bf16.bf16 {%0, %1, %2, %3, %4, %5, %6, %7, %8, %9, %10, %11, %12, %13, %14, %15, %16, %17, %18, %19, %20, %21, %22, %23, %24, %25, %26, %27, %28, %29, %30, %31, %32, %33, %34, %35, %36, %37, %38, %39, %40, %41, %42, %43, %44, %45, %46, %47, %48, %49, %50, %51, %52, %53, %54, %55}, %56, %57, %60, 1, 1, %58, %59;\n"
        : "+f"(d[0]), "+f"(d[1]), "+f"(d[2]), "+f"(d[3]), "+f"(d[4]), "+f"(d[5]), "+f"(d[6]), "+f"(d[7]), "+f"(d[8]), "+f"(d[9]), "+f"(d[10]), "+f"(d[11]), "+f"(d[12]), "+f"(d[13]), "+f"(d[14]), "+f"(d[15]), "+f"(d[16]), "+f"(d[17]), "+f"(d[18]), "+f"(d[19]), "+f"(d[20]), "+f"(d[21]), "+f"(d[22]), "+f"(d[23]), "+f"(d[24]), "+f"(d[25]), "+f"(d[26]), "+f"(d[27]), "+f"(d[28]), "+f"(d[29]), "+f"(d[30]), "+f"(d[31]), "+f"(d[32]), "+f"(d[33]), "+f"(d[34]), "+f"(d[35]), "+f"(d[36]), "+f"(d[37]), "+f"(d[38]), "+f"(d[39]), "+f"(d[40]), "+f"(d[41]), "+f"(d[42]), "+f"(d[43]), "+f"(d[44]), "+f"(d[45]), "+f"(d[46]), "+f"(d[47]), "+f"(d[48]), "+f"(d[49]), "+f"(d[50]), "+f"(d[51]), "+f"(d[52]), "+f"(d[53]), "+f"(d[54]), "+f"(d[55])
        : "l"(da), "l"(db), "n"(TA), "n"(TB), "n"(SC));
}

template<int TA, int TB, int SC = 1> __device__ __forceinline__ void wgmma_ss64(float (&d)[32], uint64_t da, uint64_t db) {
    asm volatile("wgmma.mma_async.sync.aligned.m64n64k16.f32.bf16.bf16 {%0, %1, %2, %3, %4, %5, %6, %7, %8, %9, %10, %11, %12, %13, %14, %15, %16, %17, %18, %19, %20, %21, %22, %23, %24, %25, %26, %27, %28, %29, %30, %31}, %32, %33, %36, 1, 1, %34, %35;\n"
        : "+f"(d[0]), "+f"(d[1]), "+f"(d[2]), "+f"(d[3]), "+f"(d[4]), "+f"(d[5]), "+f"(d[6]), "+f"(d[7]), "+f"(d[8]), "+f"(d[9]), "+f"(d[10]), "+f"(d[11]), "+f"(d[12]), "+f"(d[13]), "+f"(d[14]), "+f"(d[15]), "+f"(d[16]), "+f"(d[17]), "+f"(d[18]), "+f"(d[19]), "+f"(d[20]), "+f"(d[21]), "+f"(d[22]), "+f"(d[23]), "+f"(d[24]), "+f"(d[25]), "+f"(d[26]), "+f"(d[27]), "+f"(d[28]), "+f"(d[29]), "+f"(d[30]), "+f"(d[31])
        : "l"(da), "l"(db), "n"(TA), "n"(TB), "n"(SC));
}

template<int TA, int TB, int SC = 1> __device__ __forceinline__ void wgmma_ss48(float (&d)[24], uint64_t da, uint64_t db) {
    asm volatile("wgmma.mma_async.sync.aligned.m64n48k16.f32.bf16.bf16 {%0, %1, %2, %3, %4, %5, %6, %7, %8, %9, %10, %11, %12, %13, %14, %15, %16, %17, %18, %19, %20, %21, %22, %23}, %24, %25, %28, 1, 1, %26, %27;\n"
        : "+f"(d[0]), "+f"(d[1]), "+f"(d[2]), "+f"(d[3]), "+f"(d[4]), "+f"(d[5]), "+f"(d[6]), "+f"(d[7]), "+f"(d[8]), "+f"(d[9]), "+f"(d[10]), "+f"(d[11]), "+f"(d[12]), "+f"(d[13]), "+f"(d[14]), "+f"(d[15]), "+f"(d[16]), "+f"(d[17]), "+f"(d[18]), "+f"(d[19]), "+f"(d[20]), "+f"(d[21]), "+f"(d[22]), "+f"(d[23])
        : "l"(da), "l"(db), "n"(TA), "n"(TB), "n"(SC));
}

template<int NKB, bool PERM>
__device__ __forceinline__ void mix_mainloop(TSARG float (&acc)[56], uint32_t par, bool leader) {
    constexpr uint32_t sb = SB, bars = sb + SM_BAR;
    constexpr int A0 = PERM ? 0 : 16 % NA_SLOTS;
    auto aoff = [](int jj, int s) { return (PERM ? (s & 1) * 8192 + (jj * 32 + (s >> 1) * 16) * 128 : jj * 8192 + s * 2048) >> 4; };
    int bslot = 0, aslot = A0;
    reg_fence(acc);
    #pragma unroll 1
    for (int i = 0; i < NKB / 2; i++) {
        mbar_wait(bars + 8 * (B_FULLA + i), par);
        const uint64_t adesc = mkdesc(sb + SM_ARING, 8192, 1024, 1) + (uint32_t)(aslot * 1024);
        aslot = aslot == NA_SLOTS - 1 ? 0 : aslot + 1;
        #pragma unroll
        for (int jj = 0; jj < 2; jj++) {
            const int j = 2 * i + jj;
            mbar_wait(bars + 8 * (B_FULLB + j), par);
            const uint64_t bdesc = mkdesc(sb + SM_BRING, 1792, 128, 0) + (uint32_t)(bslot * 896);
            bslot = bslot == NB_SLOTS - 1 ? 0 : bslot + 1;
            wg_fence();
            #pragma unroll
            for (int s = 0; s < 4; s++) wgmma_ss112<1, 1>(acc, adesc + aoff(jj, s), bdesc + s * 224);
            wg_commit();
            wg_wait<1>();
            if (j > 0 && leader) mbar_arrive(bars + 8 * (B_DONE + j - 1));
        }
    }
    wg_wait<0>();
    reg_fence(acc);
    if (leader) mbar_arrive(bars + 8 * (B_DONE + NKB - 1));
}

constexpr uint32_t EMPTY = 0xFFFFFFFFu;
__device__ __forceinline__ void post_hint(uint4* p, uint32_t ep, int lane) { if (lane < 2) st_relaxed4(p + lane, ep, ep, ep, ep); }
__device__ __forceinline__ void post_hint_wg(int id, uint4* p, uint32_t ep, int w, int lane) {
    if (w < 3) named_arrive(id, 128);
    else { named_sync(id, 128); const uint32_t now = gtime32(); if (lane < 2) st_relaxed4(p + lane, ep, now, ep, now); }
}

template<int NKB>
__device__ __forceinline__ void mix_producer_b(TSARG uint32_t par, const uint4* hints, uint32_t ep, const uint32_t* src, int lane) {
    constexpr uint32_t sb = SB, bars = sb + SM_BAR;
    uint2 v;
    do { v = ld_relaxed2(hints + (lane >> 3) * 64 + (lane & 7) * 2); } while (!__all_sync(0xffffffffu, v.x == ep));
    const uint32_t t1 = gtime32(), age = __reduce_min_sync(0xffffffffu, t1 + 256 - v.y);
    while (gtime32() - t1 + age < (NKB == 32 ? GO_H : GO_U) + 256) {}
    __syncwarp();
    #pragma unroll 1
    for (int j = 0; j < NKB; j++) {
        if (j >= NB_SLOTS) mbar_wait(bars + 8 * (B_DONE + j - NB_SLOTS), par);
        if (j == 0 && lane == 0) STAMP(NKB == 32 ? 29 : 30);
        if (j == 7 && lane == 0) STAMP(NKB == 32 ? 35 : 36);
        if (elect()) {
            mbar_expect(bars + 8 * (B_RAW + (j & 7)), 14336);
            bulk_ld(sb + SM_BRING + (j & 7) * 14336, src + j * 3584, 14336, bars + 8 * (B_RAW + (j & 7)));
        }
    }
}
__device__ __forceinline__ void check_tiles(TSARG int n, int w, int lane, uint32_t& ph, uint32_t dst, const uint32_t* src, int full) {
    constexpr uint32_t bars = SB + SM_BAR;
    #pragma unroll 1
    for (int j = w; j < n; j += 4) {
        const uint32_t raw = bars + 8 * (B_RAW + (j & 7)), d = dst + (j & 7) * 14336, a = d + lane * 128 + (lane & 3) * 32 + (lane >> 2) * 4;
        bool bad;
        do {
            mbar_wait(raw, (ph >> (j & 4)) & 1);
            ph ^= 1u << (j & 4);
            if (j == 0 && lane == 0) STAMP(n == 4 ? 6 : n == 32 ? 31 : 32);
            uint32_t v0, v1, v2, v3;
            asm volatile("ld.shared.u32 %0, [%4];\nld.shared.u32 %1, [%4+4096];\nld.shared.u32 %2, [%4+8192];\nld.shared.u32 %3, [%4+10240];"
                         : "=r"(v0), "=r"(v1), "=r"(v2), "=r"(v3) : "r"(a) : "memory");
            bad = __any_sync(0xffffffffu, max(max(v0, v1), max(v2, v3)) == EMPTY);
            if (elect() && bad) {
                mbar_expect(raw, 14336); bulk_ld(d, src + j * 3584, 14336, raw);
            }
        } while (bad);
        if (lane == 0) mbar_arrive(bars + 8 * (full + j));
    }
}

__device__ __forceinline__ uint32_t hcol(uint32_t a, int jp) { return (a ^ ((jp & 3) << 5)) + (jp >> 2) * 8192; }

template<bool USE_SMID>
__global__ void __launch_bounds__(384, 1)
fused_kernel(Scratch* __restrict__ sc, const __nv_bfloat16* __restrict__ wo,
             const __nv_bfloat16* __restrict__ w1, const __nv_bfloat16* __restrict__ b1,
             const __nv_bfloat16* __restrict__ w2, const __nv_bfloat16* __restrict__ b2,
             const __grid_constant__ CUtensorMap tm_x, const __grid_constant__ CUtensorMap tm_wqkv,
             const __grid_constant__ CUtensorMap tm_wo64, const __grid_constant__ CUtensorMap tm_wo48,
             const __grid_constant__ CUtensorMap tm_w1, const __grid_constant__ CUtensorMap tm_w2,
             const __grid_constant__ CUtensorMap tm_xr64, const __grid_constant__ CUtensorMap tm_xr48,
             const __grid_constant__ CUtensorMap tm_out64, const __grid_constant__ CUtensorMap tm_out48) {
    extern __shared__ __align__(1024) uint8_t smem_raw[];
    constexpr uint32_t sb = SB;
    constexpr uint32_t bars = sb + SM_BAR;
    const int tid = threadIdx.x, lane = tid & 31;
    const int warp = __shfl_sync(0xffffffffu, tid >> 5, 0);
    int slot;
    if (USE_SMID) {
        asm("{\n.reg .u32 s, t, u, d, a, b, c;\n.reg .pred p, r;\n"
            "mov.u32 s, %%smid;\nshr.u32 t, s, 1;\nsub.u32 u, t, 32;\nmul.lo.u32 d, u, 37;\nshr.u32 d, d, 8;\n"
            "and.b32 a, t, 7;\nshl.b32 a, a, 3;\nshr.u32 c, t, 3;\nadd.u32 a, a, c;\n"
            "mad.lo.u32 b, d, -55, 12;\nshl.b32 c, u, 3;\nadd.u32 b, b, c;\n"
            "setp.lt.u32 p, t, 32;\nselp.u32 a, a, b, p;\n"
            "setp.lt.u32 r, t, 62;\nselp.s32 c, 4, -58, r;\nadd.u32 c, t, c;\nsetp.lt.u32 p, t, 60;\nselp.u32 a, a, c, p;\n"
            "and.b32 s, s, 1;\nshl.b32 a, a, 1;\nadd.u32 %0, a, s;\n}" : "=r"(slot));
    } else slot = blockIdx.x;
    const int G = slot >> 4, mi = slot & 15;
    const int tb = 4 * (G >> 1) + (mi >> 2), hp = 2 * (mi & 3) + (G & 1);
    const int wcol = (hp * 56) & ~15;
    if (slot >= 128) {
        const uint32_t ep = ld_volatile(&sc->epoch[slot]) + 1;
        if (warp < 4) {
            #pragma unroll 1
            for (uint32_t e = ld_volatile(&sc->clean[mi]) == ep ? ep + 1 : ep; e != ep + 2; e++) {
                constexpr int NL = sizeof(Tiles) / 512;
                uint4* p = (uint4*)&sc->tiles[e & 1] + (mi * NL + (lane >> 1)) * 8 + (lane & 7);
                if (e != ep) {
                    while (ld_relaxed(sc->hint_h) != ep) __nanosleep(200);
                    __nanosleep(CL_AT);
                }
                #pragma unroll 7
                for (int i = warp; i < NL / 16; i += 4) st_relaxed4(p + i * 128, EMPTY, EMPTY, EMPTY, EMPTY);
                named_sync(1, 128);
                if (tid == 0) st_release(&sc->clean[mi], e);
            }
        }
        if (tid == 128) {
            const long long t0 = clock64();
            while (clock64() - t0 < SP_AT) {}
            #pragma unroll 1
            for (int i = 0; i < 7; i++) bulk_prefetch((const char*)wo + (i * 4 + mi) * 14336, 14336);
            #pragma unroll 1
            for (int i = 0; i < SP_N; i++) bulk_prefetch((const char*)w1 + (i * 4 + mi) * 14336, 14336);
            while (ld_relaxed(sc->hint_u) != ep) { __nanosleep(500); if (clock64() - t0 > WD_CLKS) __trap(); }
            sc->epoch[slot] = ep;
        }
        return;
    }
    const int q = mi & 3, tt2 = 4 * G + (mi >> 2), ft = 4 * (G - 1) + (mi >> 2);
    const bool has_b1 = G > 0;
    const int c64 = 64 * q, c48 = 256 + 48 * q;

    if (warp < 8) {
        if (WARM) {
            const int w = warp & 3, wg = warp >> 2, g = lane >> 2, t = lane & 3;
            if (WARM_AT) { const uint32_t t0 = clock32(); while (clock32() - t0 < WARM_AT) {} __syncwarp(); }
            if (w == 3 && lane < 4) st_relaxed4(sc->hint_kv + ((tb * 8 + hp) * 2 + wg) * 4 + lane, 0, 0, 0, 0);
            post_hint(sc->hint_o + ((2 * tb + (w >> 1)) * 32 + hp * 4 + (w & 1) * 2 + wg) * 2, 0, lane);
            if (wg == 0) {
                if (t < 2) st_relaxed4(sc->stats + tt2 * 256 + q * 64 + 16 * w + g + 8 * t, 0, 0, 0, 0);
                if (w == 3) { post_hint(sc->hint_h + (q * 32 + tt2) * 2, 0, lane); post_hint(sc->hint_u + (q * 32 + (ft & 31)) * 2, 0, lane); }
            }
        }
        named_sync(0, 384);
        asm volatile("setmaxnreg.inc.sync.aligned.u32 232;");
        int tid; asm volatile("mov.u32 %0, %%tid.x;" : "=r"(tid));
        const int lane = tid & 31, warp = __shfl_sync(0xffffffffu, tid >> 5, 0), wg = warp >> 2;
        const uint32_t ep = ld_volatile(&sc->epoch[slot]) + 1;
        Tiles* const tl = &sc->tiles[ep & 1];
        const int w = warp & 3, g = lane >> 2, t = lane & 3;
        const bool leader = (tid & 127) == 0;
        const uint32_t never = gridDim.y - 1;
        {
            uint32_t a[28][4];
            float accK[28], accV[28], accQ[28];
            const int lrow = 16 * w + (lane & 7) + (lane & 8);
            const uint32_t lbase = sb + wg * 8192 + lrow * 128;
            const uint32_t lx = (lane >> 4) ^ (lane & 7);
            const uint32_t wofs = hp & 1;
            auto pin2 = [&](uint32_t x0, uint32_t x1) {
                asm volatile("{\n.reg .pred p;\nsetp.ne.u32 p, %2, 0;\n@p st.shared.v2.b32 [%0], {%0,%1};\n}" :: "r"(x0), "r"(x1), "r"(never) : "memory");
            };
            float cS[2][4] = {}, cA[2][4] = {}, cB[2][4] = {}, q0 = 0.f, q1 = 0.f;
            auto sq = [&](float& acc, uint32_t v) { const float lo = bf_lo(v), hi = bf_hi(v); acc = fmaf(hi, hi, fmaf(lo, lo, acc)); };
            #pragma unroll
            for (int kb = 0; kb < 8; kb++) {
                if (kb < 7) {
                    mbar_wait(bars + 8 * (B_FULLX + kb), 0);
                    if (kb == 0 && tid == 0) STAMP(0);
                    if (kb == 6 && tid == 0) STAMP(25);
                    if (kb == 0) FST(0); if (kb == 2) FST(1); if (kb == 4) FST(2); if (kb == 6) FST(3);
                    #pragma unroll
                    for (int s = 4 * kb; s < 4 * kb + 4; s++) ldsm4(a[s], lbase + slot_x(kb) + ((lx ^ (2 * (s & 3))) << 4));
                }
                if (kb == NPIPE) continue;
                const int kc = kb < NPIPE ? kb : kb - 1;
                #pragma unroll
                for (int s = 4 * kc; s < 4 * kc + 4; s++) {
                    mma16816(cS[s & 1], a[s][0], a[s][1], a[s][2], a[s][3], 0x3F803F80u, 0x3F803F80u);
                    if (kc < NSQ) {
                        mma1688(cA[0], a[s][0], a[s][1], a[s][0]); mma1688(cA[1], a[s][2], a[s][3], a[s][2]);
                        if (SQMIX) { sq(q1, a[s][1]); sq(q1, a[s][3]); }
                        else { mma1688(cB[0], a[s][0], a[s][1], a[s][1]); mma1688(cB[1], a[s][2], a[s][3], a[s][3]); }
                    }
                }
                if (SQMIX && kc < NSQ) pin2(__float_as_uint(q1), 0);
            }
            const float m0 = (cS[0][0] + cS[1][0]) * (1.f / D_), m1 = (cS[0][2] + cS[1][2]) * (1.f / D_);
            const uint32_t mm0 = pack_bf16(m0, m0), mm1 = pack_bf16(m1, m1);
            if (lane == 0) mbar_arrive(bars + 8 * B_DONEX);
            auto center = [&](int s) { sub_bf16x2(a[s][0], mm0); sub_bf16x2(a[s][1], mm1); sub_bf16x2(a[s][2], mm0); sub_bf16x2(a[s][3], mm1); };
            uint32_t Ka[8], Kb[8], Kc[8], Va[8], Vb[7], Vc[8];
            float r0, r1, ls0, ls1;
            uint32_t pm, zero;
            uint32_t* od;
            uint4* oh;
            auto kpack = [&](uint32_t (&k)[8], int j, int c, float r) {
                const uint32_t v = pack_bf16(accK[4 * j + c] * r, accK[4 * j + c + 1] * r);
                if (j == 3) { k[3] = t < 2 ? v : 0u; k[4] = t < 2 ? 0u : v; } else k[j + (j > 3)] = v;
            };
            auto batch = [&](auto c0, auto c1) {
                constexpr int n0 = c0.value, n1 = c1.value;
                wg_fence();
                static_for<n0, n1>([&](auto nc) {
                    constexpr int n = nc.value;
                    if (n == 4) { center(4); center(5); center(6); center(7); wg_fence(); }
                    const uint64_t desc = mkdesc(sb + (n < 56 ? slot_kv(n >> 3) + (n & 7) * 2048 : SM_QO + (n - 56) * 2048), 8192, 1024, 1) + wofs;
                    wgmma_rs56<1>(n < 28 ? accK : n < 56 ? accV : accQ, a[n % 28], desc, n % 28 != 0);
                });
                wg_commit();
                if (n0 > 0) wg_wait<1>();
            };
            auto hand_over = [&](const uint32_t (&v)[8], int kv) {
                if (w < 3) {
                    mbar_wait(bars + 8 * (kv ? B_DONE1 + 5 : B_DONEX), 0);
                    uint4* hs = (uint4*)(smem_raw + (kv ? SM_HALOV : SM_HALOK)) + warp * 64 + lane;
                    hs[0] = make_uint4(v[0], v[1], v[2], v[3]); hs[32] = make_uint4(v[4], v[5], v[6], v[7]);
                } else if (tb < 15) {
                    uint4* hg = sc->halo + ((((tb + 1) * 8 + hp) * 2 + wg) * 2 + kv) * 96 + lane;
                    st_relaxed4(hg, v[0], v[1], v[2], ep); st_relaxed4(hg + 32, v[3], v[4], v[5], ep); st_relaxed4(hg + 64, v[6], v[7], ep, ep);
                    post_hint(sc->hint_kv + ((tb * 8 + hp) * 2 + wg) * 4 + kv * 2, ep, lane);
                }
            };
            auto take_over = [&](uint32_t (&v)[8], int kv) {
                if (w == 0) mbar_wait(bars + 8 * (B_HALO + 2 * kv + wg), 0);
                const uint4* hs = (const uint4*)(smem_raw + (kv ? SM_HALOV : SM_HALOK)) + (w ? warp - 1 : warp + 3) * 64 + lane;
                const uint4 u0 = hs[0], u1 = hs[32];
                v[0] = u0.x; v[1] = u0.y; v[2] = u0.z; v[3] = u0.w; v[4] = u1.x; v[5] = u1.y; v[6] = u1.z; v[7] = u1.w;
            };
            center(0); center(1); center(2); center(3);
            static_for<0, 7>([&](auto pc) {
                constexpr int p = pc.value;
                mbar_wait(bars + 8 * (B_FULLKV + p), 0);
                if (p == 0 && tid == 0) STAMP(26);
                if (p == 3 && tid == 0) STAMP(27);
                FST(4 + p);
                batch(Int<8 * p>(), Int<8 * p + 8>());
                if (p > 0 && leader) mbar_arrive(bars + 8 * (B_DONE1 + p - 1));
                #pragma unroll
                for (int s = 8 * p + 8; s < 8 * p + 16 && s < 28; s++) {
                    if (s >= 4 * NSQ) { sq(q0, a[s][0]); sq(q1, a[s][1]); sq(q0, a[s][2]); sq(q1, a[s][3]); }
                    center(s);
                }
                if (p == 3) {
                    if (t == (g >> 1)) { q0 += (g & 1) ? cA[0][1] + cA[1][1] : cA[0][0] + cA[1][0]; if (!SQMIX) q1 += (g & 1) ? cB[0][3] + cB[1][3] : cB[0][2] + cB[1][2]; }
                    q0 = quad_sum(q0); q1 = quad_sum(q1);
                    r0 = rsqrt_approx(fmaxf(q0 * (1.f / D_) - m0 * m0, 0.f) + LN_EPS); r1 = rsqrt_approx(fmaxf(q1 * (1.f / D_) - m1 * m1, 0.f) + LN_EPS);
                    pin2(__float_as_uint(r0), __float_as_uint(r1));
                }
                if (p == 4) {
                    reg_fence(accK);
                    #pragma unroll
                    for (int j = 0; j < 7; j++) kpack(Kc, j, 2, r1);
                    hand_over(Kc, 0);
                }
                if (p == 5) {
                    #pragma unroll
                    for (int j = 0; j < 7; j++) kpack(Kb, j, 0, r0);
                    #pragma unroll
                    for (int j = 0; j < 8; j += 2) pin2(Kb[j], Kb[j + 1]);
                    ls0 = LOG2E_SCALE * r0; ls1 = LOG2E_SCALE * r1;
                    pm = (2 * t <= g ? 0xFFFFu : 0u) | (2 * t + 1 <= g ? 0xFFFF0000u : 0u);
                    zero = never; asm volatile("" : "+r"(zero));
                    pin2(__float_as_uint(ls0), __float_as_uint(ls1)); pin2(pm, zero);
                }
                if (p == 6) {
                    const int tt = 2 * tb + (w >> 1);
                    od = tl->o + tt * 14336 + (7 * hp) * 256 + (2 * (2 * (w & 1) + wg)) * 32 + lane;
                    oh = sc->hint_o + (tt * 32 + hp * 4 + (w & 1) * 2 + wg) * 2 + (lane & 1);
                    pin2((uint32_t)(uint64_t)od, (uint32_t)((uint64_t)od >> 32));
                    pin2((uint32_t)(uint64_t)oh, (uint32_t)((uint64_t)oh >> 32));
                }
            });
            if (tid == 0) STAMP(1);
            FST(11);
            mbar_wait(bars + 8 * B_FQ, 0);
            batch(Int<56>(), Int<60>());
            reg_fence(accV);
            if (leader) mbar_arrive(bars + 8 * (B_DONE1 + 6));
            if (tid == 0) STAMP(2);
            FST(12);
            #pragma unroll
            for (int j = 0; j < 7; j++) Vc[j] = movtrans(pack_bf16(accV[4 * j + 2] * r1, accV[4 * j + 3] * r1));
            Vc[7] = ep;
            hand_over(Vc, 1);
            if (tid == 96) STAMP(23);
            batch(Int<60>(), Int<66>());
            #pragma unroll
            for (int j = 0; j < 7; j++) {
                Vb[j] = movtrans(pack_bf16(accV[4 * j] * r0, accV[4 * j + 1] * r0));
                Vc[j] |= zero;
            }
            batch(Int<66>(), Int<72>());
            #pragma unroll
            for (int j = 0; j < 7; j++) pin2(Vb[j], Vc[j]);
            mbar_wait(bars + 8 * (B_FQ + 1), 0);
            mbar_wait(bars + 8 * B_CLR, 0);
            FST(13);
            batch(Int<72>(), Int<84>());
            FST(14);
            named_sync(1 + wg, 128);
            take_over(Ka, 0);
            if (tid == 0) STAMP(3);
            wg_wait<0>();
            reg_fence(accQ);
            if (tid == 0) STAMP(4);
            FST(15);
            const bool first = (tb == 0 && w == 0);
            uint32_t pA[2], pB0[2], pB1[2], pC[2], z0[2], z1[2];
            #pragma unroll
            for (int h = 0; h < 2; h++) {
                float sA[4] = {0.f, 0.f, 0.f, 0.f}, sB[4] = {0.f, 0.f, 0.f, 0.f}, sC[4] = {0.f, 0.f, 0.f, 0.f};
                #pragma unroll
                for (int k = 0; k < 2; k++) {
                    const float* qq = accQ + 12 * h + 8 * k;
                    uint32_t a0 = pack_bf16(qq[0], qq[1]), a1 = pack_bf16(qq[2], qq[3]);
                    if (h == 1 && k == 0) { a0 |= zero; a1 |= zero; }
                    const uint32_t a2 = pack_bf16(qq[4], qq[5]), a3 = pack_bf16(qq[6], qq[7]);
                    mma16816(sB, a0, a1, a2, a3, Kb[4 * h + 2 * k], Kb[4 * h + 2 * k + 1]);
                    mma16816(sA, a0, a1, a2, a3, Ka[4 * h + 2 * k], Ka[4 * h + 2 * k + 1]);
                    mma16816(sC, a0, a1, a2, a3, Kc[4 * h + 2 * k], Kc[4 * h + 2 * k + 1]);
                }
                const bool n0 = pm & 1, n1 = (int)pm < 0;
                const float l00 = n0 ? sB[0] : (first ? -INFINITY : sA[0]), l01 = n1 ? sB[1] : (first ? -INFINITY : sA[1]);
                const float l10 = n0 ? sC[2] : sB[2], l11 = n1 ? sC[3] : sB[3];
                const float x0 = -ls0 * quad_max(fmaxf(l00, l01)), x1 = -ls1 * quad_max(fmaxf(l10, l11));
                const float e00 = ex2(fmaf(l00, ls0, x0)), e01 = ex2(fmaf(l01, ls0, x0)), e10 = ex2(fmaf(l10, ls1, x1)), e11 = ex2(fmaf(l11, ls1, x1));
                const float i0 = rcp_approx(quad_sum(e00 + e01)), i1 = rcp_approx(quad_sum(e10 + e11));
                const uint32_t P0 = pack_bf16(e00 * i0, e01 * i0), P1 = pack_bf16(e10 * i1, e11 * i1);
                pB0[h] = P0 & pm; pA[h] = P0 & ~pm; pC[h] = P1 & pm; pB1[h] = P1 & ~pm; z0[h] = P0 & zero; z1[h] = P1 & zero;
            }
            float o[8][4];
            #pragma unroll
            for (int j = 0; j < 8; j++) {
                o[j][0] = o[j][1] = o[j][2] = o[j][3] = 0.f;
                mma16816(o[j], pB0[j >> 2], pB1[j >> 2], z0[j >> 2], pC[j >> 2], Vb[j - (j >> 2)], Vc[j - (j >> 2)]);
            }
            if (tid == 0) STAMP(12);
            FST(16);
            take_over(Va, 1);
            if (HINT_O == 1 && lane < 2) st_relaxed4(oh, ep, ep, ep, ep);
            if (lane == 0) mbar_arrive(bars + 8 * B_DONEQ);
            if (tid == 0) STAMP(16);
            #pragma unroll
            for (int j = 0; j < 8; j++) mma1688(o[j], pA[j >> 2], z1[j >> 2], Va[j - (j >> 2)]);
            #pragma unroll
            for (int j = 0; j < 7; j++) {
                float v[4];
                #pragma unroll
                for (int c = 0; c < 4; c++) v[c] = j < 3 ? o[j][c] : j > 3 ? o[j + 1][c] : (t < 2 ? o[3][c] : o[4][c]);
                od[j * 256] = pack_bf16(v[0], v[1]);
                od[j * 256 + 32] = pack_bf16(v[2], v[3]);
            }
            if (tid == 0) STAMP(5);
            FST(17);
            if (HINT_O == 0 && lane < 2) st_relaxed4(oh, ep, ep, ep, ep);
        }
        if (wg == 1) {
            uint32_t ph = 0;
            check_tiles(TSVAL 4, w, lane, ph, sb + SM_QO, tl->o + tt2 * 14336, B_FULLO);
            if (has_b1) check_tiles(TSVAL 32, w, lane, ph, sb + SM_BRING, tl->hn + q * 32 * 3584, B_FULLB);
            check_tiles(TSVAL 28, w, lane, ph, sb + SM_BRING, tl->u + q * 28 * 3584, B_FULLB);
        } else {
            const uint32_t rb10 = has_b1 ? __ldg((const unsigned short*)b1 + ft * 64 + 16 * w + g) : 0, rb11 = has_b1 ? __ldg((const unsigned short*)b1 + ft * 64 + 16 * w + g + 8) : 0;
            const uint32_t rb20 = __ldg((const unsigned short*)b2 + tt2 * 64 + 16 * w + g), rb21 = __ldg((const unsigned short*)b2 + tt2 * 64 + 16 * w + g + 8);
            {
                float acc[56];
                const int hrow = 32 * (w >> 1) + 2 * ((lane & 7) + (lane & 8)) + (w & 1);
                const uint32_t ha = sb + SM_H + hrow * 128 + (((lane >> 4) ^ (hrow & 7)) << 4);
                mbar_wait(bars + 8 * B_FULLWO, 0);
                #pragma unroll
                for (int jp = 0; jp < 7; jp++) {
                    uint32_t xx[4];
                    ldsm4(xx, hcol(ha, jp));
                    #pragma unroll
                    for (int r = 0; r < 4; r++) { acc[8 * jp + 2 * r] = bf_lo(xx[r]); acc[8 * jp + 2 * r + 1] = bf_hi(xx[r]); }
                }
                reg_fence(acc);
                float accl[32], accr[24];
                auto od_ = [&](int s) { return mkdesc(sb + SM_QO + s * 2048, 1024, 128, 0); };
                auto wd_ = [&](int s) { return mkdesc(sb + slot_wo(s >> 2) + (s & 3) * 2048, 8192, 1024, 1); };
                #pragma unroll
                for (int i = 0; i < 5; i++) {
                    if (i < 4) mbar_wait(bars + 8 * (B_FULLO + i), 0);
                    if (i == 0 && tid == 0) STAMP(7);
                    wg_fence();
                    #pragma unroll
                    for (int ss = 0; ss < 7; ss++) {
                        if (i < 3) wgmma_ss112<0, 1>(acc, od_(7 * i + ss), wd_(7 * i + ss));
                        else if (i == 3) { if (ss == 0) wgmma_ss64<0, 1, 0>(accl, od_(21), wd_(21)); else wgmma_ss64<0, 1>(accl, od_(21 + ss), wd_(21 + ss)); }
                        else wgmma_ss48<0, 1>(accr, od_(21 + ss), wd_(21 + ss) + 512);
                    }
                    wg_commit();
                    if (i > 0) {
                        wg_wait<1>();
                        if (i == 3) {
                            reg_fence(acc);
                            #pragma unroll
                            for (int c = 0; c < 24; c++) accr[c] = __uint_as_float(__float_as_uint(acc[32 + c]) | never);
                            reg_fence(accr);
                        }
                        if (i < 4 && leader) mbar_arrive(bars + 8 * (B_DONEO + i - 1));
                    }
                }
                float s0 = 0.f, s1 = 0.f, q0 = 0.f, q1 = 0.f, s2 = 0.f, s3 = 0.f, q2 = 0.f, q3 = 0.f;
                reg_fence(accl);
                #pragma unroll
                for (int c = 0; c < 32; c++) acc[c] += accl[c];
                #pragma unroll
                for (int j = 0; j < 14; j++) {
                    if (j == 8) {
                        pin4(never, s0, s1, s2, s3); pin4(never, q0, q1, q2, q3);
                        wg_wait<0>();
                        reg_fence(accr);
                        #pragma unroll
                        for (int c = 0; c < 24; c++) acc[32 + c] = accr[c];
                        if (leader) mbar_arrive(bars + 8 * (B_DONEO + 3));
                        if (tid == 0) STAMP(8);
                    }
                    s0 += acc[4 * j]; s2 += acc[4 * j + 1]; q0 = fmaf(acc[4 * j], acc[4 * j], q0); q2 = fmaf(acc[4 * j + 1], acc[4 * j + 1], q2);
                    s1 += acc[4 * j + 2]; s3 += acc[4 * j + 3]; q1 = fmaf(acc[4 * j + 2], acc[4 * j + 2], q1); q3 = fmaf(acc[4 * j + 3], acc[4 * j + 3], q3);
                }
                s0 = quad_sum(s0 + s2); s1 = quad_sum(s1 + s3); q0 = quad_sum(q0 + q2); q1 = quad_sum(q1 + q3);
                uint4* sp = sc->stats + tt2 * 256 + 16 * w + g;
                if (t < 2) st_relaxed4(sp + q * 64 + 8 * t, __float_as_uint(t ? s1 : s0), ep, __float_as_uint(t ? q1 : q0), ep);
                if (tid == 0) STAMP(9);
                #pragma unroll
                for (int jp = 0; jp < 7; jp++)
                    stsm4(hcol(ha, jp), pack_bf16(acc[8 * jp], acc[8 * jp + 1]), pack_bf16(acc[8 * jp + 2], acc[8 * jp + 3]),
                          pack_bf16(acc[8 * jp + 4], acc[8 * jp + 5]), pack_bf16(acc[8 * jp + 6], acc[8 * jp + 7]));
                {
                    uint4 v0, v1;
                    do {
                        v0 = ld_relaxed4(sp + t * 64); v1 = ld_relaxed4(sp + t * 64 + 8);
                    } while (__any_sync(0xffffffffu, t != q && (v0.y != ep || v0.w != ep || v1.y != ep || v1.w != ep)));
                    if (t != q) { s0 = __uint_as_float(v0.x); q0 = __uint_as_float(v0.z); s1 = __uint_as_float(v1.x); q1 = __uint_as_float(v1.z); }
                }
                if (tid == 0) STAMP(10);
                s0 = quad_sum(s0); s1 = quad_sum(s1); q0 = quad_sum(q0); q1 = quad_sum(q1);
                const float m0 = s0 * (1.f / D_), m1 = s1 * (1.f / D_);
                const float v0 = fmaxf(q0 * (1.f / D_) - m0 * m0, 0.f), v1 = fmaxf(q1 * (1.f / D_) - m1 * m1, 0.f);
                const float r0 = rsqrt_approx(fmaf(v0, 4.f + 4.f * LN_EPS, 4.f * LN_EPS * LN_EPS)), r1 = rsqrt_approx(fmaf(v1, 4.f + 4.f * LN_EPS, 4.f * LN_EPS * LN_EPS));
                const float c0 = -m0 * r0, c1 = -m1 * r1;
                uint32_t* hd = tl->hn + (q * 32 + tt2) * 3584 + (2 * w) * 448 + lane;
                #pragma unroll
                for (int j = 0; j < 14; j++) {
                    if (j == HINT_H) post_hint_wg(5, sc->hint_h + (q * 32 + tt2) * 2, ep, w, lane);
                    hd[j * 32] = pack_bf16(fmaf(acc[4 * j], r0, c0), fmaf(acc[4 * j + 1], r0, c0));
                    hd[j * 32 + 448] = pack_bf16(fmaf(acc[4 * j + 2], r1, c1), fmaf(acc[4 * j + 3], r1, c1));
                }
                if (tid == 0) STAMP(11);
                if (HINT_H == 14) post_hint_wg(5, sc->hint_h + (q * 32 + tt2) * 2, ep, w, lane);
                if (tid == 96) STAMP(33);
            }
            if (has_b1) {
                float acc[56];
                #pragma unroll
                for (int j = 0; j < 56; j++) acc[j] = 0.5f * bf_lo((j & 2) ? rb11 : rb10);
                uint32_t* ud = tl->u + (q * 28 + ft) * 3584 + (2 * w) * 448 + lane;
                #pragma unroll 1
                for (uint32_t pass = (DRY & 2) ? never : 1; pass < 2; pass++) {
                    if (pass) {
                        mix_mainloop<32, true>(TSVAL acc, 0, leader);
                        if (tid == 0) STAMP(14);
                    }
                    #pragma unroll
                    for (int j = 0; j < 14; j++) {
                        if (j == HINT_U) post_hint_wg(7 + pass, sc->hint_u + (q * 32 + ft) * 2, ep, w, pass ? lane : 2);
                        st_global_if(pass, ud + j * 32, pack_bf16(gelu_half(acc[4 * j]), gelu_half(acc[4 * j + 1])));
                        st_global_if(pass, ud + j * 32 + 448, pack_bf16(gelu_half(acc[4 * j + 2]), gelu_half(acc[4 * j + 3])));
                    }
                }
                if (tid == 0) STAMP(15);
                if (tid == 96) STAMP(34);
            }
            {
                float acc[56];
                const float bb0 = bf_lo(rb20), bb1 = bf_lo(rb21);
                named_sync(1, 128);
                const uint32_t ad = sb + SM_H + (16 * w + (lane & 15)) * 128 + (((lane >> 4) ^ (lane & 7)) << 4);
                #pragma unroll
                for (int jp = 0; jp < 7; jp++) {
                    uint32_t hh[4];
                    ldsm4(hh, hcol(ad, jp));
                    #pragma unroll
                    for (int r = 0; r < 4; r++) { acc[8 * jp + 2 * r] = bf_lo(hh[r]) + ((r & 1) ? bb1 : bb0); acc[8 * jp + 2 * r + 1] = bf_hi(hh[r]) + ((r & 1) ? bb1 : bb0); }
                }
                #pragma unroll 1
                for (uint32_t pass = (DRY & 4) ? never : 1; pass < 2; pass++) {
                    if (pass) {
                        mix_mainloop<28, false>(TSVAL acc, has_b1, leader);
                        if (leader) mbar_arrive(bars + 8 * B_END);
                        if (tid == 0) STAMP(18);
                    }
                    #pragma unroll
                    for (int jp = 0; jp < 7; jp++)
                        stsm4(hcol(ad, jp), pack_bf16(acc[8 * jp], acc[8 * jp + 1]), pack_bf16(acc[8 * jp + 2], acc[8 * jp + 3]),
                              pack_bf16(acc[8 * jp + 4], acc[8 * jp + 5]), pack_bf16(acc[8 * jp + 6], acc[8 * jp + 7]));
                    fence_async_smem();
                    __syncwarp();
                }
                if (elect()) {
                    tma2d_store(&tm_out64, c64, tt2 * 64 + 16 * w, sb + SM_H + w * 2048);
                    tma2d_store(&tm_out48, c48, tt2 * 64 + 16 * w, sb + SM_H + 8192 + w * 2048);
                }
                asm volatile("cp.async.bulk.commit_group;" ::: "memory");
                asm volatile("cp.async.bulk.wait_group.read 0;" ::: "memory");
                if (tid == 0) { sc->epoch[slot] = ep; STAMP(19); }
            }
        }
    } else {
        asm volatile("setmaxnreg.dec.sync.aligned.u32 40;");
        int warp2; asm("mov.u32 %0, %1;" : "=r"(warp2) : "r"(warp));
        if (warp2 > 8) {
            if (elect()) {
                if (warp == 9) {
                    #pragma unroll
                    for (int i = B_DONE1; i < B_DONEO; i++) mbar_init(bars + 8 * i, i < B_DONEX ? 2 : 8);
                    mbar_init(bars + 8 * B_CLR, 1);
                }
                #pragma unroll
                for (int i = 0; i < 34; i++) mbar_init(bars + 8 * (B_DONEO + i) + (warp - 9) * 272, 1);
                asm volatile("fence.mbarrier_init.release.cluster;" ::: "memory");
            }
            named_sync(0, 384);
            if (warp == 9) named_arrive(4, 64);
            if (warp < 11) {
                const uint32_t ep = ld_volatile(&sc->epoch[slot]) + 1;
                mbar_wait(bars + 8 * (B_DONE1 + HALO_AT), 0);
                #pragma unroll 1
                for (int kv = 0; kv < 2; kv++) {
                    uint4 v0 = {}, v1 = {}, v2 = {};
                    if (tb > 0) {
                        const uint4* hg = sc->halo + (((tb * 8 + hp) * 2 + warp - 9) * 2 + kv) * 96 + lane;
                        while (ld_relaxed(sc->hint_kv + (((tb - 1) * 8 + hp) * 2 + warp - 9) * 4 + kv * 2) != ep) {}
                        do { v0 = ld_relaxed4(hg); v1 = ld_relaxed4(hg + 32); v2 = ld_relaxed4(hg + 64); } while (!__all_sync(0xffffffffu, v0.w == ep && v1.w == ep && v2.w == ep));
                    }
                    if (kv) mbar_wait(bars + 8 * (B_DONE1 + 5), 0);
                    uint4* hs = (uint4*)(smem_raw + (kv ? SM_HALOV : SM_HALOK)) + (4 * warp - 33) * 64 + lane;
                    hs[0] = make_uint4(v0.x, v0.y, v0.z, v1.x); hs[32] = make_uint4(v1.y, v1.z, v2.x, v2.y);
                    __syncwarp();
                    if (lane == 0) mbar_arrive(bars + 8 * (B_HALO + 2 * kv + warp - 9));
                }
                if (tid == 288) STAMP(21);
            }
            if (warp == 10) {
                if (!has_b1 && lane == 0) {
                    mbar_wait(bars + 8 * (B_DONEO + 3), 0);
                    uint32_t t = clock32() + PF_AT;
                    #pragma unroll 1
                    for (int i = 0; i < PF_N; i++) {
                        while ((int)(clock32() - t) < 0) __nanosleep(40);
                        bulk_prefetch((const char*)w2 + (i * 16 + mi) * 16384, 16384);
                        t += PF_PACE;
                    }
                }
            } else if (warp == 11) {
                const uint32_t ep = ld_volatile(&sc->epoch[slot]) + 1;
                const long long t0 = clock64();
                while (__any_sync(0xffffffffu, (int)(ld_acquire(&sc->clean[lane & 3]) - ep) < 0)) if (clock64() - t0 > WD_CLKS) __trap();
                if (lane == 0) mbar_arrive(bars + 8 * B_CLR);
                if (lane == 0) {
                    mbar_wait_wd(bars + 8 * B_END, 0);
                }
            } else {
                int aslot = 0;
                if (lane == 0) { prefetch_map(&tm_out64); prefetch_map(&tm_out48); }
                if (has_b1) {
                    #pragma unroll 1
                    for (int i = 0; i < 16; i++) {
                        mbar_wait(bars + 8 * (i < NA_SLOTS ? B_DONEQ + ((A_SCHED >> (4 * i)) & 15) : B_DONE + 1 + ((i - NA_SLOTS) * A3_END) / (15 - NA_SLOTS)), 0);
                        if (elect()) {
                            const uint32_t bar = bars + 8 * (B_FULLA + i), dst = sb + SM_ARING + aslot * 16384;
                            mbar_expect(bar, 16384);
                            tma3d(dst, &tm_w1, ft * 64, 0, i * 64, bar);
                            tma3d(dst + 8192, &tm_w1, ft * 64, 1, i * 64, bar);
                        }
                        aslot = aslot == NA_SLOTS - 1 ? 0 : aslot + 1;
                    }
                }
                aslot = 16 % NA_SLOTS;
                #pragma unroll 1
                for (int i = 0; i < 14; i++) {
                    if (i >= NA_SLOTS) mbar_wait(bars + 8 * (B_DONE + 1 + ((i - NA_SLOTS) * A4_END) / (13 - NA_SLOTS)), has_b1);
                    else if (has_b1) {
                        mbar_wait(bars + 8 * (B_DONE + max(33 - 2 * NA_SLOTS + 2 * i, W2_AT)), 0);
                        if (i >= W2_HOLD) mbar_wait(bars + 8 * B_FULLB, 1);
                    } else if (i == 0) { mbar_wait(bars + 8 * (B_DONEO + 3), 0); const uint32_t t = clock32() + PF_AT + 12 * PF_PACE; while ((int)(clock32() - t) < 0) __nanosleep(100); }
                    if (elect()) {
                        const uint32_t bar = bars + 8 * (B_FULLA + i);
                        mbar_expect(bar, 16384);
                        tma2d(sb + SM_ARING + aslot * 16384, &tm_w2, tt2 * 64, i * 128, bar);
                    }
                    aslot = aslot == NA_SLOTS - 1 ? 0 : aslot + 1;
                }
            }
        } else {
            auto krot = [&](int kb) { const int k = kb * 64 + (G & 1) * 64 * ROT; return k < 448 ? k : k - 448; };
            if (elect()) {
                #pragma unroll
                for (int i = 0; i < 7; i++) mbar_init(bars + 8 * i, 1);
                asm volatile("fence.mbarrier_init.release.cluster;" ::: "memory");
                #pragma unroll 1
                for (int kb = 0; kb < 7; kb++) {
                    const uint32_t st = sb + slot_x(kb), bar = bars + 8 * (B_FULLX + kb);
                    mbar_expect(bar, 16384);
                    tma3d(st, &tm_x, krot(kb), 0, tb * 64, bar); tma3d(st + 8192, &tm_x, krot(kb), 1, tb * 64, bar);
                }
                #pragma unroll
                for (int i = 7; i < B_DONE1; i++) mbar_init(bars + 8 * i, 1);
                asm volatile("fence.mbarrier_init.release.cluster;" ::: "memory");
            }
            named_arrive(0, 384);
            #pragma unroll 1
            for (int kb = 0; kb < 7; kb++) {
                if (kb == 6) { named_sync(4, 64); mbar_wait(bars + 8 * B_DONEX, 0); }
                if (elect()) {
                    const uint32_t st = sb + slot_kv(kb), bar = bars + 8 * (B_FULLKV + kb);
                    mbar_expect(bar, 16384);
                    #pragma unroll
                    for (int i = 0; i < 2; i++) {
                        const int n = 2 * kb + (ROT ? i : i ^ (G & 1));
                        tma2d(st + (n & 1) * 8192, &tm_wqkv, (n < 7 ? 448 : 896) + wcol, krot(n < 7 ? n : n - 7), bar);
                    }
                }
            }
            if (elect()) {
                mbar_expect(bars + 8 * B_FQ, 32768);
                mbar_expect(bars + 8 * (B_FQ + 1), 24576);
                #pragma unroll 1
                for (int i = 0; i < 7; i++) { const int j = ROT || i == 6 ? i : i ^ (G & 1); tma2d(sb + SM_QO + j * 8192, &tm_wqkv, wcol, krot(j), bars + 8 * (B_FQ + (i >> 2))); }
                mbar_expect(bars + 8 * B_FULLWO, 512 * 112 * 2);
            }
            #pragma unroll 1
            for (int i = 0; i < 7; i++) {
                const int kb = ((q & 1 ? WO_ORD1 : WO_ORD0) >> (4 * i)) & 7;
                if (kb < 5) mbar_wait(bars + 8 * (B_DONE1 + kb), 0);
                if (i == WO_HOLD) { mbar_wait(bars + 8 * (B_HALO + 2), 0); mbar_wait(bars + 8 * (B_HALO + 3), 0); }
                if (elect()) {
                    tma2d(sb + slot_wo(kb), &tm_wo64, c64, kb * 64, bars + 8 * B_FULLWO);
                    tma2d(sb + slot_wo(kb) + 8192, &tm_wo48, c48, kb * 64, bars + 8 * B_FULLWO);
                }
            }
            if (XR_HOLD) { mbar_wait(bars + 8 * (B_HALO + 2), 0); mbar_wait(bars + 8 * (B_HALO + 3), 0); }
            if (elect()) {
                tma2d(sb + SM_H, &tm_xr64, c64, tt2 * 64, bars + 8 * B_FULLWO);
                tma2d(sb + SM_H + 8192, &tm_xr48, c48, tt2 * 64, bars + 8 * B_FULLWO);
            }
            if (smem_u32(smem_raw) != SB) __trap();
            const uint32_t ep = ld_volatile(&sc->epoch[slot]) + 1;
            const Tiles* const tl = &sc->tiles[ep & 1];
            mbar_wait(bars + 8 * B_DONEQ, 0);
            {
                uint32_t issued = 0;
                while (issued != 0x01010101u) {
                    uint32_t m = __ballot_sync(0xffffffffu, ld_relaxed(sc->hint_o + (tt2 * 32 + lane) * 2) == ep);
                    m &= m >> 4; m &= m >> 2; m &= m >> 1; m &= 0x01010101u & ~issued;
                    if ((m >> lane) & 1) {
                        const uint32_t bar = bars + 8 * B_RAW + lane;
                        mbar_expect(bar, 14336);
                        bulk_ld(sb + SM_QO + lane * 1792, tl->o + tt2 * 14336 + lane * 448, 14336, bar);
                    }
                    issued |= m;
                }
                __syncwarp();
            }
            if (lane == 0) STAMP(20);
            mbar_wait(bars + 8 * (B_DONEO + 3), 0);
            if (has_b1) {
                mix_producer_b<32>(TSVAL 0, sc->hint_h, ep, tl->hn + q * 32 * 3584, lane);
                mbar_wait(bars + 8 * (B_DONE + 31), 0);
            }
            mix_producer_b<28>(TSVAL has_b1, sc->hint_u, ep, tl->u + q * 28 * 3584, lane);
        }
    }
}

typedef CUresult (*EncodeFn)(CUtensorMap*, CUtensorMapDataType, cuuint32_t, void*, const cuuint64_t*, const cuuint64_t*, const cuuint32_t*,
                             const cuuint32_t*, CUtensorMapInterleave, CUtensorMapSwizzle, CUtensorMapL2promotion, CUtensorMapFloatOOBfill);

void make_map(EncodeFn fn, CUtensorMap* tm, const void* ptr, int rank, const cuuint64_t* dims, const cuuint64_t* strides, const cuuint32_t* box, CUtensorMapSwizzle sw) {
    cuuint32_t es[3] = {1, 1, 1};
    fn(tm, CU_TENSOR_MAP_DATA_TYPE_BFLOAT16, rank, const_cast<void*>(ptr), dims, strides, box, es, CU_TENSOR_MAP_INTERLEAVE_NONE, sw,
       CU_TENSOR_MAP_L2_PROMOTION_NONE, CU_TENSOR_MAP_FLOAT_OOB_FILL_NONE);
}

}

extern "C" void kernel_launch(void* const* d_in, const int* in_sizes, int n_in, void* d_out, int out_size) {
    const __nv_bfloat16* x = (const __nv_bfloat16*)d_in[0];
    const __nv_bfloat16* wqkv = (const __nv_bfloat16*)d_in[1];
    const __nv_bfloat16* wo = (const __nv_bfloat16*)d_in[2];
    const __nv_bfloat16* w1 = (const __nv_bfloat16*)d_in[4];
    const __nv_bfloat16* b1 = (const __nv_bfloat16*)d_in[5];
    const __nv_bfloat16* w2 = (const __nv_bfloat16*)d_in[6];
    const __nv_bfloat16* b2 = (const __nv_bfloat16*)d_in[7];

    void* fnp = nullptr; cudaDriverEntryPointQueryResult qr;
    cudaGetDriverEntryPoint("cuTensorMapEncodeTiled", &fnp, cudaEnableDefault, &qr);
    EncodeFn fn = (EncodeFn)fnp;
    CUtensorMap tx, twqkv, two64, two48, tw1, tw2, txr64, txr48, tout64, tout48;
    { cuuint64_t d[3] = {448, 2, 1024}, s[2] = {896, 1792}; cuuint32_t b[3] = {64, 1, 64}; make_map(fn, &tx, x, 3, d, s, b, CU_TENSOR_MAP_SWIZZLE_128B); }
    { cuuint64_t d[2] = {1344, 448}, s[1] = {2688}; cuuint32_t b[2] = {64, 64}; make_map(fn, &twqkv, wqkv, 2, d, s, b, CU_TENSOR_MAP_SWIZZLE_128B); }
    { cuuint64_t d[2] = {448, 448}, s[1] = {896}; cuuint32_t b[2] = {64, 64}; make_map(fn, &two64, wo, 2, d, s, b, CU_TENSOR_MAP_SWIZZLE_128B); }
    { cuuint64_t d[2] = {448, 448}, s[1] = {896}; cuuint32_t b[2] = {48, 64}; make_map(fn, &two48, wo, 2, d, s, b, CU_TENSOR_MAP_SWIZZLE_128B); }
    { cuuint64_t d[3] = {1792, 2, 1024}, s[2] = {3584, 7168}; cuuint32_t b[3] = {64, 1, 64}; make_map(fn, &tw1, w1, 3, d, s, b, CU_TENSOR_MAP_SWIZZLE_128B); }
    { cuuint64_t d[2] = {2048, 1792}, s[1] = {4096}; cuuint32_t b[2] = {64, 128}; make_map(fn, &tw2, w2, 2, d, s, b, CU_TENSOR_MAP_SWIZZLE_128B); }
    { cuuint64_t d[2] = {448, 2048}, s[1] = {896}; cuuint32_t b[2] = {64, 64}; make_map(fn, &txr64, x, 2, d, s, b, CU_TENSOR_MAP_SWIZZLE_128B); }
    { cuuint64_t d[2] = {448, 2048}, s[1] = {896}; cuuint32_t b[2] = {48, 64}; make_map(fn, &txr48, x, 2, d, s, b, CU_TENSOR_MAP_SWIZZLE_128B); }
    { cuuint64_t d[2] = {448, 2048}, s[1] = {896}; cuuint32_t b[2] = {64, 16}; make_map(fn, &tout64, d_out, 2, d, s, b, CU_TENSOR_MAP_SWIZZLE_128B); }
    { cuuint64_t d[2] = {448, 2048}, s[1] = {896}; cuuint32_t b[2] = {48, 16}; make_map(fn, &tout48, d_out, 2, d, s, b, CU_TENSOR_MAP_SWIZZLE_128B); }

    void* scv = nullptr;
    cudaGetSymbolAddress(&scv, g_scratch);
    Scratch* scp = (Scratch*)scv;
    int dev = 0, sms = 0;
    cudaGetDevice(&dev);
    cudaDeviceGetAttribute(&sms, cudaDevAttrMultiProcessorCount, dev);
    if (sms == 132) {
        cudaFuncSetAttribute(fused_kernel<true>, cudaFuncAttributeMaxDynamicSharedMemorySize, SM_TOTAL);
        fused_kernel<true><<<132, 384, SM_TOTAL>>>(scp, wo, w1, b1, w2, b2, tx, twqkv, two64, two48, tw1, tw2, txr64, txr48, tout64, tout48);
    } else {
        cudaFuncSetAttribute(fused_kernel<false>, cudaFuncAttributeMaxDynamicSharedMemorySize, SM_TOTAL);
        fused_kernel<false><<<132, 384, SM_TOTAL>>>(scp, wo, w1, b1, w2, b2, tx, twqkv, two64, two48, tw1, tw2, txr64, txr48, tout64, tout48);
    }
}
```

```cpp
#include <cuda_runtime.h>
#include <cuda_bf16.h>
#include <cuda.h>
#include <stdint.h>

namespace {

constexpr int D_ = 448;
constexpr float LN_EPS = 1e-5f;
constexpr float LOG2E_SCALE = 0.1889822365046136f * 1.4426950408889634f;

struct Tiles {
    uint32_t o[32 * 57344 / 4];
    uint32_t hn[4 * 32 * 14336 / 4];
    uint32_t u[4 * 28 * 14336 / 4];
};
struct Scratch {
    Tiles tiles[2];
    uint4 halo[128 * 2 * 2 * 3 * 32];
    uint4 stats[32 * 4 * 64];
    uint4 hint_kv[128 * 2 * 2 * 2];
    uint4 hint_o[32 * 32 * 2];
    uint4 hint_h[4 * 32 * 2];
    uint4 hint_u[4 * 32 * 2];
    uint32_t epoch[160];
    uint32_t clean[16];
};
__device__ __align__(1024) Scratch g_scratch;
#define STAMP(i) do {} while (0)
#define FST(i) do {} while (0)
#define TSARG
#define TSVAL

constexpr uint32_t SB = 1024;
constexpr int SM_SLOT = 16384;
__device__ __forceinline__ constexpr uint32_t slot_x(int kb) { return (kb ? 6 + kb : 0) * SM_SLOT; }
__device__ __forceinline__ constexpr uint32_t slot_kv(int kb) { return (kb < 5 ? 2 + kb : 6 - kb) * SM_SLOT; }
__device__ __forceinline__ constexpr uint32_t slot_wo(int kb) { return (kb < 6 ? 2 + kb : 12) * SM_SLOT; }
constexpr int SM_QO = 8 * SM_SLOT;
constexpr int SM_HALOK = SM_QO + 57344, SM_HALOV = 1 * SM_SLOT;
constexpr int NA_SLOTS = 6, NB_SLOTS = 8;
constexpr int SM_ARING = 0;
constexpr int SM_BRING = NA_SLOTS * 16384;
constexpr int SM_H = 212992;
constexpr int SM_MISC = 229376;
constexpr int SM_BAR = 231424;
constexpr int SM_TOTAL = 232448;
constexpr int B_FULLX = 0;
constexpr int B_FULLKV = 7;
constexpr int B_FQ = 14;
constexpr int B_DONE1 = 16;
constexpr int B_DONEX = 23;
constexpr int B_DONEQ = 24;
constexpr int B_DONEO = 25;
constexpr int B_FULLO = 29;
constexpr int B_FULLWO = 33;
constexpr int B_END = 34;
constexpr int B_HALO = 35;
constexpr int B_FULLA = 39;
constexpr int B_FULLB = 55;
constexpr int B_DONE = 87;
constexpr int B_RAW = 119;
constexpr int B_CLR = 127;

constexpr long long WD_CLKS = 2000000000ll;

template<int N> struct Int { static constexpr int value = N; };
template<int A, int B, class F> __device__ __forceinline__ void static_for(F&& f) { if constexpr (A < B) { f(Int<A>()); static_for<A + 1, B>(f); } }

__device__ __forceinline__ uint32_t smem_u32(const void* p) { return (uint32_t)__cvta_generic_to_shared(p); }
__device__ __forceinline__ void mbar_init(uint32_t bar, uint32_t cnt) { asm volatile("mbarrier.init.shared::cta.b64 [%0], %1;" :: "r"(bar), "r"(cnt) : "memory"); }
__device__ __forceinline__ void mbar_expect(uint32_t bar, uint32_t bytes) { asm volatile("mbarrier.arrive.expect_tx.shared::cta.b64 _, [%0], %1;" :: "r"(bar), "r"(bytes) : "memory"); }
__device__ __forceinline__ void mbar_arrive(uint32_t bar) { asm volatile("mbarrier.arrive.shared::cta.b64 _, [%0];" :: "r"(bar) : "memory"); }
__device__ __forceinline__ bool mbar_try(uint32_t bar, uint32_t parity) {
    uint32_t ok;
    asm volatile("{\n.reg .pred p;\nmbarrier.try_wait.parity.shared::cta.b64 p, [%1], %2;\nselp.u32 %0, 1, 0, p;\n}" : "=r"(ok) : "r"(bar), "r"(parity) : "memory");
    return ok;
}
__device__ __forceinline__ bool mbar_test(uint32_t bar, uint32_t parity) {
    uint32_t ok;
    asm volatile("{\n.reg .pred p;\nmbarrier.test_wait.parity.shared::cta.b64 p, [%1], %2;\nselp.u32 %0, 1, 0, p;\n}" : "=r"(ok) : "r"(bar), "r"(parity) : "memory");
    return ok;
}
__device__ __forceinline__ void mbar_wait(uint32_t bar, uint32_t parity) {
    asm volatile("{\n.reg .pred p;\n"
                 "WAIT_LOOP:\n"
                 "mbarrier.try_wait.parity.shared::cta.b64 p, [%0], %1;\n"
                 "@!p bra WAIT_LOOP;\n}" :: "r"(bar), "r"(parity) : "memory");
}
__device__ __forceinline__ void mbar_wait_wd(uint32_t bar, uint32_t parity) {
    const long long t0 = clock64();
    while (!mbar_try(bar, parity)) { if (clock64() - t0 > WD_CLKS) __trap(); }
}
__device__ __forceinline__ bool elect() { uint32_t p; asm volatile("{\n.reg .pred P;\nelect.sync _|P, 0xffffffff;\nselp.u32 %0, 1, 0, P;\n}" : "=r"(p)); return p; }
__device__ __forceinline__ void tma2d(uint32_t dst, const CUtensorMap* tm, int c0, int c1, uint32_t bar) {
    asm volatile("cp.async.bulk.tensor.2d.shared::cluster.global.mbarrier::complete_tx::bytes [%0], [%1, {%3, %4}], [%2];" :: "r"(dst), "l"(tm), "r"(bar), "r"(c0), "r"(c1) : "memory");
}
__device__ __forceinline__ void tma3d(uint32_t dst, const CUtensorMap* tm, int c0, int c1, int c2, uint32_t bar) {
    asm volatile("cp.async.bulk.tensor.3d.shared::cluster.global.mbarrier::complete_tx::bytes [%0], [%1, {%3, %4, %5}], [%2];" :: "r"(dst), "l"(tm), "r"(bar), "r"(c0), "r"(c1), "r"(c2) : "memory");
}
__device__ __forceinline__ void tma2d_store(const CUtensorMap* tm, int c0, int c1, uint32_t src) {
    asm volatile("cp.async.bulk.tensor.2d.global.shared::cta.bulk_group [%0, {%2, %3}], [%1];" :: "l"(tm), "r"(src), "r"(c0), "r"(c1) : "memory");
}
__device__ __forceinline__ void bulk_ld(uint32_t dst, const void* src, uint32_t bytes, uint32_t bar) {
    asm volatile("cp.async.bulk.shared::cluster.global.mbarrier::complete_tx::bytes [%0], [%1], %2, [%3];" :: "r"(dst), "l"(src), "r"(bytes), "r"(bar) : "memory");
}
__device__ __forceinline__ void bulk_prefetch(const void* src, uint32_t bytes) { asm volatile("cp.async.bulk.prefetch.L2.global [%0], %1;" :: "l"(src), "r"(bytes) : "memory"); }
__device__ __forceinline__ void prefetch_map(const CUtensorMap* tm) { asm volatile("prefetch.tensormap [%0];" :: "l"(tm) : "memory"); }
__device__ __forceinline__ void st_global_if(uint32_t c, uint32_t* p, uint32_t v) {
    asm volatile("{\n.reg .pred p;\nsetp.ne.u32 p, %2, 0;\n@p st.global.u32 [%0], %1;\n}" :: "l"(p), "r"(v), "r"(c) : "memory");
}
__device__ __forceinline__ void pin4(uint32_t never, float a, float b, float c, float d) {
    asm volatile("{\n.reg .pred p;\nsetp.ne.u32 p, %4, 0;\n@p st.shared.v4.f32 [%4], {%0,%1,%2,%3};\n}" :: "f"(a), "f"(b), "f"(c), "f"(d), "r"(never) : "memory");
}
__device__ __forceinline__ void fence_async_smem() { asm volatile("fence.proxy.async.shared::cta;" ::: "memory"); }
__device__ __forceinline__ uint32_t ld_acquire(const void* p) { uint32_t v; asm volatile("ld.acquire.gpu.global.u32 %0, [%1];" : "=r"(v) : "l"(p) : "memory"); return v; }
__device__ __forceinline__ void st_release(void* p, uint32_t v) { asm volatile("st.release.gpu.global.u32 [%0], %1;" :: "l"(p), "r"(v) : "memory"); }
__device__ __forceinline__ uint32_t ld_relaxed(const void* p) { uint32_t v; asm volatile("ld.relaxed.gpu.global.u32 %0, [%1];" : "=r"(v) : "l"(p) : "memory"); return v; }
__device__ __forceinline__ uint2 ld_relaxed2(const void* p) {
    uint2 v; asm volatile("{\n.reg .b64 a;\nld.relaxed.gpu.global.b64 a, [%2];\nmov.b64 {%0, %1}, a;\n}" : "=r"(v.x), "=r"(v.y) : "l"(p) : "memory"); return v;
}
__device__ __forceinline__ uint4 ld_relaxed4(const uint4* p) {
    uint4 v;
    asm volatile("{\n.reg .b128 t;\n.reg .b64 a, b;\nld.relaxed.gpu.global.b128 t, [%4];\nmov.b128 {a, b}, t;\nmov.b64 {%0, %1}, a;\nmov.b64 {%2, %3}, b;\n}" : "=r"(v.x), "=r"(v.y), "=r"(v.z), "=r"(v.w) : "l"(p) : "memory");
    return v;
}
__device__ __forceinline__ void st_relaxed4(uint4* p, uint32_t a, uint32_t b, uint32_t c, uint32_t d) {
    asm volatile("{\n.reg .b128 t;\n.reg .b64 a, b;\nmov.b64 a, {%1, %2};\nmov.b64 b, {%3, %4};\nmov.b128 t, {a, b};\nst.relaxed.gpu.global.b128 [%0], t;\n}" :: "l"(p), "r"(a), "r"(b), "r"(c), "r"(d) : "memory");
}
__device__ __forceinline__ uint32_t ld_volatile(const uint32_t* p) { uint32_t v; asm volatile("ld.volatile.global.u32 %0, [%1];" : "=r"(v) : "l"(p) : "memory"); return v; }
__device__ __forceinline__ void named_arrive(int id, int n) { asm volatile("bar.arrive %0, %1;" :: "r"(id), "r"(n) : "memory"); }
__device__ __forceinline__ void named_sync(int id, int n) { asm volatile("bar.sync %0, %1;" :: "r"(id), "r"(n) : "memory"); }
__device__ __forceinline__ void wg_fence() { asm volatile("wgmma.fence.sync.aligned;" ::: "memory"); }
__device__ __forceinline__ void wg_commit() { asm volatile("wgmma.commit_group.sync.aligned;" ::: "memory"); }
template<int N> __device__ __forceinline__ void wg_wait() { asm volatile("wgmma.wait_group.sync.aligned %0;" :: "n"(N) : "memory"); }
template<int N> __device__ __forceinline__ void reg_fence(float (&d)[N]) {
    #pragma unroll
    for (int i = 0; i < N; i++) asm volatile("" : "+f"(d[i]) :: "memory");
}
__device__ __forceinline__ constexpr uint64_t mkdesc(uint32_t addr, uint32_t lbo, uint32_t sbo, uint32_t sw) {
    return (uint64_t)((addr & 0x3FFFF) >> 4) | ((uint64_t)(lbo >> 4) << 16) | ((uint64_t)(sbo >> 4) << 32) | ((uint64_t)sw << 62);
}
__device__ __forceinline__ void ldsm4(uint32_t (&r)[4], uint32_t addr) {
    asm volatile("ldmatrix.sync.aligned.m8n8.x4.shared.b16 {%0,%1,%2,%3}, [%4];" : "=r"(r[0]), "=r"(r[1]), "=r"(r[2]), "=r"(r[3]) : "r"(addr) : "memory");
}
__device__ __forceinline__ void stsm4(uint32_t addr, uint32_t r0, uint32_t r1, uint32_t r2, uint32_t r3) {
    asm volatile("stmatrix.sync.aligned.m8n8.x4.shared.b16 [%0], {%1,%2,%3,%4};" :: "r"(addr), "r"(r0), "r"(r1), "r"(r2), "r"(r3) : "memory");
}
__device__ __forceinline__ uint32_t movtrans(uint32_t a) { uint32_t d; asm volatile("movmatrix.sync.aligned.m8n8.trans.b16 %0, %1;" : "=r"(d) : "r"(a)); return d; }
__device__ __forceinline__ uint32_t pack_bf16(float lo, float hi) { uint32_t r; asm("cvt.rn.bf16x2.f32 %0, %1, %2;" : "=r"(r) : "f"(hi), "f"(lo)); return r; }
__device__ __forceinline__ void sub_bf16x2(uint32_t& a, uint32_t b) { asm volatile("sub.rn.bf16x2 %0, %0, %1;" : "+r"(a) : "r"(b)); }
__device__ __forceinline__ float bf_lo(uint32_t v) { return __uint_as_float(v << 16); }
__device__ __forceinline__ float bf_hi(uint32_t v) { return __uint_as_float(v & 0xffff0000u); }
__device__ __forceinline__ void mma16816(float (&c)[4], uint32_t a0, uint32_t a1, uint32_t a2, uint32_t a3, uint32_t b0, uint32_t b1) {
    asm volatile("mma.sync.aligned.m16n8k16.row.col.f32.bf16.bf16.f32 {%0,%1,%2,%3}, {%4,%5,%6,%7}, {%8,%9}, {%0,%1,%2,%3};"
        : "+f"(c[0]), "+f"(c[1]), "+f"(c[2]), "+f"(c[3]) : "r"(a0), "r"(a1), "r"(a2), "r"(a3), "r"(b0), "r"(b1));
}
__device__ __forceinline__ void mma1688(float (&c)[4], uint32_t a0, uint32_t a1, uint32_t b0) {
    asm volatile("mma.sync.aligned.m16n8k8.row.col.f32.bf16.bf16.f32 {%0,%1,%2,%3}, {%4,%5}, {%6}, {%0,%1,%2,%3};"
        : "+f"(c[0]), "+f"(c[1]), "+f"(c[2]), "+f"(c[3]) : "r"(a0), "r"(a1), "r"(b0));
}
__device__ __forceinline__ float quad_sum(float v) { v += __shfl_xor_sync(0xffffffffu, v, 1); v += __shfl_xor_sync(0xffffffffu, v, 2); return v; }
__device__ __forceinline__ float quad_max(float v) { v = fmaxf(v, __shfl_xor_sync(0xffffffffu, v, 1)); v = fmaxf(v, __shfl_xor_sync(0xffffffffu, v, 2)); return v; }
__device__ __forceinline__ float ex2(float x) { float y; asm("ex2.approx.ftz.f32 %0, %1;" : "=f"(y) : "f"(x)); return y; }
__device__ __forceinline__ float rsqrt_approx(float x) { float y; asm("rsqrt.approx.ftz.f32 %0, %1;" : "=f"(y) : "f"(x)); return y; }
__device__ __forceinline__ float rcp_approx(float x) { float y; asm("rcp.approx.ftz.f32 %0, %1;" : "=f"(y) : "f"(x)); return y; }
__device__ __forceinline__ float gelu_half(float hx) {
    const float z = hx * fmaf(hx * hx, 8.f * 0.044715f * 0.7978845608028654f, 2.f * 0.7978845608028654f);
    float t; asm("tanh.approx.f32 %0, %1;" : "=f"(t) : "f"(z));
    return fmaf(hx, t, hx);
}
__device__ __forceinline__ uint32_t gtime32() { uint32_t t; asm volatile("mov.u32 %0, %%globaltimer_lo;" : "=r"(t)); return t; }
__device__ __forceinline__ uint32_t clock32() { uint32_t t; asm volatile("mov.u32 %0, %%clock;" : "=r"(t)); return t; }
#define PF_PACE 400

#define PF_AT 4000
#define NSQ 6
#define HALO_AT 3
#define PF_N 12
#define HINT_H 0
#define HINT_U 28
#define SP_AT 2000
#define SP_N 0
#define WO_HOLD 7
#define A_SCHED 0x322188
#define WO_ORD0 0x4321065
#define WO_ORD1 0x3465210
#define XR_HOLD 0
#define ROT 0
#define SQMIX 0
#define NPIPE 1
#define CL_AT 4000
#define WARM 1
#define WARM_AT 300
#define W2_AT 23
#define W2_HOLD 5
#define A3_END 20
#define A4_END 16
#define DRY 7
#define GO_H 608
#define GO_U 928
#define STAG 0
#define GO_O 1216
#define LATE_O 832
template<int TB> __device__ __forceinline__ void wgmma_rs56(float (&d)[28], const uint32_t (&a)[4], uint64_t db, int sc) {
    asm volatile("{\n.reg .pred p;\nsetp.ne.b32 p, %33, 0;\n"
        "wgmma.mma_async.sync.aligned.m64n56k16.f32.bf16.bf16 {%0, %1, %2, %3, %4, %5, %6, %7, %8, %9, %10, %11, %12, %13, %14, %15, %16, %17, %18, %19, %20, %21, %22, %23, %24, %25, %26, %27}, {%28, %29, %30, %31}, %32, p, 1, 1, %34;\n}\n"
        : "+f"(d[0]), "+f"(d[1]), "+f"(d[2]), "+f"(d[3]), "+f"(d[4]), "+f"(d[5]), "+f"(d[6]), "+f"(d[7]), "+f"(d[8]), "+f"(d[9]), "+f"(d[10]), "+f"(d[11]), "+f"(d[12]), "+f"(d[13]), "+f"(d[14]), "+f"(d[15]), "+f"(d[16]), "+f"(d[17]), "+f"(d[18]), "+f"(d[19]), "+f"(d[20]), "+f"(d[21]), "+f"(d[22]), "+f"(d[23]), "+f"(d[24]), "+f"(d[25]), "+f"(d[26]), "+f"(d[27])
        : "r"(a[0]), "r"(a[1]), "r"(a[2]), "r"(a[3]), "l"(db), "r"(sc), "n"(TB));
}

template<int TA, int TB, int SC = 1> __device__ __forceinline__ void wgmma_ss112(float (&d)[56], uint64_t da, uint64_t db) {
    asm volatile("wgmma.mma_async.sync.aligned.m64n112k16.f32.bf16.bf16 {%0, %1, %2, %3, %4, %5, %6, %7, %8, %9, %10, %11, %12, %13, %14, %15, %16, %17, %18, %19, %20, %21, %22, %23, %24, %25, %26, %27, %28, %29, %30, %31, %32, %33, %34, %35, %36, %37, %38, %39, %40, %41, %42, %43, %44, %45, %46, %47, %48, %49, %50, %51, %52, %53, %54, %55}, %56, %57, %60, 1, 1, %58, %59;\n"
        : "+f"(d[0]), "+f"(d[1]), "+f"(d[2]), "+f"(d[3]), "+f"(d[4]), "+f"(d[5]), "+f"(d[6]), "+f"(d[7]), "+f"(d[8]), "+f"(d[9]), "+f"(d[10]), "+f"(d[11]), "+f"(d[12]), "+f"(d[13]), "+f"(d[14]), "+f"(d[15]), "+f"(d[16]), "+f"(d[17]), "+f"(d[18]), "+f"(d[19]), "+f"(d[20]), "+f"(d[21]), "+f"(d[22]), "+f"(d[23]), "+f"(d[24]), "+f"(d[25]), "+f"(d[26]), "+f"(d[27]), "+f"(d[28]), "+f"(d[29]), "+f"(d[30]), "+f"(d[31]), "+f"(d[32]), "+f"(d[33]), "+f"(d[34]), "+f"(d[35]), "+f"(d[36]), "+f"(d[37]), "+f"(d[38]), "+f"(d[39]), "+f"(d[40]), "+f"(d[41]), "+f"(d[42]), "+f"(d[43]), "+f"(d[44]), "+f"(d[45]), "+f"(d[46]), "+f"(d[47]), "+f"(d[48]), "+f"(d[49]), "+f"(d[50]), "+f"(d[51]), "+f"(d[52]), "+f"(d[53]), "+f"(d[54]), "+f"(d[55])
        : "l"(da), "l"(db), "n"(TA), "n"(TB), "n"(SC));
}

template<int TA, int TB, int SC = 1> __device__ __forceinline__ void wgmma_ss64(float (&d)[32], uint64_t da, uint64_t db) {
    asm volatile("wgmma.mma_async.sync.aligned.m64n64k16.f32.bf16.bf16 {%0, %1, %2, %3, %4, %5, %6, %7, %8, %9, %10, %11, %12, %13, %14, %15, %16, %17, %18, %19, %20, %21, %22, %23, %24, %25, %26, %27, %28, %29, %30, %31}, %32, %33, %36, 1, 1, %34, %35;\n"
        : "+f"(d[0]), "+f"(d[1]), "+f"(d[2]), "+f"(d[3]), "+f"(d[4]), "+f"(d[5]), "+f"(d[6]), "+f"(d[7]), "+f"(d[8]), "+f"(d[9]), "+f"(d[10]), "+f"(d[11]), "+f"(d[12]), "+f"(d[13]), "+f"(d[14]), "+f"(d[15]), "+f"(d[16]), "+f"(d[17]), "+f"(d[18]), "+f"(d[19]), "+f"(d[20]), "+f"(d[21]), "+f"(d[22]), "+f"(d[23]), "+f"(d[24]), "+f"(d[25]), "+f"(d[26]), "+f"(d[27]), "+f"(d[28]), "+f"(d[29]), "+f"(d[30]), "+f"(d[31])
        : "l"(da), "l"(db), "n"(TA), "n"(TB), "n"(SC));
}

template<int TA, int TB, int SC = 1> __device__ __forceinline__ void wgmma_ss48(float (&d)[24], uint64_t da, uint64_t db) {
    asm volatile("wgmma.mma_async.sync.aligned.m64n48k16.f32.bf16.bf16 {%0, %1, %2, %3, %4, %5, %6, %7, %8, %9, %10, %11, %12, %13, %14, %15, %16, %17, %18, %19, %20, %21, %22, %23}, %24, %25, %28, 1, 1, %26, %27;\n"
        : "+f"(d[0]), "+f"(d[1]), "+f"(d[2]), "+f"(d[3]), "+f"(d[4]), "+f"(d[5]), "+f"(d[6]), "+f"(d[7]), "+f"(d[8]), "+f"(d[9]), "+f"(d[10]), "+f"(d[11]), "+f"(d[12]), "+f"(d[13]), "+f"(d[14]), "+f"(d[15]), "+f"(d[16]), "+f"(d[17]), "+f"(d[18]), "+f"(d[19]), "+f"(d[20]), "+f"(d[21]), "+f"(d[22]), "+f"(d[23])
        : "l"(da), "l"(db), "n"(TA), "n"(TB), "n"(SC));
}

template<int NKB, bool PERM>
__device__ __forceinline__ void mix_mainloop(TSARG float (&acc)[56], uint32_t par, bool leader) {
    constexpr uint32_t sb = SB, bars = sb + SM_BAR;
    constexpr int A0 = PERM ? 0 : 16 % NA_SLOTS;
    auto aoff = [](int jj, int s) { return (PERM ? (s & 1) * 8192 + (jj * 32 + (s >> 1) * 16) * 128 : jj * 8192 + s * 2048) >> 4; };
    int bslot = 0, aslot = A0;
    reg_fence(acc);
    #pragma unroll 1
    for (int i = 0; i < NKB / 2; i++) {
        mbar_wait(bars + 8 * (B_FULLA + i), par);
        const uint64_t adesc = mkdesc(sb + SM_ARING, 8192, 1024, 1) + (uint32_t)(aslot * 1024);
        aslot = aslot == NA_SLOTS - 1 ? 0 : aslot + 1;
        #pragma unroll
        for (int jj = 0; jj < 2; jj++) {
            const int j = 2 * i + jj;
            mbar_wait(bars + 8 * (B_FULLB + j), par);
            const uint64_t bdesc = mkdesc(sb + SM_BRING, 1792, 128, 0) + (uint32_t)(bslot * 896);
            bslot = bslot == NB_SLOTS - 1 ? 0 : bslot + 1;
            wg_fence();
            #pragma unroll
            for (int s = 0; s < 4; s++) wgmma_ss112<1, 1>(acc, adesc + aoff(jj, s), bdesc + s * 224);
            wg_commit();
            wg_wait<1>();
            if (j > 0 && leader) mbar_arrive(bars + 8 * (B_DONE + j - 1));
        }
    }
    wg_wait<0>();
    reg_fence(acc);
    if (leader) mbar_arrive(bars + 8 * (B_DONE + NKB - 1));
}

constexpr uint32_t EMPTY = 0xFFFFFFFFu;
__device__ __forceinline__ void post_hint(uint4* p, uint32_t ep, int lane) { if (lane < 2) st_relaxed4(p + lane, ep, ep, ep, ep); }
__device__ __forceinline__ void post_hint_wg(int id, uint4* p, uint32_t ep, int w, int lane) {
    if (w < 3) named_arrive(id, 128);
    else { named_sync(id, 128); const uint32_t now = gtime32(); if (lane < 2) st_relaxed4(p + lane, ep, now, ep, now); }
}

__device__ __forceinline__ void wait_hints(TSARG const uint4* hint, uint32_t ep, uint32_t delay, int st) {
    uint2 v;
    do { v = ld_relaxed2(hint); } while (!__all_sync(0xffffffffu, v.x == ep));
    const uint32_t t1 = gtime32(), age = __reduce_min_sync(0xffffffffu, t1 + 256 - v.y);
    if (elect()) STAMP(st);
    while (gtime32() - t1 + age < delay + 256) {}
    __syncwarp();
}

template<int NKB>
__device__ __forceinline__ void mix_producer_b(TSARG uint32_t par, const uint4* hints, uint32_t ep, const uint32_t* src, int lane) {
    constexpr uint32_t sb = SB, bars = sb + SM_BAR;
    wait_hints(TSVAL hints + (lane >> 3) * 64 + (lane & 7) * 2, ep, NKB == 32 ? GO_H : GO_U, NKB == 32 ? 42 : 43);
    if (par) mbar_wait(bars + 8 * (B_DONE + 31), 0);
    #pragma unroll 1
    for (int j = 0; j < NKB; j++) {
        if (j >= NB_SLOTS) mbar_wait(bars + 8 * (B_DONE + j - NB_SLOTS), par);
        if (j == 0 && lane == 0) STAMP(NKB == 32 ? 29 : 30);
        if (j == 7 && lane == 0) STAMP(NKB == 32 ? 35 : 36);
        if (elect()) {
            mbar_expect(bars + 8 * (B_RAW + (j & 7)), 14336);
            bulk_ld(sb + SM_BRING + (j & 7) * 14336, src + j * 3584, 14336, bars + 8 * (B_RAW + (j & 7)));
        }
    }
}
__device__ __forceinline__ void check_tiles(TSARG int n, int w, int lane, uint32_t& ph, uint32_t dst, const uint32_t* src, int full) {
    constexpr uint32_t bars = SB + SM_BAR;
    #pragma unroll 1
    for (int j = w; j < n; j += 4) {
        const uint32_t raw = bars + 8 * (B_RAW + (j & 7)), d = dst + (j & 7) * 14336, a = d + lane * 128 + (lane & 3) * 32 + (lane >> 2) * 4;
        bool bad;
        do {
            mbar_wait(raw, (ph >> (j & 4)) & 1);
            ph ^= 1u << (j & 4);
            if (j == 0 && lane == 0) STAMP(n == 4 ? 6 : n == 32 ? 31 : 32);
            uint32_t v0, v1, v2, v3;
            asm volatile("ld.shared.u32 %0, [%4];\nld.shared.u32 %1, [%4+4096];\nld.shared.u32 %2, [%4+8192];\nld.shared.u32 %3, [%4+10240];"
                         : "=r"(v0), "=r"(v1), "=r"(v2), "=r"(v3) : "r"(a) : "memory");
            bad = __any_sync(0xffffffffu, max(max(v0, v1), max(v2, v3)) == EMPTY);
            if (elect() && bad) {
                mbar_expect(raw, 14336); bulk_ld(d, src + j * 3584, 14336, raw);
            }
        } while (bad);
        if (lane == 0) mbar_arrive(bars + 8 * (full + j));
    }
}

__device__ __forceinline__ uint32_t hcol(uint32_t a, int jp) { return (a ^ ((jp & 3) << 5)) + (jp >> 2) * 8192; }

template<bool USE_SMID>
__global__ void __launch_bounds__(384, 1)
fused_kernel(Scratch* __restrict__ sc, const __nv_bfloat16* __restrict__ wo,
             const __nv_bfloat16* __restrict__ w1, const __nv_bfloat16* __restrict__ b1,
             const __nv_bfloat16* __restrict__ w2, const __nv_bfloat16* __restrict__ b2,
             const __grid_constant__ CUtensorMap tm_x, const __grid_constant__ CUtensorMap tm_wqkv,
             const __grid_constant__ CUtensorMap tm_wo64, const __grid_constant__ CUtensorMap tm_wo48,
             const __grid_constant__ CUtensorMap tm_w1, const __grid_constant__ CUtensorMap tm_w2,
             const __grid_constant__ CUtensorMap tm_xr64, const __grid_constant__ CUtensorMap tm_xr48,
             const __grid_constant__ CUtensorMap tm_out64, const __grid_constant__ CUtensorMap tm_out48) {
    extern __shared__ __align__(1024) uint8_t smem_raw[];
    constexpr uint32_t sb = SB;
    constexpr uint32_t bars = sb + SM_BAR;
    const int tid = threadIdx.x, lane = tid & 31;
    const int warp = __shfl_sync(0xffffffffu, tid >> 5, 0);
    int slot;
    if (USE_SMID) {
        asm("{\n.reg .u32 s, t, u, d, a, b, c;\n.reg .pred p, r;\n"
            "mov.u32 s, %%smid;\nshr.u32 t, s, 1;\nsub.u32 u, t, 32;\nmul.lo.u32 d, u, 37;\nshr.u32 d, d, 8;\n"
            "and.b32 a, t, 7;\nshl.b32 a, a, 3;\nshr.u32 c, t, 3;\nadd.u32 a, a, c;\n"
            "mad.lo.u32 b, d, -55, 12;\nshl.b32 c, u, 3;\nadd.u32 b, b, c;\n"
            "setp.lt.u32 p, t, 32;\nselp.u32 a, a, b, p;\n"
            "setp.lt.u32 r, t, 62;\nselp.s32 c, 4, -58, r;\nadd.u32 c, t, c;\nsetp.lt.u32 p, t, 60;\nselp.u32 a, a, c, p;\n"
            "and.b32 s, s, 1;\nshl.b32 a, a, 1;\nadd.u32 %0, a, s;\n}" : "=r"(slot));
    } else slot = blockIdx.x;
    const int G = slot >> 4, mi = slot & 15;
    const int tb = 4 * (G >> 1) + (mi >> 2), hp = 2 * (mi & 3) + (G & 1);
    const int wcol = (hp * 56) & ~15;
    if (slot >= 128) {
        if (tid == 0) {
            const uint32_t ep = ld_volatile(&sc->epoch[slot]) + 1;
            const long long t0 = clock64();
            while (clock64() - t0 < SP_AT) {}
            #pragma unroll 1
            for (int i = 0; i < 7; i++) bulk_prefetch((const char*)wo + (i * 4 + mi) * 14336, 14336);
            #pragma unroll 1
            for (int i = 0; i < SP_N; i++) bulk_prefetch((const char*)w1 + (i * 4 + mi) * 14336, 14336);
            while (ld_relaxed(sc->hint_u) != ep) { __nanosleep(500); if (clock64() - t0 > WD_CLKS) __trap(); }
            sc->epoch[slot] = ep;
        }
        return;
    }
    const int q = mi & 3, tt2 = 4 * G + (mi >> 2), ft = 4 * (G - 1) + (mi >> 2);
    const bool has_b1 = G > 0;
    const int c64 = 64 * q, c48 = 256 + 48 * q;

    if (warp < 8) {
        if (WARM) {
            const int w = warp & 3, wg = warp >> 2, g = lane >> 2, t = lane & 3;
            if (WARM_AT) { const uint32_t t0 = clock32(); while (clock32() - t0 < WARM_AT) {} __syncwarp(); }
            if (w == 3 && lane < 4) st_relaxed4(sc->hint_kv + ((tb * 8 + hp) * 2 + wg) * 4 + lane, 0, 0, 0, 0);
            if (w > 0) post_hint(sc->hint_o + ((2 * tb + (w >> 1)) * 32 + hp * 4 + (w & 1) * 2 + wg) * 2, 0, lane);
            if (wg == 0) {
                if (t < 2) st_relaxed4(sc->stats + tt2 * 256 + q * 64 + 16 * w + g + 8 * t, 0, 0, 0, 0);
                if (w == 3) post_hint(sc->hint_h + (q * 32 + tt2) * 2, 0, lane);
            }
        }
        named_sync(0, 384);
        asm volatile("setmaxnreg.inc.sync.aligned.u32 232;");
        int tid; asm volatile("mov.u32 %0, %%tid.x;" : "=r"(tid));
        const int lane = tid & 31, warp = __shfl_sync(0xffffffffu, tid >> 5, 0), wg = warp >> 2;
        const uint32_t ep = ld_volatile(&sc->epoch[slot]) + 1;
        Tiles* const tl = &sc->tiles[ep & 1];
        const int w = warp & 3, g = lane >> 2, t = lane & 3;
        const bool leader = (tid & 127) == 0;
        const uint32_t never = gridDim.y - 1;
        {
            uint32_t a[28][4];
            float accK[28], accV[28], accQ[28];
            const int lrow = 16 * w + (lane & 7) + (lane & 8);
            const uint32_t lbase = sb + wg * 8192 + lrow * 128;
            const uint32_t lx = (lane >> 4) ^ (lane & 7);
            const uint32_t wofs = hp & 1;
            auto pin2 = [&](uint32_t x0, uint32_t x1) {
                asm volatile("{\n.reg .pred p;\nsetp.ne.u32 p, %2, 0;\n@p st.shared.v2.b32 [%0], {%0,%1};\n}" :: "r"(x0), "r"(x1), "r"(never) : "memory");
            };
            float cS[2][4] = {}, cA[2][4] = {}, cB[2][4] = {}, q0 = 0.f, q1 = 0.f;
            auto sq = [&](float& acc, uint32_t v) { const float lo = bf_lo(v), hi = bf_hi(v); acc = fmaf(hi, hi, fmaf(lo, lo, acc)); };
            #pragma unroll
            for (int kb = 0; kb < 8; kb++) {
                if (kb < 7) {
                    mbar_wait(bars + 8 * (B_FULLX + kb), 0);
                    if (kb == 0 && tid == 0) STAMP(0);
                    if (kb == 6 && tid == 0) STAMP(25);
                    if (kb == 0) FST(0); if (kb == 2) FST(1); if (kb == 4) FST(2); if (kb == 6) FST(3);
                    #pragma unroll
                    for (int s = 4 * kb; s < 4 * kb + 4; s++) ldsm4(a[s], lbase + slot_x(kb) + ((lx ^ (2 * (s & 3))) << 4));
                }
                if (kb == NPIPE) continue;
                const int kc = kb < NPIPE ? kb : kb - 1;
                #pragma unroll
                for (int s = 4 * kc; s < 4 * kc + 4; s++) {
                    mma16816(cS[s & 1], a[s][0], a[s][1], a[s][2], a[s][3], 0x3F803F80u, 0x3F803F80u);
                    if (kc < NSQ) {
                        mma1688(cA[0], a[s][0], a[s][1], a[s][0]); mma1688(cA[1], a[s][2], a[s][3], a[s][2]);
                        if (SQMIX) { sq(q1, a[s][1]); sq(q1, a[s][3]); }
                        else { mma1688(cB[0], a[s][0], a[s][1], a[s][1]); mma1688(cB[1], a[s][2], a[s][3], a[s][3]); }
                    }
                }
                if (SQMIX && kc < NSQ) pin2(__float_as_uint(q1), 0);
            }
            const float m0 = (cS[0][0] + cS[1][0]) * (1.f / D_), m1 = (cS[0][2] + cS[1][2]) * (1.f / D_);
            const uint32_t mm0 = pack_bf16(m0, m0), mm1 = pack_bf16(m1, m1);
            if (lane == 0) mbar_arrive(bars + 8 * B_DONEX);
            auto center = [&](int s) { sub_bf16x2(a[s][0], mm0); sub_bf16x2(a[s][1], mm1); sub_bf16x2(a[s][2], mm0); sub_bf16x2(a[s][3], mm1); };
            uint32_t Ka[8], Kb[8], Kc[8], Va[8], Vb[7], Vc[8];
            float r0, r1, ls0, ls1;
            uint32_t pm, zero;
            uint32_t* od;
            uint4* oh;
            auto kpack = [&](uint32_t (&k)[8], int j, int c, float r) {
                const uint32_t v = pack_bf16(accK[4 * j + c] * r, accK[4 * j + c + 1] * r);
                if (j == 3) { k[3] = t < 2 ? v : 0u; k[4] = t < 2 ? 0u : v; } else k[j + (j > 3)] = v;
            };
            auto batch = [&](auto c0, auto c1) {
                constexpr int n0 = c0.value, n1 = c1.value;
                wg_fence();
                static_for<n0, n1>([&](auto nc) {
                    constexpr int n = nc.value;
                    if (n == 4) { center(4); center(5); center(6); center(7); wg_fence(); }
                    const uint64_t desc = mkdesc(sb + (n < 56 ? slot_kv(n >> 3) + (n & 7) * 2048 : SM_QO + (n - 56) * 2048), 8192, 1024, 1) + wofs;
                    wgmma_rs56<1>(n < 28 ? accK : n < 56 ? accV : accQ, a[n % 28], desc, n % 28 != 0);
                });
                wg_commit();
                if (n0 > 0) wg_wait<1>();
            };
            auto hand_over = [&](const uint32_t (&v)[8], int kv) {
                if (w < 3) {
                    mbar_wait(bars + 8 * (kv ? B_DONE1 + 5 : B_DONEX), 0);
                    uint4* hs = (uint4*)(smem_raw + (kv ? SM_HALOV : SM_HALOK)) + warp * 64 + lane;
                    hs[0] = make_uint4(v[0], v[1], v[2], v[3]); hs[32] = make_uint4(v[4], v[5], v[6], v[7]);
                } else if (tb < 15) {
                    uint4* hg = sc->halo + ((((tb + 1) * 8 + hp) * 2 + wg) * 2 + kv) * 96 + lane;
                    st_relaxed4(hg, v[0], v[1], v[2], ep); st_relaxed4(hg + 32, v[3], v[4], v[5], ep); st_relaxed4(hg + 64, v[6], v[7], ep, ep);
                    post_hint(sc->hint_kv + ((tb * 8 + hp) * 2 + wg) * 4 + kv * 2, ep, lane);
                }
            };
            auto take_over = [&](uint32_t (&v)[8], int kv) {
                if (w == 0) mbar_wait(bars + 8 * (B_HALO + 2 * kv + wg), 0);
                const uint4* hs = (const uint4*)(smem_raw + (kv ? SM_HALOV : SM_HALOK)) + (w ? warp - 1 : warp + 3) * 64 + lane;
                const uint4 u0 = hs[0], u1 = hs[32];
                v[0] = u0.x; v[1] = u0.y; v[2] = u0.z; v[3] = u0.w; v[4] = u1.x; v[5] = u1.y; v[6] = u1.z; v[7] = u1.w;
            };
            center(0); center(1); center(2); center(3);
            static_for<0, 7>([&](auto pc) {
                constexpr int p = pc.value;
                mbar_wait(bars + 8 * (B_FULLKV + p), 0);
                if (p == 0 && tid == 0) STAMP(26);
                if (p == 3 && tid == 0) STAMP(27);
                FST(4 + p);
                batch(Int<8 * p>(), Int<8 * p + 8>());
                if (p > 0 && leader) mbar_arrive(bars + 8 * (B_DONE1 + p - 1));
                #pragma unroll
                for (int s = 8 * p + 8; s < 8 * p + 16 && s < 28; s++) {
                    if (s >= 4 * NSQ) { sq(q0, a[s][0]); sq(q1, a[s][1]); sq(q0, a[s][2]); sq(q1, a[s][3]); }
                    center(s);
                }
                if (p == 3) {
                    if (t == (g >> 1)) { q0 += (g & 1) ? cA[0][1] + cA[1][1] : cA[0][0] + cA[1][0]; if (!SQMIX) q1 += (g & 1) ? cB[0][3] + cB[1][3] : cB[0][2] + cB[1][2]; }
                    q0 = quad_sum(q0); q1 = quad_sum(q1);
                    r0 = rsqrt_approx(fmaxf(q0 * (1.f / D_) - m0 * m0, 0.f) + LN_EPS); r1 = rsqrt_approx(fmaxf(q1 * (1.f / D_) - m1 * m1, 0.f) + LN_EPS);
                    pin2(__float_as_uint(r0), __float_as_uint(r1));
                }
                if (p == 4) {
                    reg_fence(accK);
                    #pragma unroll
                    for (int j = 0; j < 7; j++) kpack(Kc, j, 2, r1);
                    hand_over(Kc, 0);
                }
                if (p == 5) {
                    #pragma unroll
                    for (int j = 0; j < 7; j++) kpack(Kb, j, 0, r0);
                    #pragma unroll
                    for (int j = 0; j < 8; j += 2) pin2(Kb[j], Kb[j + 1]);
                    ls0 = LOG2E_SCALE * r0; ls1 = LOG2E_SCALE * r1;
                    pm = (2 * t <= g ? 0xFFFFu : 0u) | (2 * t + 1 <= g ? 0xFFFF0000u : 0u);
                    zero = never; asm volatile("" : "+r"(zero));
                    pin2(__float_as_uint(ls0), __float_as_uint(ls1)); pin2(pm, zero);
                }
                if (p == 6) {
                    const int tt = 2 * tb + (w >> 1);
                    od = tl->o + tt * 14336 + (7 * hp) * 256 + (2 * (2 * (w & 1) + wg)) * 32 + lane;
                    oh = sc->hint_o + (tt * 32 + hp * 4 + (w & 1) * 2 + wg) * 2 + (lane & 1);
                    pin2((uint32_t)(uint64_t)od, (uint32_t)((uint64_t)od >> 32));
                    pin2((uint32_t)(uint64_t)oh, (uint32_t)((uint64_t)oh >> 32));
                }
            });
            if (tid == 0) STAMP(1);
            FST(11);
            mbar_wait(bars + 8 * B_FQ, 0);
            batch(Int<56>(), Int<60>());
            reg_fence(accV);
            if (leader) mbar_arrive(bars + 8 * (B_DONE1 + 6));
            if (tid == 0) STAMP(2);
            FST(12);
            #pragma unroll
            for (int j = 0; j < 7; j++) Vc[j] = movtrans(pack_bf16(accV[4 * j + 2] * r1, accV[4 * j + 3] * r1));
            Vc[7] = ep;
            hand_over(Vc, 1);
            if (tid == 96) STAMP(23);
            batch(Int<60>(), Int<66>());
            #pragma unroll
            for (int j = 0; j < 7; j++) {
                Vb[j] = movtrans(pack_bf16(accV[4 * j] * r0, accV[4 * j + 1] * r0));
                Vc[j] |= zero;
            }
            batch(Int<66>(), Int<72>());
            #pragma unroll
            for (int j = 0; j < 7; j++) pin2(Vb[j], Vc[j]);
            mbar_wait(bars + 8 * (B_FQ + 1), 0);
            mbar_wait(bars + 8 * B_CLR, 0);
            FST(13);
            if (w > 0 && lane < 2) { const uint32_t now = gtime32(); st_relaxed4(oh, ep, now, ep, now); }
            batch(Int<72>(), Int<84>());
            FST(14);
            named_sync(1 + wg, 128);
            take_over(Ka, 0);
            if (tid == 0) STAMP(3);
            wg_wait<0>();
            reg_fence(accQ);
            if (tid == 0) STAMP(4);
            FST(15);
            const bool first = (tb == 0 && w == 0);
            uint32_t pA[2], pB0[2], pB1[2], pC[2], z0[2], z1[2];
            #pragma unroll
            for (int h = 0; h < 2; h++) {
                float sA[4] = {0.f, 0.f, 0.f, 0.f}, sB[4] = {0.f, 0.f, 0.f, 0.f}, sC[4] = {0.f, 0.f, 0.f, 0.f};
                #pragma unroll
                for (int k = 0; k < 2; k++) {
                    const float* qq = accQ + 12 * h + 8 * k;
                    uint32_t a0 = pack_bf16(qq[0], qq[1]), a1 = pack_bf16(qq[2], qq[3]);
                    if (h == 1 && k == 0) { a0 |= zero; a1 |= zero; }
                    const uint32_t a2 = pack_bf16(qq[4], qq[5]), a3 = pack_bf16(qq[6], qq[7]);
                    mma16816(sB, a0, a1, a2, a3, Kb[4 * h + 2 * k], Kb[4 * h + 2 * k + 1]);
                    mma16816(sA, a0, a1, a2, a3, Ka[4 * h + 2 * k], Ka[4 * h + 2 * k + 1]);
                    mma16816(sC, a0, a1, a2, a3, Kc[4 * h + 2 * k], Kc[4 * h + 2 * k + 1]);
                }
                const bool n0 = pm & 1, n1 = (int)pm < 0;
                const float l00 = n0 ? sB[0] : (first ? -INFINITY : sA[0]), l01 = n1 ? sB[1] : (first ? -INFINITY : sA[1]);
                const float l10 = n0 ? sC[2] : sB[2], l11 = n1 ? sC[3] : sB[3];
                const float x0 = -ls0 * quad_max(fmaxf(l00, l01)), x1 = -ls1 * quad_max(fmaxf(l10, l11));
                const float e00 = ex2(fmaf(l00, ls0, x0)), e01 = ex2(fmaf(l01, ls0, x0)), e10 = ex2(fmaf(l10, ls1, x1)), e11 = ex2(fmaf(l11, ls1, x1));
                const float i0 = rcp_approx(quad_sum(e00 + e01)), i1 = rcp_approx(quad_sum(e10 + e11));
                const uint32_t P0 = pack_bf16(e00 * i0, e01 * i0), P1 = pack_bf16(e10 * i1, e11 * i1);
                pB0[h] = P0 & pm; pA[h] = P0 & ~pm; pC[h] = P1 & pm; pB1[h] = P1 & ~pm; z0[h] = P0 & zero; z1[h] = P1 & zero;
            }
            float o[8][4];
            #pragma unroll
            for (int j = 0; j < 8; j++) {
                o[j][0] = o[j][1] = o[j][2] = o[j][3] = 0.f;
                mma16816(o[j], pB0[j >> 2], pB1[j >> 2], z0[j >> 2], pC[j >> 2], Vb[j - (j >> 2)], Vc[j - (j >> 2)]);
            }
            if (tid == 0) STAMP(12);
            FST(16);
            take_over(Va, 1);
            if (lane == 0) mbar_arrive(bars + 8 * B_DONEQ);
            if (tid == 0) STAMP(16);
            #pragma unroll
            for (int j = 0; j < 8; j++) mma1688(o[j], pA[j >> 2], z1[j >> 2], Va[j - (j >> 2)]);
            #pragma unroll
            for (int j = 0; j < 7; j++) {
                float v[4];
                #pragma unroll
                for (int c = 0; c < 4; c++) v[c] = j < 3 ? o[j][c] : j > 3 ? o[j + 1][c] : (t < 2 ? o[3][c] : o[4][c]);
                od[j * 256] = pack_bf16(v[0], v[1]);
                od[j * 256 + 32] = pack_bf16(v[2], v[3]);
            }
            if (tid == 0) STAMP(5);
            FST(17);
        }
        if (wg == 1) {
            uint32_t ph = 0;
            check_tiles(TSVAL 4, w, lane, ph, sb + SM_QO, tl->o + tt2 * 14336, B_FULLO);
            if (has_b1) check_tiles(TSVAL 32, w, lane, ph, sb + SM_BRING, tl->hn + q * 32 * 3584, B_FULLB);
            check_tiles(TSVAL 28, w, lane, ph, sb + SM_BRING, tl->u + q * 28 * 3584, B_FULLB);
        } else {
            const uint32_t rb10 = has_b1 ? __ldg((const unsigned short*)b1 + ft * 64 + 16 * w + g) : 0, rb11 = has_b1 ? __ldg((const unsigned short*)b1 + ft * 64 + 16 * w + g + 8) : 0;
            const uint32_t rb20 = __ldg((const unsigned short*)b2 + tt2 * 64 + 16 * w + g), rb21 = __ldg((const unsigned short*)b2 + tt2 * 64 + 16 * w + g + 8);
            {
                float acc[56];
                const int hrow = 32 * (w >> 1) + 2 * ((lane & 7) + (lane & 8)) + (w & 1);
                const uint32_t ha = sb + SM_H + hrow * 128 + (((lane >> 4) ^ (hrow & 7)) << 4);
                mbar_wait(bars + 8 * B_FULLWO, 0);
                #pragma unroll
                for (int jp = 0; jp < 7; jp++) {
                    uint32_t xx[4];
                    ldsm4(xx, hcol(ha, jp));
                    #pragma unroll
                    for (int r = 0; r < 4; r++) { acc[8 * jp + 2 * r] = bf_lo(xx[r]); acc[8 * jp + 2 * r + 1] = bf_hi(xx[r]); }
                }
                reg_fence(acc);
                float accl[32], accr[24];
                auto od_ = [&](int s) { return mkdesc(sb + SM_QO + s * 2048, 1024, 128, 0); };
                auto wd_ = [&](int s) { return mkdesc(sb + slot_wo(s >> 2) + (s & 3) * 2048, 8192, 1024, 1); };
                #pragma unroll
                for (int i = 0; i < 5; i++) {
                    if (i < 4) mbar_wait(bars + 8 * (B_FULLO + i), 0);
                    if (i == 0 && tid == 0) STAMP(7);
                    wg_fence();
                    #pragma unroll
                    for (int ss = 0; ss < 7; ss++) {
                        if (i < 3) wgmma_ss112<0, 1>(acc, od_(7 * i + ss), wd_(7 * i + ss));
                        else if (i == 3) { if (ss == 0) wgmma_ss64<0, 1, 0>(accl, od_(21), wd_(21)); else wgmma_ss64<0, 1>(accl, od_(21 + ss), wd_(21 + ss)); }
                        else wgmma_ss48<0, 1>(accr, od_(21 + ss), wd_(21 + ss) + 512);
                    }
                    wg_commit();
                    if (i > 0) {
                        wg_wait<1>();
                        if (i == 3) {
                            reg_fence(acc);
                            #pragma unroll
                            for (int c = 0; c < 24; c++) accr[c] = __uint_as_float(__float_as_uint(acc[32 + c]) | never);
                            reg_fence(accr);
                        }
                        if (i < 4 && leader) mbar_arrive(bars + 8 * (B_DONEO + i - 1));
                    }
                }
                float s0 = 0.f, s1 = 0.f, q0 = 0.f, q1 = 0.f, s2 = 0.f, s3 = 0.f, q2 = 0.f, q3 = 0.f;
                reg_fence(accl);
                #pragma unroll
                for (int c = 0; c < 32; c++) acc[c] += accl[c];
                #pragma unroll
                for (int j = 0; j < 14; j++) {
                    if (j == 8) {
                        pin4(never, s0, s1, s2, s3); pin4(never, q0, q1, q2, q3);
                        wg_wait<0>();
                        reg_fence(accr);
                        #pragma unroll
                        for (int c = 0; c < 24; c++) acc[32 + c] = accr[c];
                        if (leader) mbar_arrive(bars + 8 * (B_DONEO + 3));
                        if (tid == 0) STAMP(8);
                    }
                    s0 += acc[4 * j]; s2 += acc[4 * j + 1]; q0 = fmaf(acc[4 * j], acc[4 * j], q0); q2 = fmaf(acc[4 * j + 1], acc[4 * j + 1], q2);
                    s1 += acc[4 * j + 2]; s3 += acc[4 * j + 3]; q1 = fmaf(acc[4 * j + 2], acc[4 * j + 2], q1); q3 = fmaf(acc[4 * j + 3], acc[4 * j + 3], q3);
                }
                s0 = quad_sum(s0 + s2); s1 = quad_sum(s1 + s3); q0 = quad_sum(q0 + q2); q1 = quad_sum(q1 + q3);
                uint4* sp = sc->stats + tt2 * 256 + 16 * w + g;
                if (t < 2) st_relaxed4(sp + q * 64 + 8 * t, __float_as_uint(t ? s1 : s0), ep, __float_as_uint(t ? q1 : q0), ep);
                if (tid == 0) STAMP(9);
                #pragma unroll
                for (int jp = 0; jp < 7; jp++)
                    stsm4(hcol(ha, jp), pack_bf16(acc[8 * jp], acc[8 * jp + 1]), pack_bf16(acc[8 * jp + 2], acc[8 * jp + 3]),
                          pack_bf16(acc[8 * jp + 4], acc[8 * jp + 5]), pack_bf16(acc[8 * jp + 6], acc[8 * jp + 7]));
                {
                    uint4 v0, v1;
                    do {
                        v0 = ld_relaxed4(sp + t * 64); v1 = ld_relaxed4(sp + t * 64 + 8);
                    } while (__any_sync(0xffffffffu, t != q && (v0.y != ep || v0.w != ep || v1.y != ep || v1.w != ep)));
                    if (t != q) { s0 = __uint_as_float(v0.x); q0 = __uint_as_float(v0.z); s1 = __uint_as_float(v1.x); q1 = __uint_as_float(v1.z); }
                }
                if (tid == 0) STAMP(10);
                s0 = quad_sum(s0); s1 = quad_sum(s1); q0 = quad_sum(q0); q1 = quad_sum(q1);
                const float m0 = s0 * (1.f / D_), m1 = s1 * (1.f / D_);
                const float v0 = fmaxf(q0 * (1.f / D_) - m0 * m0, 0.f), v1 = fmaxf(q1 * (1.f / D_) - m1 * m1, 0.f);
                const float r0 = rsqrt_approx(fmaf(v0, 4.f + 4.f * LN_EPS, 4.f * LN_EPS * LN_EPS)), r1 = rsqrt_approx(fmaf(v1, 4.f + 4.f * LN_EPS, 4.f * LN_EPS * LN_EPS));
                const float c0 = -m0 * r0, c1 = -m1 * r1;
                uint32_t* hd = tl->hn + (q * 32 + tt2) * 3584 + (2 * w) * 448 + lane;
                #pragma unroll
                for (int j = 0; j < 14; j++) {
                    if (j == HINT_H) post_hint_wg(5, sc->hint_h + (q * 32 + tt2) * 2, ep, w, lane);
                    hd[j * 32] = pack_bf16(fmaf(acc[4 * j], r0, c0), fmaf(acc[4 * j + 1], r0, c0));
                    hd[j * 32 + 448] = pack_bf16(fmaf(acc[4 * j + 2], r1, c1), fmaf(acc[4 * j + 3], r1, c1));
                }
                if (tid == 0) STAMP(11);
                if (HINT_H == 14) post_hint_wg(5, sc->hint_h + (q * 32 + tt2) * 2, ep, w, lane);
                if (tid == 96) STAMP(33);
            }
            if (has_b1) {
                float acc[56];
                #pragma unroll
                for (int j = 0; j < 56; j++) acc[j] = 0.5f * bf_lo((j & 2) ? rb11 : rb10);
                uint32_t* ud = tl->u + (q * 28 + ft) * 3584 + (2 * w) * 448 + lane;
                #pragma unroll 1
                for (uint32_t pass = (DRY & 2) ? never : 1; pass < 2; pass++) {
                    if (pass) {
                        mix_mainloop<32, true>(TSVAL acc, 0, leader);
                        if (tid == 0) STAMP(14);
                    }
                    #pragma unroll
                    for (int j = 0; j < 14; j++) {
                        st_global_if(pass, ud + j * 32, pack_bf16(gelu_half(acc[4 * j]), gelu_half(acc[4 * j + 1])));
                        st_global_if(pass, ud + j * 32 + 448, pack_bf16(gelu_half(acc[4 * j + 2]), gelu_half(acc[4 * j + 3])));
                    }
                }
                if (tid == 0) STAMP(15);
                if (tid == 96) STAMP(34);
            }
            {
                float acc[56];
                const float bb0 = bf_lo(rb20), bb1 = bf_lo(rb21);
                named_sync(1, 128);
                const uint32_t ad = sb + SM_H + (16 * w + (lane & 15)) * 128 + (((lane >> 4) ^ (lane & 7)) << 4);
                #pragma unroll
                for (int jp = 0; jp < 7; jp++) {
                    uint32_t hh[4];
                    ldsm4(hh, hcol(ad, jp));
                    #pragma unroll
                    for (int r = 0; r < 4; r++) { acc[8 * jp + 2 * r] = bf_lo(hh[r]) + ((r & 1) ? bb1 : bb0); acc[8 * jp + 2 * r + 1] = bf_hi(hh[r]) + ((r & 1) ? bb1 : bb0); }
                }
                #pragma unroll 1
                for (uint32_t pass = (DRY & 4) ? never : 1; pass < 2; pass++) {
                    if (pass) {
                        mix_mainloop<28, false>(TSVAL acc, has_b1, leader);
                        if (leader) mbar_arrive(bars + 8 * B_END);
                        if (tid == 0) STAMP(18);
                    }
                    #pragma unroll
                    for (int jp = 0; jp < 7; jp++)
                        stsm4(hcol(ad, jp), pack_bf16(acc[8 * jp], acc[8 * jp + 1]), pack_bf16(acc[8 * jp + 2], acc[8 * jp + 3]),
                              pack_bf16(acc[8 * jp + 4], acc[8 * jp + 5]), pack_bf16(acc[8 * jp + 6], acc[8 * jp + 7]));
                    fence_async_smem();
                    __syncwarp();
                }
                if (elect()) {
                    tma2d_store(&tm_out64, c64, tt2 * 64 + 16 * w, sb + SM_H + w * 2048);
                    tma2d_store(&tm_out48, c48, tt2 * 64 + 16 * w, sb + SM_H + 8192 + w * 2048);
                }
                asm volatile("cp.async.bulk.commit_group;" ::: "memory");
                asm volatile("cp.async.bulk.wait_group.read 0;" ::: "memory");
                if (tid == 0) { sc->epoch[slot] = ep; STAMP(19); }
            }
        }
    } else {
        asm volatile("setmaxnreg.dec.sync.aligned.u32 40;");
        int warp2; asm("mov.u32 %0, %1;" : "=r"(warp2) : "r"(warp));
        if (warp2 > 8) {
            if (elect()) {
                if (warp == 9) {
                    #pragma unroll
                    for (int i = B_DONE1; i < B_DONEO; i++) mbar_init(bars + 8 * i, i < B_DONEX ? 2 : 8);
                    mbar_init(bars + 8 * B_CLR, 1);
                }
                #pragma unroll
                for (int i = 0; i < 34; i++) mbar_init(bars + 8 * (B_DONEO + i) + (warp - 9) * 272, 1);
                asm volatile("fence.mbarrier_init.release.cluster;" ::: "memory");
            }
            named_sync(0, 384);
            if (warp == 9) named_arrive(4, 64);
            const uint32_t ep = ld_volatile(&sc->epoch[slot]) + 1;
            if (warp < 11) {
                uint4* oh = sc->hint_o + (2 * tb * 32 + hp * 4 + warp - 9) * 2 + (lane & 1);
                if (lane < 2) st_relaxed4(oh, 0, 0, 0, 0);
                mbar_wait(bars + 8 * (B_DONE1 + HALO_AT), 0);
                #pragma unroll 1
                for (int kv = 0; kv < 2; kv++) {
                    uint4 v0 = {}, v1 = {}, v2 = {};
                    if (tb > 0) {
                        const uint4* hg = sc->halo + (((tb * 8 + hp) * 2 + warp - 9) * 2 + kv) * 96 + lane;
                        while (ld_relaxed(sc->hint_kv + (((tb - 1) * 8 + hp) * 2 + warp - 9) * 4 + kv * 2) != ep) {}
                        do { v0 = ld_relaxed4(hg); v1 = ld_relaxed4(hg + 32); v2 = ld_relaxed4(hg + 64); } while (!__all_sync(0xffffffffu, v0.w == ep && v1.w == ep && v2.w == ep));
                    }
                    if (kv) mbar_wait(bars + 8 * (B_DONE1 + 5), 0);
                    uint4* hs = (uint4*)(smem_raw + (kv ? SM_HALOV : SM_HALOK)) + (4 * warp - 33) * 64 + lane;
                    hs[0] = make_uint4(v0.x, v0.y, v0.z, v1.x); hs[32] = make_uint4(v1.y, v1.z, v2.x, v2.y);
                    __syncwarp();
                    if (lane == 0) mbar_arrive(bars + 8 * (B_HALO + 2 * kv + warp - 9));
                }
                if (lane < 2) { const uint32_t now = gtime32() - LATE_O; st_relaxed4(oh, ep, now, ep, now); }
                if (tid == 288) STAMP(21);
            }
            if (warp == 10) {
                if (!has_b1 && lane == 0) {
                    mbar_wait(bars + 8 * (B_DONEO + 3), 0);
                    uint32_t t = clock32() + PF_AT;
                    #pragma unroll 1
                    for (int i = 0; i < PF_N; i++) {
                        while ((int)(clock32() - t) < 0) __nanosleep(40);
                        bulk_prefetch((const char*)w2 + (i * 16 + mi) * 16384, 16384);
                        t += PF_PACE;
                    }
                }
                if (has_b1) {
                    post_hint(sc->hint_u + (q * 32 + ft) * 2, 0, lane);
                    mbar_wait(bars + 8 * (B_DONE + HINT_U), 0);
                    const uint32_t now = gtime32();
                    if (lane < 2) st_relaxed4(sc->hint_u + (q * 32 + ft) * 2 + lane, ep, now, ep, now);
                }
            } else if (warp == 11) {
                #pragma unroll 1
                for (uint32_t e = ep; e != ep + 2; e++) {
                    if (!has_b1 && ld_volatile(&sc->clean[mi]) != e) {
                        if (e != ep) { mbar_wait_wd(bars + 8 * (B_DONEO + 3), 0); const uint32_t t = clock32(); while (clock32() - t < CL_AT) __nanosleep(100); __syncwarp(); }
                        constexpr int NL = sizeof(Tiles) / 2048;
                        uint4* p = (uint4*)&sc->tiles[e & 1] + (mi * NL + (lane >> 1)) * 8 + (lane & 7);
                        #pragma unroll 7
                        for (int i = 0; i < NL / 16; i++) st_relaxed4(p + i * 128, EMPTY, EMPTY, EMPTY, EMPTY);
                        __syncwarp();
                        if (lane == 0) { st_release(&sc->clean[mi], e); STAMP(24); }
                        __syncwarp();
                    }
                    if (e == ep) {
                        const long long t0 = clock64();
                        while (__any_sync(0xffffffffu, (int)(ld_acquire(&sc->clean[lane & 15]) - ep) < 0)) if (clock64() - t0 > WD_CLKS) __trap();
                        if (lane == 0) mbar_arrive(bars + 8 * B_CLR);
                    }
                }
                if (lane == 0) {
                    mbar_wait_wd(bars + 8 * B_END, 0);
                }
            } else {
                int aslot = 0;
                if (lane == 0) { prefetch_map(&tm_out64); prefetch_map(&tm_out48); }
                if (has_b1) {
                    #pragma unroll 1
                    for (int i = 0; i < 16; i++) {
                        mbar_wait(bars + 8 * (i < NA_SLOTS ? B_DONEQ + ((A_SCHED >> (4 * i)) & 15) : B_DONE + 1 + ((i - NA_SLOTS) * A3_END) / (15 - NA_SLOTS)), 0);
                        if (elect()) {
                            const uint32_t bar = bars + 8 * (B_FULLA + i), dst = sb + SM_ARING + aslot * 16384;
                            mbar_expect(bar, 16384);
                            tma3d(dst, &tm_w1, ft * 64, 0, i * 64, bar);
                            tma3d(dst + 8192, &tm_w1, ft * 64, 1, i * 64, bar);
                        }
                        aslot = aslot == NA_SLOTS - 1 ? 0 : aslot + 1;
                    }
                }
                aslot = 16 % NA_SLOTS;
                #pragma unroll 1
                for (int i = 0; i < 14; i++) {
                    if (i >= NA_SLOTS) mbar_wait(bars + 8 * (B_DONE + 1 + ((i - NA_SLOTS) * A4_END) / (13 - NA_SLOTS)), has_b1);
                    else if (has_b1) {
                        mbar_wait(bars + 8 * (B_DONE + max(33 - 2 * NA_SLOTS + 2 * i, W2_AT)), 0);
                        if (i >= W2_HOLD) mbar_wait(bars + 8 * B_FULLB, 1);
                    } else if (i == 0) { mbar_wait(bars + 8 * (B_DONEO + 3), 0); const uint32_t t = clock32() + PF_AT + 12 * PF_PACE; while ((int)(clock32() - t) < 0) __nanosleep(100); }
                    if (elect()) {
                        const uint32_t bar = bars + 8 * (B_FULLA + i);
                        mbar_expect(bar, 16384);
                        tma2d(sb + SM_ARING + aslot * 16384, &tm_w2, tt2 * 64, i * 128, bar);
                    }
                    aslot = aslot == NA_SLOTS - 1 ? 0 : aslot + 1;
                }
            }
        } else {
            auto krot = [&](int kb) { const int k = kb * 64 + (G & 1) * 64 * ROT; return k < 448 ? k : k - 448; };
            if (elect()) {
                #pragma unroll
                for (int i = 0; i < 7; i++) mbar_init(bars + 8 * i, 1);
                asm volatile("fence.mbarrier_init.release.cluster;" ::: "memory");
                if (STAG && G >= 2) { const uint32_t t0 = clock32(); while (clock32() - t0 < STAG) {} }
                #pragma unroll 1
                for (int kb = 0; kb < 7; kb++) {
                    const uint32_t st = sb + slot_x(kb), bar = bars + 8 * (B_FULLX + kb);
                    mbar_expect(bar, 16384);
                    tma3d(st, &tm_x, krot(kb), 0, tb * 64, bar); tma3d(st + 8192, &tm_x, krot(kb), 1, tb * 64, bar);
                }
                #pragma unroll
                for (int i = 7; i < B_DONE1; i++) mbar_init(bars + 8 * i, 1);
                asm volatile("fence.mbarrier_init.release.cluster;" ::: "memory");
            }
            named_arrive(0, 384);
            #pragma unroll 1
            for (int kb = 0; kb < 7; kb++) {
                if (kb == 6) { named_sync(4, 64); mbar_wait(bars + 8 * B_DONEX, 0); }
                if (elect()) {
                    const uint32_t st = sb + slot_kv(kb), bar = bars + 8 * (B_FULLKV + kb);
                    mbar_expect(bar, 16384);
                    #pragma unroll
                    for (int i = 0; i < 2; i++) {
                        const int n = 2 * kb + (ROT ? i : i ^ (G & 1));
                        tma2d(st + (n & 1) * 8192, &tm_wqkv, (n < 7 ? 448 : 896) + wcol, krot(n < 7 ? n : n - 7), bar);
                    }
                }
            }
            if (elect()) {
                mbar_expect(bars + 8 * B_FQ, 32768);
                mbar_expect(bars + 8 * (B_FQ + 1), 24576);
                #pragma unroll 1
                for (int i = 0; i < 7; i++) { const int j = ROT || i == 6 ? i : i ^ (G & 1); tma2d(sb + SM_QO + j * 8192, &tm_wqkv, wcol, krot(j), bars + 8 * (B_FQ + (i >> 2))); }
                mbar_expect(bars + 8 * B_FULLWO, 512 * 112 * 2);
            }
            #pragma unroll 1
            for (int i = 0; i < 7; i++) {
                const int kb = ((q & 1 ? WO_ORD1 : WO_ORD0) >> (4 * i)) & 7;
                if (kb < 5) mbar_wait(bars + 8 * (B_DONE1 + kb), 0);
                if (i == WO_HOLD) { mbar_wait(bars + 8 * (B_HALO + 2), 0); mbar_wait(bars + 8 * (B_HALO + 3), 0); }
                if (elect()) {
                    tma2d(sb + slot_wo(kb), &tm_wo64, c64, kb * 64, bars + 8 * B_FULLWO);
                    tma2d(sb + slot_wo(kb) + 8192, &tm_wo48, c48, kb * 64, bars + 8 * B_FULLWO);
                }
            }
            if (XR_HOLD) { mbar_wait(bars + 8 * (B_HALO + 2), 0); mbar_wait(bars + 8 * (B_HALO + 3), 0); }
            if (elect()) {
                tma2d(sb + SM_H, &tm_xr64, c64, tt2 * 64, bars + 8 * B_FULLWO);
                tma2d(sb + SM_H + 8192, &tm_xr48, c48, tt2 * 64, bars + 8 * B_FULLWO);
            }
            if (smem_u32(smem_raw) != SB) __trap();
            const uint32_t ep = ld_volatile(&sc->epoch[slot]) + 1;
            const Tiles* const tl = &sc->tiles[ep & 1];
            mbar_wait(bars + 8 * (B_DONE1 + 6), 0);
            wait_hints(TSVAL sc->hint_o + (tt2 * 32 + lane) * 2, ep, GO_O, 38);
            mbar_wait(bars + 8 * B_DONEQ, 0);
            if (elect()) {
                #pragma unroll
                for (int i = 0; i < 4; i++) {
                    mbar_expect(bars + 8 * (B_RAW + i), 14336);
                    bulk_ld(sb + SM_QO + i * 14336, tl->o + tt2 * 14336 + i * 3584, 14336, bars + 8 * (B_RAW + i));
                }
            }
            if (lane == 0) STAMP(20);
            mbar_wait(bars + 8 * (B_DONEO + 3), 0);
            if (has_b1) {
                mix_producer_b<32>(TSVAL 0, sc->hint_h, ep, tl->hn + q * 32 * 3584, lane);
            }
            mix_producer_b<28>(TSVAL has_b1, sc->hint_u, ep, tl->u + q * 28 * 3584, lane);
        }
    }
}

typedef CUresult (*EncodeFn)(CUtensorMap*, CUtensorMapDataType, cuuint32_t, void*, const cuuint64_t*, const cuuint64_t*, const cuuint32_t*,
                             const cuuint32_t*, CUtensorMapInterleave, CUtensorMapSwizzle, CUtensorMapL2promotion, CUtensorMapFloatOOBfill);

void make_map(EncodeFn fn, CUtensorMap* tm, const void* ptr, int rank, const cuuint64_t* dims, const cuuint64_t* strides, const cuuint32_t* box, CUtensorMapSwizzle sw) {
    cuuint32_t es[3] = {1, 1, 1};
    fn(tm, CU_TENSOR_MAP_DATA_TYPE_BFLOAT16, rank, const_cast<void*>(ptr), dims, strides, box, es, CU_TENSOR_MAP_INTERLEAVE_NONE, sw,
       CU_TENSOR_MAP_L2_PROMOTION_NONE, CU_TENSOR_MAP_FLOAT_OOB_FILL_NONE);
}

}

extern "C" void kernel_launch(void* const* d_in, const int* in_sizes, int n_in, void* d_out, int out_size) {
    const __nv_bfloat16* x = (const __nv_bfloat16*)d_in[0];
    const __nv_bfloat16* wqkv = (const __nv_bfloat16*)d_in[1];
    const __nv_bfloat16* wo = (const __nv_bfloat16*)d_in[2];
    const __nv_bfloat16* w1 = (const __nv_bfloat16*)d_in[4];
    const __nv_bfloat16* b1 = (const __nv_bfloat16*)d_in[5];
    const __nv_bfloat16* w2 = (const __nv_bfloat16*)d_in[6];
    const __nv_bfloat16* b2 = (const __nv_bfloat16*)d_in[7];

    void* fnp = nullptr; cudaDriverEntryPointQueryResult qr;
    cudaGetDriverEntryPoint("cuTensorMapEncodeTiled", &fnp, cudaEnableDefault, &qr);
    EncodeFn fn = (EncodeFn)fnp;
    CUtensorMap tx, twqkv, two64, two48, tw1, tw2, txr64, txr48, tout64, tout48;
    { cuuint64_t d[3] = {448, 2, 1024}, s[2] = {896, 1792}; cuuint32_t b[3] = {64, 1, 64}; make_map(fn, &tx, x, 3, d, s, b, CU_TENSOR_MAP_SWIZZLE_128B); }
    { cuuint64_t d[2] = {1344, 448}, s[1] = {2688}; cuuint32_t b[2] = {64, 64}; make_map(fn, &twqkv, wqkv, 2, d, s, b, CU_TENSOR_MAP_SWIZZLE_128B); }
    { cuuint64_t d[2] = {448, 448}, s[1] = {896}; cuuint32_t b[2] = {64, 64}; make_map(fn, &two64, wo, 2, d, s, b, CU_TENSOR_MAP_SWIZZLE_128B); }
    { cuuint64_t d[2] = {448, 448}, s[1] = {896}; cuuint32_t b[2] = {48, 64}; make_map(fn, &two48, wo, 2, d, s, b, CU_TENSOR_MAP_SWIZZLE_128B); }
    { cuuint64_t d[3] = {1792, 2, 1024}, s[2] = {3584, 7168}; cuuint32_t b[3] = {64, 1, 64}; make_map(fn, &tw1, w1, 3, d, s, b, CU_TENSOR_MAP_SWIZZLE_128B); }
    { cuuint64_t d[2] = {2048, 1792}, s[1] = {4096}; cuuint32_t b[2] = {64, 128}; make_map(fn, &tw2, w2, 2, d, s, b, CU_TENSOR_MAP_SWIZZLE_128B); }
    { cuuint64_t d[2] = {448, 2048}, s[1] = {896}; cuuint32_t b[2] = {64, 64}; make_map(fn, &txr64, x, 2, d, s, b, CU_TENSOR_MAP_SWIZZLE_128B); }
    { cuuint64_t d[2] = {448, 2048}, s[1] = {896}; cuuint32_t b[2] = {48, 64}; make_map(fn, &txr48, x, 2, d, s, b, CU_TENSOR_MAP_SWIZZLE_128B); }
    { cuuint64_t d[2] = {448, 2048}, s[1] = {896}; cuuint32_t b[2] = {64, 16}; make_map(fn, &tout64, d_out, 2, d, s, b, CU_TENSOR_MAP_SWIZZLE_128B); }
    { cuuint64_t d[2] = {448, 2048}, s[1] = {896}; cuuint32_t b[2] = {48, 16}; make_map(fn, &tout48, d_out, 2, d, s, b, CU_TENSOR_MAP_SWIZZLE_128B); }

    void* scv = nullptr;
    cudaGetSymbolAddress(&scv, g_scratch);
    Scratch* scp = (Scratch*)scv;
    int dev = 0, sms = 0;
    cudaGetDevice(&dev);
    cudaDeviceGetAttribute(&sms, cudaDevAttrMultiProcessorCount, dev);
    if (sms == 132) {
        cudaFuncSetAttribute(fused_kernel<true>, cudaFuncAttributeMaxDynamicSharedMemorySize, SM_TOTAL);
        fused_kernel<true><<<132, 384, SM_TOTAL>>>(scp, wo, w1, b1, w2, b2, tx, twqkv, two64, two48, tw1, tw2, txr64, txr48, tout64, tout48);
    } else {
        cudaFuncSetAttribute(fused_kernel<false>, cudaFuncAttributeMaxDynamicSharedMemorySize, SM_TOTAL);
        fused_kernel<false><<<132, 384, SM_TOTAL>>>(scp, wo, w1, b1, w2, b2, tx, twqkv, two64, two48, tw1, tw2, txr64, txr48, tout64, tout48);
    }
}
```

```cpp
#include <cuda_runtime.h>
#include <cuda_bf16.h>
#include <cuda.h>
#include <stdint.h>

namespace {

constexpr int D_ = 448;
constexpr float LN_EPS = 1e-5f;
constexpr float LOG2E_SCALE = 0.1889822365046136f * 1.4426950408889634f;

struct Tiles {
    uint32_t o[32 * 57344 / 4];
    uint32_t hn[4 * 32 * 14336 / 4];
    uint32_t u[4 * 28 * 14336 / 4];
};
struct Scratch {
    Tiles tiles[2];
    uint4 halo[128 * 2 * 2 * 3 * 32];
    uint4 stats[32 * 4 * 64];
    uint4 hint_k[128 * 2];
    uint4 hint_o[32 * 32 * 2];
    uint4 hint_h[4 * 32 * 2];
    uint4 hint_u[4 * 32 * 2];
    uint32_t epoch[160];
    uint32_t clean[16];
};
__device__ __align__(1024) Scratch g_scratch;
#define STAMP(i) do {} while (0)
#define FST(i) do {} while (0)
#define TSARG
#define TSVAL

constexpr uint32_t SB = 1024;
constexpr int SM_SLOT = 16384;
__device__ __forceinline__ constexpr uint32_t slot_x(int kb) { return (kb ? 6 + kb : 0) * SM_SLOT; }
__device__ __forceinline__ constexpr uint32_t slot_kv(int kb) { return (kb < 5 ? 2 + kb : 6 - kb) * SM_SLOT; }
__device__ __forceinline__ constexpr uint32_t slot_wo(int kb) { return (kb < 6 ? 2 + kb : 12) * SM_SLOT; }
constexpr int SM_QO = 8 * SM_SLOT;
constexpr int SM_HALOK = SM_QO + 57344, SM_HALOV = 1 * SM_SLOT;
constexpr int NA_SLOTS = 6, NB_SLOTS = 8;
constexpr int SM_ARING = 0;
constexpr int SM_BRING = NA_SLOTS * 16384;
constexpr int SM_H = 212992;
constexpr int SM_TAG = SM_H + 8192 + 96;
constexpr int SM_HALOKIN = 229376;
constexpr int SM_BAR = 231424;
constexpr int SM_TOTAL = 232448;
constexpr int B_FULLX = 0;
constexpr int B_FULLKV = 7;
constexpr int B_FQ = 14;
constexpr int B_DONE1 = 16;
constexpr int B_DONEX = 23;
constexpr int B_DONEQ = 24;
constexpr int B_DONEO = 25;
constexpr int B_FULLO = 29;
constexpr int B_FULLWO = 33;
constexpr int B_END = 34;
constexpr int B_HALO = 35;
constexpr int B_FULLA = 39;
constexpr int B_FULLB = 55;
constexpr int B_DONE = 87;
constexpr int B_RAW = 119;
constexpr int B_CLR = 127;

constexpr long long WD_CLKS = 2000000000ll;

template<int N> struct Int { static constexpr int value = N; };
template<int A, int B, class F> __device__ __forceinline__ void static_for(F&& f) { if constexpr (A < B) { f(Int<A>()); static_for<A + 1, B>(f); } }

__device__ __forceinline__ uint32_t smem_u32(const void* p) { return (uint32_t)__cvta_generic_to_shared(p); }
__device__ __forceinline__ void mbar_init(uint32_t bar, uint32_t cnt) { asm volatile("mbarrier.init.shared::cta.b64 [%0], %1;" :: "r"(bar), "r"(cnt) : "memory"); }
__device__ __forceinline__ void mbar_expect(uint32_t bar, uint32_t bytes) { asm volatile("mbarrier.arrive.expect_tx.shared::cta.b64 _, [%0], %1;" :: "r"(bar), "r"(bytes) : "memory"); }
__device__ __forceinline__ void mbar_arrive(uint32_t bar) { asm volatile("mbarrier.arrive.shared::cta.b64 _, [%0];" :: "r"(bar) : "memory"); }
__device__ __forceinline__ bool mbar_try(uint32_t bar, uint32_t parity) {
    uint32_t ok;
    asm volatile("{\n.reg .pred p;\nmbarrier.try_wait.parity.shared::cta.b64 p, [%1], %2;\nselp.u32 %0, 1, 0, p;\n}" : "=r"(ok) : "r"(bar), "r"(parity) : "memory");
    return ok;
}
__device__ __forceinline__ bool mbar_test(uint32_t bar, uint32_t parity) {
    uint32_t ok;
    asm volatile("{\n.reg .pred p;\nmbarrier.test_wait.parity.shared::cta.b64 p, [%1], %2;\nselp.u32 %0, 1, 0, p;\n}" : "=r"(ok) : "r"(bar), "r"(parity) : "memory");
    return ok;
}
__device__ __forceinline__ void mbar_wait(uint32_t bar, uint32_t parity) {
    asm volatile("{\n.reg .pred p;\n"
                 "WAIT_LOOP:\n"
                 "mbarrier.try_wait.parity.shared::cta.b64 p, [%0], %1;\n"
                 "@!p bra WAIT_LOOP;\n}" :: "r"(bar), "r"(parity) : "memory");
}
__device__ __forceinline__ void mbar_wait_wd(uint32_t bar, uint32_t parity) {
    const long long t0 = clock64();
    while (!mbar_try(bar, parity)) { if (clock64() - t0 > WD_CLKS) __trap(); }
}
__device__ __forceinline__ bool elect() { uint32_t p; asm volatile("{\n.reg .pred P;\nelect.sync _|P, 0xffffffff;\nselp.u32 %0, 1, 0, P;\n}" : "=r"(p)); return p; }
__device__ __forceinline__ void tma2d(uint32_t dst, const CUtensorMap* tm, int c0, int c1, uint32_t bar) {
    asm volatile("cp.async.bulk.tensor.2d.shared::cluster.global.mbarrier::complete_tx::bytes [%0], [%1, {%3, %4}], [%2];" :: "r"(dst), "l"(tm), "r"(bar), "r"(c0), "r"(c1) : "memory");
}
__device__ __forceinline__ void tma3d(uint32_t dst, const CUtensorMap* tm, int c0, int c1, int c2, uint32_t bar) {
    asm volatile("cp.async.bulk.tensor.3d.shared::cluster.global.mbarrier::complete_tx::bytes [%0], [%1, {%3, %4, %5}], [%2];" :: "r"(dst), "l"(tm), "r"(bar), "r"(c0), "r"(c1), "r"(c2) : "memory");
}
__device__ __forceinline__ void tma2d_store(const CUtensorMap* tm, int c0, int c1, uint32_t src) {
    asm volatile("cp.async.bulk.tensor.2d.global.shared::cta.bulk_group [%0, {%2, %3}], [%1];" :: "l"(tm), "r"(src), "r"(c0), "r"(c1) : "memory");
}
__device__ __forceinline__ void bulk_ld(uint32_t dst, const void* src, uint32_t bytes, uint32_t bar) {
    asm volatile("cp.async.bulk.shared::cluster.global.mbarrier::complete_tx::bytes [%0], [%1], %2, [%3];" :: "r"(dst), "l"(src), "r"(bytes), "r"(bar) : "memory");
}
__device__ __forceinline__ void bulk_prefetch(const void* src, uint32_t bytes) { asm volatile("cp.async.bulk.prefetch.L2.global [%0], %1;" :: "l"(src), "r"(bytes) : "memory"); }
__device__ __forceinline__ void prefetch_map(const CUtensorMap* tm) { asm volatile("prefetch.tensormap [%0];" :: "l"(tm) : "memory"); }
__device__ __forceinline__ void st_global_if(uint32_t c, uint32_t* p, uint32_t v) {
    asm volatile("{\n.reg .pred p;\nsetp.ne.u32 p, %2, 0;\n@p st.global.u32 [%0], %1;\n}" :: "l"(p), "r"(v), "r"(c) : "memory");
}
__device__ __forceinline__ void pin4(uint32_t never, float a, float b, float c, float d) {
    asm volatile("{\n.reg .pred p;\nsetp.ne.u32 p, %4, 0;\n@p st.shared.v4.f32 [%4], {%0,%1,%2,%3};\n}" :: "f"(a), "f"(b), "f"(c), "f"(d), "r"(never) : "memory");
}
__device__ __forceinline__ void fence_async_smem() { asm volatile("fence.proxy.async.shared::cta;" ::: "memory"); }
__device__ __forceinline__ uint32_t ld_acquire(const void* p) { uint32_t v; asm volatile("ld.acquire.gpu.global.u32 %0, [%1];" : "=r"(v) : "l"(p) : "memory"); return v; }
__device__ __forceinline__ void st_release(void* p, uint32_t v) { asm volatile("st.release.gpu.global.u32 [%0], %1;" :: "l"(p), "r"(v) : "memory"); }
__device__ __forceinline__ uint32_t ld_relaxed(const void* p) { uint32_t v; asm volatile("ld.relaxed.gpu.global.u32 %0, [%1];" : "=r"(v) : "l"(p) : "memory"); return v; }
__device__ __forceinline__ uint2 ld_relaxed2(const void* p) {
    uint2 v; asm volatile("{\n.reg .b64 a;\nld.relaxed.gpu.global.b64 a, [%2];\nmov.b64 {%0, %1}, a;\n}" : "=r"(v.x), "=r"(v.y) : "l"(p) : "memory"); return v;
}
__device__ __forceinline__ uint4 ld_relaxed4(const uint4* p) {
    uint4 v;
    asm volatile("{\n.reg .b128 t;\n.reg .b64 a, b;\nld.relaxed.gpu.global.b128 t, [%4];\nmov.b128 {a, b}, t;\nmov.b64 {%0, %1}, a;\nmov.b64 {%2, %3}, b;\n}" : "=r"(v.x), "=r"(v.y), "=r"(v.z), "=r"(v.w) : "l"(p) : "memory");
    return v;
}
__device__ __forceinline__ void st_relaxed4(uint4* p, uint32_t a, uint32_t b, uint32_t c, uint32_t d) {
    asm volatile("{\n.reg .b128 t;\n.reg .b64 a, b;\nmov.b64 a, {%1, %2};\nmov.b64 b, {%3, %4};\nmov.b128 t, {a, b};\nst.relaxed.gpu.global.b128 [%0], t;\n}" :: "l"(p), "r"(a), "r"(b), "r"(c), "r"(d) : "memory");
}
__device__ __forceinline__ uint32_t ld_volatile(const uint32_t* p) { uint32_t v; asm volatile("ld.volatile.global.u32 %0, [%1];" : "=r"(v) : "l"(p) : "memory"); return v; }
__device__ __forceinline__ void named_arrive(int id, int n) { asm volatile("bar.arrive %0, %1;" :: "r"(id), "r"(n) : "memory"); }
__device__ __forceinline__ void named_sync(int id, int n) { asm volatile("bar.sync %0, %1;" :: "r"(id), "r"(n) : "memory"); }
__device__ __forceinline__ void wg_fence() { asm volatile("wgmma.fence.sync.aligned;" ::: "memory"); }
__device__ __forceinline__ void wg_commit() { asm volatile("wgmma.commit_group.sync.aligned;" ::: "memory"); }
template<int N> __device__ __forceinline__ void wg_wait() { asm volatile("wgmma.wait_group.sync.aligned %0;" :: "n"(N) : "memory"); }
template<int N> __device__ __forceinline__ void reg_fence(float (&d)[N]) {
    #pragma unroll
    for (int i = 0; i < N; i++) asm volatile("" : "+f"(d[i]) :: "memory");
}
__device__ __forceinline__ constexpr uint64_t mkdesc(uint32_t addr, uint32_t lbo, uint32_t sbo, uint32_t sw) {
    return (uint64_t)((addr & 0x3FFFF) >> 4) | ((uint64_t)(lbo >> 4) << 16) | ((uint64_t)(sbo >> 4) << 32) | ((uint64_t)sw << 62);
}
__device__ __forceinline__ void ldsm4(uint32_t (&r)[4], uint32_t addr) {
    asm volatile("ldmatrix.sync.aligned.m8n8.x4.shared.b16 {%0,%1,%2,%3}, [%4];" : "=r"(r[0]), "=r"(r[1]), "=r"(r[2]), "=r"(r[3]) : "r"(addr) : "memory");
}
__device__ __forceinline__ void stsm4(uint32_t addr, uint32_t r0, uint32_t r1, uint32_t r2, uint32_t r3) {
    asm volatile("stmatrix.sync.aligned.m8n8.x4.shared.b16 [%0], {%1,%2,%3,%4};" :: "r"(addr), "r"(r0), "r"(r1), "r"(r2), "r"(r3) : "memory");
}
__device__ __forceinline__ void sts4(uint32_t a, uint32_t x, uint32_t y, uint32_t z, uint32_t w) { asm volatile("st.shared.v4.u32 [%0], {%1,%2,%3,%4};" :: "r"(a), "r"(x), "r"(y), "r"(z), "r"(w) : "memory"); }
__device__ __forceinline__ uint4 lds4(uint32_t a) { uint4 v; asm volatile("ld.shared.v4.u32 {%0,%1,%2,%3}, [%4];" : "=r"(v.x), "=r"(v.y), "=r"(v.z), "=r"(v.w) : "r"(a) : "memory"); return v; }
__device__ __forceinline__ uint32_t movtrans(uint32_t a) { uint32_t d; asm volatile("movmatrix.sync.aligned.m8n8.trans.b16 %0, %1;" : "=r"(d) : "r"(a)); return d; }
__device__ __forceinline__ uint32_t pack_bf16(float lo, float hi) { uint32_t r; asm("cvt.rn.bf16x2.f32 %0, %1, %2;" : "=r"(r) : "f"(hi), "f"(lo)); return r; }
__device__ __forceinline__ void sub_bf16x2(uint32_t& a, uint32_t b) { asm volatile("sub.rn.bf16x2 %0, %0, %1;" : "+r"(a) : "r"(b)); }
__device__ __forceinline__ float bf_lo(uint32_t v) { return __uint_as_float(v << 16); }
__device__ __forceinline__ float bf_hi(uint32_t v) { return __uint_as_float(v & 0xffff0000u); }
__device__ __forceinline__ void mma16816(float (&c)[4], uint32_t a0, uint32_t a1, uint32_t a2, uint32_t a3, uint32_t b0, uint32_t b1) {
    asm volatile("mma.sync.aligned.m16n8k16.row.col.f32.bf16.bf16.f32 {%0,%1,%2,%3}, {%4,%5,%6,%7}, {%8,%9}, {%0,%1,%2,%3};"
        : "+f"(c[0]), "+f"(c[1]), "+f"(c[2]), "+f"(c[3]) : "r"(a0), "r"(a1), "r"(a2), "r"(a3), "r"(b0), "r"(b1));
}
__device__ __forceinline__ void mma1688(float (&c)[4], uint32_t a0, uint32_t a1, uint32_t b0) {
    asm volatile("mma.sync.aligned.m16n8k8.row.col.f32.bf16.bf16.f32 {%0,%1,%2,%3}, {%4,%5}, {%6}, {%0,%1,%2,%3};"
        : "+f"(c[0]), "+f"(c[1]), "+f"(c[2]), "+f"(c[3]) : "r"(a0), "r"(a1), "r"(b0));
}
__device__ __forceinline__ float quad_sum(float v) { v += __shfl_xor_sync(0xffffffffu, v, 1); v += __shfl_xor_sync(0xffffffffu, v, 2); return v; }
__device__ __forceinline__ float quad_max(float v) { v = fmaxf(v, __shfl_xor_sync(0xffffffffu, v, 1)); v = fmaxf(v, __shfl_xor_sync(0xffffffffu, v, 2)); return v; }
__device__ __forceinline__ float ex2(float x) { float y; asm("ex2.approx.ftz.f32 %0, %1;" : "=f"(y) : "f"(x)); return y; }
__device__ __forceinline__ float rsqrt_approx(float x) { float y; asm("rsqrt.approx.ftz.f32 %0, %1;" : "=f"(y) : "f"(x)); return y; }
__device__ __forceinline__ float rcp_approx(float x) { float y; asm("rcp.approx.ftz.f32 %0, %1;" : "=f"(y) : "f"(x)); return y; }
__device__ __forceinline__ float gelu_half(float hx) {
    const float z = hx * fmaf(hx * hx, 8.f * 0.044715f * 0.7978845608028654f, 2.f * 0.7978845608028654f);
    float t; asm("tanh.approx.f32 %0, %1;" : "=f"(t) : "f"(z));
    return fmaf(hx, t, hx);
}
__device__ __forceinline__ uint32_t gtime32() { uint32_t t; asm volatile("mov.u32 %0, %%globaltimer_lo;" : "=r"(t)); return t; }
__device__ __forceinline__ uint32_t clock32() { uint32_t t; asm volatile("mov.u32 %0, %%clock;" : "=r"(t)); return t; }
#define PF_PACE 400

#define PF_AT 4000
#define NSQ 6
#define HALO_AT 3
#define PF_N 12
#define HINT_H 0
#define HINT_U 28
#define SP_AT 2000
#define SP_N 0
#define WO_HOLD 7
#define A_SCHED 0x322188
#define WO_ORD0 0x4321065
#define WO_ORD1 0x3465210
#define XR_HOLD 0
#define ROT 0
#define SQMIX 0
#define NPIPE 1
#define CL_AT 4000
#define WARM 1
#define WARM_AT 300
#define W2_AT 23
#define W2_HOLD 5
#define A3_END 20
#define A4_END 16
#define DRY 7
#define GO_H 608
#define GO_U 928
#define STAG 0
#define GO_O 1216
#define LATE_O 256
#define PP 0
template<int TB> __device__ __forceinline__ void wgmma_rs56(float (&d)[28], const uint32_t (&a)[4], uint64_t db, int sc) {
    asm volatile("{\n.reg .pred p;\nsetp.ne.b32 p, %33, 0;\n"
        "wgmma.mma_async.sync.aligned.m64n56k16.f32.bf16.bf16 {%0, %1, %2, %3, %4, %5, %6, %7, %8, %9, %10, %11, %12, %13, %14, %15, %16, %17, %18, %19, %20, %21, %22, %23, %24, %25, %26, %27}, {%28, %29, %30, %31}, %32, p, 1, 1, %34;\n}\n"
        : "+f"(d[0]), "+f"(d[1]), "+f"(d[2]), "+f"(d[3]), "+f"(d[4]), "+f"(d[5]), "+f"(d[6]), "+f"(d[7]), "+f"(d[8]), "+f"(d[9]), "+f"(d[10]), "+f"(d[11]), "+f"(d[12]), "+f"(d[13]), "+f"(d[14]), "+f"(d[15]), "+f"(d[16]), "+f"(d[17]), "+f"(d[18]), "+f"(d[19]), "+f"(d[20]), "+f"(d[21]), "+f"(d[22]), "+f"(d[23]), "+f"(d[24]), "+f"(d[25]), "+f"(d[26]), "+f"(d[27])
        : "r"(a[0]), "r"(a[1]), "r"(a[2]), "r"(a[3]), "l"(db), "r"(sc), "n"(TB));
}

template<int TA, int TB, int SC = 1> __device__ __forceinline__ void wgmma_ss112(float (&d)[56], uint64_t da, uint64_t db) {
    asm volatile("wgmma.mma_async.sync.aligned.m64n112k16.f32.bf16.bf16 {%0, %1, %2, %3, %4, %5, %6, %7, %8, %9, %10, %11, %12, %13, %14, %15, %16, %17, %18, %19, %20, %21, %22, %23, %24, %25, %26, %27, %28, %29, %30, %31, %32, %33, %34, %35, %36, %37, %38, %39, %40, %41, %42, %43, %44, %45, %46, %47, %48, %49, %50, %51, %52, %53, %54, %55}, %56, %57, %60, 1, 1, %58, %59;\n"
        : "+f"(d[0]), "+f"(d[1]), "+f"(d[2]), "+f"(d[3]), "+f"(d[4]), "+f"(d[5]), "+f"(d[6]), "+f"(d[7]), "+f"(d[8]), "+f"(d[9]), "+f"(d[10]), "+f"(d[11]), "+f"(d[12]), "+f"(d[13]), "+f"(d[14]), "+f"(d[15]), "+f"(d[16]), "+f"(d[17]), "+f"(d[18]), "+f"(d[19]), "+f"(d[20]), "+f"(d[21]), "+f"(d[22]), "+f"(d[23]), "+f"(d[24]), "+f"(d[25]), "+f"(d[26]), "+f"(d[27]), "+f"(d[28]), "+f"(d[29]), "+f"(d[30]), "+f"(d[31]), "+f"(d[32]), "+f"(d[33]), "+f"(d[34]), "+f"(d[35]), "+f"(d[36]), "+f"(d[37]), "+f"(d[38]), "+f"(d[39]), "+f"(d[40]), "+f"(d[41]), "+f"(d[42]), "+f"(d[43]), "+f"(d[44]), "+f"(d[45]), "+f"(d[46]), "+f"(d[47]), "+f"(d[48]), "+f"(d[49]), "+f"(d[50]), "+f"(d[51]), "+f"(d[52]), "+f"(d[53]), "+f"(d[54]), "+f"(d[55])
        : "l"(da), "l"(db), "n"(TA), "n"(TB), "n"(SC));
}

template<int TA, int TB, int SC = 1> __device__ __forceinline__ void wgmma_ss64(float (&d)[32], uint64_t da, uint64_t db) {
    asm volatile("wgmma.mma_async.sync.aligned.m64n64k16.f32.bf16.bf16 {%0, %1, %2, %3, %4, %5, %6, %7, %8, %9, %10, %11, %12, %13, %14, %15, %16, %17, %18, %19, %20, %21, %22, %23, %24, %25, %26, %27, %28, %29, %30, %31}, %32, %33, %36, 1, 1, %34, %35;\n"
        : "+f"(d[0]), "+f"(d[1]), "+f"(d[2]), "+f"(d[3]), "+f"(d[4]), "+f"(d[5]), "+f"(d[6]), "+f"(d[7]), "+f"(d[8]), "+f"(d[9]), "+f"(d[10]), "+f"(d[11]), "+f"(d[12]), "+f"(d[13]), "+f"(d[14]), "+f"(d[15]), "+f"(d[16]), "+f"(d[17]), "+f"(d[18]), "+f"(d[19]), "+f"(d[20]), "+f"(d[21]), "+f"(d[22]), "+f"(d[23]), "+f"(d[24]), "+f"(d[25]), "+f"(d[26]), "+f"(d[27]), "+f"(d[28]), "+f"(d[29]), "+f"(d[30]), "+f"(d[31])
        : "l"(da), "l"(db), "n"(TA), "n"(TB), "n"(SC));
}

template<int TA, int TB, int SC = 1> __device__ __forceinline__ void wgmma_ss48(float (&d)[24], uint64_t da, uint64_t db) {
    asm volatile("wgmma.mma_async.sync.aligned.m64n48k16.f32.bf16.bf16 {%0, %1, %2, %3, %4, %5, %6, %7, %8, %9, %10, %11, %12, %13, %14, %15, %16, %17, %18, %19, %20, %21, %22, %23}, %24, %25, %28, 1, 1, %26, %27;\n"
        : "+f"(d[0]), "+f"(d[1]), "+f"(d[2]), "+f"(d[3]), "+f"(d[4]), "+f"(d[5]), "+f"(d[6]), "+f"(d[7]), "+f"(d[8]), "+f"(d[9]), "+f"(d[10]), "+f"(d[11]), "+f"(d[12]), "+f"(d[13]), "+f"(d[14]), "+f"(d[15]), "+f"(d[16]), "+f"(d[17]), "+f"(d[18]), "+f"(d[19]), "+f"(d[20]), "+f"(d[21]), "+f"(d[22]), "+f"(d[23])
        : "l"(da), "l"(db), "n"(TA), "n"(TB), "n"(SC));
}

template<int NKB, bool PERM>
__device__ __forceinline__ void mix_mainloop(TSARG float (&acc)[56], uint32_t par, bool leader) {
    constexpr uint32_t sb = SB, bars = sb + SM_BAR;
    constexpr int A0 = PERM ? 0 : 16 % NA_SLOTS;
    auto aoff = [](int jj, int s) { return (PERM ? (s & 1) * 8192 + (jj * 32 + (s >> 1) * 16) * 128 : jj * 8192 + s * 2048) >> 4; };
    int bslot = 0, aslot = A0;
    reg_fence(acc);
    #pragma unroll 1
    for (int i = 0; i < NKB / 2; i++) {
        mbar_wait(bars + 8 * (B_FULLA + i), par);
        const uint64_t adesc = mkdesc(sb + SM_ARING, 8192, 1024, 1) + (uint32_t)(aslot * 1024);
        aslot = aslot == NA_SLOTS - 1 ? 0 : aslot + 1;
        #pragma unroll
        for (int jj = 0; jj < 2; jj++) {
            const int j = 2 * i + jj;
            mbar_wait(bars + 8 * (B_FULLB + j), par);
            const uint64_t bdesc = mkdesc(sb + SM_BRING, 1792, 128, 0) + (uint32_t)(bslot * 896);
            bslot = bslot == NB_SLOTS - 1 ? 0 : bslot + 1;
            wg_fence();
            #pragma unroll
            for (int s = 0; s < 4; s++) wgmma_ss112<1, 1>(acc, adesc + aoff(jj, s), bdesc + s * 224);
            wg_commit();
            wg_wait<1>();
            if (j > 0 && leader) mbar_arrive(bars + 8 * (B_DONE + j - 1));
        }
    }
    wg_wait<0>();
    reg_fence(acc);
    if (leader) mbar_arrive(bars + 8 * (B_DONE + NKB - 1));
}

constexpr uint32_t EMPTY = 0xFFFFFFFFu;
__device__ __forceinline__ void post_hint(uint4* p, uint32_t ep, int lane) { if (lane < 2) st_relaxed4(p + lane, ep, ep, ep, ep); }
__device__ __forceinline__ void post_hint_wg(int id, uint4* p, uint32_t ep, int w, int lane) {
    if (w < 3) named_arrive(id, 128);
    else { named_sync(id, 128); const uint32_t now = gtime32(); if (lane < 2) st_relaxed4(p + lane, ep, now, ep, now); }
}

__device__ __forceinline__ void wait_hints(TSARG const uint4* hint, uint32_t ep, uint32_t delay, int st) {
    uint2 v;
    do { v = ld_relaxed2(hint); } while (!__all_sync(0xffffffffu, v.x == ep));
    const uint32_t t1 = gtime32(), age = __reduce_min_sync(0xffffffffu, t1 + 256 - v.y);
    if (elect()) STAMP(st);
    while (gtime32() - t1 + age < delay + 256) {}
    __syncwarp();
}

template<int NKB>
__device__ __forceinline__ void mix_producer_b(TSARG uint32_t par, const uint4* hints, uint32_t ep, const uint32_t* src, int lane) {
    constexpr uint32_t sb = SB, bars = sb + SM_BAR;
    wait_hints(TSVAL hints + (lane >> 3) * 64 + (lane & 7) * 2, ep, NKB == 32 ? GO_H : GO_U, NKB == 32 ? 42 : 43);
    if (par) mbar_wait(bars + 8 * (B_DONE + 31), 0);
    #pragma unroll 1
    for (int j = 0; j < NKB; j++) {
        if (j >= NB_SLOTS) mbar_wait(bars + 8 * (B_DONE + j - NB_SLOTS), par);
        if (j == 0 && lane == 0) STAMP(NKB == 32 ? 29 : 30);
        if (j == 7 && lane == 0) STAMP(NKB == 32 ? 35 : 36);
        if (elect()) {
            mbar_expect(bars + 8 * (B_RAW + (j & 7)), 14336);
            bulk_ld(sb + SM_BRING + (j & 7) * 14336, src + j * 3584, 14336, bars + 8 * (B_RAW + (j & 7)));
        }
    }
}
__device__ __forceinline__ void check_tiles(TSARG int n, int w, int lane, uint32_t& ph, uint32_t dst, const uint32_t* src, int full) {
    constexpr uint32_t bars = SB + SM_BAR;
    #pragma unroll 1
    for (int j = w; j < n; j += 4) {
        const uint32_t raw = bars + 8 * (B_RAW + (j & 7)), d = dst + (j & 7) * 14336, a = d + lane * 128 + (lane & 3) * 32 + (lane >> 2) * 4;
        bool bad;
        do {
            mbar_wait(raw, (ph >> (j & 4)) & 1);
            ph ^= 1u << (j & 4);
            if (j == 0 && lane == 0) STAMP(n == 4 ? 6 : n == 32 ? 31 : 32);
            uint32_t v0, v1, v2, v3;
            asm volatile("ld.shared.u32 %0, [%4];\nld.shared.u32 %1, [%4+4096];\nld.shared.u32 %2, [%4+8192];\nld.shared.u32 %3, [%4+10240];"
                         : "=r"(v0), "=r"(v1), "=r"(v2), "=r"(v3) : "r"(a) : "memory");
            bad = __any_sync(0xffffffffu, max(max(v0, v1), max(v2, v3)) == EMPTY);
            if (elect() && bad) {
                mbar_expect(raw, 14336); bulk_ld(d, src + j * 3584, 14336, raw);
            }
        } while (bad);
        if (lane == 0) mbar_arrive(bars + 8 * (full + j));
    }
}

__device__ __forceinline__ uint32_t hcol(uint32_t a, int jp) { return (a ^ ((jp & 3) << 5)) + (jp >> 2) * 8192; }

__device__ __forceinline__ uint32_t get_tag() {
    mbar_wait(SB + SM_BAR + 8 * B_CLR, 0);
    uint32_t v; asm volatile("ld.shared.u32 %0, [%1];" : "=r"(v) : "r"(SB + SM_TAG) : "memory"); return v;
}

template<bool USE_SMID>
__global__ void __launch_bounds__(384, 1)
fused_kernel(Scratch* __restrict__ sc, const __nv_bfloat16* __restrict__ wo,
             const __nv_bfloat16* __restrict__ w1, const __nv_bfloat16* __restrict__ b1,
             const __nv_bfloat16* __restrict__ w2, const __nv_bfloat16* __restrict__ b2,
             const __grid_constant__ CUtensorMap tm_x, const __grid_constant__ CUtensorMap tm_wqkv,
             const __grid_constant__ CUtensorMap tm_wo64, const __grid_constant__ CUtensorMap tm_wo48,
             const __grid_constant__ CUtensorMap tm_w1, const __grid_constant__ CUtensorMap tm_w2,
             const __grid_constant__ CUtensorMap tm_xr64, const __grid_constant__ CUtensorMap tm_xr48,
             const __grid_constant__ CUtensorMap tm_out64, const __grid_constant__ CUtensorMap tm_out48) {
    extern __shared__ __align__(1024) uint8_t smem_raw[];
    constexpr uint32_t sb = SB;
    constexpr uint32_t bars = sb + SM_BAR;
    const int tid = threadIdx.x, lane = tid & 31;
    const int warp = __shfl_sync(0xffffffffu, tid >> 5, 0);
    int slot;
    if (USE_SMID) {
        asm("{\n.reg .u32 s, t, u, d, a, b, c;\n.reg .pred p, r;\n"
            "mov.u32 s, %%smid;\nshr.u32 t, s, 1;\nsub.u32 u, t, 32;\nmul.lo.u32 d, u, 37;\nshr.u32 d, d, 8;\n"
            "and.b32 a, t, 7;\nshl.b32 a, a, 3;\nshr.u32 c, t, 3;\nadd.u32 a, a, c;\n"
            "mad.lo.u32 b, d, -55, 12;\nshl.b32 c, u, 3;\nadd.u32 b, b, c;\n"
            "setp.lt.u32 p, t, 32;\nselp.u32 a, a, b, p;\n"
            "setp.lt.u32 r, t, 62;\nselp.s32 c, 4, -58, r;\nadd.u32 c, t, c;\nsetp.lt.u32 p, t, 60;\nselp.u32 a, a, c, p;\n"
            "and.b32 s, s, 1;\nshl.b32 a, a, 1;\nadd.u32 %0, a, s;\n}" : "=r"(slot));
    } else slot = blockIdx.x;
    const int G = slot >> 4, mi = slot & 15;
    const int tb = 4 * (G >> 1) + (mi >> 2), hp = 2 * (mi & 3) + (G & 1);
    const int wcol = (hp * 56) & ~15;
    if (slot >= 128) {
        if (tid == 0) {
            const uint32_t ep = ld_volatile(&sc->epoch[slot]) + 1;
            const long long t0 = clock64();
            while (clock64() - t0 < SP_AT) {}
            #pragma unroll 1
            for (int i = 0; i < 7; i++) bulk_prefetch((const char*)wo + (i * 4 + mi) * 14336, 14336);
            #pragma unroll 1
            for (int i = 0; i < SP_N; i++) bulk_prefetch((const char*)w1 + (i * 4 + mi) * 14336, 14336);
            while (ld_relaxed(sc->hint_u) != ep) { __nanosleep(500); if (clock64() - t0 > WD_CLKS) __trap(); }
            sc->epoch[slot] = ep;
        }
        return;
    }
    const int q = mi & 3, tt2 = 4 * G + (mi >> 2), ft = 4 * (G - 1) + (mi >> 2);
    const bool has_b1 = G > 0;
    const int c64 = 64 * q, c48 = 256 + 48 * q;

    if (warp < 8) {
        if (WARM) {
            const int w = warp & 3, wg = warp >> 2, g = lane >> 2, t = lane & 3;
            if (WARM_AT) { const uint32_t t0 = clock32(); while (clock32() - t0 < WARM_AT) {} __syncwarp(); }
            if (w > 0) post_hint(sc->hint_o + ((2 * tb + (w >> 1)) * 32 + hp * 4 + (w & 1) * 2 + wg) * 2, 0, lane);
            if (wg == 0) {
                if (t < 2) st_relaxed4(sc->stats + tt2 * 256 + q * 64 + 16 * w + g + 8 * t, 0, 0, 0, 0);
                if (w == 3) post_hint(sc->hint_h + (q * 32 + tt2) * 2, 0, lane);
            }
        }
        named_sync(0, 384);
        asm volatile("setmaxnreg.inc.sync.aligned.u32 224;");
        int tid; asm volatile("mov.u32 %0, %%tid.x;" : "=r"(tid));
        const int lane = tid & 31, warp = __shfl_sync(0xffffffffu, tid >> 5, 0), wg = warp >> 2;
        uint32_t ep;
        Tiles* tl;
        const int w = warp & 3, g = lane >> 2, t = lane & 3;
        const bool leader = (tid & 127) == 0;
        const uint32_t never = gridDim.y - 1;
        {
            uint32_t a[28][4];
            float accK[28], accV[28], accQ[28];
            const int lrow = 16 * w + (lane & 7) + (lane & 8);
            const uint32_t lbase = sb + wg * 8192 + lrow * 128;
            const uint32_t lx = (lane >> 4) ^ (lane & 7);
            const uint32_t wofs = hp & 1;
            auto pin2 = [&](uint32_t x0, uint32_t x1) {
                asm volatile("{\n.reg .pred p;\nsetp.ne.u32 p, %2, 0;\n@p st.shared.v2.b32 [%0], {%0,%1};\n}" :: "r"(x0), "r"(x1), "r"(never) : "memory");
            };
            float cS[2][4] = {}, cA[2][4] = {}, cB[2][4] = {}, q0, q1, p0, p1;
            auto sq = [&](float& acc, uint32_t v) { const float lo = bf_lo(v), hi = bf_hi(v); acc = fmaf(hi, hi, fmaf(lo, lo, acc)); };
            #pragma unroll
            for (int kb = 0; kb < 8; kb++) {
                if (kb < 7) {
                    mbar_wait(bars + 8 * (B_FULLX + kb), 0);
                    if (kb == 0 && tid == 0) STAMP(0);
                    if (kb == 6 && tid == 0) STAMP(25);
                    if (kb == 0) FST(0); if (kb == 2) FST(1); if (kb == 4) FST(2); if (kb == 6) FST(3);
                    #pragma unroll
                    for (int s = 4 * kb; s < 4 * kb + 4; s++) ldsm4(a[s], lbase + slot_x(kb) + ((lx ^ (2 * (s & 3))) << 4));
                }
                if (kb == NPIPE) continue;
                const int kc = kb < NPIPE ? kb : kb - 1;
                if (kc == NSQ) { p0 = cS[0][0] + cS[1][0]; p1 = cS[0][2] + cS[1][2]; }
                #pragma unroll
                for (int s = 4 * kc; s < 4 * kc + 4; s++) {
                    mma16816(cS[s & 1], a[s][0], a[s][1], a[s][2], a[s][3], 0x3F803F80u, 0x3F803F80u);
                    if (kc < NSQ) {
                        mma1688(cA[0], a[s][0], a[s][1], a[s][0]); mma1688(cA[1], a[s][2], a[s][3], a[s][2]);
                        mma1688(cB[0], a[s][0], a[s][1], a[s][1]); mma1688(cB[1], a[s][2], a[s][3], a[s][3]);
                    }
                }
            }
            const float m0 = (cS[0][0] + cS[1][0]) * (1.f / D_), m1 = (cS[0][2] + cS[1][2]) * (1.f / D_);
            const uint32_t mm0 = pack_bf16(m0, m0), mm1 = pack_bf16(m1, m1);
            if (lane == 0) mbar_arrive(bars + 8 * B_DONEX);
            auto center = [&](int s) { sub_bf16x2(a[s][0], mm0); sub_bf16x2(a[s][1], mm1); sub_bf16x2(a[s][2], mm0); sub_bf16x2(a[s][3], mm1); };
            uint32_t Ka[8], Kb[8], Kc[8], Va[8], Vb[7], Vc[8];
            float r0, r1, ls0, ls1;
            uint32_t pm, zero;
            uint32_t* od;
            uint4* oh;
            auto kpack = [&](uint32_t (&k)[8], int j, int c, float r) {
                const uint32_t v = pack_bf16(accK[4 * j + c] * r, accK[4 * j + c + 1] * r);
                if (j == 3) { k[3] = t < 2 ? v : 0u; k[4] = t < 2 ? 0u : v; } else k[j + (j > 3)] = v;
            };
            auto batch = [&](auto c0, auto c1) {
                constexpr int n0 = c0.value, n1 = c1.value;
                if (PP && n0 < PP) named_sync(10 + wg, 256);
                wg_fence();
                static_for<n0, n1>([&](auto nc) {
                    constexpr int n = nc.value;
                    if (n == 4) { center(4); center(5); center(6); center(7); wg_fence(); }
                    const uint64_t desc = mkdesc(sb + (n < 56 ? slot_kv(n >> 3) + (n & 7) * 2048 : SM_QO + (n - 56) * 2048), 8192, 1024, 1) + wofs;
                    wgmma_rs56<1>(n < 28 ? accK : n < 56 ? accV : accQ, a[n % 28], desc, n % 28 != 0);
                });
                wg_commit();
                if (PP && n0 < PP && (n1 < PP || wg == 0)) named_arrive(11 - wg, 256);
                if (n0 > 0) wg_wait<1>();
            };
            const uint32_t hs = sb + tid * 16 + warp * 512;
            auto hand_over = [&](const uint32_t (&v)[8], int kv) {
                mbar_wait(bars + 8 * (kv ? B_DONE1 + 5 : B_DONEX), 0);
                sts4(hs + (kv ? SM_HALOV : SM_HALOK), v[0], v[1], v[2], v[3]); sts4(hs + (kv ? SM_HALOV : SM_HALOK) + 512, v[4], v[5], v[6], v[7]);
                if (w == 3) named_arrive(6 + kv, 96);
            };
            auto take_over = [&](uint32_t (&v)[8], int kv) {
                if (w == 0) mbar_wait(bars + 8 * (B_HALO + 2 * kv + wg), 0);
                const uint32_t ad = w ? hs + (kv ? SM_HALOV : SM_HALOK) - 1024 : sb + lane * 16 + wg * 1024 + (kv ? SM_HALOV + 8192 : SM_HALOKIN);
                const uint4 u0 = lds4(ad), u1 = lds4(ad + 512);
                v[0] = u0.x; v[1] = u0.y; v[2] = u0.z; v[3] = u0.w; v[4] = u1.x; v[5] = u1.y; v[6] = u1.z; v[7] = u1.w;
            };
            if (PP && wg == 1) { pin2(mm0, mm1); named_arrive(10, 256); }
            center(0); center(1); center(2); center(3);
            static_for<0, 7>([&](auto pc) {
                constexpr int p = pc.value;
                mbar_wait(bars + 8 * (B_FULLKV + p), 0);
                if (p == 0 && tid == 0) STAMP(26);
                if (p == 3 && tid == 0) STAMP(27);
                FST(4 + p);
                batch(Int<8 * p>(), Int<8 * p + 8>());
                if (p > 0 && leader) mbar_arrive(bars + 8 * (B_DONE1 + p - 1));
                #pragma unroll
                for (int s = 8 * p + 8; s < 8 * p + 16 && s < 28; s++) center(s);
                if (p == 1) {
                    const float c0 = bf_hi(mm0), c1 = bf_hi(mm1);
                    q0 = fmaf(c0, fmaf(c0, 64.f * NSQ, -2.f * p0), (g & 1) ? cA[0][1] + cA[1][1] : cA[0][0] + cA[1][0]) - D_ * (m0 - c0) * (m0 - c0);
                    q1 = fmaf(c1, fmaf(c1, 64.f * NSQ, -2.f * p1), (g & 1) ? cB[0][3] + cB[1][3] : cB[0][2] + cB[1][2]) - D_ * (m1 - c1) * (m1 - c1);
                    asm("" : "+f"(q0), "+f"(q1));
                    q0 = t == (g >> 1) ? q0 : 0.f; q1 = t == (g >> 1) ? q1 : 0.f;
                    pin2(__float_as_uint(q0), __float_as_uint(q1));
                }
                constexpr int PK = NSQ < 5 ? 5 : 4, NR = 28 - 4 * NSQ;
                if (p >= 2 && p < PK) {
                    #pragma unroll
                    for (int s = 4 * NSQ + NR * (p - 2) / (PK - 2); s < 4 * NSQ + NR * (p - 1) / (PK - 2); s++) { sq(q0, a[s][0]); sq(q1, a[s][1]); sq(q0, a[s][2]); sq(q1, a[s][3]); }
                    pin2(__float_as_uint(q0), __float_as_uint(q1));
                }
                if (p == PK - 1) { q0 = quad_sum(q0); q1 = quad_sum(q1); }
                if (p == PK) {
                    r0 = rsqrt_approx(fmaxf(q0 * (1.f / D_), 0.f) + LN_EPS); r1 = rsqrt_approx(fmaxf(q1 * (1.f / D_), 0.f) + LN_EPS);
                    reg_fence(accK);
                    #pragma unroll
                    for (int j = 0; j < 7; j++) kpack(Kc, j, 2, r1);
                    hand_over(Kc, 0);
                }
                if (p == PK + 1) {
                    #pragma unroll
                    for (int j = 0; j < 7; j++) kpack(Kb, j, 0, r0);
                    #pragma unroll
                    for (int j = 0; j < 8; j += 2) pin2(Kb[j], Kb[j + 1]);
                    ls0 = LOG2E_SCALE * r0; ls1 = LOG2E_SCALE * r1;
                    pm = (2 * t <= g ? 0xFFFFu : 0u) | (2 * t + 1 <= g ? 0xFFFF0000u : 0u);
                    zero = never; asm volatile("" : "+r"(zero));
                    pin2(__float_as_uint(ls0), __float_as_uint(ls1)); pin2(pm, zero);
                }
                if (p == 2) ep = get_tag();
                if (p == 6) {
                    tl = &sc->tiles[ep & 1];
                    const int tt = 2 * tb + (w >> 1);
                    od = tl->o + tt * 14336 + (7 * hp) * 256 + (2 * (2 * (w & 1) + wg)) * 32 + lane;
                    oh = sc->hint_o + (tt * 32 + hp * 4 + (w & 1) * 2 + wg) * 2 + (lane & 1);
                    pin2((uint32_t)(uint64_t)od, (uint32_t)((uint64_t)od >> 32));
                    pin2((uint32_t)(uint64_t)oh, (uint32_t)((uint64_t)oh >> 32));
                }
            });
            if (tid == 0) STAMP(1);
            FST(11);
            mbar_wait(bars + 8 * B_FQ, 0);
            batch(Int<56>(), Int<60>());
            reg_fence(accV);
            if (leader) mbar_arrive(bars + 8 * (B_DONE1 + 6));
            if (tid == 0) STAMP(2);
            FST(12);
            #pragma unroll
            for (int j = 0; j < 7; j++) Vc[j] = movtrans(pack_bf16(accV[4 * j + 2] * r1, accV[4 * j + 3] * r1));
            Vc[7] = Vc[6];
            hand_over(Vc, 1);
            batch(Int<60>(), Int<66>());
            #pragma unroll
            for (int j = 0; j < 7; j++) {
                Vb[j] = movtrans(pack_bf16(accV[4 * j] * r0, accV[4 * j + 1] * r0));
                Vc[j] |= zero;
            }
            batch(Int<66>(), Int<72>());
            #pragma unroll
            for (int j = 0; j < 7; j++) pin2(Vb[j], Vc[j]);
            mbar_wait(bars + 8 * (B_FQ + 1), 0);
            FST(13);
            if (w > 0 && lane < 2) { const uint32_t now = gtime32(); st_relaxed4(oh, ep, now, ep, now); }
            batch(Int<72>(), Int<84>());
            FST(14);
            named_sync(1 + wg, 128);
            take_over(Ka, 0);
            if (tid == 0) STAMP(3);
            wg_wait<0>();
            reg_fence(accQ);
            if (tid == 0) STAMP(4);
            FST(15);
            const bool first = (tb == 0 && w == 0);
            uint32_t pA[2], pB0[2], pB1[2], pC[2], z0[2], z1[2];
            #pragma unroll
            for (int h = 0; h < 2; h++) {
                float sA[4] = {0.f, 0.f, 0.f, 0.f}, sB[4] = {0.f, 0.f, 0.f, 0.f}, sC[4] = {0.f, 0.f, 0.f, 0.f};
                #pragma unroll
                for (int k = 0; k < 2; k++) {
                    const float* qq = accQ + 12 * h + 8 * k;
                    uint32_t a0 = pack_bf16(qq[0], qq[1]), a1 = pack_bf16(qq[2], qq[3]);
                    if (h == 1 && k == 0) { a0 |= zero; a1 |= zero; }
                    const uint32_t a2 = pack_bf16(qq[4], qq[5]), a3 = pack_bf16(qq[6], qq[7]);
                    mma16816(sB, a0, a1, a2, a3, Kb[4 * h + 2 * k], Kb[4 * h + 2 * k + 1]);
                    mma16816(sA, a0, a1, a2, a3, Ka[4 * h + 2 * k], Ka[4 * h + 2 * k + 1]);
                    mma16816(sC, a0, a1, a2, a3, Kc[4 * h + 2 * k], Kc[4 * h + 2 * k + 1]);
                }
                const bool n0 = pm & 1, n1 = (int)pm < 0;
                const float l00 = n0 ? sB[0] : (first ? -INFINITY : sA[0]), l01 = n1 ? sB[1] : (first ? -INFINITY : sA[1]);
                const float l10 = n0 ? sC[2] : sB[2], l11 = n1 ? sC[3] : sB[3];
                const float x0 = -ls0 * quad_max(fmaxf(l00, l01)), x1 = -ls1 * quad_max(fmaxf(l10, l11));
                const float e00 = ex2(fmaf(l00, ls0, x0)), e01 = ex2(fmaf(l01, ls0, x0)), e10 = ex2(fmaf(l10, ls1, x1)), e11 = ex2(fmaf(l11, ls1, x1));
                const float i0 = rcp_approx(quad_sum(e00 + e01)), i1 = rcp_approx(quad_sum(e10 + e11));
                const uint32_t P0 = pack_bf16(e00 * i0, e01 * i0), P1 = pack_bf16(e10 * i1, e11 * i1);
                pB0[h] = P0 & pm; pA[h] = P0 & ~pm; pC[h] = P1 & pm; pB1[h] = P1 & ~pm; z0[h] = P0 & zero; z1[h] = P1 & zero;
            }
            float o[8][4];
            #pragma unroll
            for (int j = 0; j < 8; j++) {
                o[j][0] = o[j][1] = o[j][2] = o[j][3] = 0.f;
                mma16816(o[j], pB0[j >> 2], pB1[j >> 2], z0[j >> 2], pC[j >> 2], Vb[j - (j >> 2)], Vc[j - (j >> 2)]);
            }
            if (tid == 0) STAMP(12);
            FST(16);
            take_over(Va, 1);
            if (lane == 0) mbar_arrive(bars + 8 * B_DONEQ);
            if (tid == 0) STAMP(16);
            #pragma unroll
            for (int j = 0; j < 8; j++) mma1688(o[j], pA[j >> 2], z1[j >> 2], Va[j - (j >> 2)]);
            #pragma unroll
            for (int j = 0; j < 7; j++) {
                float v[4];
                #pragma unroll
                for (int c = 0; c < 4; c++) v[c] = j < 3 ? o[j][c] : j > 3 ? o[j + 1][c] : (t < 2 ? o[3][c] : o[4][c]);
                od[j * 256] = pack_bf16(v[0], v[1]);
                od[j * 256 + 32] = pack_bf16(v[2], v[3]);
            }
            if (tid == 0) STAMP(5);
            FST(17);
        }
        if (wg == 1) {
            uint32_t ph = 0;
            check_tiles(TSVAL 4, w, lane, ph, sb + SM_QO, tl->o + tt2 * 14336, B_FULLO);
            if (has_b1) check_tiles(TSVAL 32, w, lane, ph, sb + SM_BRING, tl->hn + q * 32 * 3584, B_FULLB);
            check_tiles(TSVAL 28, w, lane, ph, sb + SM_BRING, tl->u + q * 28 * 3584, B_FULLB);
        } else {
            const uint32_t rb10 = has_b1 ? __ldg((const unsigned short*)b1 + ft * 64 + 16 * w + g) : 0, rb11 = has_b1 ? __ldg((const unsigned short*)b1 + ft * 64 + 16 * w + g + 8) : 0;
            const uint32_t rb20 = __ldg((const unsigned short*)b2 + tt2 * 64 + 16 * w + g), rb21 = __ldg((const unsigned short*)b2 + tt2 * 64 + 16 * w + g + 8);
            {
                float acc[56];
                const int hrow = 32 * (w >> 1) + 2 * ((lane & 7) + (lane & 8)) + (w & 1);
                const uint32_t ha = sb + SM_H + hrow * 128 + (((lane >> 4) ^ (hrow & 7)) << 4);
                mbar_wait(bars + 8 * B_FULLWO, 0);
                #pragma unroll
                for (int jp = 0; jp < 7; jp++) {
                    uint32_t xx[4];
                    ldsm4(xx, hcol(ha, jp));
                    #pragma unroll
                    for (int r = 0; r < 4; r++) { acc[8 * jp + 2 * r] = bf_lo(xx[r]); acc[8 * jp + 2 * r + 1] = bf_hi(xx[r]); }
                }
                reg_fence(acc);
                float accl[32], accr[24];
                auto od_ = [&](int s) { return mkdesc(sb + SM_QO + s * 2048, 1024, 128, 0); };
                auto wd_ = [&](int s) { return mkdesc(sb + slot_wo(s >> 2) + (s & 3) * 2048, 8192, 1024, 1); };
                #pragma unroll
                for (int i = 0; i < 5; i++) {
                    if (i < 4) mbar_wait(bars + 8 * (B_FULLO + i), 0);
                    if (i == 0 && tid == 0) STAMP(7);
                    wg_fence();
                    #pragma unroll
                    for (int ss = 0; ss < 7; ss++) {
                        if (i < 3) wgmma_ss112<0, 1>(acc, od_(7 * i + ss), wd_(7 * i + ss));
                        else if (i == 3) { if (ss == 0) wgmma_ss64<0, 1, 0>(accl, od_(21), wd_(21)); else wgmma_ss64<0, 1>(accl, od_(21 + ss), wd_(21 + ss)); }
                        else wgmma_ss48<0, 1>(accr, od_(21 + ss), wd_(21 + ss) + 512);
                    }
                    wg_commit();
                    if (i > 0) {
                        wg_wait<1>();
                        if (i == 3) {
                            reg_fence(acc);
                            #pragma unroll
                            for (int c = 0; c < 24; c++) accr[c] = __uint_as_float(__float_as_uint(acc[32 + c]) | never);
                            reg_fence(accr);
                        }
                        if (i < 4 && leader) mbar_arrive(bars + 8 * (B_DONEO + i - 1));
                    }
                }
                float s0 = 0.f, s1 = 0.f, q0 = 0.f, q1 = 0.f, s2 = 0.f, s3 = 0.f, q2 = 0.f, q3 = 0.f;
                reg_fence(accl);
                #pragma unroll
                for (int c = 0; c < 32; c++) acc[c] += accl[c];
                #pragma unroll
                for (int j = 0; j < 14; j++) {
                    if (j == 8) {
                        pin4(never, s0, s1, s2, s3); pin4(never, q0, q1, q2, q3);
                        wg_wait<0>();
                        reg_fence(accr);
                        #pragma unroll
                        for (int c = 0; c < 24; c++) acc[32 + c] = accr[c];
                        if (leader) mbar_arrive(bars + 8 * (B_DONEO + 3));
                        if (tid == 0) STAMP(8);
                    }
                    s0 += acc[4 * j]; s2 += acc[4 * j + 1]; q0 = fmaf(acc[4 * j], acc[4 * j], q0); q2 = fmaf(acc[4 * j + 1], acc[4 * j + 1], q2);
                    s1 += acc[4 * j + 2]; s3 += acc[4 * j + 3]; q1 = fmaf(acc[4 * j + 2], acc[4 * j + 2], q1); q3 = fmaf(acc[4 * j + 3], acc[4 * j + 3], q3);
                }
                s0 = quad_sum(s0 + s2); s1 = quad_sum(s1 + s3); q0 = quad_sum(q0 + q2); q1 = quad_sum(q1 + q3);
                uint4* sp = sc->stats + tt2 * 256 + 16 * w + g;
                if (t < 2) st_relaxed4(sp + q * 64 + 8 * t, __float_as_uint(t ? s1 : s0), ep, __float_as_uint(t ? q1 : q0), ep);
                if (tid == 0) STAMP(9);
                #pragma unroll
                for (int jp = 0; jp < 7; jp++)
                    stsm4(hcol(ha, jp), pack_bf16(acc[8 * jp], acc[8 * jp + 1]), pack_bf16(acc[8 * jp + 2], acc[8 * jp + 3]),
                          pack_bf16(acc[8 * jp + 4], acc[8 * jp + 5]), pack_bf16(acc[8 * jp + 6], acc[8 * jp + 7]));
                {
                    uint4 v0, v1;
                    do {
                        v0 = ld_relaxed4(sp + t * 64); v1 = ld_relaxed4(sp + t * 64 + 8);
                    } while (__any_sync(0xffffffffu, t != q && (v0.y != ep || v0.w != ep || v1.y != ep || v1.w != ep)));
                    if (t != q) { s0 = __uint_as_float(v0.x); q0 = __uint_as_float(v0.z); s1 = __uint_as_float(v1.x); q1 = __uint_as_float(v1.z); }
                }
                if (tid == 0) STAMP(10);
                s0 = quad_sum(s0); s1 = quad_sum(s1); q0 = quad_sum(q0); q1 = quad_sum(q1);
                const float m0 = s0 * (1.f / D_), m1 = s1 * (1.f / D_);
                const float v0 = fmaxf(q0 * (1.f / D_) - m0 * m0, 0.f), v1 = fmaxf(q1 * (1.f / D_) - m1 * m1, 0.f);
                const float r0 = rsqrt_approx(fmaf(v0, 4.f + 4.f * LN_EPS, 4.f * LN_EPS * LN_EPS)), r1 = rsqrt_approx(fmaf(v1, 4.f + 4.f * LN_EPS, 4.f * LN_EPS * LN_EPS));
                const float c0 = -m0 * r0, c1 = -m1 * r1;
                uint32_t* hd = tl->hn + (q * 32 + tt2) * 3584 + (2 * w) * 448 + lane;
                #pragma unroll
                for (int j = 0; j < 14; j++) {
                    if (j == HINT_H) post_hint_wg(5, sc->hint_h + (q * 32 + tt2) * 2, ep, w, lane);
                    hd[j * 32] = pack_bf16(fmaf(acc[4 * j], r0, c0), fmaf(acc[4 * j + 1], r0, c0));
                    hd[j * 32 + 448] = pack_bf16(fmaf(acc[4 * j + 2], r1, c1), fmaf(acc[4 * j + 3], r1, c1));
                }
                if (tid == 0) STAMP(11);
                if (HINT_H == 14) post_hint_wg(5, sc->hint_h + (q * 32 + tt2) * 2, ep, w, lane);
                if (tid == 96) STAMP(33);
            }
            if (has_b1) {
                float acc[56];
                #pragma unroll
                for (int j = 0; j < 56; j++) acc[j] = 0.5f * bf_lo((j & 2) ? rb11 : rb10);
                uint32_t* ud = tl->u + (q * 28 + ft) * 3584 + (2 * w) * 448 + lane;
                #pragma unroll 1
                for (uint32_t pass = (DRY & 2) ? never : 1; pass < 2; pass++) {
                    if (pass) {
                        mix_mainloop<32, true>(TSVAL acc, 0, leader);
                        if (tid == 0) STAMP(14);
                    }
                    #pragma unroll
                    for (int j = 0; j < 14; j++) {
                        st_global_if(pass, ud + j * 32, pack_bf16(gelu_half(acc[4 * j]), gelu_half(acc[4 * j + 1])));
                        st_global_if(pass, ud + j * 32 + 448, pack_bf16(gelu_half(acc[4 * j + 2]), gelu_half(acc[4 * j + 3])));
                    }
                }
                if (tid == 0) STAMP(15);
                if (tid == 96) STAMP(34);
            }
            {
                float acc[56];
                const float bb0 = bf_lo(rb20), bb1 = bf_lo(rb21);
                named_sync(1, 128);
                const uint32_t ad = sb + SM_H + (16 * w + (lane & 15)) * 128 + (((lane >> 4) ^ (lane & 7)) << 4);
                #pragma unroll
                for (int jp = 0; jp < 7; jp++) {
                    uint32_t hh[4];
                    ldsm4(hh, hcol(ad, jp));
                    #pragma unroll
                    for (int r = 0; r < 4; r++) { acc[8 * jp + 2 * r] = bf_lo(hh[r]) + ((r & 1) ? bb1 : bb0); acc[8 * jp + 2 * r + 1] = bf_hi(hh[r]) + ((r & 1) ? bb1 : bb0); }
                }
                #pragma unroll 1
                for (uint32_t pass = (DRY & 4) ? never : 1; pass < 2; pass++) {
                    if (pass) {
                        mix_mainloop<28, false>(TSVAL acc, has_b1, leader);
                        if (leader) mbar_arrive(bars + 8 * B_END);
                        if (tid == 0) STAMP(18);
                    }
                    #pragma unroll
                    for (int jp = 0; jp < 7; jp++)
                        stsm4(hcol(ad, jp), pack_bf16(acc[8 * jp], acc[8 * jp + 1]), pack_bf16(acc[8 * jp + 2], acc[8 * jp + 3]),
                              pack_bf16(acc[8 * jp + 4], acc[8 * jp + 5]), pack_bf16(acc[8 * jp + 6], acc[8 * jp + 7]));
                    fence_async_smem();
                    __syncwarp();
                }
                if (elect()) {
                    tma2d_store(&tm_out64, c64, tt2 * 64 + 16 * w, sb + SM_H + w * 2048);
                    tma2d_store(&tm_out48, c48, tt2 * 64 + 16 * w, sb + SM_H + 8192 + w * 2048);
                }
                asm volatile("cp.async.bulk.commit_group;" ::: "memory");
                asm volatile("cp.async.bulk.wait_group.read 0;" ::: "memory");
                if (tid == 0) { sc->epoch[slot] = ep; STAMP(19); }
            }
        }
    } else {
        asm volatile("setmaxnreg.dec.sync.aligned.u32 56;");
        int warp2; asm("mov.u32 %0, %1;" : "=r"(warp2) : "r"(warp));
        if (warp2 > 8) {
            uint32_t ep, cl;
            uint4* const oh = sc->hint_o + (2 * tb * 32 + hp * 4) * 2 + (lane & 3);
            if (warp == 11) {
                ep = ld_volatile(&sc->epoch[slot]) + 1; cl = ld_acquire(&sc->clean[lane & 15]);
                post_hint(sc->hint_k + (tb * 8 + hp) * 2, 0, lane);
                if (lane < (tb < 15 ? 4 : 0)) st_relaxed4(oh + 128, 0, 0, 0, 0);
                if (lane < (tb ? 0 : 4)) st_relaxed4(oh, 0, 0, 0, 0);
            }
            if (elect()) {
                if (warp == 9) {
                    #pragma unroll
                    for (int i = B_DONE1; i < B_DONEO; i++) mbar_init(bars + 8 * i, i < B_DONEX ? 2 : i == B_DONEX ? 8 : 9);
                    mbar_init(bars + 8 * B_CLR, 1);
                }
                #pragma unroll
                for (int i = 0; i < 34; i++) mbar_init(bars + 8 * (B_DONEO + i) + (warp - 9) * 272, 1);
                asm volatile("fence.mbarrier_init.release.cluster;" ::: "memory");
            }
            named_sync(0, 384);
            if (warp == 9) named_arrive(4, 64);
            if (warp < 11) {
                ep = get_tag();
                mbar_wait(bars + 8 * (B_DONE1 + HALO_AT), 0);
                #pragma unroll 1
                for (int kv = 0; kv < 2; kv++) {
                    uint4 v0 = {}, v1 = {}, v2 = {};
                    if (tb > 0) {
                        const uint4* hg = sc->halo + ((((tb - 1) * 8 + hp) * 2 + warp - 9) * 2 + kv) * 96 + lane;
                        if (kv == 0) while (ld_relaxed(sc->hint_k + ((tb - 1) * 8 + hp) * 2) != ep) {}
                        do { v0 = ld_relaxed4(hg); v1 = ld_relaxed4(hg + 32); v2 = ld_relaxed4(hg + 64); } while (!__all_sync(0xffffffffu, v0.w == ep && v1.w == ep && v2.w == ep));
                    }
                    if (kv) mbar_wait(bars + 8 * (B_DONE1 + 5), 0);
                    const uint32_t hs = sb + lane * 16 + (warp - 9) * 1024 + (kv ? SM_HALOV + 8192 : SM_HALOKIN);
                    sts4(hs, v0.x, v0.y, v0.z, v1.x); sts4(hs + 512, v1.y, v1.z, v2.x, v2.y);
                    __syncwarp();
                    if (lane == 0) mbar_arrive(bars + 8 * (B_HALO + 2 * kv + warp - 9));
                }
                if (tid == 288) STAMP(21);
            }
            if (warp == 10) {
                if (!has_b1 && lane == 0) {
                    mbar_wait(bars + 8 * (B_DONEO + 3), 0);
                    uint32_t t = clock32() + PF_AT;
                    #pragma unroll 1
                    for (int i = 0; i < PF_N; i++) {
                        while ((int)(clock32() - t) < 0) __nanosleep(40);
                        bulk_prefetch((const char*)w2 + (i * 16 + mi) * 16384, 16384);
                        t += PF_PACE;
                    }
                }
                if (has_b1) {
                    post_hint(sc->hint_u + (q * 32 + ft) * 2, 0, lane);
                    mbar_wait(bars + 8 * (B_DONE + HINT_U), 0);
                    const uint32_t now = gtime32();
                    if (lane < 2) st_relaxed4(sc->hint_u + (q * 32 + ft) * 2 + lane, ep, now, ep, now);
                }
            } else if (warp == 11) {
                #pragma unroll 1
                for (uint32_t e = ep; e != ep + 2; e++) {
                    if (!has_b1 && __shfl_sync(0xffffffffu, cl, mi) != e) {
                        if (e != ep) { mbar_wait_wd(bars + 8 * (B_DONEO + 3), 0); const uint32_t t = clock32(); while (clock32() - t < CL_AT) __nanosleep(100); __syncwarp(); }
                        constexpr int NL = sizeof(Tiles) / 2048;
                        uint4* p = (uint4*)&sc->tiles[e & 1] + (mi * NL + (lane >> 1)) * 8 + (lane & 7);
                        #pragma unroll 7
                        for (int i = 0; i < NL / 16; i++) st_relaxed4(p + i * 128, EMPTY, EMPTY, EMPTY, EMPTY);
                        __syncwarp();
                        if (lane == 0) { st_release(&sc->clean[mi], e); STAMP(24); }
                        __syncwarp();
                    }
                    if (e == ep) {
                        const long long t0 = clock64();
                        while (__any_sync(0xffffffffu, (int)(cl - ep) < 0)) { cl = ld_acquire(&sc->clean[lane & 15]); if (clock64() - t0 > WD_CLKS) __trap(); }
                        if (lane == 0) { *(volatile uint32_t*)(smem_raw + SM_TAG) = ep; mbar_arrive(bars + 8 * B_CLR); }
                        uint4* hg = sc->halo + (tb * 8 + hp) * 384 + lane;
                        #pragma unroll 1
                        for (int kv = 0; kv < 2; kv++) {
                            const uint32_t hs = sb + lane * 16 + 3072 + (kv ? SM_HALOV : SM_HALOK);
                            named_sync(6 + kv, 96);
                            #pragma unroll
                            for (int p = 0; p < 2; p++) {
                                const uint4 u0 = lds4(hs + p * 4096), u1 = lds4(hs + p * 4096 + 512);
                                st_relaxed4(hg + p * 192, u0.x, u0.y, u0.z, ep); st_relaxed4(hg + p * 192 + 32, u0.w, u1.x, u1.y, ep); st_relaxed4(hg + p * 192 + 64, u1.z, u1.w, ep, ep);
                            }
                            hg += 96;
                            if (kv == 0) {
                                post_hint(sc->hint_k + (tb * 8 + hp) * 2, ep, lane);
                                #pragma unroll
                                for (int j = 0; j < 6; j++) st_relaxed4(hg + j * 32 + (j / 3) * 96, 0, 0, 0, 0);
                            }
                        }
                        const uint32_t now = gtime32() - LATE_O;
                        if (lane < (tb < 15 ? 4 : 0)) st_relaxed4(oh + 128, ep, now, ep, now);
                        if (lane < (tb ? 0 : 4)) st_relaxed4(oh, ep, now, ep, now);
                        if (lane == 0) STAMP(23);
                        if (lane == 0) mbar_arrive(bars + 8 * B_DONEQ);
                    }
                }
                if (lane == 0) {
                    mbar_wait_wd(bars + 8 * B_END, 0);
                }
            } else {
                int aslot = 0;
                if (lane == 0) { prefetch_map(&tm_out64); prefetch_map(&tm_out48); }
                if (has_b1) {
                    #pragma unroll 1
                    for (int i = 0; i < 16; i++) {
                        mbar_wait(bars + 8 * (i < NA_SLOTS ? B_DONEQ + ((A_SCHED >> (4 * i)) & 15) : B_DONE + 1 + ((i - NA_SLOTS) * A3_END) / (15 - NA_SLOTS)), 0);
                        if (elect()) {
                            const uint32_t bar = bars + 8 * (B_FULLA + i), dst = sb + SM_ARING + aslot * 16384;
                            mbar_expect(bar, 16384);
                            tma3d(dst, &tm_w1, ft * 64, 0, i * 64, bar);
                            tma3d(dst + 8192, &tm_w1, ft * 64, 1, i * 64, bar);
                        }
                        aslot = aslot == NA_SLOTS - 1 ? 0 : aslot + 1;
                    }
                }
                aslot = 16 % NA_SLOTS;
                #pragma unroll 1
                for (int i = 0; i < 14; i++) {
                    if (i >= NA_SLOTS) mbar_wait(bars + 8 * (B_DONE + 1 + ((i - NA_SLOTS) * A4_END) / (13 - NA_SLOTS)), has_b1);
                    else if (has_b1) {
                        mbar_wait(bars + 8 * (B_DONE + max(33 - 2 * NA_SLOTS + 2 * i, W2_AT)), 0);
                        if (i >= W2_HOLD) mbar_wait(bars + 8 * B_FULLB, 1);
                    } else if (i == 0) { mbar_wait(bars + 8 * (B_DONEO + 3), 0); const uint32_t t = clock32() + PF_AT + 12 * PF_PACE; while ((int)(clock32() - t) < 0) __nanosleep(100); }
                    if (elect()) {
                        const uint32_t bar = bars + 8 * (B_FULLA + i);
                        mbar_expect(bar, 16384);
                        tma2d(sb + SM_ARING + aslot * 16384, &tm_w2, tt2 * 64, i * 128, bar);
                    }
                    aslot = aslot == NA_SLOTS - 1 ? 0 : aslot + 1;
                }
            }
        } else {
            auto krot = [&](int kb) { const int k = kb * 64 + (G & 1) * 64 * ROT; return k < 448 ? k : k - 448; };
            if (elect()) {
                #pragma unroll
                for (int i = 0; i < 7; i++) mbar_init(bars + 8 * i, 1);
                asm volatile("fence.mbarrier_init.release.cluster;" ::: "memory");
                if (STAG && G >= 2) { const uint32_t t0 = clock32(); while (clock32() - t0 < STAG) {} }
                #pragma unroll 1
                for (int kb = 0; kb < 7; kb++) {
                    const uint32_t st = sb + slot_x(kb), bar = bars + 8 * (B_FULLX + kb);
                    mbar_expect(bar, 16384);
                    tma3d(st, &tm_x, krot(kb), 0, tb * 64, bar); tma3d(st + 8192, &tm_x, krot(kb), 1, tb * 64, bar);
                }
                #pragma unroll
                for (int i = 7; i < B_DONE1; i++) mbar_init(bars + 8 * i, 1);
                asm volatile("fence.mbarrier_init.release.cluster;" ::: "memory");
            }
            named_arrive(0, 384);
            #pragma unroll 1
            for (int kb = 0; kb < 7; kb++) {
                if (kb == 6) { named_sync(4, 64); mbar_wait(bars + 8 * B_DONEX, 0); }
                if (elect()) {
                    const uint32_t st = sb + slot_kv(kb), bar = bars + 8 * (B_FULLKV + kb);
                    mbar_expect(bar, 16384);
                    #pragma unroll
                    for (int i = 0; i < 2; i++) {
                        const int n = 2 * kb + (ROT ? i : i ^ (G & 1));
                        tma2d(st + (n & 1) * 8192, &tm_wqkv, (n < 7 ? 448 : 896) + wcol, krot(n < 7 ? n : n - 7), bar);
                    }
                }
            }
            if (elect()) {
                mbar_expect(bars + 8 * B_FQ, 32768);
                mbar_expect(bars + 8 * (B_FQ + 1), 24576);
                #pragma unroll 1
                for (int i = 0; i < 7; i++) { const int j = ROT || i == 6 ? i : i ^ (G & 1); tma2d(sb + SM_QO + j * 8192, &tm_wqkv, wcol, krot(j), bars + 8 * (B_FQ + (i >> 2))); }
                mbar_expect(bars + 8 * B_FULLWO, 512 * 112 * 2);
            }
            #pragma unroll 1
            for (int i = 0; i < 7; i++) {
                const int kb = ((q & 1 ? WO_ORD1 : WO_ORD0) >> (4 * i)) & 7;
                if (kb < 5) mbar_wait(bars + 8 * (B_DONE1 + kb), 0);
                if (i == WO_HOLD) { mbar_wait(bars + 8 * (B_HALO + 2), 0); mbar_wait(bars + 8 * (B_HALO + 3), 0); }
                if (elect()) {
                    tma2d(sb + slot_wo(kb), &tm_wo64, c64, kb * 64, bars + 8 * B_FULLWO);
                    tma2d(sb + slot_wo(kb) + 8192, &tm_wo48, c48, kb * 64, bars + 8 * B_FULLWO);
                }
            }
            if (XR_HOLD) { mbar_wait(bars + 8 * (B_HALO + 2), 0); mbar_wait(bars + 8 * (B_HALO + 3), 0); }
            if (elect()) {
                tma2d(sb + SM_H, &tm_xr64, c64, tt2 * 64, bars + 8 * B_FULLWO);
                tma2d(sb + SM_H + 8192, &tm_xr48, c48, tt2 * 64, bars + 8 * B_FULLWO);
            }
            if (smem_u32(smem_raw) != SB) __trap();
            const uint32_t ep = get_tag();
            const Tiles* const tl = &sc->tiles[ep & 1];
            mbar_wait(bars + 8 * (B_DONE1 + 6), 0);
            wait_hints(TSVAL sc->hint_o + (tt2 * 32 + lane) * 2, ep, GO_O, 38);
            mbar_wait(bars + 8 * B_DONEQ, 0);
            if (elect()) {
                #pragma unroll
                for (int i = 0; i < 4; i++) {
                    mbar_expect(bars + 8 * (B_RAW + i), 14336);
                    bulk_ld(sb + SM_QO + i * 14336, tl->o + tt2 * 14336 + i * 3584, 14336, bars + 8 * (B_RAW + i));
                }
            }
            if (lane == 0) STAMP(20);
            mbar_wait(bars + 8 * (B_DONEO + 3), 0);
            if (has_b1) {
                mix_producer_b<32>(TSVAL 0, sc->hint_h, ep, tl->hn + q * 32 * 3584, lane);
            }
            mix_producer_b<28>(TSVAL has_b1, sc->hint_u, ep, tl->u + q * 28 * 3584, lane);
        }
    }
}

typedef CUresult (*EncodeFn)(CUtensorMap*, CUtensorMapDataType, cuuint32_t, void*, const cuuint64_t*, const cuuint64_t*, const cuuint32_t*,
                             const cuuint32_t*, CUtensorMapInterleave, CUtensorMapSwizzle, CUtensorMapL2promotion, CUtensorMapFloatOOBfill);

void make_map(EncodeFn fn, CUtensorMap* tm, const void* ptr, int rank, const cuuint64_t* dims, const cuuint64_t* strides, const cuuint32_t* box, CUtensorMapSwizzle sw) {
    cuuint32_t es[3] = {1, 1, 1};
    fn(tm, CU_TENSOR_MAP_DATA_TYPE_BFLOAT16, rank, const_cast<void*>(ptr), dims, strides, box, es, CU_TENSOR_MAP_INTERLEAVE_NONE, sw,
       CU_TENSOR_MAP_L2_PROMOTION_NONE, CU_TENSOR_MAP_FLOAT_OOB_FILL_NONE);
}

}

extern "C" void kernel_launch(void* const* d_in, const int* in_sizes, int n_in, void* d_out, int out_size) {
    const __nv_bfloat16* x = (const __nv_bfloat16*)d_in[0];
    const __nv_bfloat16* wqkv = (const __nv_bfloat16*)d_in[1];
    const __nv_bfloat16* wo = (const __nv_bfloat16*)d_in[2];
    const __nv_bfloat16* w1 = (const __nv_bfloat16*)d_in[4];
    const __nv_bfloat16* b1 = (const __nv_bfloat16*)d_in[5];
    const __nv_bfloat16* w2 = (const __nv_bfloat16*)d_in[6];
    const __nv_bfloat16* b2 = (const __nv_bfloat16*)d_in[7];

    void* fnp = nullptr; cudaDriverEntryPointQueryResult qr;
    cudaGetDriverEntryPoint("cuTensorMapEncodeTiled", &fnp, cudaEnableDefault, &qr);
    EncodeFn fn = (EncodeFn)fnp;
    CUtensorMap tx, twqkv, two64, two48, tw1, tw2, txr64, txr48, tout64, tout48;
    { cuuint64_t d[3] = {448, 2, 1024}, s[2] = {896, 1792}; cuuint32_t b[3] = {64, 1, 64}; make_map(fn, &tx, x, 3, d, s, b, CU_TENSOR_MAP_SWIZZLE_128B); }
    { cuuint64_t d[2] = {1344, 448}, s[1] = {2688}; cuuint32_t b[2] = {64, 64}; make_map(fn, &twqkv, wqkv, 2, d, s, b, CU_TENSOR_MAP_SWIZZLE_128B); }
    { cuuint64_t d[2] = {448, 448}, s[1] = {896}; cuuint32_t b[2] = {64, 64}; make_map(fn, &two64, wo, 2, d, s, b, CU_TENSOR_MAP_SWIZZLE_128B); }
    { cuuint64_t d[2] = {448, 448}, s[1] = {896}; cuuint32_t b[2] = {48, 64}; make_map(fn, &two48, wo, 2, d, s, b, CU_TENSOR_MAP_SWIZZLE_128B); }
    { cuuint64_t d[3] = {1792, 2, 1024}, s[2] = {3584, 7168}; cuuint32_t b[3] = {64, 1, 64}; make_map(fn, &tw1, w1, 3, d, s, b, CU_TENSOR_MAP_SWIZZLE_128B); }
    { cuuint64_t d[2] = {2048, 1792}, s[1] = {4096}; cuuint32_t b[2] = {64, 128}; make_map(fn, &tw2, w2, 2, d, s, b, CU_TENSOR_MAP_SWIZZLE_128B); }
    { cuuint64_t d[2] = {448, 2048}, s[1] = {896}; cuuint32_t b[2] = {64, 64}; make_map(fn, &txr64, x, 2, d, s, b, CU_TENSOR_MAP_SWIZZLE_128B); }
    { cuuint64_t d[2] = {448, 2048}, s[1] = {896}; cuuint32_t b[2] = {48, 64}; make_map(fn, &txr48, x, 2, d, s, b, CU_TENSOR_MAP_SWIZZLE_128B); }
    { cuuint64_t d[2] = {448, 2048}, s[1] = {896}; cuuint32_t b[2] = {64, 16}; make_map(fn, &tout64, d_out, 2, d, s, b, CU_TENSOR_MAP_SWIZZLE_128B); }
    { cuuint64_t d[2] = {448, 2048}, s[1] = {896}; cuuint32_t b[2] = {48, 16}; make_map(fn, &tout48, d_out, 2, d, s, b, CU_TENSOR_MAP_SWIZZLE_128B); }

    void* scv = nullptr;
    cudaGetSymbolAddress(&scv, g_scratch);
    Scratch* scp = (Scratch*)scv;
    int dev = 0, sms = 0;
    cudaGetDevice(&dev);
    cudaDeviceGetAttribute(&sms, cudaDevAttrMultiProcessorCount, dev);
    if (sms == 132) {
        cudaFuncSetAttribute(fused_kernel<true>, cudaFuncAttributeMaxDynamicSharedMemorySize, SM_TOTAL);
        fused_kernel<true><<<132, 384, SM_TOTAL>>>(scp, wo, w1, b1, w2, b2, tx, twqkv, two64, two48, tw1, tw2, txr64, txr48, tout64, tout48);
    } else {
        cudaFuncSetAttribute(fused_kernel<false>, cudaFuncAttributeMaxDynamicSharedMemorySize, SM_TOTAL);
        fused_kernel<false><<<132, 384, SM_TOTAL>>>(scp, wo, w1, b1, w2, b2, tx, twqkv, two64, two48, tw1, tw2, txr64, txr48, tout64, tout48);
    }
}
```

```cpp
#include <cuda_runtime.h>
#include <cuda_bf16.h>
#include <cuda.h>
#include <stdint.h>

namespace {

constexpr int D_ = 448;
constexpr float LN_EPS = 1e-5f;
constexpr float LOG2E_SCALE = 0.1889822365046136f * 1.4426950408889634f;

struct Tiles {
    uint32_t o[32 * 57344 / 4];
    uint32_t hn[4 * 32 * 14336 / 4];
    uint32_t u[4 * 28 * 14336 / 4];
};
struct Scratch {
    Tiles tiles[2];
    uint4 halo[128 * 2 * 2 * 3 * 32];
    uint4 stats[32 * 4 * 64];
    uint4 hint_k[128 * 2];
    uint4 hint_o[32 * 32 * 2];
    uint4 hint_h[4 * 32 * 2];
    uint4 hint_u[4 * 32 * 2];
    uint32_t epoch[160];
    uint32_t clean[16];
};
__device__ __align__(1024) Scratch g_scratch;
#define STAMP(i) do {} while (0)
#define FST(i) do {} while (0)
#define TSARG
#define TSVAL

constexpr uint32_t SB = 1024;
constexpr int SM_SLOT = 16384;
__device__ __forceinline__ constexpr uint32_t slot_x(int kb) { return (kb ? 6 + kb : 0) * SM_SLOT; }
__device__ __forceinline__ constexpr uint32_t slot_kv(int kb) { return (kb < 5 ? 2 + kb : 6 - kb) * SM_SLOT; }
__device__ __forceinline__ constexpr uint32_t slot_wo(int kb) { return (kb < 6 ? 2 + kb : 12) * SM_SLOT; }
constexpr int SM_QO = 8 * SM_SLOT;
constexpr int SM_HALOK = SM_QO + 57344, SM_HALOV = 1 * SM_SLOT;
constexpr int NA_SLOTS = 6, NB_SLOTS = 8;
constexpr int SM_ARING = 0;
constexpr int SM_BRING = NA_SLOTS * 16384;
constexpr int SM_H = 212992;
constexpr int SM_TAG = SM_H + 8192 + 96;
constexpr int SM_HALOKIN = 229376;
constexpr int SM_BAR = 231424;
constexpr int SM_TOTAL = 232448;
constexpr int B_FULLX = 0;
constexpr int B_FULLKV = 7;
constexpr int B_FQ = 14;
constexpr int B_DONE1 = 16;
constexpr int B_DONEX = 23;
constexpr int B_DONEQ = 24;
constexpr int B_DONEO = 25;
constexpr int B_FULLO = 29;
constexpr int B_FULLWO = 33;
constexpr int B_END = 34;
constexpr int B_HALO = 35;
constexpr int B_FULLA = 39;
constexpr int B_FULLB = 55;
constexpr int B_DONE = 87;
constexpr int B_RAW = 119;
constexpr int B_CLR = 127;

constexpr long long WD_CLKS = 2000000000ll;

template<int N> struct Int { static constexpr int value = N; };
template<int A, int B, class F> __device__ __forceinline__ void static_for(F&& f) { if constexpr (A < B) { f(Int<A>()); static_for<A + 1, B>(f); } }

__device__ __forceinline__ uint32_t smem_u32(const void* p) { return (uint32_t)__cvta_generic_to_shared(p); }
__device__ __forceinline__ void mbar_init(uint32_t bar, uint32_t cnt) { asm volatile("mbarrier.init.shared::cta.b64 [%0], %1;" :: "r"(bar), "r"(cnt) : "memory"); }
__device__ __forceinline__ void mbar_expect(uint32_t bar, uint32_t bytes) { asm volatile("mbarrier.arrive.expect_tx.shared::cta.b64 _, [%0], %1;" :: "r"(bar), "r"(bytes) : "memory"); }
__device__ __forceinline__ void mbar_arrive(uint32_t bar) { asm volatile("mbarrier.arrive.shared::cta.b64 _, [%0];" :: "r"(bar) : "memory"); }
__device__ __forceinline__ bool mbar_try(uint32_t bar, uint32_t parity) {
    uint32_t ok;
    asm volatile("{\n.reg .pred p;\nmbarrier.try_wait.parity.shared::cta.b64 p, [%1], %2;\nselp.u32 %0, 1, 0, p;\n}" : "=r"(ok) : "r"(bar), "r"(parity) : "memory");
    return ok;
}
__device__ __forceinline__ bool mbar_test(uint32_t bar, uint32_t parity) {
    uint32_t ok;
    asm volatile("{\n.reg .pred p;\nmbarrier.test_wait.parity.shared::cta.b64 p, [%1], %2;\nselp.u32 %0, 1, 0, p;\n}" : "=r"(ok) : "r"(bar), "r"(parity) : "memory");
    return ok;
}
__device__ __forceinline__ void mbar_wait(uint32_t bar, uint32_t parity) {
    asm volatile("{\n.reg .pred p;\n"
                 "WAIT_LOOP:\n"
                 "mbarrier.try_wait.parity.shared::cta.b64 p, [%0], %1;\n"
                 "@!p bra WAIT_LOOP;\n}" :: "r"(bar), "r"(parity) : "memory");
}
__device__ __forceinline__ void mbar_wait_wd(uint32_t bar, uint32_t parity) {
    const long long t0 = clock64();
    while (!mbar_try(bar, parity)) { if (clock64() - t0 > WD_CLKS) __trap(); }
}
__device__ __forceinline__ bool elect() { uint32_t p; asm volatile("{\n.reg .pred P;\nelect.sync _|P, 0xffffffff;\nselp.u32 %0, 1, 0, P;\n}" : "=r"(p)); return p; }
__device__ __forceinline__ void tma2d(uint32_t dst, const CUtensorMap* tm, int c0, int c1, uint32_t bar) {
    asm volatile("cp.async.bulk.tensor.2d.shared::cluster.global.mbarrier::complete_tx::bytes [%0], [%1, {%3, %4}], [%2];" :: "r"(dst), "l"(tm), "r"(bar), "r"(c0), "r"(c1) : "memory");
}
__device__ __forceinline__ void tma3d(uint32_t dst, const CUtensorMap* tm, int c0, int c1, int c2, uint32_t bar) {
    asm volatile("cp.async.bulk.tensor.3d.shared::cluster.global.mbarrier::complete_tx::bytes [%0], [%1, {%3, %4, %5}], [%2];" :: "r"(dst), "l"(tm), "r"(bar), "r"(c0), "r"(c1), "r"(c2) : "memory");
}
__device__ __forceinline__ void tma2d_store(const CUtensorMap* tm, int c0, int c1, uint32_t src) {
    asm volatile("cp.async.bulk.tensor.2d.global.shared::cta.bulk_group [%0, {%2, %3}], [%1];" :: "l"(tm), "r"(src), "r"(c0), "r"(c1) : "memory");
}
__device__ __forceinline__ void bulk_ld(uint32_t dst, const void* src, uint32_t bytes, uint32_t bar) {
    asm volatile("cp.async.bulk.shared::cluster.global.mbarrier::complete_tx::bytes [%0], [%1], %2, [%3];" :: "r"(dst), "l"(src), "r"(bytes), "r"(bar) : "memory");
}
__device__ __forceinline__ void bulk_prefetch(const void* src, uint32_t bytes) { asm volatile("cp.async.bulk.prefetch.L2.global [%0], %1;" :: "l"(src), "r"(bytes) : "memory"); }
__device__ __forceinline__ void prefetch_map(const CUtensorMap* tm) { asm volatile("prefetch.tensormap [%0];" :: "l"(tm) : "memory"); }
__device__ __forceinline__ void st_global_if(uint32_t c, uint32_t* p, uint32_t v) {
    asm volatile("{\n.reg .pred p;\nsetp.ne.u32 p, %2, 0;\n@p st.global.u32 [%0], %1;\n}" :: "l"(p), "r"(v), "r"(c) : "memory");
}
__device__ __forceinline__ void pin4(uint32_t never, float a, float b, float c, float d) {
    asm volatile("{\n.reg .pred p;\nsetp.ne.u32 p, %4, 0;\n@p st.shared.v4.f32 [%4], {%0,%1,%2,%3};\n}" :: "f"(a), "f"(b), "f"(c), "f"(d), "r"(never) : "memory");
}
__device__ __forceinline__ void fence_async_smem() { asm volatile("fence.proxy.async.shared::cta;" ::: "memory"); }
__device__ __forceinline__ uint32_t ld_acquire(const void* p) { uint32_t v; asm volatile("ld.acquire.gpu.global.u32 %0, [%1];" : "=r"(v) : "l"(p) : "memory"); return v; }
__device__ __forceinline__ void st_release(void* p, uint32_t v) { asm volatile("st.release.gpu.global.u32 [%0], %1;" :: "l"(p), "r"(v) : "memory"); }
__device__ __forceinline__ uint32_t ld_relaxed(const void* p) { uint32_t v; asm volatile("ld.relaxed.gpu.global.u32 %0, [%1];" : "=r"(v) : "l"(p) : "memory"); return v; }
__device__ __forceinline__ uint2 ld_relaxed2(const void* p) {
    uint2 v; asm volatile("{\n.reg .b64 a;\nld.relaxed.gpu.global.b64 a, [%2];\nmov.b64 {%0, %1}, a;\n}" : "=r"(v.x), "=r"(v.y) : "l"(p) : "memory"); return v;
}
__device__ __forceinline__ uint4 ld_relaxed4(const uint4* p) {
    uint4 v;
    asm volatile("{\n.reg .b128 t;\n.reg .b64 a, b;\nld.relaxed.gpu.global.b128 t, [%4];\nmov.b128 {a, b}, t;\nmov.b64 {%0, %1}, a;\nmov.b64 {%2, %3}, b;\n}" : "=r"(v.x), "=r"(v.y), "=r"(v.z), "=r"(v.w) : "l"(p) : "memory");
    return v;
}
__device__ __forceinline__ void st_relaxed4(uint4* p, uint32_t a, uint32_t b, uint32_t c, uint32_t d) {
    asm volatile("{\n.reg .b128 t;\n.reg .b64 a, b;\nmov.b64 a, {%1, %2};\nmov.b64 b, {%3, %4};\nmov.b128 t, {a, b};\nst.relaxed.gpu.global.b128 [%0], t;\n}" :: "l"(p), "r"(a), "r"(b), "r"(c), "r"(d) : "memory");
}
__device__ __forceinline__ uint32_t ld_u16(const unsigned short* p) { uint32_t v; asm volatile("ld.volatile.global.u16 %0, [%1];" : "=r"(v) : "l"(p) : "memory"); return v; }
__device__ __forceinline__ uint32_t ld_volatile(const uint32_t* p) { uint32_t v; asm volatile("ld.volatile.global.u32 %0, [%1];" : "=r"(v) : "l"(p) : "memory"); return v; }
__device__ __forceinline__ void named_arrive(int id, int n) { asm volatile("bar.arrive %0, %1;" :: "r"(id), "r"(n) : "memory"); }
__device__ __forceinline__ void named_sync(int id, int n) { asm volatile("bar.sync %0, %1;" :: "r"(id), "r"(n) : "memory"); }
__device__ __forceinline__ void wg_fence() { asm volatile("wgmma.fence.sync.aligned;" ::: "memory"); }
__device__ __forceinline__ void wg_commit() { asm volatile("wgmma.commit_group.sync.aligned;" ::: "memory"); }
template<int N> __device__ __forceinline__ void wg_wait() { asm volatile("wgmma.wait_group.sync.aligned %0;" :: "n"(N) : "memory"); }
template<int N> __device__ __forceinline__ void reg_fence(float (&d)[N]) {
    #pragma unroll
    for (int i = 0; i < N; i++) asm volatile("" : "+f"(d[i]) :: "memory");
}
__device__ __forceinline__ constexpr uint64_t mkdesc(uint32_t addr, uint32_t lbo, uint32_t sbo, uint32_t sw) {
    return (uint64_t)((addr & 0x3FFFF) >> 4) | ((uint64_t)(lbo >> 4) << 16) | ((uint64_t)(sbo >> 4) << 32) | ((uint64_t)sw << 62);
}
__device__ __forceinline__ void ldsm4(uint32_t (&r)[4], uint32_t addr) {
    asm volatile("ldmatrix.sync.aligned.m8n8.x4.shared.b16 {%0,%1,%2,%3}, [%4];" : "=r"(r[0]), "=r"(r[1]), "=r"(r[2]), "=r"(r[3]) : "r"(addr) : "memory");
}
__device__ __forceinline__ void stsm4_if(uint32_t c, uint32_t addr, uint32_t r0, uint32_t r1, uint32_t r2, uint32_t r3) {
    asm volatile("{\n.reg .pred p;\nsetp.ne.u32 p, %5, 0;\n@p stmatrix.sync.aligned.m8n8.x4.shared.b16 [%0], {%1,%2,%3,%4};\n}" :: "r"(addr), "r"(r0), "r"(r1), "r"(r2), "r"(r3), "r"(c) : "memory");
}
__device__ __forceinline__ void sts4(uint32_t a, uint32_t x, uint32_t y, uint32_t z, uint32_t w) { asm volatile("st.shared.v4.u32 [%0], {%1,%2,%3,%4};" :: "r"(a), "r"(x), "r"(y), "r"(z), "r"(w) : "memory"); }
__device__ __forceinline__ uint4 lds4(uint32_t a) { uint4 v; asm volatile("ld.shared.v4.u32 {%0,%1,%2,%3}, [%4];" : "=r"(v.x), "=r"(v.y), "=r"(v.z), "=r"(v.w) : "r"(a) : "memory"); return v; }
__device__ __forceinline__ uint32_t movtrans(uint32_t a) { uint32_t d; asm volatile("movmatrix.sync.aligned.m8n8.trans.b16 %0, %1;" : "=r"(d) : "r"(a)); return d; }
__device__ __forceinline__ uint32_t pack_bf16(float lo, float hi) { uint32_t r; asm("cvt.rn.bf16x2.f32 %0, %1, %2;" : "=r"(r) : "f"(hi), "f"(lo)); return r; }
__device__ __forceinline__ void sub_bf16x2(uint32_t& a, uint32_t b) { asm volatile("sub.rn.bf16x2 %0, %0, %1;" : "+r"(a) : "r"(b)); }
__device__ __forceinline__ float bf_lo(uint32_t v) { return __uint_as_float(v << 16); }
__device__ __forceinline__ float bf_hi(uint32_t v) { return __uint_as_float(v & 0xffff0000u); }
__device__ __forceinline__ void mma16816(float (&c)[4], uint32_t a0, uint32_t a1, uint32_t a2, uint32_t a3, uint32_t b0, uint32_t b1) {
    asm volatile("mma.sync.aligned.m16n8k16.row.col.f32.bf16.bf16.f32 {%0,%1,%2,%3}, {%4,%5,%6,%7}, {%8,%9}, {%0,%1,%2,%3};"
        : "+f"(c[0]), "+f"(c[1]), "+f"(c[2]), "+f"(c[3]) : "r"(a0), "r"(a1), "r"(a2), "r"(a3), "r"(b0), "r"(b1));
}
__device__ __forceinline__ void mma1688(float (&c)[4], uint32_t a0, uint32_t a1, uint32_t b0) {
    asm volatile("mma.sync.aligned.m16n8k8.row.col.f32.bf16.bf16.f32 {%0,%1,%2,%3}, {%4,%5}, {%6}, {%0,%1,%2,%3};"
        : "+f"(c[0]), "+f"(c[1]), "+f"(c[2]), "+f"(c[3]) : "r"(a0), "r"(a1), "r"(b0));
}
__device__ __forceinline__ float quad_sum(float v) { v += __shfl_xor_sync(0xffffffffu, v, 1); v += __shfl_xor_sync(0xffffffffu, v, 2); return v; }
__device__ __forceinline__ float quad_max(float v) { v = fmaxf(v, __shfl_xor_sync(0xffffffffu, v, 1)); v = fmaxf(v, __shfl_xor_sync(0xffffffffu, v, 2)); return v; }
__device__ __forceinline__ float ex2(float x) { float y; asm("ex2.approx.ftz.f32 %0, %1;" : "=f"(y) : "f"(x)); return y; }
__device__ __forceinline__ float rsqrt_approx(float x) { float y; asm("rsqrt.approx.ftz.f32 %0, %1;" : "=f"(y) : "f"(x)); return y; }
__device__ __forceinline__ float rcp_approx(float x) { float y; asm("rcp.approx.ftz.f32 %0, %1;" : "=f"(y) : "f"(x)); return y; }
__device__ __forceinline__ float gelu_half(float hx) {
    const float z = hx * fmaf(hx * hx, 8.f * 0.044715f * 0.7978845608028654f, 2.f * 0.7978845608028654f);
    float t; asm("tanh.approx.f32 %0, %1;" : "=f"(t) : "f"(z));
    return fmaf(hx, t, hx);
}
__device__ __forceinline__ uint32_t gtime32() { uint32_t t; asm volatile("mov.u32 %0, %%globaltimer_lo;" : "=r"(t)); return t; }
__device__ __forceinline__ uint32_t clock32() { uint32_t t; asm volatile("mov.u32 %0, %%clock;" : "=r"(t)); return t; }
#define PF_PACE 400

#define PF_AT 4000
#define NSQ 6
#define HALO_AT 3
#define PF_N 12
#define HINT_U 28
#define SP_AT 2000
#define SP_N 0
#define WO_HOLD 7
#define A_SCHED 0x322188
#define WO_ORD0 0x4321065
#define WO_ORD1 0x3465210
#define XR_HOLD 0
#define ROT 0
#define NPIPE 1
#define CL_AT 4000
#define WARM 1
#define WARM_AT 300
#define W2_AT 23
#define W2_HOLD 5
#define A3_END 20
#define A4_END 16
#define GO_H 608
#define GO_U 928
#define STAG 0
#define GO_O 1216
#define LATE_O 256
#define PP 0
#define DRY2 1
template<int TB> __device__ __forceinline__ void wgmma_rs56(float (&d)[28], const uint32_t (&a)[4], uint64_t db, int sc) {
    asm volatile("{\n.reg .pred p;\nsetp.ne.b32 p, %33, 0;\n"
        "wgmma.mma_async.sync.aligned.m64n56k16.f32.bf16.bf16 {%0, %1, %2, %3, %4, %5, %6, %7, %8, %9, %10, %11, %12, %13, %14, %15, %16, %17, %18, %19, %20, %21, %22, %23, %24, %25, %26, %27}, {%28, %29, %30, %31}, %32, p, 1, 1, %34;\n}\n"
        : "+f"(d[0]), "+f"(d[1]), "+f"(d[2]), "+f"(d[3]), "+f"(d[4]), "+f"(d[5]), "+f"(d[6]), "+f"(d[7]), "+f"(d[8]), "+f"(d[9]), "+f"(d[10]), "+f"(d[11]), "+f"(d[12]), "+f"(d[13]), "+f"(d[14]), "+f"(d[15]), "+f"(d[16]), "+f"(d[17]), "+f"(d[18]), "+f"(d[19]), "+f"(d[20]), "+f"(d[21]), "+f"(d[22]), "+f"(d[23]), "+f"(d[24]), "+f"(d[25]), "+f"(d[26]), "+f"(d[27])
        : "r"(a[0]), "r"(a[1]), "r"(a[2]), "r"(a[3]), "l"(db), "r"(sc), "n"(TB));
}

template<int TA, int TB, int SC = 1> __device__ __forceinline__ void wgmma_ss112(float (&d)[56], uint64_t da, uint64_t db) {
    asm volatile("wgmma.mma_async.sync.aligned.m64n112k16.f32.bf16.bf16 {%0, %1, %2, %3, %4, %5, %6, %7, %8, %9, %10, %11, %12, %13, %14, %15, %16, %17, %18, %19, %20, %21, %22, %23, %24, %25, %26, %27, %28, %29, %30, %31, %32, %33, %34, %35, %36, %37, %38, %39, %40, %41, %42, %43, %44, %45, %46, %47, %48, %49, %50, %51, %52, %53, %54, %55}, %56, %57, %60, 1, 1, %58, %59;\n"
        : "+f"(d[0]), "+f"(d[1]), "+f"(d[2]), "+f"(d[3]), "+f"(d[4]), "+f"(d[5]), "+f"(d[6]), "+f"(d[7]), "+f"(d[8]), "+f"(d[9]), "+f"(d[10]), "+f"(d[11]), "+f"(d[12]), "+f"(d[13]), "+f"(d[14]), "+f"(d[15]), "+f"(d[16]), "+f"(d[17]), "+f"(d[18]), "+f"(d[19]), "+f"(d[20]), "+f"(d[21]), "+f"(d[22]), "+f"(d[23]), "+f"(d[24]), "+f"(d[25]), "+f"(d[26]), "+f"(d[27]), "+f"(d[28]), "+f"(d[29]), "+f"(d[30]), "+f"(d[31]), "+f"(d[32]), "+f"(d[33]), "+f"(d[34]), "+f"(d[35]), "+f"(d[36]), "+f"(d[37]), "+f"(d[38]), "+f"(d[39]), "+f"(d[40]), "+f"(d[41]), "+f"(d[42]), "+f"(d[43]), "+f"(d[44]), "+f"(d[45]), "+f"(d[46]), "+f"(d[47]), "+f"(d[48]), "+f"(d[49]), "+f"(d[50]), "+f"(d[51]), "+f"(d[52]), "+f"(d[53]), "+f"(d[54]), "+f"(d[55])
        : "l"(da), "l"(db), "n"(TA), "n"(TB), "n"(SC));
}

template<int TA, int TB, int SC = 1> __device__ __forceinline__ void wgmma_ss64(float (&d)[32], uint64_t da, uint64_t db) {
    asm volatile("wgmma.mma_async.sync.aligned.m64n64k16.f32.bf16.bf16 {%0, %1, %2, %3, %4, %5, %6, %7, %8, %9, %10, %11, %12, %13, %14, %15, %16, %17, %18, %19, %20, %21, %22, %23, %24, %25, %26, %27, %28, %29, %30, %31}, %32, %33, %36, 1, 1, %34, %35;\n"
        : "+f"(d[0]), "+f"(d[1]), "+f"(d[2]), "+f"(d[3]), "+f"(d[4]), "+f"(d[5]), "+f"(d[6]), "+f"(d[7]), "+f"(d[8]), "+f"(d[9]), "+f"(d[10]), "+f"(d[11]), "+f"(d[12]), "+f"(d[13]), "+f"(d[14]), "+f"(d[15]), "+f"(d[16]), "+f"(d[17]), "+f"(d[18]), "+f"(d[19]), "+f"(d[20]), "+f"(d[21]), "+f"(d[22]), "+f"(d[23]), "+f"(d[24]), "+f"(d[25]), "+f"(d[26]), "+f"(d[27]), "+f"(d[28]), "+f"(d[29]), "+f"(d[30]), "+f"(d[31])
        : "l"(da), "l"(db), "n"(TA), "n"(TB), "n"(SC));
}

template<int TA, int TB, int SC = 1> __device__ __forceinline__ void wgmma_ss48(float (&d)[24], uint64_t da, uint64_t db) {
    asm volatile("wgmma.mma_async.sync.aligned.m64n48k16.f32.bf16.bf16 {%0, %1, %2, %3, %4, %5, %6, %7, %8, %9, %10, %11, %12, %13, %14, %15, %16, %17, %18, %19, %20, %21, %22, %23}, %24, %25, %28, 1, 1, %26, %27;\n"
        : "+f"(d[0]), "+f"(d[1]), "+f"(d[2]), "+f"(d[3]), "+f"(d[4]), "+f"(d[5]), "+f"(d[6]), "+f"(d[7]), "+f"(d[8]), "+f"(d[9]), "+f"(d[10]), "+f"(d[11]), "+f"(d[12]), "+f"(d[13]), "+f"(d[14]), "+f"(d[15]), "+f"(d[16]), "+f"(d[17]), "+f"(d[18]), "+f"(d[19]), "+f"(d[20]), "+f"(d[21]), "+f"(d[22]), "+f"(d[23])
        : "l"(da), "l"(db), "n"(TA), "n"(TB), "n"(SC));
}

template<int NKB, bool PERM>
__device__ __forceinline__ void mix_mainloop(TSARG float (&acc)[56], uint32_t par, bool leader) {
    constexpr uint32_t sb = SB, bars = sb + SM_BAR;
    constexpr int A0 = PERM ? 0 : 16 % NA_SLOTS;
    auto aoff = [](int jj, int s) { return (PERM ? (s & 1) * 8192 + (jj * 32 + (s >> 1) * 16) * 128 : jj * 8192 + s * 2048) >> 4; };
    int bslot = 0, aslot = A0;
    reg_fence(acc);
    #pragma unroll 1
    for (int i = 0; i < NKB / 2; i++) {
        mbar_wait(bars + 8 * (B_FULLA + i), par);
        const uint64_t adesc = mkdesc(sb + SM_ARING, 8192, 1024, 1) + (uint32_t)(aslot * 1024);
        aslot = aslot == NA_SLOTS - 1 ? 0 : aslot + 1;
        #pragma unroll
        for (int jj = 0; jj < 2; jj++) {
            const int j = 2 * i + jj;
            mbar_wait(bars + 8 * (B_FULLB + j), par);
            const uint64_t bdesc = mkdesc(sb + SM_BRING, 1792, 128, 0) + (uint32_t)(bslot * 896);
            bslot = bslot == NB_SLOTS - 1 ? 0 : bslot + 1;
            wg_fence();
            #pragma unroll
            for (int s = 0; s < 4; s++) wgmma_ss112<1, 1>(acc, adesc + aoff(jj, s), bdesc + s * 224);
            wg_commit();
            wg_wait<1>();
            if (j > 0 && leader) mbar_arrive(bars + 8 * (B_DONE + j - 1));
        }
    }
    wg_wait<0>();
    reg_fence(acc);
    if (leader) mbar_arrive(bars + 8 * (B_DONE + NKB - 1));
}

constexpr uint32_t EMPTY = 0xFFFFFFFFu;
__device__ __forceinline__ void post_hint(uint4* p, uint32_t ep, int lane) { if (lane < 2) st_relaxed4(p + lane, ep, ep, ep, ep); }
__device__ __forceinline__ void post_hint_wg(int id, uint4* p, uint32_t ep, int w, int lane) {
    if (w < 3) named_arrive(id, 128);
    else { named_sync(id, 128); const uint32_t now = gtime32(); if (lane < 2) st_relaxed4(p + lane, ep, now, ep, now); }
}

__device__ __forceinline__ void wait_hints(TSARG const uint4* hint, uint32_t ep, uint32_t delay, int st) {
    uint2 v;
    do { v = ld_relaxed2(hint); } while (!__all_sync(0xffffffffu, v.x == ep));
    const uint32_t t1 = gtime32(), age = __reduce_min_sync(0xffffffffu, t1 + 256 - v.y);
    if (elect()) STAMP(st);
    while (gtime32() - t1 + age < delay + 256) {}
    __syncwarp();
}

template<int NKB>
__device__ __forceinline__ void mix_producer_b(TSARG uint32_t par, const uint4* hints, uint32_t ep, const uint32_t* src, int lane) {
    constexpr uint32_t sb = SB, bars = sb + SM_BAR;
    wait_hints(TSVAL hints + (lane >> 3) * 64 + (lane & 7) * 2, ep, NKB == 32 ? GO_H : GO_U, NKB == 32 ? 42 : 43);
    if (par) mbar_wait(bars + 8 * (B_DONE + 31), 0);
    #pragma unroll 1
    for (int j = 0; j < NKB; j++) {
        if (j >= NB_SLOTS) mbar_wait(bars + 8 * (B_DONE + j - NB_SLOTS), par);
        if (j == 0 && lane == 0) STAMP(NKB == 32 ? 29 : 30);
        if (j == 7 && lane == 0) STAMP(NKB == 32 ? 35 : 36);
        if (elect()) {
            mbar_expect(bars + 8 * (B_RAW + (j & 7)), 14336);
            bulk_ld(sb + SM_BRING + (j & 7) * 14336, src + j * 3584, 14336, bars + 8 * (B_RAW + (j & 7)));
        }
    }
}
__device__ __forceinline__ void check_tiles(TSARG int n, int w, int lane, uint32_t& ph, uint32_t dst, const uint32_t* src, int full) {
    constexpr uint32_t bars = SB + SM_BAR;
    #pragma unroll 1
    for (int j = w; j < n; j += 4) {
        const uint32_t raw = bars + 8 * (B_RAW + (j & 7)), d = dst + (j & 7) * 14336, a = d + lane * 128 + (lane & 3) * 32 + (lane >> 2) * 4;
        bool bad;
        do {
            mbar_wait(raw, (ph >> (j & 4)) & 1);
            ph ^= 1u << (j & 4);
            if (j == 0 && lane == 0) STAMP(n == 4 ? 6 : n == 32 ? 31 : 32);
            uint32_t v0, v1, v2, v3;
            asm volatile("ld.shared.u32 %0, [%4];\nld.shared.u32 %1, [%4+4096];\nld.shared.u32 %2, [%4+8192];\nld.shared.u32 %3, [%4+10240];"
                         : "=r"(v0), "=r"(v1), "=r"(v2), "=r"(v3) : "r"(a) : "memory");
            bad = __any_sync(0xffffffffu, max(max(v0, v1), max(v2, v3)) == EMPTY);
            if (elect() && bad) {
                mbar_expect(raw, 14336); bulk_ld(d, src + j * 3584, 14336, raw);
            }
        } while (bad);
        if (lane == 0) mbar_arrive(bars + 8 * (full + j));
    }
}

__device__ __forceinline__ uint32_t hcol(uint32_t a, int jp) { return (a ^ ((jp & 3) << 5)) + (jp >> 2) * 8192; }

__device__ __forceinline__ uint32_t get_tag() {
    mbar_wait(SB + SM_BAR + 8 * B_CLR, 0);
    uint32_t v; asm volatile("ld.shared.u32 %0, [%1];" : "=r"(v) : "r"(SB + SM_TAG) : "memory"); return v;
}

template<bool USE_SMID>
__global__ void __launch_bounds__(384, 1)
fused_kernel(Scratch* __restrict__ sc, const __nv_bfloat16* __restrict__ wo,
             const __nv_bfloat16* __restrict__ w1, const __nv_bfloat16* __restrict__ b1,
             const __nv_bfloat16* __restrict__ w2, const __nv_bfloat16* __restrict__ b2,
             const __grid_constant__ CUtensorMap tm_x, const __grid_constant__ CUtensorMap tm_wqkv,
             const __grid_constant__ CUtensorMap tm_wo64, const __grid_constant__ CUtensorMap tm_wo48,
             const __grid_constant__ CUtensorMap tm_w1, const __grid_constant__ CUtensorMap tm_w2,
             const __grid_constant__ CUtensorMap tm_xr64, const __grid_constant__ CUtensorMap tm_xr48,
             const __grid_constant__ CUtensorMap tm_out64, const __grid_constant__ CUtensorMap tm_out48) {
    extern __shared__ __align__(1024) uint8_t smem_raw[];
    constexpr uint32_t sb = SB;
    constexpr uint32_t bars = sb + SM_BAR;
    const int tid = threadIdx.x, lane = tid & 31;
    const int warp = __shfl_sync(0xffffffffu, tid >> 5, 0);
    int slot;
    if (USE_SMID) {
        asm("{\n.reg .u32 s, t, u, d, a, b, c;\n.reg .pred p, r;\n"
            "mov.u32 s, %%smid;\nshr.u32 t, s, 1;\nsub.u32 u, t, 32;\nmul.lo.u32 d, u, 37;\nshr.u32 d, d, 8;\n"
            "and.b32 a, t, 7;\nshl.b32 a, a, 3;\nshr.u32 c, t, 3;\nadd.u32 a, a, c;\n"
            "mad.lo.u32 b, d, -55, 12;\nshl.b32 c, u, 3;\nadd.u32 b, b, c;\n"
            "setp.lt.u32 p, t, 32;\nselp.u32 a, a, b, p;\n"
            "setp.lt.u32 r, t, 62;\nselp.s32 c, 4, -58, r;\nadd.u32 c, t, c;\nsetp.lt.u32 p, t, 60;\nselp.u32 a, a, c, p;\n"
            "and.b32 s, s, 1;\nshl.b32 a, a, 1;\nadd.u32 %0, a, s;\n}" : "=r"(slot));
    } else slot = blockIdx.x;
    const int G = slot >> 4, mi = slot & 15;
    const int tb = 4 * (G >> 1) + (mi >> 2), hp = 2 * (mi & 3) + (G & 1);
    const int wcol = (hp * 56) & ~15;
    if (slot >= 128) {
        if (tid == 0) {
            const uint32_t ep = ld_volatile(&sc->epoch[slot]) + 1;
            const long long t0 = clock64();
            while (clock64() - t0 < SP_AT) {}
            #pragma unroll 1
            for (int i = 0; i < 7; i++) bulk_prefetch((const char*)wo + (i * 4 + mi) * 14336, 14336);
            #pragma unroll 1
            for (int i = 0; i < SP_N; i++) bulk_prefetch((const char*)w1 + (i * 4 + mi) * 14336, 14336);
            while (ld_relaxed(sc->hint_u) != ep) { __nanosleep(500); if (clock64() - t0 > WD_CLKS) __trap(); }
            sc->epoch[slot] = ep;
        }
        return;
    }
    const int q = mi & 3, tt2 = 4 * G + (mi >> 2), ft = 4 * (G - 1) + (mi >> 2);
    const bool has_b1 = G > 0;
    const int c64 = 64 * q, c48 = 256 + 48 * q;

    if (warp < 8) {
        if (WARM) {
            const int w = warp & 3, wg = warp >> 2, g = lane >> 2, t = lane & 3;
            if (WARM_AT) { const uint32_t t0 = clock32(); while (clock32() - t0 < WARM_AT) {} __syncwarp(); }
            if (w > 0) post_hint(sc->hint_o + ((2 * tb + (w >> 1)) * 32 + hp * 4 + (w & 1) * 2 + wg) * 2, 0, lane);
            if (wg == 0) {
                if (t < 2) st_relaxed4(sc->stats + tt2 * 256 + q * 64 + 16 * w + g + 8 * t, 0, 0, 0, 0);
                if (w == 3) post_hint(sc->hint_h + (q * 32 + tt2) * 2, 0, lane);
            }
        }
        named_sync(0, 384);
        asm volatile("setmaxnreg.inc.sync.aligned.u32 224;");
        int tid; asm volatile("mov.u32 %0, %%tid.x;" : "=r"(tid));
        const int lane = tid & 31, warp = __shfl_sync(0xffffffffu, tid >> 5, 0), wg = warp >> 2;
        uint32_t ep;
        Tiles* tl;
        const int w = warp & 3, g = lane >> 2, t = lane & 3;
        const bool leader = (tid & 127) == 0;
        const uint32_t never = gridDim.y - 1;
        {
            uint32_t a[28][4];
            float accK[28], accV[28], accQ[28];
            const int lrow = 16 * w + (lane & 7) + (lane & 8);
            const uint32_t lbase = sb + wg * 8192 + lrow * 128;
            const uint32_t lx = (lane >> 4) ^ (lane & 7);
            const uint32_t wofs = hp & 1;
            auto pin2 = [&](uint32_t x0, uint32_t x1) {
                asm volatile("{\n.reg .pred p;\nsetp.ne.u32 p, %2, 0;\n@p st.shared.v2.b32 [%0], {%0,%1};\n}" :: "r"(x0), "r"(x1), "r"(never) : "memory");
            };
            float cS[2][4] = {}, cA[2][4] = {}, cB[2][4] = {}, q0, q1, p0, p1;
            auto sq = [&](float& acc, uint32_t v) { const float lo = bf_lo(v), hi = bf_hi(v); acc = fmaf(hi, hi, fmaf(lo, lo, acc)); };
            #pragma unroll
            for (int kb = 0; kb < 8; kb++) {
                if (kb < 7) {
                    mbar_wait(bars + 8 * (B_FULLX + kb), 0);
                    if (kb == 0 && tid == 0) STAMP(0);
                    if (kb == 6 && tid == 0) STAMP(25);
                    if (kb == 0) FST(0); if (kb == 2) FST(1); if (kb == 4) FST(2); if (kb == 6) FST(3);
                    #pragma unroll
                    for (int s = 4 * kb; s < 4 * kb + 4; s++) ldsm4(a[s], lbase + slot_x(kb) + ((lx ^ (2 * (s & 3))) << 4));
                }
                if (kb == NPIPE) continue;
                const int kc = kb < NPIPE ? kb : kb - 1;
                if (kc == NSQ) { p0 = cS[0][0] + cS[1][0]; p1 = cS[0][2] + cS[1][2]; }
                #pragma unroll
                for (int s = 4 * kc; s < 4 * kc + 4; s++) {
                    mma16816(cS[s & 1], a[s][0], a[s][1], a[s][2], a[s][3], 0x3F803F80u, 0x3F803F80u);
                    if (kc < NSQ) {
                        mma1688(cA[0], a[s][0], a[s][1], a[s][0]); mma1688(cA[1], a[s][2], a[s][3], a[s][2]);
                        mma1688(cB[0], a[s][0], a[s][1], a[s][1]); mma1688(cB[1], a[s][2], a[s][3], a[s][3]);
                    }
                }
            }
            const float m0 = (cS[0][0] + cS[1][0]) * (1.f / D_), m1 = (cS[0][2] + cS[1][2]) * (1.f / D_);
            const uint32_t mm0 = pack_bf16(m0, m0), mm1 = pack_bf16(m1, m1);
            if (lane == 0) mbar_arrive(bars + 8 * B_DONEX);
            auto center = [&](int s) { sub_bf16x2(a[s][0], mm0); sub_bf16x2(a[s][1], mm1); sub_bf16x2(a[s][2], mm0); sub_bf16x2(a[s][3], mm1); };
            uint32_t Ka[8], Kb[8], Kc[8], Va[8], Vb[7], Vc[8];
            float r0, r1, ls0, ls1;
            uint32_t pm, zero;
            uint32_t* od;
            uint4* oh;
            auto kpack = [&](uint32_t (&k)[8], int j, int c, float r) {
                const uint32_t v = pack_bf16(accK[4 * j + c] * r, accK[4 * j + c + 1] * r);
                if (j == 3) { k[3] = t < 2 ? v : 0u; k[4] = t < 2 ? 0u : v; } else k[j + (j > 3)] = v;
            };
            auto batch = [&](auto c0, auto c1) {
                constexpr int n0 = c0.value, n1 = c1.value;
                if (PP && n0 < PP) named_sync(10 + wg, 256);
                wg_fence();
                static_for<n0, n1>([&](auto nc) {
                    constexpr int n = nc.value;
                    if (n == 4) { center(4); center(5); center(6); center(7); wg_fence(); }
                    const uint64_t desc = mkdesc(sb + (n < 56 ? slot_kv(n >> 3) + (n & 7) * 2048 : SM_QO + (n - 56) * 2048), 8192, 1024, 1) + wofs;
                    wgmma_rs56<1>(n < 28 ? accK : n < 56 ? accV : accQ, a[n % 28], desc, n % 28 != 0);
                });
                wg_commit();
                if (PP && n0 < PP && (n1 < PP || wg == 0)) named_arrive(11 - wg, 256);
                if (n0 > 0) wg_wait<1>();
            };
            const uint32_t hs = sb + tid * 16 + warp * 512;
            auto hand_over = [&](const uint32_t (&v)[8], int kv) {
                mbar_wait(bars + 8 * (kv ? B_DONE1 + 5 : B_DONEX), 0);
                sts4(hs + (kv ? SM_HALOV : SM_HALOK), v[0], v[1], v[2], v[3]); sts4(hs + (kv ? SM_HALOV : SM_HALOK) + 512, v[4], v[5], v[6], v[7]);
                if (w == 3) named_arrive(6 + kv, 96);
            };
            auto take_over = [&](uint32_t (&v)[8], int kv) {
                if (w == 0) mbar_wait(bars + 8 * (B_HALO + 2 * kv + wg), 0);
                const uint32_t ad = w ? hs + (kv ? SM_HALOV : SM_HALOK) - 1024 : sb + lane * 16 + wg * 1024 + (kv ? SM_HALOV + 8192 : SM_HALOKIN);
                const uint4 u0 = lds4(ad), u1 = lds4(ad + 512);
                v[0] = u0.x; v[1] = u0.y; v[2] = u0.z; v[3] = u0.w; v[4] = u1.x; v[5] = u1.y; v[6] = u1.z; v[7] = u1.w;
            };
            if (PP && wg == 1) { pin2(mm0, mm1); named_arrive(10, 256); }
            center(0); center(1); center(2); center(3);
            static_for<0, 7>([&](auto pc) {
                constexpr int p = pc.value;
                mbar_wait(bars + 8 * (B_FULLKV + p), 0);
                if (p == 0 && tid == 0) STAMP(26);
                if (p == 3 && tid == 0) STAMP(27);
                FST(4 + p);
                batch(Int<8 * p>(), Int<8 * p + 8>());
                if (p > 0 && leader) mbar_arrive(bars + 8 * (B_DONE1 + p - 1));
                #pragma unroll
                for (int s = 8 * p + 8; s < 8 * p + 16 && s < 28; s++) center(s);
                if (p == 1) {
                    const float c0 = bf_hi(mm0), c1 = bf_hi(mm1);
                    q0 = fmaf(c0, fmaf(c0, 64.f * NSQ, -2.f * p0), (g & 1) ? cA[0][1] + cA[1][1] : cA[0][0] + cA[1][0]) - D_ * (m0 - c0) * (m0 - c0);
                    q1 = fmaf(c1, fmaf(c1, 64.f * NSQ, -2.f * p1), (g & 1) ? cB[0][3] + cB[1][3] : cB[0][2] + cB[1][2]) - D_ * (m1 - c1) * (m1 - c1);
                    asm("" : "+f"(q0), "+f"(q1));
                    q0 = t == (g >> 1) ? q0 : 0.f; q1 = t == (g >> 1) ? q1 : 0.f;
                    pin2(__float_as_uint(q0), __float_as_uint(q1));
                }
                constexpr int PK = NSQ < 5 ? 5 : 4, NR = 28 - 4 * NSQ;
                if (p >= 2 && p < PK) {
                    #pragma unroll
                    for (int s = 4 * NSQ + NR * (p - 2) / (PK - 2); s < 4 * NSQ + NR * (p - 1) / (PK - 2); s++) { sq(q0, a[s][0]); sq(q1, a[s][1]); sq(q0, a[s][2]); sq(q1, a[s][3]); }
                    pin2(__float_as_uint(q0), __float_as_uint(q1));
                }
                if (p == PK - 1) { q0 = quad_sum(q0); q1 = quad_sum(q1); }
                if (p == PK) {
                    r0 = rsqrt_approx(fmaxf(q0 * (1.f / D_), 0.f) + LN_EPS); r1 = rsqrt_approx(fmaxf(q1 * (1.f / D_), 0.f) + LN_EPS);
                    reg_fence(accK);
                    #pragma unroll
                    for (int j = 0; j < 7; j++) kpack(Kc, j, 2, r1);
                    hand_over(Kc, 0);
                }
                if (p == PK + 1) {
                    #pragma unroll
                    for (int j = 0; j < 7; j++) kpack(Kb, j, 0, r0);
                    #pragma unroll
                    for (int j = 0; j < 8; j += 2) pin2(Kb[j], Kb[j + 1]);
                    ls0 = LOG2E_SCALE * r0; ls1 = LOG2E_SCALE * r1;
                    pm = (2 * t <= g ? 0xFFFFu : 0u) | (2 * t + 1 <= g ? 0xFFFF0000u : 0u);
                    zero = never; asm volatile("" : "+r"(zero));
                    pin2(__float_as_uint(ls0), __float_as_uint(ls1)); pin2(pm, zero);
                }
                if (p == 2) ep = get_tag();
                if (p == 6) {
                    tl = &sc->tiles[ep & 1];
                    const int tt = 2 * tb + (w >> 1);
                    od = tl->o + tt * 14336 + (7 * hp) * 256 + (2 * (2 * (w & 1) + wg)) * 32 + lane;
                    oh = sc->hint_o + (tt * 32 + hp * 4 + (w & 1) * 2 + wg) * 2 + (lane & 1);
                    pin2((uint32_t)(uint64_t)od, (uint32_t)((uint64_t)od >> 32));
                    pin2((uint32_t)(uint64_t)oh, (uint32_t)((uint64_t)oh >> 32));
                }
            });
            if (tid == 0) STAMP(1);
            FST(11);
            mbar_wait(bars + 8 * B_FQ, 0);
            batch(Int<56>(), Int<60>());
            reg_fence(accV);
            if (leader) mbar_arrive(bars + 8 * (B_DONE1 + 6));
            if (tid == 0) STAMP(2);
            FST(12);
            #pragma unroll
            for (int j = 0; j < 7; j++) Vc[j] = movtrans(pack_bf16(accV[4 * j + 2] * r1, accV[4 * j + 3] * r1));
            Vc[7] = Vc[6];
            hand_over(Vc, 1);
            batch(Int<60>(), Int<66>());
            #pragma unroll
            for (int j = 0; j < 7; j++) {
                Vb[j] = movtrans(pack_bf16(accV[4 * j] * r0, accV[4 * j + 1] * r0));
                Vc[j] |= zero;
            }
            batch(Int<66>(), Int<72>());
            #pragma unroll
            for (int j = 0; j < 7; j++) pin2(Vb[j], Vc[j]);
            mbar_wait(bars + 8 * (B_FQ + 1), 0);
            FST(13);
            if (w > 0 && lane < 2) { const uint32_t now = gtime32(); st_relaxed4(oh, ep, now, ep, now); }
            batch(Int<72>(), Int<84>());
            FST(14);
            named_sync(1 + wg, 128);
            take_over(Ka, 0);
            if (tid == 0) STAMP(3);
            wg_wait<0>();
            reg_fence(accQ);
            if (tid == 0) STAMP(4);
            FST(15);
            const bool first = (tb == 0 && w == 0);
            uint32_t pA[2], pB0[2], pB1[2], pC[2], z0[2], z1[2];
            #pragma unroll
            for (int h = 0; h < 2; h++) {
                float sA[4] = {0.f, 0.f, 0.f, 0.f}, sB[4] = {0.f, 0.f, 0.f, 0.f}, sC[4] = {0.f, 0.f, 0.f, 0.f};
                #pragma unroll
                for (int k = 0; k < 2; k++) {
                    const float* qq = accQ + 12 * h + 8 * k;
                    uint32_t a0 = pack_bf16(qq[0], qq[1]), a1 = pack_bf16(qq[2], qq[3]);
                    if (h == 1 && k == 0) { a0 |= zero; a1 |= zero; }
                    const uint32_t a2 = pack_bf16(qq[4], qq[5]), a3 = pack_bf16(qq[6], qq[7]);
                    mma16816(sB, a0, a1, a2, a3, Kb[4 * h + 2 * k], Kb[4 * h + 2 * k + 1]);
                    mma16816(sA, a0, a1, a2, a3, Ka[4 * h + 2 * k], Ka[4 * h + 2 * k + 1]);
                    mma16816(sC, a0, a1, a2, a3, Kc[4 * h + 2 * k], Kc[4 * h + 2 * k + 1]);
                }
                const bool n0 = pm & 1, n1 = (int)pm < 0;
                const float l00 = n0 ? sB[0] : (first ? -INFINITY : sA[0]), l01 = n1 ? sB[1] : (first ? -INFINITY : sA[1]);
                const float l10 = n0 ? sC[2] : sB[2], l11 = n1 ? sC[3] : sB[3];
                const float x0 = -ls0 * quad_max(fmaxf(l00, l01)), x1 = -ls1 * quad_max(fmaxf(l10, l11));
                const float e00 = ex2(fmaf(l00, ls0, x0)), e01 = ex2(fmaf(l01, ls0, x0)), e10 = ex2(fmaf(l10, ls1, x1)), e11 = ex2(fmaf(l11, ls1, x1));
                const float i0 = rcp_approx(quad_sum(e00 + e01)), i1 = rcp_approx(quad_sum(e10 + e11));
                const uint32_t P0 = pack_bf16(e00 * i0, e01 * i0), P1 = pack_bf16(e10 * i1, e11 * i1);
                pB0[h] = P0 & pm; pA[h] = P0 & ~pm; pC[h] = P1 & pm; pB1[h] = P1 & ~pm; z0[h] = P0 & zero; z1[h] = P1 & zero;
            }
            float o[8][4];
            #pragma unroll
            for (int j = 0; j < 8; j++) {
                o[j][0] = o[j][1] = o[j][2] = o[j][3] = 0.f;
                mma16816(o[j], pB0[j >> 2], pB1[j >> 2], z0[j >> 2], pC[j >> 2], Vb[j - (j >> 2)], Vc[j - (j >> 2)]);
            }
            if (tid == 0) STAMP(12);
            FST(16);
            take_over(Va, 1);
            if (lane == 0) mbar_arrive(bars + 8 * B_DONEQ);
            if (tid == 0) STAMP(16);
            #pragma unroll
            for (int j = 0; j < 8; j++) mma1688(o[j], pA[j >> 2], z1[j >> 2], Va[j - (j >> 2)]);
            #pragma unroll
            for (int j = 0; j < 7; j++) {
                float v[4];
                #pragma unroll
                for (int c = 0; c < 4; c++) v[c] = j < 3 ? o[j][c] : j > 3 ? o[j + 1][c] : (t < 2 ? o[3][c] : o[4][c]);
                od[j * 256] = pack_bf16(v[0], v[1]);
                od[j * 256 + 32] = pack_bf16(v[2], v[3]);
            }
            if (tid == 0) STAMP(5);
            FST(17);
        }
        const uint32_t live = wg ^ 1;
        uint32_t ph = 0, rb10, rb11, rb20, rb21;
        auto undef = [](float (&v)[56]) {
            #pragma unroll
            for (int i = 0; i < 56; i++) asm volatile("" : "=f"(v[i]));
        };
        {
            float acc[56];
            const int hrow = 32 * (w >> 1) + 2 * ((lane & 7) + (lane & 8)) + (w & 1);
            const uint32_t ha = sb + SM_H + hrow * 128 + (((lane >> 4) ^ (hrow & 7)) << 4);
            uint4* sp = sc->stats + tt2 * 256 + 16 * w + g;
            uint32_t* hd = tl->hn + (q * 32 + tt2) * 3584 + (2 * w) * 448 + lane;
            float s0 = 0.f, s1 = 0.f, q0 = 0.f, q1 = 0.f, s2 = 0.f, s3 = 0.f, q2 = 0.f, q3 = 0.f;
            auto sums = [&](int j0, int j1) {
                #pragma unroll
                for (int j = j0; j < j1; j++) {
                    s0 += acc[4 * j]; s2 += acc[4 * j + 1]; q0 = fmaf(acc[4 * j], acc[4 * j], q0); q2 = fmaf(acc[4 * j + 1], acc[4 * j + 1], q2);
                    s1 += acc[4 * j + 2]; s3 += acc[4 * j + 3]; q1 = fmaf(acc[4 * j + 2], acc[4 * j + 2], q1); q3 = fmaf(acc[4 * j + 3], acc[4 * j + 3], q3);
                }
            };
            if (live) {
                mbar_wait(bars + 8 * B_FULLWO, 0);
                #pragma unroll
                for (int jp = 0; jp < 7; jp++) {
                    uint32_t xx[4];
                    ldsm4(xx, hcol(ha, jp));
                    #pragma unroll
                    for (int r = 0; r < 4; r++) { acc[8 * jp + 2 * r] = bf_lo(xx[r]); acc[8 * jp + 2 * r + 1] = bf_hi(xx[r]); }
                }
                reg_fence(acc);
                auto od_ = [&](int s) { return mkdesc(sb + SM_QO + s * 2048, 1024, 128, 0); };
                auto wd_ = [&](int s) { return mkdesc(sb + slot_wo(s >> 2) + (s & 3) * 2048, 8192, 1024, 1); };
                float accl[32], accr[24];
                #pragma unroll
                for (int i = 0; i < 5; i++) {
                    if (i < 4) mbar_wait(bars + 8 * (B_FULLO + i), 0);
                    if (i == 0 && tid == 0) STAMP(7);
                    if (i == 1) {
                        const unsigned short* p1 = (const unsigned short*)b1 + max(ft, 0) * 64 + 16 * w + g;
                        const unsigned short* p2 = (const unsigned short*)b2 + tt2 * 64 + 16 * w + g;
                        rb10 = ld_u16(p1); rb11 = ld_u16(p1 + 8); rb20 = ld_u16(p2); rb21 = ld_u16(p2 + 8);
                    }
                    wg_fence();
                    #pragma unroll
                    for (int ss = 0; ss < 7; ss++) {
                        if (i < 3) wgmma_ss112<0, 1>(acc, od_(7 * i + ss), wd_(7 * i + ss));
                        else if (i == 4) wgmma_ss64<0, 1>(accl, od_(21 + ss), wd_(21 + ss));
                        else if (ss == 0) wgmma_ss48<0, 1, 0>(accr, od_(21), wd_(21) + 512);
                        else wgmma_ss48<0, 1>(accr, od_(21 + ss), wd_(21 + ss) + 512);
                    }
                    wg_commit();
                    if (i > 0) {
                        wg_wait<1>();
                        if (i == 3) {
                            reg_fence(acc);
                            #pragma unroll
                            for (int c = 0; c < 32; c++) accl[c] = __uint_as_float(__float_as_uint(acc[c]) | never);
                            reg_fence(accl);
                        }
                        if (i < 4 && leader) mbar_arrive(bars + 8 * (B_DONEO + i - 1));
                    }
                }
                reg_fence(accr);
                #pragma unroll
                for (int c = 0; c < 24; c++) acc[32 + c] += accr[c];
                sums(8, 14);
                pin4(never, s0, s1, s2, s3); pin4(never, q0, q1, q2, q3);
                wg_wait<0>();
                reg_fence(accl);
                #pragma unroll
                for (int c = 0; c < 32; c++) acc[c] = accl[c];
                if (leader) mbar_arrive(bars + 8 * (B_DONEO + 3));
                if (tid == 0) STAMP(8);
            } else undef(acc);
            if (live || (DRY2 && w == 3)) {
            sums(0, 8);
            s0 = quad_sum(s0 + s2); s1 = quad_sum(s1 + s3); q0 = quad_sum(q0 + q2); q1 = quad_sum(q1 + q3);
            if (t < 2 * live) st_relaxed4(sp + q * 64 + 8 * t, __float_as_uint(t ? s1 : s0), __float_as_uint(t ? q1 : q0), ep, ep);
            if (tid == 0) STAMP(9);
            #pragma unroll
            for (int jp = 0; jp < 7; jp++)
                stsm4_if(live, hcol(ha, jp), pack_bf16(acc[8 * jp], acc[8 * jp + 1]), pack_bf16(acc[8 * jp + 2], acc[8 * jp + 3]),
                      pack_bf16(acc[8 * jp + 4], acc[8 * jp + 5]), pack_bf16(acc[8 * jp + 6], acc[8 * jp + 7]));
            if (live) {
                uint4 v0, v1;
                do {
                    v0 = ld_relaxed4(sp + t * 64); v1 = ld_relaxed4(sp + t * 64 + 8);
                } while (__any_sync(0xffffffffu, t != q && (v0.w != ep || v1.w != ep)));
                if (t != q) { s0 = __uint_as_float(v0.x); q0 = __uint_as_float(v0.y); s1 = __uint_as_float(v1.x); q1 = __uint_as_float(v1.y); }
            }
            if (tid == 0) STAMP(10);
            if (live) post_hint_wg(5, sc->hint_h + (q * 32 + tt2) * 2, ep, w, lane);
            s0 = quad_sum(s0); s1 = quad_sum(s1); q0 = quad_sum(q0); q1 = quad_sum(q1);
            const float m0 = s0 * (1.f / D_), m1 = s1 * (1.f / D_);
            const float v0 = fmaxf(q0 * (1.f / D_) - m0 * m0, 0.f), v1 = fmaxf(q1 * (1.f / D_) - m1 * m1, 0.f);
            const float r0 = rsqrt_approx(fmaf(v0, 4.f + 4.f * LN_EPS, 4.f * LN_EPS * LN_EPS)), r1 = rsqrt_approx(fmaf(v1, 4.f + 4.f * LN_EPS, 4.f * LN_EPS * LN_EPS));
            const float c0 = -m0 * r0, c1 = -m1 * r1;
            #pragma unroll
            for (int j = 0; j < 14; j++) {
                st_global_if(live, hd + j * 32, pack_bf16(fmaf(acc[4 * j], r0, c0), fmaf(acc[4 * j + 1], r0, c0)));
                st_global_if(live, hd + j * 32 + 448, pack_bf16(fmaf(acc[4 * j + 2], r1, c1), fmaf(acc[4 * j + 3], r1, c1)));
            }
            if (tid == 0) STAMP(11);
            if (tid == 96) STAMP(33);
            }
        }
        if (!live) {
            check_tiles(TSVAL 4, w, lane, ph, sb + SM_QO, tl->o + tt2 * 14336, B_FULLO);
            if (has_b1) check_tiles(TSVAL 32, w, lane, ph, sb + SM_BRING, tl->hn + q * 32 * 3584, B_FULLB);
            check_tiles(TSVAL 28, w, lane, ph, sb + SM_BRING, tl->u + q * 28 * 3584, B_FULLB);
            return;
        }
        if (has_b1) {
            float acc[56];
            uint32_t* ud = tl->u + (q * 28 + ft) * 3584 + (2 * w) * 448 + lane;
            #pragma unroll
            for (int j = 0; j < 56; j++) acc[j] = 0.5f * bf_lo((j & 2) ? rb11 : rb10);
            #pragma unroll 1
            for (uint32_t pass = never; pass < 2; pass++) {
                if (pass) {
                    mix_mainloop<32, true>(TSVAL acc, 0, leader);
                    if (tid == 0) STAMP(14);
                }
                #pragma unroll
                for (int j = 0; j < 14; j++) {
                    st_global_if(pass, ud + j * 32, pack_bf16(gelu_half(acc[4 * j]), gelu_half(acc[4 * j + 1])));
                    st_global_if(pass, ud + j * 32 + 448, pack_bf16(gelu_half(acc[4 * j + 2]), gelu_half(acc[4 * j + 3])));
                }
            }
            if (tid == 0) STAMP(15);
        }
        {
            float acc[56];
            const uint32_t ad = sb + SM_H + (16 * w + (lane & 15)) * 128 + (((lane >> 4) ^ (lane & 7)) << 4);
            const float bb0 = bf_lo(rb20), bb1 = bf_lo(rb21);
            named_sync(1, 128);
            #pragma unroll
            for (int jp = 0; jp < 7; jp++) {
                uint32_t hh[4];
                ldsm4(hh, hcol(ad, jp));
                #pragma unroll
                for (int r = 0; r < 4; r++) { acc[8 * jp + 2 * r] = bf_lo(hh[r]) + ((r & 1) ? bb1 : bb0); acc[8 * jp + 2 * r + 1] = bf_hi(hh[r]) + ((r & 1) ? bb1 : bb0); }
            }
            #pragma unroll 1
            for (uint32_t pass = never; pass < 2; pass++) {
                if (pass) {
                    mix_mainloop<28, false>(TSVAL acc, has_b1, leader);
                    if (leader) mbar_arrive(bars + 8 * B_END);
                    if (tid == 0) STAMP(18);
                }
                #pragma unroll
                for (int jp = 0; jp < 7; jp++)
                    stsm4_if(1, hcol(ad, jp), pack_bf16(acc[8 * jp], acc[8 * jp + 1]), pack_bf16(acc[8 * jp + 2], acc[8 * jp + 3]),
                             pack_bf16(acc[8 * jp + 4], acc[8 * jp + 5]), pack_bf16(acc[8 * jp + 6], acc[8 * jp + 7]));
                fence_async_smem();
                __syncwarp();
            }
            if (elect()) {
                tma2d_store(&tm_out64, c64, tt2 * 64 + 16 * w, sb + SM_H + w * 2048);
                tma2d_store(&tm_out48, c48, tt2 * 64 + 16 * w, sb + SM_H + 8192 + w * 2048);
            }
            asm volatile("cp.async.bulk.commit_group;" ::: "memory");
            asm volatile("cp.async.bulk.wait_group.read 0;" ::: "memory");
            if (tid == 0) { sc->epoch[slot] = ep; STAMP(19); }
        }
    } else {
        asm volatile("setmaxnreg.dec.sync.aligned.u32 56;");
        int warp2; asm("mov.u32 %0, %1;" : "=r"(warp2) : "r"(warp));
        if (warp2 > 8) {
            uint32_t ep, cl;
            uint4* const oh = sc->hint_o + (2 * tb * 32 + hp * 4) * 2 + (lane & 3);
            if (warp == 11) {
                ep = ld_volatile(&sc->epoch[slot]) + 1; cl = ld_acquire(&sc->clean[lane & 15]);
                post_hint(sc->hint_k + (tb * 8 + hp) * 2, 0, lane);
                if (lane < (tb < 15 ? 4 : 0)) st_relaxed4(oh + 128, 0, 0, 0, 0);
                if (lane < (tb ? 0 : 4)) st_relaxed4(oh, 0, 0, 0, 0);
            }
            if (elect()) {
                if (warp == 9) {
                    #pragma unroll
                    for (int i = B_DONE1; i < B_DONEO; i++) mbar_init(bars + 8 * i, i < B_DONEX ? 2 : i == B_DONEX ? 8 : 9);
                    mbar_init(bars + 8 * B_CLR, 1);
                }
                #pragma unroll
                for (int i = 0; i < 34; i++) mbar_init(bars + 8 * (B_DONEO + i) + (warp - 9) * 272, 1);
                asm volatile("fence.mbarrier_init.release.cluster;" ::: "memory");
            }
            named_sync(0, 384);
            if (warp == 9) named_arrive(4, 64);
            if (warp < 11) {
                ep = get_tag();
                mbar_wait(bars + 8 * (B_DONE1 + HALO_AT), 0);
                #pragma unroll 1
                for (int kv = 0; kv < 2; kv++) {
                    uint4 v0 = {}, v1 = {}, v2 = {};
                    if (tb > 0) {
                        const uint4* hg = sc->halo + ((((tb - 1) * 8 + hp) * 2 + warp - 9) * 2 + kv) * 96 + lane;
                        if (kv == 0) while (ld_relaxed(sc->hint_k + ((tb - 1) * 8 + hp) * 2) != ep) {}
                        do { v0 = ld_relaxed4(hg); v1 = ld_relaxed4(hg + 32); v2 = ld_relaxed4(hg + 64); } while (!__all_sync(0xffffffffu, v0.w == ep && v1.w == ep && v2.w == ep));
                    }
                    if (kv) mbar_wait(bars + 8 * (B_DONE1 + 5), 0);
                    const uint32_t hs = sb + lane * 16 + (warp - 9) * 1024 + (kv ? SM_HALOV + 8192 : SM_HALOKIN);
                    sts4(hs, v0.x, v0.y, v0.z, v1.x); sts4(hs + 512, v1.y, v1.z, v2.x, v2.y);
                    __syncwarp();
                    if (lane == 0) mbar_arrive(bars + 8 * (B_HALO + 2 * kv + warp - 9));
                }
                if (tid == 288) STAMP(21);
            }
            if (warp == 10) {
                if (!has_b1 && lane == 0) {
                    mbar_wait(bars + 8 * (B_DONEO + 3), 0);
                    uint32_t t = clock32() + PF_AT;
                    #pragma unroll 1
                    for (int i = 0; i < PF_N; i++) {
                        while ((int)(clock32() - t) < 0) __nanosleep(40);
                        bulk_prefetch((const char*)w2 + (i * 16 + mi) * 16384, 16384);
                        t += PF_PACE;
                    }
                }
                if (has_b1) {
                    post_hint(sc->hint_u + (q * 32 + ft) * 2, 0, lane);
                    mbar_wait(bars + 8 * (B_DONE + HINT_U), 0);
                    const uint32_t now = gtime32();
                    if (lane < 2) st_relaxed4(sc->hint_u + (q * 32 + ft) * 2 + lane, ep, now, ep, now);
                }
            } else if (warp == 11) {
                #pragma unroll 1
                for (uint32_t e = ep; e != ep + 2; e++) {
                    if (!has_b1 && __shfl_sync(0xffffffffu, cl, mi) != e) {
                        if (e != ep) { mbar_wait_wd(bars + 8 * (B_DONEO + 3), 0); const uint32_t t = clock32(); while (clock32() - t < CL_AT) __nanosleep(100); __syncwarp(); }
                        constexpr int NL = sizeof(Tiles) / 2048;
                        uint4* p = (uint4*)&sc->tiles[e & 1] + (mi * NL + (lane >> 1)) * 8 + (lane & 7);
                        #pragma unroll 7
                        for (int i = 0; i < NL / 16; i++) st_relaxed4(p + i * 128, EMPTY, EMPTY, EMPTY, EMPTY);
                        __syncwarp();
                        if (lane == 0) { st_release(&sc->clean[mi], e); STAMP(24); }
                        __syncwarp();
                    }
                    if (e == ep) {
                        const long long t0 = clock64();
                        while (__any_sync(0xffffffffu, (int)(cl - ep) < 0)) { cl = ld_acquire(&sc->clean[lane & 15]); if (clock64() - t0 > WD_CLKS) __trap(); }
                        if (lane == 0) { *(volatile uint32_t*)(smem_raw + SM_TAG) = ep; mbar_arrive(bars + 8 * B_CLR); }
                        uint4* hg = sc->halo + (tb * 8 + hp) * 384 + lane;
                        #pragma unroll 1
                        for (int kv = 0; kv < 2; kv++) {
                            const uint32_t hs = sb + lane * 16 + 3072 + (kv ? SM_HALOV : SM_HALOK);
                            named_sync(6 + kv, 96);
                            #pragma unroll
                            for (int p = 0; p < 2; p++) {
                                const uint4 u0 = lds4(hs + p * 4096), u1 = lds4(hs + p * 4096 + 512);
                                st_relaxed4(hg + p * 192, u0.x, u0.y, u0.z, ep); st_relaxed4(hg + p * 192 + 32, u0.w, u1.x, u1.y, ep); st_relaxed4(hg + p * 192 + 64, u1.z, u1.w, ep, ep);
                            }
                            hg += 96;
                            if (kv == 0) {
                                post_hint(sc->hint_k + (tb * 8 + hp) * 2, ep, lane);
                                #pragma unroll
                                for (int j = 0; j < 6; j++) st_relaxed4(hg + j * 32 + (j / 3) * 96, 0, 0, 0, 0);
                            }
                        }
                        const uint32_t now = gtime32() - LATE_O;
                        if (lane < (tb < 15 ? 4 : 0)) st_relaxed4(oh + 128, ep, now, ep, now);
                        if (lane < (tb ? 0 : 4)) st_relaxed4(oh, ep, now, ep, now);
                        if (lane == 0) STAMP(23);
                        if (lane == 0) mbar_arrive(bars + 8 * B_DONEQ);
                    }
                }
                if (lane == 0) {
                    mbar_wait_wd(bars + 8 * B_END, 0);
                }
            } else {
                int aslot = 0;
                if (lane == 0) { prefetch_map(&tm_out64); prefetch_map(&tm_out48); }
                if (has_b1) {
                    #pragma unroll 1
                    for (int i = 0; i < 16; i++) {
                        mbar_wait(bars + 8 * (i < NA_SLOTS ? B_DONEQ + ((A_SCHED >> (4 * i)) & 15) : B_DONE + 1 + ((i - NA_SLOTS) * A3_END) / (15 - NA_SLOTS)), 0);
                        if (elect()) {
                            const uint32_t bar = bars + 8 * (B_FULLA + i), dst = sb + SM_ARING + aslot * 16384;
                            mbar_expect(bar, 16384);
                            tma3d(dst, &tm_w1, ft * 64, 0, i * 64, bar);
                            tma3d(dst + 8192, &tm_w1, ft * 64, 1, i * 64, bar);
                        }
                        aslot = aslot == NA_SLOTS - 1 ? 0 : aslot + 1;
                    }
                }
                aslot = 16 % NA_SLOTS;
                #pragma unroll 1
                for (int i = 0; i < 14; i++) {
                    if (i >= NA_SLOTS) mbar_wait(bars + 8 * (B_DONE + 1 + ((i - NA_SLOTS) * A4_END) / (13 - NA_SLOTS)), has_b1);
                    else if (has_b1) {
                        mbar_wait(bars + 8 * (B_DONE + max(33 - 2 * NA_SLOTS + 2 * i, W2_AT)), 0);
                        if (i >= W2_HOLD) mbar_wait(bars + 8 * B_FULLB, 1);
                    } else if (i == 0) { mbar_wait(bars + 8 * (B_DONEO + 3), 0); const uint32_t t = clock32() + PF_AT + 12 * PF_PACE; while ((int)(clock32() - t) < 0) __nanosleep(100); }
                    if (elect()) {
                        const uint32_t bar = bars + 8 * (B_FULLA + i);
                        mbar_expect(bar, 16384);
                        tma2d(sb + SM_ARING + aslot * 16384, &tm_w2, tt2 * 64, i * 128, bar);
                    }
                    aslot = aslot == NA_SLOTS - 1 ? 0 : aslot + 1;
                }
            }
        } else {
            auto krot = [&](int kb) { const int k = kb * 64 + (G & 1) * 64 * ROT; return k < 448 ? k : k - 448; };
            if (elect()) {
                #pragma unroll
                for (int i = 0; i < 7; i++) mbar_init(bars + 8 * i, 1);
                asm volatile("fence.mbarrier_init.release.cluster;" ::: "memory");
                if (STAG && G >= 2) { const uint32_t t0 = clock32(); while (clock32() - t0 < STAG) {} }
                #pragma unroll 1
                for (int kb = 0; kb < 7; kb++) {
                    const uint32_t st = sb + slot_x(kb), bar = bars + 8 * (B_FULLX + kb);
                    mbar_expect(bar, 16384);
                    tma3d(st, &tm_x, krot(kb), 0, tb * 64, bar); tma3d(st + 8192, &tm_x, krot(kb), 1, tb * 64, bar);
                }
                #pragma unroll
                for (int i = 7; i < B_DONE1; i++) mbar_init(bars + 8 * i, 1);
                asm volatile("fence.mbarrier_init.release.cluster;" ::: "memory");
            }
            named_arrive(0, 384);
            #pragma unroll 1
            for (int kb = 0; kb < 7; kb++) {
                if (kb == 6) { named_sync(4, 64); mbar_wait(bars + 8 * B_DONEX, 0); }
                if (elect()) {
                    const uint32_t st = sb + slot_kv(kb), bar = bars + 8 * (B_FULLKV + kb);
                    mbar_expect(bar, 16384);
                    #pragma unroll
                    for (int i = 0; i < 2; i++) {
                        const int n = 2 * kb + (ROT ? i : i ^ (G & 1));
                        tma2d(st + (n & 1) * 8192, &tm_wqkv, (n < 7 ? 448 : 896) + wcol, krot(n < 7 ? n : n - 7), bar);
                    }
                }
            }
            if (elect()) {
                mbar_expect(bars + 8 * B_FQ, 32768);
                mbar_expect(bars + 8 * (B_FQ + 1), 24576);
                #pragma unroll 1
                for (int i = 0; i < 7; i++) { const int j = ROT || i == 6 ? i : i ^ (G & 1); tma2d(sb + SM_QO + j * 8192, &tm_wqkv, wcol, krot(j), bars + 8 * (B_FQ + (i >> 2))); }
                mbar_expect(bars + 8 * B_FULLWO, 512 * 112 * 2);
            }
            #pragma unroll 1
            for (int i = 0; i < 7; i++) {
                const int kb = ((q & 1 ? WO_ORD1 : WO_ORD0) >> (4 * i)) & 7;
                if (kb < 5) mbar_wait(bars + 8 * (B_DONE1 + kb), 0);
                if (i == WO_HOLD) { mbar_wait(bars + 8 * (B_HALO + 2), 0); mbar_wait(bars + 8 * (B_HALO + 3), 0); }
                if (elect()) {
                    tma2d(sb + slot_wo(kb), &tm_wo64, c64, kb * 64, bars + 8 * B_FULLWO);
                    tma2d(sb + slot_wo(kb) + 8192, &tm_wo48, c48, kb * 64, bars + 8 * B_FULLWO);
                }
            }
            if (XR_HOLD) { mbar_wait(bars + 8 * (B_HALO + 2), 0); mbar_wait(bars + 8 * (B_HALO + 3), 0); }
            if (elect()) {
                tma2d(sb + SM_H, &tm_xr64, c64, tt2 * 64, bars + 8 * B_FULLWO);
                tma2d(sb + SM_H + 8192, &tm_xr48, c48, tt2 * 64, bars + 8 * B_FULLWO);
            }
            if (smem_u32(smem_raw) != SB) __trap();
            const uint32_t ep = get_tag();
            const Tiles* const tl = &sc->tiles[ep & 1];
            mbar_wait(bars + 8 * (B_DONE1 + 6), 0);
            wait_hints(TSVAL sc->hint_o + (tt2 * 32 + lane) * 2, ep, GO_O, 38);
            mbar_wait(bars + 8 * B_DONEQ, 0);
            if (elect()) {
                #pragma unroll
                for (int i = 0; i < 4; i++) {
                    mbar_expect(bars + 8 * (B_RAW + i), 14336);
                    bulk_ld(sb + SM_QO + i * 14336, tl->o + tt2 * 14336 + i * 3584, 14336, bars + 8 * (B_RAW + i));
                }
            }
            if (lane == 0) STAMP(20);
            mbar_wait(bars + 8 * (B_DONEO + 3), 0);
            if (has_b1) {
                mix_producer_b<32>(TSVAL 0, sc->hint_h, ep, tl->hn + q * 32 * 3584, lane);
            }
            mix_producer_b<28>(TSVAL has_b1, sc->hint_u, ep, tl->u + q * 28 * 3584, lane);
        }
    }
}

typedef CUresult (*EncodeFn)(CUtensorMap*, CUtensorMapDataType, cuuint32_t, void*, const cuuint64_t*, const cuuint64_t*, const cuuint32_t*,
                             const cuuint32_t*, CUtensorMapInterleave, CUtensorMapSwizzle, CUtensorMapL2promotion, CUtensorMapFloatOOBfill);

void make_map(EncodeFn fn, CUtensorMap* tm, const void* ptr, int rank, const cuuint64_t* dims, const cuuint64_t* strides, const cuuint32_t* box, CUtensorMapSwizzle sw) {
    cuuint32_t es[3] = {1, 1, 1};
    fn(tm, CU_TENSOR_MAP_DATA_TYPE_BFLOAT16, rank, const_cast<void*>(ptr), dims, strides, box, es, CU_TENSOR_MAP_INTERLEAVE_NONE, sw,
       CU_TENSOR_MAP_L2_PROMOTION_NONE, CU_TENSOR_MAP_FLOAT_OOB_FILL_NONE);
}

}

extern "C" void kernel_launch(void* const* d_in, const int* in_sizes, int n_in, void* d_out, int out_size) {
    const __nv_bfloat16* x = (const __nv_bfloat16*)d_in[0];
    const __nv_bfloat16* wqkv = (const __nv_bfloat16*)d_in[1];
    const __nv_bfloat16* wo = (const __nv_bfloat16*)d_in[2];
    const __nv_bfloat16* w1 = (const __nv_bfloat16*)d_in[4];
    const __nv_bfloat16* b1 = (const __nv_bfloat16*)d_in[5];
    const __nv_bfloat16* w2 = (const __nv_bfloat16*)d_in[6];
    const __nv_bfloat16* b2 = (const __nv_bfloat16*)d_in[7];

    void* fnp = nullptr; cudaDriverEntryPointQueryResult qr;
    cudaGetDriverEntryPoint("cuTensorMapEncodeTiled", &fnp, cudaEnableDefault, &qr);
    EncodeFn fn = (EncodeFn)fnp;
    CUtensorMap tx, twqkv, two64, two48, tw1, tw2, txr64, txr48, tout64, tout48;
    { cuuint64_t d[3] = {448, 2, 1024}, s[2] = {896, 1792}; cuuint32_t b[3] = {64, 1, 64}; make_map(fn, &tx, x, 3, d, s, b, CU_TENSOR_MAP_SWIZZLE_128B); }
    { cuuint64_t d[2] = {1344, 448}, s[1] = {2688}; cuuint32_t b[2] = {64, 64}; make_map(fn, &twqkv, wqkv, 2, d, s, b, CU_TENSOR_MAP_SWIZZLE_128B); }
    { cuuint64_t d[2] = {448, 448}, s[1] = {896}; cuuint32_t b[2] = {64, 64}; make_map(fn, &two64, wo, 2, d, s, b, CU_TENSOR_MAP_SWIZZLE_128B); }
    { cuuint64_t d[2] = {448, 448}, s[1] = {896}; cuuint32_t b[2] = {48, 64}; make_map(fn, &two48, wo, 2, d, s, b, CU_TENSOR_MAP_SWIZZLE_128B); }
    { cuuint64_t d[3] = {1792, 2, 1024}, s[2] = {3584, 7168}; cuuint32_t b[3] = {64, 1, 64}; make_map(fn, &tw1, w1, 3, d, s, b, CU_TENSOR_MAP_SWIZZLE_128B); }
    { cuuint64_t d[2] = {2048, 1792}, s[1] = {4096}; cuuint32_t b[2] = {64, 128}; make_map(fn, &tw2, w2, 2, d, s, b, CU_TENSOR_MAP_SWIZZLE_128B); }
    { cuuint64_t d[2] = {448, 2048}, s[1] = {896}; cuuint32_t b[2] = {64, 64}; make_map(fn, &txr64, x, 2, d, s, b, CU_TENSOR_MAP_SWIZZLE_128B); }
    { cuuint64_t d[2] = {448, 2048}, s[1] = {896}; cuuint32_t b[2] = {48, 64}; make_map(fn, &txr48, x, 2, d, s, b, CU_TENSOR_MAP_SWIZZLE_128B); }
    { cuuint64_t d[2] = {448, 2048}, s[1] = {896}; cuuint32_t b[2] = {64, 16}; make_map(fn, &tout64, d_out, 2, d, s, b, CU_TENSOR_MAP_SWIZZLE_128B); }
    { cuuint64_t d[2] = {448, 2048}, s[1] = {896}; cuuint32_t b[2] = {48, 16}; make_map(fn, &tout48, d_out, 2, d, s, b, CU_TENSOR_MAP_SWIZZLE_128B); }

    void* scv = nullptr;
    cudaGetSymbolAddress(&scv, g_scratch);
    Scratch* scp = (Scratch*)scv;
    int dev = 0, sms = 0;
    cudaGetDevice(&dev);
    cudaDeviceGetAttribute(&sms, cudaDevAttrMultiProcessorCount, dev);
    if (sms == 132) {
        cudaFuncSetAttribute(fused_kernel<true>, cudaFuncAttributeMaxDynamicSharedMemorySize, SM_TOTAL);
        fused_kernel<true><<<132, 384, SM_TOTAL>>>(scp, wo, w1, b1, w2, b2, tx, twqkv, two64, two48, tw1, tw2, txr64, txr48, tout64, tout48);
    } else {
        cudaFuncSetAttribute(fused_kernel<false>, cudaFuncAttributeMaxDynamicSharedMemorySize, SM_TOTAL);
        fused_kernel<false><<<132, 384, SM_TOTAL>>>(scp, wo, w1, b1, w2, b2, tx, twqkv, two64, two48, tw1, tw2, txr64, txr48, tout64, tout48);
    }
}
```

```cpp
#include <cuda_runtime.h>
#include <cuda_bf16.h>
#include <cuda.h>
#include <stdint.h>

namespace {

constexpr int D_ = 448;
constexpr float LN_EPS = 1e-5f;
constexpr float LOG2E_SCALE = 0.1889822365046136f * 1.4426950408889634f;

struct Tiles {
    uint32_t o[32 * 57344 / 4];
    uint32_t hn[4 * 32 * 14336 / 4];
    uint32_t u[4 * 28 * 14336 / 4];
};
struct Scratch {
    uint4 halo[128 * 2 * 2 * 3 * 32];
    uint4 stats[32 * 4 * 64];
    uint4 hint_k[128 * 2];
    uint4 hint_o[32 * 32 * 2];
    uint4 hint_h[4 * 32 * 2];
    uint4 hint_u[4 * 32 * 2];
    uint4 go[16];
    uint32_t epoch[160];
    uint32_t clean[16];
    alignas(1024) Tiles tiles[2];
};
__device__ Scratch g_scratch;
#define STAMP(i) do {} while (0)
#define FST(i) do {} while (0)
#define TSARG
#define TSVAL

constexpr uint32_t SB = 1024;
constexpr int SM_SLOT = 16384;
__device__ __forceinline__ constexpr uint32_t slot_x(int kb) { return (kb ? 6 + kb : 0) * SM_SLOT; }
__device__ __forceinline__ constexpr uint32_t slot_kv(int kb) { return (kb < 5 ? 2 + kb : 6 - kb) * SM_SLOT; }
__device__ __forceinline__ constexpr uint32_t slot_wo(int kb) { return (kb < 6 ? 2 + kb : 12) * SM_SLOT; }
constexpr int SM_QO = 8 * SM_SLOT;
constexpr int SM_HALOK = SM_QO + 57344, SM_HALOV = 1 * SM_SLOT;
constexpr int NA_SLOTS = 6, NB_SLOTS = 8;
constexpr int SM_ARING = 0;
constexpr int SM_BRING = NA_SLOTS * 16384;
constexpr int SM_H = 212992;
constexpr int SM_TAG = SM_H + 8192 + 96;
constexpr int SM_HALOKIN = 229376;
constexpr int SM_BAR = 231424;
constexpr int SM_TOTAL = 232448;
constexpr int B_FULLX = 0;
constexpr int B_FULLKV = 7;
constexpr int B_FQ = 14;
constexpr int B_DONE1 = 16;
constexpr int B_DONEX = 23;
constexpr int B_DONEQ = 24;
constexpr int B_DONEO = 25;
constexpr int B_FULLO = 29;
constexpr int B_FULLWO = 33;
constexpr int B_END = 34;
constexpr int B_HALO = 35;
constexpr int B_FULLA = 39;
constexpr int B_FULLB = 55;
constexpr int B_DONE = 87;
constexpr int B_RAW = 119;
constexpr int B_CLR = 127;

constexpr long long WD_CLKS = 2000000000ll;

template<int N> struct Int { static constexpr int value = N; };
template<int A, int B, class F> __device__ __forceinline__ void static_for(F&& f) { if constexpr (A < B) { f(Int<A>()); static_for<A + 1, B>(f); } }

__device__ __forceinline__ uint32_t smem_u32(const void* p) { return (uint32_t)__cvta_generic_to_shared(p); }
__device__ __forceinline__ void mbar_init(uint32_t bar, uint32_t cnt) { asm volatile("mbarrier.init.shared::cta.b64 [%0], %1;" :: "r"(bar), "r"(cnt) : "memory"); }
__device__ __forceinline__ void mbar_expect(uint32_t bar, uint32_t bytes) { asm volatile("mbarrier.arrive.expect_tx.shared::cta.b64 _, [%0], %1;" :: "r"(bar), "r"(bytes) : "memory"); }
__device__ __forceinline__ void mbar_arrive(uint32_t bar) { asm volatile("mbarrier.arrive.shared::cta.b64 _, [%0];" :: "r"(bar) : "memory"); }
__device__ __forceinline__ bool mbar_try(uint32_t bar, uint32_t parity) {
    uint32_t ok;
    asm volatile("{\n.reg .pred p;\nmbarrier.try_wait.parity.shared::cta.b64 p, [%1], %2;\nselp.u32 %0, 1, 0, p;\n}" : "=r"(ok) : "r"(bar), "r"(parity) : "memory");
    return ok;
}
__device__ __forceinline__ bool mbar_test(uint32_t bar, uint32_t parity) {
    uint32_t ok;
    asm volatile("{\n.reg .pred p;\nmbarrier.test_wait.parity.shared::cta.b64 p, [%1], %2;\nselp.u32 %0, 1, 0, p;\n}" : "=r"(ok) : "r"(bar), "r"(parity) : "memory");
    return ok;
}
__device__ __forceinline__ void mbar_wait(uint32_t bar, uint32_t parity) {
    asm volatile("{\n.reg .pred p;\n"
                 "WAIT_LOOP:\n"
                 "mbarrier.try_wait.parity.shared::cta.b64 p, [%0], %1;\n"
                 "@!p bra WAIT_LOOP;\n}" :: "r"(bar), "r"(parity) : "memory");
}
__device__ __forceinline__ void mbar_wait_wd(uint32_t bar, uint32_t parity) {
    const long long t0 = clock64();
    while (!mbar_try(bar, parity)) { if (clock64() - t0 > WD_CLKS) __trap(); }
}
__device__ __forceinline__ bool elect() { uint32_t p; asm volatile("{\n.reg .pred P;\nelect.sync _|P, 0xffffffff;\nselp.u32 %0, 1, 0, P;\n}" : "=r"(p)); return p; }
__device__ __forceinline__ void tma2d(uint32_t dst, const CUtensorMap* tm, int c0, int c1, uint32_t bar) {
    asm volatile("cp.async.bulk.tensor.2d.shared::cluster.global.mbarrier::complete_tx::bytes [%0], [%1, {%3, %4}], [%2];" :: "r"(dst), "l"(tm), "r"(bar), "r"(c0), "r"(c1) : "memory");
}
__device__ __forceinline__ void tma3d(uint32_t dst, const CUtensorMap* tm, int c0, int c1, int c2, uint32_t bar) {
    asm volatile("cp.async.bulk.tensor.3d.shared::cluster.global.mbarrier::complete_tx::bytes [%0], [%1, {%3, %4, %5}], [%2];" :: "r"(dst), "l"(tm), "r"(bar), "r"(c0), "r"(c1), "r"(c2) : "memory");
}
__device__ __forceinline__ void tma5d(uint32_t dst, const CUtensorMap* tm, int c0, int c3, int c4, uint32_t bar) {
    asm volatile("cp.async.bulk.tensor.5d.shared::cluster.global.mbarrier::complete_tx::bytes [%0], [%1, {%3, 0, 0, %4, %5}], [%2];" :: "r"(dst), "l"(tm), "r"(bar), "r"(c0), "r"(c3), "r"(c4) : "memory");
}
__device__ __forceinline__ void tma2d_store(const CUtensorMap* tm, int c0, int c1, uint32_t src) {
    asm volatile("cp.async.bulk.tensor.2d.global.shared::cta.bulk_group [%0, {%2, %3}], [%1];" :: "l"(tm), "r"(src), "r"(c0), "r"(c1) : "memory");
}
__device__ __forceinline__ void bulk_ld(uint32_t dst, const void* src, uint32_t bytes, uint32_t bar) {
    asm volatile("cp.async.bulk.shared::cluster.global.mbarrier::complete_tx::bytes [%0], [%1], %2, [%3];" :: "r"(dst), "l"(src), "r"(bytes), "r"(bar) : "memory");
}
__device__ __forceinline__ void bulk_prefetch(const void* src, uint32_t bytes) { asm volatile("cp.async.bulk.prefetch.L2.global [%0], %1;" :: "l"(src), "r"(bytes) : "memory"); }
__device__ __forceinline__ void prefetch_map(const CUtensorMap* tm) { asm volatile("prefetch.tensormap [%0];" :: "l"(tm) : "memory"); }
__device__ __forceinline__ void st_global_if(uint32_t c, uint32_t* p, uint32_t v) {
    asm volatile("{\n.reg .pred p;\nsetp.ne.u32 p, %2, 0;\n@p st.global.u32 [%0], %1;\n}" :: "l"(p), "r"(v), "r"(c) : "memory");
}
__device__ __forceinline__ void st_relaxed4_if(bool c, uint4* p, uint32_t a, uint32_t b, uint32_t d) {
    asm volatile("{\n.reg .b128 t;\n.reg .b64 a, b;\n.reg .pred p;\nsetp.ne.u32 p, %4, 0;\nmov.b64 a, {%1, %2};\nmov.b64 b, {%3, %3};\nmov.b128 t, {a, b};\n@p st.relaxed.gpu.global.b128 [%0], t;\n}" :: "l"(p), "r"(a), "r"(b), "r"(d), "r"((uint32_t)c) : "memory");
}
__device__ __forceinline__ void pin_ptr(uint32_t never, const void* a) {
    asm volatile("{\n.reg .pred p;\nsetp.ne.u32 p, %1, 0;\n@p st.shared.u64 [%1], %0;\n}" :: "l"(a), "r"(never) : "memory");
}
__device__ __forceinline__ void pin4(uint32_t never, float a, float b, float c, float d) {
    asm volatile("{\n.reg .pred p;\nsetp.ne.u32 p, %4, 0;\n@p st.shared.v4.f32 [%4], {%0,%1,%2,%3};\n}" :: "f"(a), "f"(b), "f"(c), "f"(d), "r"(never) : "memory");
}
__device__ __forceinline__ void fence_async_smem() { asm volatile("fence.proxy.async.shared::cta;" ::: "memory"); }
__device__ __forceinline__ uint32_t ld_acquire(const void* p) { uint32_t v; asm volatile("ld.acquire.gpu.global.u32 %0, [%1];" : "=r"(v) : "l"(p) : "memory"); return v; }
__device__ __forceinline__ void st_release(void* p, uint32_t v) { asm volatile("st.release.gpu.global.u32 [%0], %1;" :: "l"(p), "r"(v) : "memory"); }
__device__ __forceinline__ uint32_t ld_relaxed(const void* p) { uint32_t v; asm volatile("ld.relaxed.gpu.global.u32 %0, [%1];" : "=r"(v) : "l"(p) : "memory"); return v; }
__device__ __forceinline__ uint2 ld_relaxed2(const void* p) {
    uint2 v; asm volatile("{\n.reg .b64 a;\nld.relaxed.gpu.global.b64 a, [%2];\nmov.b64 {%0, %1}, a;\n}" : "=r"(v.x), "=r"(v.y) : "l"(p) : "memory"); return v;
}
__device__ __forceinline__ uint4 ld_relaxed4(const uint4* p) {
    uint4 v;
    asm volatile("{\n.reg .b128 t;\n.reg .b64 a, b;\nld.relaxed.gpu.global.b128 t, [%4];\nmov.b128 {a, b}, t;\nmov.b64 {%0, %1}, a;\nmov.b64 {%2, %3}, b;\n}" : "=r"(v.x), "=r"(v.y), "=r"(v.z), "=r"(v.w) : "l"(p) : "memory");
    return v;
}
__device__ __forceinline__ void st_relaxed4(uint4* p, uint32_t a, uint32_t b, uint32_t c, uint32_t d) {
    asm volatile("{\n.reg .b128 t;\n.reg .b64 a, b;\nmov.b64 a, {%1, %2};\nmov.b64 b, {%3, %4};\nmov.b128 t, {a, b};\nst.relaxed.gpu.global.b128 [%0], t;\n}" :: "l"(p), "r"(a), "r"(b), "r"(c), "r"(d) : "memory");
}
__device__ __forceinline__ uint32_t ld_u16(const unsigned short* p) { uint32_t v; asm volatile("ld.volatile.global.u16 %0, [%1];" : "=r"(v) : "l"(p) : "memory"); return v; }
__device__ __forceinline__ uint32_t ld_volatile(const uint32_t* p) { uint32_t v; asm volatile("ld.volatile.global.u32 %0, [%1];" : "=r"(v) : "l"(p) : "memory"); return v; }
__device__ __forceinline__ void named_arrive(int id, int n) { asm volatile("bar.arrive %0, %1;" :: "r"(id), "r"(n) : "memory"); }
__device__ __forceinline__ void named_sync(int id, int n) { asm volatile("bar.sync %0, %1;" :: "r"(id), "r"(n) : "memory"); }
__device__ __forceinline__ void wg_fence() { asm volatile("wgmma.fence.sync.aligned;" ::: "memory"); }
__device__ __forceinline__ void wg_commit() { asm volatile("wgmma.commit_group.sync.aligned;" ::: "memory"); }
template<int N> __device__ __forceinline__ void wg_wait() { asm volatile("wgmma.wait_group.sync.aligned %0;" :: "n"(N) : "memory"); }
template<int N> __device__ __forceinline__ void reg_fence(float (&d)[N]) {
    #pragma unroll
    for (int i = 0; i < N; i++) asm volatile("" : "+f"(d[i]) :: "memory");
}
__device__ __forceinline__ constexpr uint64_t mkdesc(uint32_t addr, uint32_t lbo, uint32_t sbo, uint32_t sw) {
    return (uint64_t)((addr & 0x3FFFF) >> 4) | ((uint64_t)(lbo >> 4) << 16) | ((uint64_t)(sbo >> 4) << 32) | ((uint64_t)sw << 62);
}
__device__ __forceinline__ void ldsm4(uint32_t (&r)[4], uint32_t addr) {
    asm volatile("ldmatrix.sync.aligned.m8n8.x4.shared.b16 {%0,%1,%2,%3}, [%4];" : "=r"(r[0]), "=r"(r[1]), "=r"(r[2]), "=r"(r[3]) : "r"(addr) : "memory");
}
__device__ __forceinline__ void stsm4_if(uint32_t c, uint32_t addr, uint32_t r0, uint32_t r1, uint32_t r2, uint32_t r3) {
    asm volatile("{\n.reg .pred p;\nsetp.ne.u32 p, %5, 0;\n@p stmatrix.sync.aligned.m8n8.x4.shared.b16 [%0], {%1,%2,%3,%4};\n}" :: "r"(addr), "r"(r0), "r"(r1), "r"(r2), "r"(r3), "r"(c) : "memory");
}
__device__ __forceinline__ void sts4(uint32_t a, uint32_t x, uint32_t y, uint32_t z, uint32_t w) { asm volatile("st.shared.v4.u32 [%0], {%1,%2,%3,%4};" :: "r"(a), "r"(x), "r"(y), "r"(z), "r"(w) : "memory"); }
__device__ __forceinline__ uint4 lds4(uint32_t a) { uint4 v; asm volatile("ld.shared.v4.u32 {%0,%1,%2,%3}, [%4];" : "=r"(v.x), "=r"(v.y), "=r"(v.z), "=r"(v.w) : "r"(a) : "memory"); return v; }
__device__ __forceinline__ uint32_t movtrans(uint32_t a) { uint32_t d; asm volatile("movmatrix.sync.aligned.m8n8.trans.b16 %0, %1;" : "=r"(d) : "r"(a)); return d; }
__device__ __forceinline__ uint32_t pack_bf16(float lo, float hi) { uint32_t r; asm("cvt.rn.bf16x2.f32 %0, %1, %2;" : "=r"(r) : "f"(hi), "f"(lo)); return r; }
__device__ __forceinline__ void sub_bf16x2(uint32_t& a, uint32_t b) { asm volatile("sub.rn.bf16x2 %0, %0, %1;" : "+r"(a) : "r"(b)); }
__device__ __forceinline__ float bf_lo(uint32_t v) { return __uint_as_float(v << 16); }
__device__ __forceinline__ float bf_hi(uint32_t v) { return __uint_as_float(v & 0xffff0000u); }
__device__ __forceinline__ void mma16816(float (&c)[4], uint32_t a0, uint32_t a1, uint32_t a2, uint32_t a3, uint32_t b0, uint32_t b1) {
    asm volatile("mma.sync.aligned.m16n8k16.row.col.f32.bf16.bf16.f32 {%0,%1,%2,%3}, {%4,%5,%6,%7}, {%8,%9}, {%0,%1,%2,%3};"
        : "+f"(c[0]), "+f"(c[1]), "+f"(c[2]), "+f"(c[3]) : "r"(a0), "r"(a1), "r"(a2), "r"(a3), "r"(b0), "r"(b1));
}
__device__ __forceinline__ void mma1688(float (&c)[4], uint32_t a0, uint32_t a1, uint32_t b0) {
    asm volatile("mma.sync.aligned.m16n8k8.row.col.f32.bf16.bf16.f32 {%0,%1,%2,%3}, {%4,%5}, {%6}, {%0,%1,%2,%3};"
        : "+f"(c[0]), "+f"(c[1]), "+f"(c[2]), "+f"(c[3]) : "r"(a0), "r"(a1), "r"(b0));
}
__device__ __forceinline__ float quad_sum(float v) { v += __shfl_xor_sync(0xffffffffu, v, 1); v += __shfl_xor_sync(0xffffffffu, v, 2); return v; }
__device__ __forceinline__ float quad_max(float v) { v = fmaxf(v, __shfl_xor_sync(0xffffffffu, v, 1)); v = fmaxf(v, __shfl_xor_sync(0xffffffffu, v, 2)); return v; }
__device__ __forceinline__ float ex2(float x) { float y; asm("ex2.approx.ftz.f32 %0, %1;" : "=f"(y) : "f"(x)); return y; }
__device__ __forceinline__ float rsqrt_approx(float x) { float y; asm("rsqrt.approx.ftz.f32 %0, %1;" : "=f"(y) : "f"(x)); return y; }
__device__ __forceinline__ float rcp_approx(float x) { float y; asm("rcp.approx.ftz.f32 %0, %1;" : "=f"(y) : "f"(x)); return y; }
__device__ __forceinline__ float gelu_half(float hx) {
    const float z = hx * fmaf(hx * hx, 8.f * 0.044715f * 0.7978845608028654f, 2.f * 0.7978845608028654f);
    float t; asm("tanh.approx.f32 %0, %1;" : "=f"(t) : "f"(z));
    return fmaf(hx, t, hx);
}
__device__ __forceinline__ uint32_t gtime32() { uint32_t t; asm volatile("mov.u32 %0, %%globaltimer_lo;" : "=r"(t)); return t; }
__device__ __forceinline__ uint32_t clock32() { uint32_t t; asm volatile("mov.u32 %0, %%clock;" : "=r"(t)); return t; }
#define PF_PACE 400

#define PF_AT 4000
#define NSQ 6
#define HALO_AT 3
#define PF_N 12
#define HINT_U 24
#define SP_AT 2000
#define SP_N 0
#define WO_HOLD 7
#define A_SCHED 0x322188
#define WO_ORD0 0x4321065
#define WO_ORD1 0x3465210
#define XR_HOLD 0
#define ROT 0
#define NPIPE 1
#define CL_AT 4000
#define WARM 1
#define WARM_AT 300
#define W2_AT 23
#define W2_HOLD 5
#define A3_END 20
#define A4_END 16
#define GO_H 1216
#define GO_U 1184
#define STAG 0
#define GO_O 1216
#define LATE_O 256
#define PP 0
#define DRY2 1
#define LATE_AT 1
#define LATE_ODD 1
#define HINT_H 1
#define SLACK 256
template<int TB> __device__ __forceinline__ void wgmma_rs56(float (&d)[28], const uint32_t (&a)[4], uint64_t db, int sc) {
    asm volatile("{\n.reg .pred p;\nsetp.ne.b32 p, %33, 0;\n"
        "wgmma.mma_async.sync.aligned.m64n56k16.f32.bf16.bf16 {%0, %1, %2, %3, %4, %5, %6, %7, %8, %9, %10, %11, %12, %13, %14, %15, %16, %17, %18, %19, %20, %21, %22, %23, %24, %25, %26, %27}, {%28, %29, %30, %31}, %32, p, 1, 1, %34;\n}\n"
        : "+f"(d[0]), "+f"(d[1]), "+f"(d[2]), "+f"(d[3]), "+f"(d[4]), "+f"(d[5]), "+f"(d[6]), "+f"(d[7]), "+f"(d[8]), "+f"(d[9]), "+f"(d[10]), "+f"(d[11]), "+f"(d[12]), "+f"(d[13]), "+f"(d[14]), "+f"(d[15]), "+f"(d[16]), "+f"(d[17]), "+f"(d[18]), "+f"(d[19]), "+f"(d[20]), "+f"(d[21]), "+f"(d[22]), "+f"(d[23]), "+f"(d[24]), "+f"(d[25]), "+f"(d[26]), "+f"(d[27])
        : "r"(a[0]), "r"(a[1]), "r"(a[2]), "r"(a[3]), "l"(db), "r"(sc), "n"(TB));
}

template<int TA, int TB, int SC = 1> __device__ __forceinline__ void wgmma_ss112(float (&d)[56], uint64_t da, uint64_t db) {
    asm volatile("wgmma.mma_async.sync.aligned.m64n112k16.f32.bf16.bf16 {%0, %1, %2, %3, %4, %5, %6, %7, %8, %9, %10, %11, %12, %13, %14, %15, %16, %17, %18, %19, %20, %21, %22, %23, %24, %25, %26, %27, %28, %29, %30, %31, %32, %33, %34, %35, %36, %37, %38, %39, %40, %41, %42, %43, %44, %45, %46, %47, %48, %49, %50, %51, %52, %53, %54, %55}, %56, %57, %60, 1, 1, %58, %59;\n"
        : "+f"(d[0]), "+f"(d[1]), "+f"(d[2]), "+f"(d[3]), "+f"(d[4]), "+f"(d[5]), "+f"(d[6]), "+f"(d[7]), "+f"(d[8]), "+f"(d[9]), "+f"(d[10]), "+f"(d[11]), "+f"(d[12]), "+f"(d[13]), "+f"(d[14]), "+f"(d[15]), "+f"(d[16]), "+f"(d[17]), "+f"(d[18]), "+f"(d[19]), "+f"(d[20]), "+f"(d[21]), "+f"(d[22]), "+f"(d[23]), "+f"(d[24]), "+f"(d[25]), "+f"(d[26]), "+f"(d[27]), "+f"(d[28]), "+f"(d[29]), "+f"(d[30]), "+f"(d[31]), "+f"(d[32]), "+f"(d[33]), "+f"(d[34]), "+f"(d[35]), "+f"(d[36]), "+f"(d[37]), "+f"(d[38]), "+f"(d[39]), "+f"(d[40]), "+f"(d[41]), "+f"(d[42]), "+f"(d[43]), "+f"(d[44]), "+f"(d[45]), "+f"(d[46]), "+f"(d[47]), "+f"(d[48]), "+f"(d[49]), "+f"(d[50]), "+f"(d[51]), "+f"(d[52]), "+f"(d[53]), "+f"(d[54]), "+f"(d[55])
        : "l"(da), "l"(db), "n"(TA), "n"(TB), "n"(SC));
}

template<int TA, int TB, int SC = 1> __device__ __forceinline__ void wgmma_ss64(float (&d)[32], uint64_t da, uint64_t db) {
    asm volatile("wgmma.mma_async.sync.aligned.m64n64k16.f32.bf16.bf16 {%0, %1, %2, %3, %4, %5, %6, %7, %8, %9, %10, %11, %12, %13, %14, %15, %16, %17, %18, %19, %20, %21, %22, %23, %24, %25, %26, %27, %28, %29, %30, %31}, %32, %33, %36, 1, 1, %34, %35;\n"
        : "+f"(d[0]), "+f"(d[1]), "+f"(d[2]), "+f"(d[3]), "+f"(d[4]), "+f"(d[5]), "+f"(d[6]), "+f"(d[7]), "+f"(d[8]), "+f"(d[9]), "+f"(d[10]), "+f"(d[11]), "+f"(d[12]), "+f"(d[13]), "+f"(d[14]), "+f"(d[15]), "+f"(d[16]), "+f"(d[17]), "+f"(d[18]), "+f"(d[19]), "+f"(d[20]), "+f"(d[21]), "+f"(d[22]), "+f"(d[23]), "+f"(d[24]), "+f"(d[25]), "+f"(d[26]), "+f"(d[27]), "+f"(d[28]), "+f"(d[29]), "+f"(d[30]), "+f"(d[31])
        : "l"(da), "l"(db), "n"(TA), "n"(TB), "n"(SC));
}

template<int TA, int TB, int SC = 1> __device__ __forceinline__ void wgmma_ss48(float (&d)[24], uint64_t da, uint64_t db) {
    asm volatile("wgmma.mma_async.sync.aligned.m64n48k16.f32.bf16.bf16 {%0, %1, %2, %3, %4, %5, %6, %7, %8, %9, %10, %11, %12, %13, %14, %15, %16, %17, %18, %19, %20, %21, %22, %23}, %24, %25, %28, 1, 1, %26, %27;\n"
        : "+f"(d[0]), "+f"(d[1]), "+f"(d[2]), "+f"(d[3]), "+f"(d[4]), "+f"(d[5]), "+f"(d[6]), "+f"(d[7]), "+f"(d[8]), "+f"(d[9]), "+f"(d[10]), "+f"(d[11]), "+f"(d[12]), "+f"(d[13]), "+f"(d[14]), "+f"(d[15]), "+f"(d[16]), "+f"(d[17]), "+f"(d[18]), "+f"(d[19]), "+f"(d[20]), "+f"(d[21]), "+f"(d[22]), "+f"(d[23])
        : "l"(da), "l"(db), "n"(TA), "n"(TB), "n"(SC));
}

template<int NKB>
__device__ __forceinline__ void mix_mainloop(TSARG float (&acc)[56], uint32_t par, bool leader, const uint32_t (&late)[14], uint32_t* late_ptr, bool has_late) {
    constexpr uint32_t sb = SB, bars = sb + SM_BAR;
    constexpr int A0 = NKB == 32 ? 0 : 16 % NA_SLOTS;
    int bslot = 0, aslot = A0;
    reg_fence(acc);
    #pragma unroll 1
    for (int i = 0; i < NKB / 2; i++) {
        mbar_wait(bars + 8 * (B_FULLA + i), par);
        const uint64_t adesc = mkdesc(sb + SM_ARING, 8192, 1024, 1) + (uint32_t)(aslot * 1024);
        aslot = aslot == NA_SLOTS - 1 ? 0 : aslot + 1;
        #pragma unroll
        for (int jj = 0; jj < 2; jj++) {
            const int j = 2 * i + jj;
            mbar_wait(bars + 8 * (B_FULLB + j), par);
            const uint64_t bdesc = mkdesc(sb + SM_BRING, 1792, 128, 0) + (uint32_t)(bslot * 896);
            bslot = bslot == NB_SLOTS - 1 ? 0 : bslot + 1;
            wg_fence();
            #pragma unroll
            for (int s = 0; s < 4; s++) wgmma_ss112<1, 1>(acc, adesc + jj * 512 + s * 128, bdesc + s * 224);
            wg_commit();
            if (i == LATE_AT - (LATE_ODD & jj) && has_late) {
                #pragma unroll
                for (int c = 7 * jj; c < 7 * jj + 7; c++) st_global_if(1, late_ptr + c * 32, late[c]);
            }
            wg_wait<1>();
            if (j > 0 && leader) mbar_arrive(bars + 8 * (B_DONE + j - 1));
        }
    }
    wg_wait<0>();
    reg_fence(acc);
    if (leader) mbar_arrive(bars + 8 * (B_DONE + NKB - 1));
}

constexpr uint32_t EMPTY = 0xFFFFFFFFu;
__device__ __forceinline__ void post_hint(uint4* p, uint32_t ep, int lane) { if (lane < 2) st_relaxed4(p + lane, ep, ep, ep, ep); }
__device__ __forceinline__ void post_time(uint4* p, uint32_t ep, int lane) { const uint32_t now = gtime32(); if (lane < 2) st_relaxed4(p + lane, ep, now, ep, now); }

__device__ __forceinline__ void wait_hints(TSARG const uint4* hint, uint32_t ep, uint32_t delay, int st) {
    uint2 v;
    do { v = ld_relaxed2(hint); } while (!__all_sync(0xffffffffu, v.x == ep));
    const uint32_t t1 = gtime32(), age = __reduce_min_sync(0xffffffffu, t1 + 256 - v.y);
    if (elect()) STAMP(st);
    while (gtime32() - t1 + age < delay + 256) {}
    __syncwarp();
}

template<int NKB>
__device__ __forceinline__ void mix_producer_b(TSARG uint32_t par, const uint4* hints, uint32_t ep, const uint32_t* src, int lane) {
    constexpr uint32_t sb = SB, bars = sb + SM_BAR;
    wait_hints(TSVAL hints, ep, NKB == 32 ? GO_H : GO_U, NKB == 32 ? 42 : 43);
    mbar_wait(bars + 8 * (par ? B_DONE + 31 : B_DONEO + 3), 0);
    #pragma unroll 1
    for (int j = 0; j < NKB; j++) {
        if (j >= NB_SLOTS) mbar_wait(bars + 8 * (B_DONE + j - NB_SLOTS), par);
        if (j == 0 && lane == 0) STAMP(NKB == 32 ? 29 : 30);
        if (j == 7 && lane == 0) STAMP(NKB == 32 ? 35 : 36);
        if (elect()) {
            mbar_expect(bars + 8 * (B_RAW + (j & 7)), 14336);
            bulk_ld(sb + SM_BRING + (j & 7) * 14336, src + j * 3584, 14336, bars + 8 * (B_RAW + (j & 7)));
        }
    }
}
__device__ __forceinline__ void check_tiles(TSARG int n, int w, int lane, uint32_t& ph, uint32_t dst, const uint32_t* src, int full) {
    constexpr uint32_t bars = SB + SM_BAR;
    #pragma unroll 1
    for (int j = w; j < n; j += 4) {
        const uint32_t raw = bars + 8 * (B_RAW + (j & 7)), d = dst + (j & 7) * 14336, a = d + lane * 128 + (lane & 3) * 32 + (lane >> 2) * 4;
        bool bad;
        do {
            mbar_wait(raw, (ph >> (j & 4)) & 1);
            ph ^= 1u << (j & 4);
            if (j == 0 && lane == 0) STAMP(n == 4 ? 6 : n == 32 ? 31 : 32);
            uint32_t v0, v1, v2, v3;
            asm volatile("ld.shared.u32 %0, [%4];\nld.shared.u32 %1, [%4+4096];\nld.shared.u32 %2, [%4+8192];\nld.shared.u32 %3, [%4+10240];"
                         : "=r"(v0), "=r"(v1), "=r"(v2), "=r"(v3) : "r"(a) : "memory");
            bad = __any_sync(0xffffffffu, max(max(v0, v1), max(v2, v3)) == EMPTY);
            if (elect() && bad) {
                mbar_expect(raw, 14336); bulk_ld(d, src + j * 3584, 14336, raw);
            }
        } while (bad);
        if (lane == 0) mbar_arrive(bars + 8 * (full + j));
    }
}

__device__ __forceinline__ uint32_t hcol(uint32_t a, int jp) { return (a ^ ((jp & 3) << 5)) + (jp >> 2) * 8192; }

__device__ __forceinline__ uint32_t get_tag() {
    mbar_wait(SB + SM_BAR + 8 * B_CLR, 0);
    uint32_t v; asm volatile("ld.shared.u32 %0, [%1];" : "=r"(v) : "r"(SB + SM_TAG) : "memory"); return v;
}

template<bool USE_SMID>
__global__ void __launch_bounds__(384, 1)
fused_kernel(Scratch* __restrict__ sc, const __nv_bfloat16* __restrict__ wo,
             const __nv_bfloat16* __restrict__ w1, const __nv_bfloat16* __restrict__ b1,
             const __nv_bfloat16* __restrict__ w2, const __nv_bfloat16* __restrict__ b2,
             const __grid_constant__ CUtensorMap tm_x, const __grid_constant__ CUtensorMap tm_wqkv,
             const __grid_constant__ CUtensorMap tm_wo64, const __grid_constant__ CUtensorMap tm_wo48,
             const __grid_constant__ CUtensorMap tm_w1, const __grid_constant__ CUtensorMap tm_w2,
             const __grid_constant__ CUtensorMap tm_xr64, const __grid_constant__ CUtensorMap tm_xr48,
             const __grid_constant__ CUtensorMap tm_out64, const __grid_constant__ CUtensorMap tm_out48) {
    extern __shared__ __align__(1024) uint8_t smem_raw[];
    constexpr uint32_t sb = SB;
    constexpr uint32_t bars = sb + SM_BAR;
    const int tid = threadIdx.x, lane = tid & 31;
    const int warp = __shfl_sync(0xffffffffu, tid >> 5, 0);
    int slot;
    if (USE_SMID) {
        asm("{\n.reg .u32 s, t, u, d, a, b, c;\n.reg .pred p, r;\n"
            "mov.u32 s, %%smid;\nshr.u32 t, s, 1;\nsub.u32 u, t, 32;\nmul.lo.u32 d, u, 37;\nshr.u32 d, d, 8;\n"
            "and.b32 a, t, 7;\nshl.b32 a, a, 3;\nshr.u32 c, t, 3;\nadd.u32 a, a, c;\n"
            "mad.lo.u32 b, d, -55, 12;\nshl.b32 c, u, 3;\nadd.u32 b, b, c;\n"
            "setp.lt.u32 p, t, 32;\nselp.u32 a, a, b, p;\n"
            "setp.lt.u32 r, t, 62;\nselp.s32 c, 4, -58, r;\nadd.u32 c, t, c;\nsetp.lt.u32 p, t, 60;\nselp.u32 a, a, c, p;\n"
            "and.b32 s, s, 1;\nshl.b32 a, a, 1;\nadd.u32 %0, a, s;\n}" : "=r"(slot));
    } else slot = blockIdx.x;
    const int G = slot >> 4, mi = slot & 15;
    const int tb = 4 * (G >> 1) + (mi >> 2), hp = 2 * (mi & 3) + (G & 1);
    const int wcol = (hp * 56) & ~15;
    if (slot >= 128) {
        const uint32_t ep = ld_volatile(&sc->epoch[slot]) + 1;
        if (warp == 1 && mi < 2) {
            post_hint(sc->go + 8 * mi, 0, lane);
            const uint4* hint = (mi ? sc->hint_u : sc->hint_h) + 2 * min(lane, mi ? 27 : 31);
            while (ld_relaxed(sc->hint_k) != ep) __nanosleep(200);
            uint2 v[4];
            do {
                #pragma unroll
                for (int i = 0; i < 4; i++) v[i] = ld_relaxed2(hint + 64 * i);
            } while (!__all_sync(0xffffffffu, v[0].x == ep && v[1].x == ep && v[2].x == ep && v[3].x == ep));
            const uint32_t t1 = gtime32() + 256;
            const uint32_t age = min(min(t1 - v[0].y, t1 - v[1].y), min(t1 - v[2].y, t1 - v[3].y)) + (lane < 16 ? 0 : SLACK);
            const uint32_t ts = t1 - __reduce_min_sync(0xffffffffu, age);
            if (lane < 2) st_relaxed4(sc->go + 8 * mi + lane, ep, ts, ep, ts);
        }
        if (tid == 0) {
            const long long t0 = clock64();
            while (clock64() - t0 < SP_AT) {}
            #pragma unroll 1
            for (int i = 0; i < 7; i++) bulk_prefetch((const char*)wo + (i * 4 + mi) * 14336, 14336);
            #pragma unroll 1
            for (int i = 0; i < SP_N; i++) bulk_prefetch((const char*)w1 + (i * 4 + mi) * 14336, 14336);
            while (ld_relaxed(sc->hint_u) != ep) { __nanosleep(500); if (clock64() - t0 > WD_CLKS) __trap(); }
            sc->epoch[slot] = ep;
        }
        return;
    }
    const int q = mi & 3, tt2 = 4 * G + (mi >> 2), ft = 4 * (G - 1) + (mi >> 2);
    const bool has_b1 = G > 0;
    const int c64 = 64 * q, c48 = 256 + 48 * q;

    if (warp < 8) {
        if (WARM) {
            const int w = warp & 3, wg = warp >> 2, g = lane >> 2, t = lane & 3;
            if (WARM_AT) { const uint32_t t0 = clock32(); while (clock32() - t0 < WARM_AT) {} __syncwarp(); }
            if (w > 0) post_hint(sc->hint_o + ((2 * tb + (w >> 1)) * 32 + hp * 4 + (w & 1) * 2 + wg) * 2, 0, lane);
            if (wg == 0) {
                if (t < 2) st_relaxed4(sc->stats + tt2 * 256 + q * 64 + 16 * w + g + 8 * t, 0, 0, 0, 0);
            }
        }
        named_sync(0, 384);
        asm volatile("setmaxnreg.inc.sync.aligned.u32 224;");
        int tid; asm volatile("mov.u32 %0, %%tid.x;" : "=r"(tid));
        const int lane = tid & 31, warp = __shfl_sync(0xffffffffu, tid >> 5, 0), wg = warp >> 2;
        uint32_t ep;
        Tiles* tl;
        const int w = warp & 3, g = lane >> 2, t = lane & 3;
        const bool leader = (tid & 127) == 0;
        const uint32_t never = gridDim.y - 1;
        {
            uint32_t a[28][4];
            float accK[28], accV[28], accQ[28];
            const int lrow = 16 * w + (lane & 7) + (lane & 8);
            const uint32_t lbase = sb + wg * 8192 + lrow * 128;
            const uint32_t lx = (lane >> 4) ^ (lane & 7);
            const uint32_t wofs = hp & 1;
            auto pin2 = [&](uint32_t x0, uint32_t x1) {
                asm volatile("{\n.reg .pred p;\nsetp.ne.u32 p, %2, 0;\n@p st.shared.v2.b32 [%0], {%0,%1};\n}" :: "r"(x0), "r"(x1), "r"(never) : "memory");
            };
            float cS[2][4] = {}, cA[2][4] = {}, cB[2][4] = {}, q0, q1, p0, p1;
            auto sq = [&](float& acc, uint32_t v) { const float lo = bf_lo(v), hi = bf_hi(v); acc = fmaf(hi, hi, fmaf(lo, lo, acc)); };
            #pragma unroll
            for (int kb = 0; kb < 8; kb++) {
                if (kb < 7) {
                    mbar_wait(bars + 8 * (B_FULLX + kb), 0);
                    if (kb == 0 && tid == 0) STAMP(0);
                    if (kb == 6 && tid == 0) STAMP(25);
                    if (kb == 0) FST(0); if (kb == 2) FST(1); if (kb == 4) FST(2); if (kb == 6) FST(3);
                    #pragma unroll
                    for (int s = 4 * kb; s < 4 * kb + 4; s++) ldsm4(a[s], lbase + slot_x(kb) + ((lx ^ (2 * (s & 3))) << 4));
                }
                if (kb == NPIPE) continue;
                const int kc = kb < NPIPE ? kb : kb - 1;
                if (kc == NSQ) { p0 = cS[0][0] + cS[1][0]; p1 = cS[0][2] + cS[1][2]; }
                #pragma unroll
                for (int s = 4 * kc; s < 4 * kc + 4; s++) {
                    mma16816(cS[s & 1], a[s][0], a[s][1], a[s][2], a[s][3], 0x3F803F80u, 0x3F803F80u);
                    if (kc < NSQ) {
                        mma1688(cA[0], a[s][0], a[s][1], a[s][0]); mma1688(cA[1], a[s][2], a[s][3], a[s][2]);
                        mma1688(cB[0], a[s][0], a[s][1], a[s][1]); mma1688(cB[1], a[s][2], a[s][3], a[s][3]);
                    }
                }
            }
            const float m0 = (cS[0][0] + cS[1][0]) * (1.f / D_), m1 = (cS[0][2] + cS[1][2]) * (1.f / D_);
            const uint32_t mm0 = pack_bf16(m0, m0), mm1 = pack_bf16(m1, m1);
            if (lane == 0) mbar_arrive(bars + 8 * B_DONEX);
            auto center = [&](int s) { sub_bf16x2(a[s][0], mm0); sub_bf16x2(a[s][1], mm1); sub_bf16x2(a[s][2], mm0); sub_bf16x2(a[s][3], mm1); };
            uint32_t Ka[8], Kb[8], Kc[8], Va[8], Vb[7], Vc[8];
            float r0, r1, ls0, ls1;
            uint32_t pm, zero;
            uint32_t* od;
            uint4* oh;
            auto kpack = [&](uint32_t (&k)[8], int j, int c, float r) {
                const uint32_t v = pack_bf16(accK[4 * j + c] * r, accK[4 * j + c + 1] * r);
                if (j == 3) { k[3] = t < 2 ? v : 0u; k[4] = t < 2 ? 0u : v; } else k[j + (j > 3)] = v;
            };
            auto batch = [&](auto c0, auto c1) {
                constexpr int n0 = c0.value, n1 = c1.value;
                if (PP && n0 < PP) named_sync(10 + wg, 256);
                wg_fence();
                static_for<n0, n1>([&](auto nc) {
                    constexpr int n = nc.value;
                    if (n == 4) { center(4); center(5); center(6); center(7); wg_fence(); }
                    const uint64_t desc = mkdesc(sb + (n < 56 ? slot_kv(n >> 3) + (n & 7) * 2048 : SM_QO + (n - 56) * 2048), 8192, 1024, 1) + wofs;
                    wgmma_rs56<1>(n < 28 ? accK : n < 56 ? accV : accQ, a[n % 28], desc, n % 28 != 0);
                });
                wg_commit();
                if (PP && n0 < PP && (n1 < PP || wg == 0)) named_arrive(11 - wg, 256);
                if (n0 > 0) wg_wait<1>();
            };
            const uint32_t hs = sb + tid * 16 + warp * 512;
            auto hand_over = [&](const uint32_t (&v)[8], int kv) {
                mbar_wait(bars + 8 * (kv ? B_DONE1 + 5 : B_DONEX), 0);
                sts4(hs + (kv ? SM_HALOV : SM_HALOK), v[0], v[1], v[2], v[3]); sts4(hs + (kv ? SM_HALOV : SM_HALOK) + 512, v[4], v[5], v[6], v[7]);
                if (w == 3) named_arrive(6 + kv, 96);
            };
            auto take_over = [&](uint32_t (&v)[8], int kv) {
                if (w == 0) mbar_wait(bars + 8 * (B_HALO + 2 * kv + wg), 0);
                const uint32_t ad = w ? hs + (kv ? SM_HALOV : SM_HALOK) - 1024 : sb + lane * 16 + wg * 1024 + (kv ? SM_HALOV + 8192 : SM_HALOKIN);
                const uint4 u0 = lds4(ad), u1 = lds4(ad + 512);
                v[0] = u0.x; v[1] = u0.y; v[2] = u0.z; v[3] = u0.w; v[4] = u1.x; v[5] = u1.y; v[6] = u1.z; v[7] = u1.w;
            };
            if (PP && wg == 1) { pin2(mm0, mm1); named_arrive(10, 256); }
            center(0); center(1); center(2); center(3);
            static_for<0, 7>([&](auto pc) {
                constexpr int p = pc.value;
                mbar_wait(bars + 8 * (B_FULLKV + p), 0);
                if (p == 0 && tid == 0) STAMP(26);
                if (p == 3 && tid == 0) STAMP(27);
                FST(4 + p);
                batch(Int<8 * p>(), Int<8 * p + 8>());
                if (p > 0 && leader) mbar_arrive(bars + 8 * (B_DONE1 + p - 1));
                #pragma unroll
                for (int s = 8 * p + 8; s < 8 * p + 16 && s < 28; s++) center(s);
                if (p == 1) {
                    const float c0 = bf_hi(mm0), c1 = bf_hi(mm1);
                    q0 = fmaf(c0, fmaf(c0, 64.f * NSQ, -2.f * p0), (g & 1) ? cA[0][1] + cA[1][1] : cA[0][0] + cA[1][0]) - D_ * (m0 - c0) * (m0 - c0);
                    q1 = fmaf(c1, fmaf(c1, 64.f * NSQ, -2.f * p1), (g & 1) ? cB[0][3] + cB[1][3] : cB[0][2] + cB[1][2]) - D_ * (m1 - c1) * (m1 - c1);
                    asm("" : "+f"(q0), "+f"(q1));
                    q0 = t == (g >> 1) ? q0 : 0.f; q1 = t == (g >> 1) ? q1 : 0.f;
                    pin2(__float_as_uint(q0), __float_as_uint(q1));
                }
                constexpr int PK = NSQ < 5 ? 5 : 4, NR = 28 - 4 * NSQ;
                if (p >= 2 && p < PK) {
                    #pragma unroll
                    for (int s = 4 * NSQ + NR * (p - 2) / (PK - 2); s < 4 * NSQ + NR * (p - 1) / (PK - 2); s++) { sq(q0, a[s][0]); sq(q1, a[s][1]); sq(q0, a[s][2]); sq(q1, a[s][3]); }
                    pin2(__float_as_uint(q0), __float_as_uint(q1));
                }
                if (p == PK - 1) { q0 = quad_sum(q0); q1 = quad_sum(q1); }
                if (p == PK) {
                    r0 = rsqrt_approx(fmaxf(q0 * (1.f / D_), 0.f) + LN_EPS); r1 = rsqrt_approx(fmaxf(q1 * (1.f / D_), 0.f) + LN_EPS);
                    reg_fence(accK);
                    #pragma unroll
                    for (int j = 0; j < 7; j++) kpack(Kc, j, 2, r1);
                    hand_over(Kc, 0);
                }
                if (p == PK + 1) {
                    #pragma unroll
                    for (int j = 0; j < 7; j++) kpack(Kb, j, 0, r0);
                    #pragma unroll
                    for (int j = 0; j < 8; j += 2) pin2(Kb[j], Kb[j + 1]);
                    ls0 = LOG2E_SCALE * r0; ls1 = LOG2E_SCALE * r1;
                    pm = (2 * t <= g ? 0xFFFFu : 0u) | (2 * t + 1 <= g ? 0xFFFF0000u : 0u);
                    zero = never; asm volatile("" : "+r"(zero));
                    pin2(__float_as_uint(ls0), __float_as_uint(ls1)); pin2(pm, zero);
                }
                if (p == 2) ep = get_tag();
                if (p == 6) {
                    tl = &sc->tiles[ep & 1];
                    const int tt = 2 * tb + (w >> 1);
                    od = tl->o + tt * 14336 + (7 * hp) * 256 + (2 * (2 * (w & 1) + wg)) * 32 + lane;
                    oh = sc->hint_o + (tt * 32 + hp * 4 + (w & 1) * 2 + wg) * 2 + (lane & 1);
                    pin2((uint32_t)(uint64_t)od, (uint32_t)((uint64_t)od >> 32));
                    pin2((uint32_t)(uint64_t)oh, (uint32_t)((uint64_t)oh >> 32));
                }
            });
            if (tid == 0) STAMP(1);
            FST(11);
            mbar_wait(bars + 8 * B_FQ, 0);
            batch(Int<56>(), Int<60>());
            reg_fence(accV);
            if (leader) mbar_arrive(bars + 8 * (B_DONE1 + 6));
            if (tid == 0) STAMP(2);
            FST(12);
            #pragma unroll
            for (int j = 0; j < 7; j++) Vc[j] = movtrans(pack_bf16(accV[4 * j + 2] * r1, accV[4 * j + 3] * r1));
            Vc[7] = Vc[6];
            hand_over(Vc, 1);
            batch(Int<60>(), Int<66>());
            #pragma unroll
            for (int j = 0; j < 7; j++) {
                Vb[j] = movtrans(pack_bf16(accV[4 * j] * r0, accV[4 * j + 1] * r0));
                Vc[j] |= zero;
            }
            batch(Int<66>(), Int<72>());
            #pragma unroll
            for (int j = 0; j < 7; j++) pin2(Vb[j], Vc[j]);
            mbar_wait(bars + 8 * (B_FQ + 1), 0);
            FST(13);
            if (w > 0 && lane < 2) { const uint32_t now = gtime32(); st_relaxed4(oh, ep, now, ep, now); }
            batch(Int<72>(), Int<84>());
            FST(14);
            named_sync(1 + wg, 128);
            take_over(Ka, 0);
            if (tid == 0) STAMP(3);
            wg_wait<0>();
            reg_fence(accQ);
            if (tid == 0) STAMP(4);
            FST(15);
            const bool first = (tb == 0 && w == 0);
            uint32_t pA[2], pB0[2], pB1[2], pC[2], z0[2], z1[2];
            #pragma unroll
            for (int h = 0; h < 2; h++) {
                float sA[4] = {0.f, 0.f, 0.f, 0.f}, sB[4] = {0.f, 0.f, 0.f, 0.f}, sC[4] = {0.f, 0.f, 0.f, 0.f};
                #pragma unroll
                for (int k = 0; k < 2; k++) {
                    const float* qq = accQ + 12 * h + 8 * k;
                    uint32_t a0 = pack_bf16(qq[0], qq[1]), a1 = pack_bf16(qq[2], qq[3]);
                    if (h == 1 && k == 0) { a0 |= zero; a1 |= zero; }
                    const uint32_t a2 = pack_bf16(qq[4], qq[5]), a3 = pack_bf16(qq[6], qq[7]);
                    mma16816(sB, a0, a1, a2, a3, Kb[4 * h + 2 * k], Kb[4 * h + 2 * k + 1]);
                    mma16816(sA, a0, a1, a2, a3, Ka[4 * h + 2 * k], Ka[4 * h + 2 * k + 1]);
                    mma16816(sC, a0, a1, a2, a3, Kc[4 * h + 2 * k], Kc[4 * h + 2 * k + 1]);
                }
                const bool n0 = pm & 1, n1 = (int)pm < 0;
                const float l00 = n0 ? sB[0] : (first ? -INFINITY : sA[0]), l01 = n1 ? sB[1] : (first ? -INFINITY : sA[1]);
                const float l10 = n0 ? sC[2] : sB[2], l11 = n1 ? sC[3] : sB[3];
                const float x0 = -ls0 * quad_max(fmaxf(l00, l01)), x1 = -ls1 * quad_max(fmaxf(l10, l11));
                const float e00 = ex2(fmaf(l00, ls0, x0)), e01 = ex2(fmaf(l01, ls0, x0)), e10 = ex2(fmaf(l10, ls1, x1)), e11 = ex2(fmaf(l11, ls1, x1));
                const float i0 = rcp_approx(quad_sum(e00 + e01)), i1 = rcp_approx(quad_sum(e10 + e11));
                const uint32_t P0 = pack_bf16(e00 * i0, e01 * i0), P1 = pack_bf16(e10 * i1, e11 * i1);
                pB0[h] = P0 & pm; pA[h] = P0 & ~pm; pC[h] = P1 & pm; pB1[h] = P1 & ~pm; z0[h] = P0 & zero; z1[h] = P1 & zero;
            }
            float o[8][4];
            #pragma unroll
            for (int j = 0; j < 8; j++) {
                o[j][0] = o[j][1] = o[j][2] = o[j][3] = 0.f;
                mma16816(o[j], pB0[j >> 2], pB1[j >> 2], z0[j >> 2], pC[j >> 2], Vb[j - (j >> 2)], Vc[j - (j >> 2)]);
            }
            if (tid == 0) STAMP(12);
            FST(16);
            take_over(Va, 1);
            if (lane == 0) mbar_arrive(bars + 8 * B_DONEQ);
            if (tid == 0) STAMP(16);
            #pragma unroll
            for (int j = 0; j < 8; j++) mma1688(o[j], pA[j >> 2], z1[j >> 2], Va[j - (j >> 2)]);
            #pragma unroll
            for (int j = 0; j < 7; j++) {
                float v[4];
                #pragma unroll
                for (int c = 0; c < 4; c++) v[c] = j < 3 ? o[j][c] : j > 3 ? o[j + 1][c] : (t < 2 ? o[3][c] : o[4][c]);
                od[j * 256] = pack_bf16(v[0], v[1]);
                od[j * 256 + 32] = pack_bf16(v[2], v[3]);
            }
            if (tid == 0) STAMP(5);
            FST(17);
        }
        const uint32_t live = wg ^ 1;
        uint32_t ph = 0, rb10, rb11, rb20, rb21, late[14];
        uint32_t* late_ptr;
        auto undef = [](float (&v)[56]) {
            #pragma unroll
            for (int i = 0; i < 56; i++) asm volatile("" : "=f"(v[i]));
        };
        {
            float acc[56];
            const int hrow = 32 * (w >> 1) + 2 * ((lane & 7) + (lane & 8)) + (w & 1);
            const uint32_t ha = sb + SM_H + hrow * 128 + (((lane >> 4) ^ (hrow & 7)) << 4);
            uint4* sp = sc->stats + tt2 * 256 + 16 * w + g + 8 * (t & 1);
            uint4* sp_out = sp + q * 64;
            const uint4* sp_in = sp + (t & 2) * 64;
            uint32_t* hd = tl->hn + (q * 64 + tt2) * 1792 + w * 448 + lane;
            pin_ptr(never, sp_out); pin_ptr(never, sp_in); pin_ptr(never, hd);
            float s0 = 0.f, s1 = 0.f, q0 = 0.f, q1 = 0.f, s2 = 0.f, s3 = 0.f, q2 = 0.f, q3 = 0.f;
            auto sums = [&](int j0, int j1) {
                #pragma unroll
                for (int j = j0; j < j1; j++) {
                    s0 += acc[4 * j]; s2 += acc[4 * j + 1]; q0 = fmaf(acc[4 * j], acc[4 * j], q0); q2 = fmaf(acc[4 * j + 1], acc[4 * j + 1], q2);
                    s1 += acc[4 * j + 2]; s3 += acc[4 * j + 3]; q1 = fmaf(acc[4 * j + 2], acc[4 * j + 2], q1); q3 = fmaf(acc[4 * j + 3], acc[4 * j + 3], q3);
                }
            };
            if (live) {
                mbar_wait(bars + 8 * B_FULLWO, 0);
                #pragma unroll
                for (int jp = 0; jp < 7; jp++) {
                    uint32_t xx[4];
                    ldsm4(xx, hcol(ha, jp));
                    #pragma unroll
                    for (int r = 0; r < 4; r++) { acc[8 * jp + 2 * r] = bf_lo(xx[r]); acc[8 * jp + 2 * r + 1] = bf_hi(xx[r]); }
                }
                reg_fence(acc);
                auto od_ = [&](int s) { return mkdesc(sb + SM_QO + s * 2048, 1024, 128, 0); };
                auto wd_ = [&](int s) { return mkdesc(sb + slot_wo(s >> 2) + (s & 3) * 2048, 8192, 1024, 1); };
                float accl[32], accr[24];
                #pragma unroll
                for (int i = 0; i < 5; i++) {
                    if (i < 4) mbar_wait(bars + 8 * (B_FULLO + i), 0);
                    if (i == 0 && tid == 0) STAMP(7);
                    if (i == 1) {
                        const unsigned short* p1 = (const unsigned short*)b1 + max(ft, 0) * 64 + 16 * w + g;
                        const unsigned short* p2 = (const unsigned short*)b2 + tt2 * 64 + 16 * w + g;
                        rb10 = ld_u16(p1); rb11 = ld_u16(p1 + 8); rb20 = ld_u16(p2); rb21 = ld_u16(p2 + 8);
                    }
                    wg_fence();
                    #pragma unroll
                    for (int ss = 0; ss < 7; ss++) {
                        if (i < 3) wgmma_ss112<0, 1>(acc, od_(7 * i + ss), wd_(7 * i + ss));
                        else if (i == 4) wgmma_ss64<0, 1>(accl, od_(21 + ss), wd_(21 + ss));
                        else if (ss == 0) wgmma_ss48<0, 1, 0>(accr, od_(21), wd_(21) + 512);
                        else wgmma_ss48<0, 1>(accr, od_(21 + ss), wd_(21 + ss) + 512);
                    }
                    wg_commit();
                    if (i > 0) {
                        wg_wait<1>();
                        if (i == 3) {
                            reg_fence(acc);
                            #pragma unroll
                            for (int c = 0; c < 32; c++) accl[c] = __uint_as_float(__float_as_uint(acc[c]) | never);
                            reg_fence(accl);
                        }
                        if (i < 4 && leader) mbar_arrive(bars + 8 * (B_DONEO + i - 1));
                    }
                }
                reg_fence(accr);
                #pragma unroll
                for (int c = 0; c < 24; c++) acc[32 + c] += accr[c];
                sums(8, 14);
                pin4(never, s0, s1, s2, s3); pin4(never, q0, q1, q2, q3);
                wg_wait<0>();
                reg_fence(accl);
                #pragma unroll
                for (int c = 0; c < 32; c++) acc[c] = accl[c];
                if (leader) mbar_arrive(bars + 8 * (B_DONEO + 3));
                if (tid == 0) STAMP(8);
            } else undef(acc);
            if (live || (DRY2 && w == 3)) {
            sums(0, 8);
            s0 += s2; s1 += s3; q0 += q2; q1 += q3;
            float sr = ((t & 1) ? s1 : s0) + __shfl_xor_sync(0xffffffffu, (t & 1) ? s0 : s1, 1), qr = ((t & 1) ? q1 : q0) + __shfl_xor_sync(0xffffffffu, (t & 1) ? q0 : q1, 1);
            sr += __shfl_xor_sync(0xffffffffu, sr, 2); qr += __shfl_xor_sync(0xffffffffu, qr, 2);
            st_relaxed4_if(t < 2 * live, sp_out, __float_as_uint(sr), __float_as_uint(qr), ep);
            if (never) mbar_arrive(bars);
            if (tid == 0) STAMP(9);
            #pragma unroll
            for (int jp = 0; jp < 7; jp++)
                stsm4_if(live, hcol(ha, jp), pack_bf16(acc[8 * jp], acc[8 * jp + 1]), pack_bf16(acc[8 * jp + 2], acc[8 * jp + 3]),
                      pack_bf16(acc[8 * jp + 4], acc[8 * jp + 5]), pack_bf16(acc[8 * jp + 6], acc[8 * jp + 7]));
            uint4 v0, v1;
            do { v0 = ld_relaxed4(sp_in); v1 = ld_relaxed4(sp_in + 64); } while (live && __any_sync(0xffffffffu, v0.w != ep || v1.w != ep));
            if (tid == 0) STAMP(10);
            sr = __uint_as_float(v0.x) + __uint_as_float(v1.x); qr = __uint_as_float(v0.y) + __uint_as_float(v1.y);
            sr += __shfl_xor_sync(0xffffffffu, sr, 2); qr += __shfl_xor_sync(0xffffffffu, qr, 2);
            const float m = sr * (1.f / D_), v = fmaxf(qr * (1.f / D_) - m * m, 0.f);
            const float r = rsqrt_approx(fmaf(v, 4.f + 4.f * LN_EPS, 4.f * LN_EPS * LN_EPS)), c = -m * r;
            const float r0 = __shfl_sync(0xffffffffu, r, lane & ~1), c0 = __shfl_sync(0xffffffffu, c, lane & ~1);
            const float r1 = __shfl_sync(0xffffffffu, r, lane | 1), c1 = __shfl_sync(0xffffffffu, c, lane | 1);
            #pragma unroll
            for (int j = 0; j < 14; j++) st_global_if(live, hd + j * 32, pack_bf16(fmaf(acc[4 * j], r0, c0), fmaf(acc[4 * j + 1], r0, c0)));
            if (never) mbar_arrive(bars);
            #pragma unroll
            for (int j = 0; j < 14; j++) late[j] = pack_bf16(fmaf(acc[4 * j + 2], r1, c1), fmaf(acc[4 * j + 3], r1, c1));
            late_ptr = hd + 32 * 1792;
            if (tid == 0) STAMP(11);
            }
        }
        if (!live) {
            check_tiles(TSVAL 4, w, lane, ph, sb + SM_QO, tl->o + tt2 * 14336, B_FULLO);
            if (has_b1) check_tiles(TSVAL 32, w, lane, ph, sb + SM_BRING, tl->hn + q * 32 * 3584, B_FULLB);
            check_tiles(TSVAL 28, w, lane, ph, sb + SM_BRING, tl->u + q * 28 * 3584, B_FULLB);
            return;
        }
        if (has_b1) {
            float acc[56];
            uint32_t* ud = tl->u + (q * 56 + ft) * 1792 + w * 448 + lane;
            #pragma unroll
            for (int j = 0; j < 56; j++) acc[j] = 0.5f * bf_lo((j & 2) ? rb11 : rb10);
            #pragma unroll 1
            for (uint32_t pass = never; pass < 2; pass++) {
                if (pass) {
                    mix_mainloop<32>(TSVAL acc, 0, leader, late, late_ptr, true);
                    if (tid == 0) STAMP(14);
                }
                #pragma unroll
                for (int j = 0; j < 14; j++) st_global_if(pass, ud + j * 32, pack_bf16(gelu_half(acc[4 * j]), gelu_half(acc[4 * j + 1])));
            }
            if (tid == 0) STAMP(15);
            #pragma unroll
            for (int j = 0; j < 14; j++) late[j] = pack_bf16(gelu_half(acc[4 * j + 2]), gelu_half(acc[4 * j + 3]));
            late_ptr = ud + 28 * 1792;
        } else {
            #pragma unroll
            for (int c = 0; c < 14; c++) st_global_if(1, late_ptr + c * 32, late[c]);
        }
        {
            float acc[56];
            const uint32_t ad = sb + SM_H + (16 * w + (lane & 15)) * 128 + (((lane >> 4) ^ (lane & 7)) << 4);
            const float bb0 = bf_lo(rb20), bb1 = bf_lo(rb21);
            named_sync(1, 128);
            #pragma unroll
            for (int jp = 0; jp < 7; jp++) {
                uint32_t hh[4];
                ldsm4(hh, hcol(ad, jp));
                #pragma unroll
                for (int r = 0; r < 4; r++) { acc[8 * jp + 2 * r] = bf_lo(hh[r]) + ((r & 1) ? bb1 : bb0); acc[8 * jp + 2 * r + 1] = bf_hi(hh[r]) + ((r & 1) ? bb1 : bb0); }
            }
            #pragma unroll 1
            for (uint32_t pass = never; pass < 2; pass++) {
                if (pass) {
                    mix_mainloop<28>(TSVAL acc, has_b1, leader, late, late_ptr, has_b1);
                    if (leader) mbar_arrive(bars + 8 * B_END);
                    if (tid == 0) STAMP(18);
                }
                #pragma unroll
                for (int jp = 0; jp < 7; jp++)
                    stsm4_if(1, hcol(ad, jp), pack_bf16(acc[8 * jp], acc[8 * jp + 1]), pack_bf16(acc[8 * jp + 2], acc[8 * jp + 3]),
                             pack_bf16(acc[8 * jp + 4], acc[8 * jp + 5]), pack_bf16(acc[8 * jp + 6], acc[8 * jp + 7]));
                fence_async_smem();
                __syncwarp();
            }
            if (elect()) {
                tma2d_store(&tm_out64, c64, tt2 * 64 + 16 * w, sb + SM_H + w * 2048);
                tma2d_store(&tm_out48, c48, tt2 * 64 + 16 * w, sb + SM_H + 8192 + w * 2048);
            }
            asm volatile("cp.async.bulk.commit_group;" ::: "memory");
            asm volatile("cp.async.bulk.wait_group.read 0;" ::: "memory");
            if (tid == 0) { sc->epoch[slot] = ep; STAMP(19); }
        }
    } else {
        asm volatile("setmaxnreg.dec.sync.aligned.u32 56;");
        int warp2; asm("mov.u32 %0, %1;" : "=r"(warp2) : "r"(warp));
        if (warp2 > 8) {
            uint32_t ep, cl;
            uint4* const oh = sc->hint_o + (2 * tb * 32 + hp * 4) * 2 + (lane & 3);
            if (warp == 10) {
                post_hint(sc->hint_h + (q * 32 + tt2) * 2, 0, lane);
                if (has_b1) post_hint(sc->hint_u + (q * 32 + ft) * 2, 0, lane);
            }
            if (warp == 11) {
                ep = ld_volatile(&sc->epoch[slot]) + 1; cl = ld_acquire(&sc->clean[lane & 15]);
                post_hint(sc->hint_k + (tb * 8 + hp) * 2, 0, lane);
                if (lane < (tb < 15 ? 4 : 0)) st_relaxed4(oh + 128, 0, 0, 0, 0);
                if (lane < (tb ? 0 : 4)) st_relaxed4(oh, 0, 0, 0, 0);
            }
            if (elect()) {
                if (warp == 9) {
                    #pragma unroll
                    for (int i = B_DONE1; i < B_DONEO; i++) mbar_init(bars + 8 * i, i < B_DONEX ? 2 : i == B_DONEX ? 8 : 9);
                    mbar_init(bars + 8 * B_CLR, 1);
                }
                #pragma unroll
                for (int i = 0; i < 34; i++) mbar_init(bars + 8 * (B_DONEO + i) + (warp - 9) * 272, 1);
                asm volatile("fence.mbarrier_init.release.cluster;" ::: "memory");
            }
            named_sync(0, 384);
            if (warp == 9) named_arrive(4, 64);
            if (warp < 11) {
                ep = get_tag();
                mbar_wait(bars + 8 * (B_DONE1 + HALO_AT), 0);
                #pragma unroll 1
                for (int kv = 0; kv < 2; kv++) {
                    uint4 v0 = {}, v1 = {}, v2 = {};
                    if (tb > 0) {
                        const uint4* hg = sc->halo + ((((tb - 1) * 8 + hp) * 2 + warp - 9) * 2 + kv) * 96 + lane;
                        if (kv == 0) while (ld_relaxed(sc->hint_k + ((tb - 1) * 8 + hp) * 2) != ep) {}
                        do { v0 = ld_relaxed4(hg); v1 = ld_relaxed4(hg + 32); v2 = ld_relaxed4(hg + 64); } while (!__all_sync(0xffffffffu, v0.w == ep && v1.w == ep && v2.w == ep));
                    }
                    if (kv) mbar_wait(bars + 8 * (B_DONE1 + 5), 0);
                    const uint32_t hs = sb + lane * 16 + (warp - 9) * 1024 + (kv ? SM_HALOV + 8192 : SM_HALOKIN);
                    sts4(hs, v0.x, v0.y, v0.z, v1.x); sts4(hs + 512, v1.y, v1.z, v2.x, v2.y);
                    __syncwarp();
                    if (lane == 0) mbar_arrive(bars + 8 * (B_HALO + 2 * kv + warp - 9));
                }
                if (tid == 288) STAMP(21);
            }
            if (warp == 10) {
                mbar_wait(bars + 8 * (B_FULLO + 3), 0);
                mbar_wait(bars + 8 * (B_DONEO + HINT_H), 0);
                post_time(sc->hint_h + (q * 32 + tt2) * 2, ep, lane);
                if (has_b1) {
                    mbar_wait(bars + 8 * (B_DONE + HINT_U), 0);
                    post_time(sc->hint_u + (q * 32 + ft) * 2, ep, lane);
                } else if (lane == 0) {
                    mbar_wait(bars + 8 * (B_DONEO + 3), 0);
                    uint32_t t = clock32() + PF_AT;
                    #pragma unroll 1
                    for (int i = 0; i < PF_N; i++) {
                        while ((int)(clock32() - t) < 0) __nanosleep(40);
                        const int c = i * 16 + mi;
                        bulk_prefetch((const char*)w2 + (c >> 1) * 65536 + (c & 1) * 16384, 16384);
                        t += PF_PACE;
                    }
                }
            } else if (warp == 11) {
                #pragma unroll 1
                for (uint32_t e = ep; e != ep + 2; e++) {
                    if (!has_b1 && __shfl_sync(0xffffffffu, cl, mi) != e) {
                        if (e != ep) { mbar_wait_wd(bars + 8 * (B_DONEO + 3), 0); const uint32_t t = clock32(); while (clock32() - t < CL_AT) __nanosleep(100); __syncwarp(); }
                        constexpr int NL = sizeof(Tiles) / 2048;
                        uint4* p = (uint4*)&sc->tiles[e & 1] + (mi * NL + (lane >> 1)) * 8 + (lane & 7);
                        #pragma unroll 7
                        for (int i = 0; i < NL / 16; i++) st_relaxed4(p + i * 128, EMPTY, EMPTY, EMPTY, EMPTY);
                        __syncwarp();
                        if (lane == 0) { st_release(&sc->clean[mi], e); STAMP(24); }
                        __syncwarp();
                    }
                    if (e == ep) {
                        const long long t0 = clock64();
                        while (__any_sync(0xffffffffu, (int)(cl - ep) < 0)) { cl = ld_acquire(&sc->clean[lane & 15]); if (clock64() - t0 > WD_CLKS) __trap(); }
                        if (lane == 0) { *(volatile uint32_t*)(smem_raw + SM_TAG) = ep; mbar_arrive(bars + 8 * B_CLR); }
                        uint4* hg = sc->halo + (tb * 8 + hp) * 384 + lane;
                        #pragma unroll 1
                        for (int kv = 0; kv < 2; kv++) {
                            const uint32_t hs = sb + lane * 16 + 3072 + (kv ? SM_HALOV : SM_HALOK);
                            named_sync(6 + kv, 96);
                            #pragma unroll
                            for (int p = 0; p < 2; p++) {
                                const uint4 u0 = lds4(hs + p * 4096), u1 = lds4(hs + p * 4096 + 512);
                                st_relaxed4(hg + p * 192, u0.x, u0.y, u0.z, ep); st_relaxed4(hg + p * 192 + 32, u0.w, u1.x, u1.y, ep); st_relaxed4(hg + p * 192 + 64, u1.z, u1.w, ep, ep);
                            }
                            hg += 96;
                            if (kv == 0) {
                                post_hint(sc->hint_k + (tb * 8 + hp) * 2, ep, lane);
                                #pragma unroll
                                for (int j = 0; j < 6; j++) st_relaxed4(hg + j * 32 + (j / 3) * 96, 0, 0, 0, 0);
                            }
                        }
                        const uint32_t now = gtime32() - LATE_O;
                        if (lane < (tb < 15 ? 4 : 0)) st_relaxed4(oh + 128, ep, now, ep, now);
                        if (lane < (tb ? 0 : 4)) st_relaxed4(oh, ep, now, ep, now);
                        if (lane == 0) STAMP(23);
                        if (lane == 0) mbar_arrive(bars + 8 * B_DONEQ);
                    }
                }
                if (lane == 0) {
                    mbar_wait_wd(bars + 8 * B_END, 0);
                }
            } else {
                int aslot = 0;
                if (lane == 0) { prefetch_map(&tm_out64); prefetch_map(&tm_out48); }
                if (has_b1) {
                    #pragma unroll 1
                    for (int i = 0; i < 16; i++) {
                        mbar_wait(bars + 8 * (i < NA_SLOTS ? B_DONEQ + ((A_SCHED >> (4 * i)) & 15) : B_DONE + 1 + ((i - NA_SLOTS) * A3_END) / (15 - NA_SLOTS)), 0);
                        if (elect()) {
                            const uint32_t bar = bars + 8 * (B_FULLA + i), dst = sb + SM_ARING + aslot * 16384;
                            mbar_expect(bar, 16384);
                            tma5d(dst, &tm_w1, ft * 64, (i & 7) * 8, i >> 3, bar);
                        }
                        aslot = aslot == NA_SLOTS - 1 ? 0 : aslot + 1;
                    }
                }
                aslot = 16 % NA_SLOTS;
                #pragma unroll 1
                for (int i = 0; i < 14; i++) {
                    if (i >= NA_SLOTS) mbar_wait(bars + 8 * (B_DONE + 1 + ((i - NA_SLOTS) * A4_END) / (13 - NA_SLOTS)), has_b1);
                    else if (has_b1) {
                        mbar_wait(bars + 8 * (B_DONE + max(33 - 2 * NA_SLOTS + 2 * i, W2_AT)), 0);
                        if (i >= W2_HOLD) mbar_wait(bars + 8 * B_FULLB, 1);
                    } else if (i == 0) { mbar_wait(bars + 8 * (B_DONEO + 3), 0); const uint32_t t = clock32() + PF_AT + 12 * PF_PACE; while ((int)(clock32() - t) < 0) __nanosleep(100); }
                    if (elect()) {
                        const uint32_t bar = bars + 8 * (B_FULLA + i);
                        mbar_expect(bar, 16384);
                        tma5d(sb + SM_ARING + aslot * 16384, &tm_w2, tt2 * 64, (i < 7 ? i : i - 7) * 8, i >= 7, bar);
                    }
                    aslot = aslot == NA_SLOTS - 1 ? 0 : aslot + 1;
                }
            }
        } else {
            auto krot = [&](int kb) { const int k = kb * 64 + (G & 1) * 64 * ROT; return k < 448 ? k : k - 448; };
            if (elect()) {
                #pragma unroll
                for (int i = 0; i < 7; i++) mbar_init(bars + 8 * i, 1);
                asm volatile("fence.mbarrier_init.release.cluster;" ::: "memory");
                if (STAG && G >= 2) { const uint32_t t0 = clock32(); while (clock32() - t0 < STAG) {} }
                #pragma unroll 1
                for (int kb = 0; kb < 7; kb++) {
                    const uint32_t st = sb + slot_x(kb), bar = bars + 8 * (B_FULLX + kb);
                    mbar_expect(bar, 16384);
                    tma3d(st, &tm_x, krot(kb), 0, tb * 64, bar); tma3d(st + 8192, &tm_x, krot(kb), 1, tb * 64, bar);
                }
                #pragma unroll
                for (int i = 7; i < B_DONE1; i++) mbar_init(bars + 8 * i, 1);
                asm volatile("fence.mbarrier_init.release.cluster;" ::: "memory");
            }
            named_arrive(0, 384);
            #pragma unroll 1
            for (int kb = 0; kb < 7; kb++) {
                if (kb == 6) { named_sync(4, 64); mbar_wait(bars + 8 * B_DONEX, 0); }
                if (elect()) {
                    const uint32_t st = sb + slot_kv(kb), bar = bars + 8 * (B_FULLKV + kb);
                    mbar_expect(bar, 16384);
                    #pragma unroll
                    for (int i = 0; i < 2; i++) {
                        const int n = 2 * kb + (ROT ? i : i ^ (G & 1));
                        tma2d(st + (n & 1) * 8192, &tm_wqkv, (n < 7 ? 448 : 896) + wcol, krot(n < 7 ? n : n - 7), bar);
                    }
                }
            }
            if (elect()) {
                mbar_expect(bars + 8 * B_FQ, 32768);
                mbar_expect(bars + 8 * (B_FQ + 1), 24576);
                #pragma unroll 1
                for (int i = 0; i < 7; i++) { const int j = ROT || i == 6 ? i : i ^ (G & 1); tma2d(sb + SM_QO + j * 8192, &tm_wqkv, wcol, krot(j), bars + 8 * (B_FQ + (i >> 2))); }
                mbar_expect(bars + 8 * B_FULLWO, 512 * 112 * 2);
            }
            #pragma unroll 1
            for (int i = 0; i < 7; i++) {
                const int kb = ((q & 1 ? WO_ORD1 : WO_ORD0) >> (4 * i)) & 7;
                if (kb < 5) mbar_wait(bars + 8 * (B_DONE1 + kb), 0);
                if (i == WO_HOLD) { mbar_wait(bars + 8 * (B_HALO + 2), 0); mbar_wait(bars + 8 * (B_HALO + 3), 0); }
                if (elect()) {
                    tma2d(sb + slot_wo(kb), &tm_wo64, c64, kb * 64, bars + 8 * B_FULLWO);
                    tma2d(sb + slot_wo(kb) + 8192, &tm_wo48, c48, kb * 64, bars + 8 * B_FULLWO);
                }
            }
            if (XR_HOLD) { mbar_wait(bars + 8 * (B_HALO + 2), 0); mbar_wait(bars + 8 * (B_HALO + 3), 0); }
            if (elect()) {
                tma2d(sb + SM_H, &tm_xr64, c64, tt2 * 64, bars + 8 * B_FULLWO);
                tma2d(sb + SM_H + 8192, &tm_xr48, c48, tt2 * 64, bars + 8 * B_FULLWO);
            }
            if (smem_u32(smem_raw) != SB) __trap();
            const uint32_t ep = get_tag();
            const Tiles* const tl = &sc->tiles[ep & 1];
            mbar_wait(bars + 8 * (B_DONE1 + 6), 0);
            wait_hints(TSVAL sc->hint_o + (tt2 * 32 + lane) * 2, ep, GO_O, 38);
            mbar_wait(bars + 8 * B_DONEQ, 0);
            if (elect()) {
                #pragma unroll
                for (int i = 0; i < 4; i++) {
                    mbar_expect(bars + 8 * (B_RAW + i), 14336);
                    bulk_ld(sb + SM_QO + i * 14336, tl->o + tt2 * 14336 + i * 3584, 14336, bars + 8 * (B_RAW + i));
                }
            }
            if (lane == 0) STAMP(20);
            mbar_wait(bars + 8 * (B_DONEO + 2), 0);
            if (has_b1) {
                mix_producer_b<32>(TSVAL 0, sc->go, ep, tl->hn + q * 32 * 3584, lane);
            }
            mix_producer_b<28>(TSVAL has_b1, sc->go + 8, ep, tl->u + q * 28 * 3584, lane);
        }
    }
}

typedef CUresult (*EncodeFn)(CUtensorMap*, CUtensorMapDataType, cuuint32_t, void*, const cuuint64_t*, const cuuint64_t*, const cuuint32_t*,
                             const cuuint32_t*, CUtensorMapInterleave, CUtensorMapSwizzle, CUtensorMapL2promotion, CUtensorMapFloatOOBfill);

void make_map(EncodeFn fn, CUtensorMap* tm, const void* ptr, int rank, const cuuint64_t* dims, const cuuint64_t* strides, const cuuint32_t* box, CUtensorMapSwizzle sw) {
    cuuint32_t es[5] = {1, 1, 1, 1, 1};
    fn(tm, CU_TENSOR_MAP_DATA_TYPE_BFLOAT16, rank, const_cast<void*>(ptr), dims, strides, box, es, CU_TENSOR_MAP_INTERLEAVE_NONE, sw,
       CU_TENSOR_MAP_L2_PROMOTION_NONE, CU_TENSOR_MAP_FLOAT_OOB_FILL_NONE);
}

}

extern "C" void kernel_launch(void* const* d_in, const int* in_sizes, int n_in, void* d_out, int out_size) {
    const __nv_bfloat16* x = (const __nv_bfloat16*)d_in[0];
    const __nv_bfloat16* wqkv = (const __nv_bfloat16*)d_in[1];
    const __nv_bfloat16* wo = (const __nv_bfloat16*)d_in[2];
    const __nv_bfloat16* w1 = (const __nv_bfloat16*)d_in[4];
    const __nv_bfloat16* b1 = (const __nv_bfloat16*)d_in[5];
    const __nv_bfloat16* w2 = (const __nv_bfloat16*)d_in[6];
    const __nv_bfloat16* b2 = (const __nv_bfloat16*)d_in[7];

    void* fnp = nullptr; cudaDriverEntryPointQueryResult qr;
    cudaGetDriverEntryPoint("cuTensorMapEncodeTiled", &fnp, cudaEnableDefault, &qr);
    EncodeFn fn = (EncodeFn)fnp;
    CUtensorMap tx, twqkv, two64, two48, tw1, tw2, txr64, txr48, tout64, tout48;
    { cuuint64_t d[3] = {448, 2, 1024}, s[2] = {896, 1792}; cuuint32_t b[3] = {64, 1, 64}; make_map(fn, &tx, x, 3, d, s, b, CU_TENSOR_MAP_SWIZZLE_128B); }
    { cuuint64_t d[2] = {1344, 448}, s[1] = {2688}; cuuint32_t b[2] = {64, 64}; make_map(fn, &twqkv, wqkv, 2, d, s, b, CU_TENSOR_MAP_SWIZZLE_128B); }
    { cuuint64_t d[2] = {448, 448}, s[1] = {896}; cuuint32_t b[2] = {64, 64}; make_map(fn, &two64, wo, 2, d, s, b, CU_TENSOR_MAP_SWIZZLE_128B); }
    { cuuint64_t d[2] = {448, 448}, s[1] = {896}; cuuint32_t b[2] = {48, 64}; make_map(fn, &two48, wo, 2, d, s, b, CU_TENSOR_MAP_SWIZZLE_128B); }
    { cuuint64_t d[5] = {1792, 8, 2, 64, 2}, s[4] = {2 * 3584, 3584, 32 * 3584, 16 * 3584}; cuuint32_t b[5] = {64, 8, 2, 8, 1}; make_map(fn, &tw1, w1, 5, d, s, b, CU_TENSOR_MAP_SWIZZLE_128B); }
    { cuuint64_t d[5] = {2048, 8, 2, 56, 2}, s[4] = {4096, 16 * 4096, 32 * 4096, 8 * 4096}; cuuint32_t b[5] = {64, 8, 2, 8, 1}; make_map(fn, &tw2, w2, 5, d, s, b, CU_TENSOR_MAP_SWIZZLE_128B); }
    { cuuint64_t d[2] = {448, 2048}, s[1] = {896}; cuuint32_t b[2] = {64, 64}; make_map(fn, &txr64, x, 2, d, s, b, CU_TENSOR_MAP_SWIZZLE_128B); }
    { cuuint64_t d[2] = {448, 2048}, s[1] = {896}; cuuint32_t b[2] = {48, 64}; make_map(fn, &txr48, x, 2, d, s, b, CU_TENSOR_MAP_SWIZZLE_128B); }
    { cuuint64_t d[2] = {448, 2048}, s[1] = {896}; cuuint32_t b[2] = {64, 16}; make_map(fn, &tout64, d_out, 2, d, s, b, CU_TENSOR_MAP_SWIZZLE_128B); }
    { cuuint64_t d[2] = {448, 2048}, s[1] = {896}; cuuint32_t b[2] = {48, 16}; make_map(fn, &tout48, d_out, 2, d, s, b, CU_TENSOR_MAP_SWIZZLE_128B); }

    void* scv = nullptr;
    cudaGetSymbolAddress(&scv, g_scratch);
    Scratch* scp = (Scratch*)scv;
    int dev = 0, sms = 0;
    cudaGetDevice(&dev);
    cudaDeviceGetAttribute(&sms, cudaDevAttrMultiProcessorCount, dev);
    if (sms == 132) {
        cudaFuncSetAttribute(fused_kernel<true>, cudaFuncAttributeMaxDynamicSharedMemorySize, SM_TOTAL);
        fused_kernel<true><<<132, 384, SM_TOTAL>>>(scp, wo, w1, b1, w2, b2, tx, twqkv, two64, two48, tw1, tw2, txr64, txr48, tout64, tout48);
    } else {
        cudaFuncSetAttribute(fused_kernel<false>, cudaFuncAttributeMaxDynamicSharedMemorySize, SM_TOTAL);
        fused_kernel<false><<<132, 384, SM_TOTAL>>>(scp, wo, w1, b1, w2, b2, tx, twqkv, two64, two48, tw1, tw2, txr64, txr48, tout64, tout48);
    }
}
```

```cpp
#include <cuda_runtime.h>
#include <cuda_bf16.h>
#include <cuda.h>
#include <stdint.h>

namespace {

constexpr int D_ = 448;
constexpr float LN_EPS = 1e-5f;
constexpr float LOG2E_SCALE = 0.1889822365046136f * 1.4426950408889634f;

struct Tiles {
    uint32_t o[32 * 57344 / 4];
    uint32_t hn[4 * 32 * 14336 / 4];
    uint32_t u[4 * 28 * 14336 / 4];
};
struct Scratch {
    uint4 halo[128 * 2 * 2 * 3 * 32];
    uint4 stats[32 * 4 * 64];
    uint4 hint_k[128 * 2];
    uint4 hint_o[32 * 32 * 2];
    uint4 hint_h[4 * 32 * 2];
    uint4 hint_u[4 * 32 * 2];
    uint4 go[16];
    uint32_t epoch[160];
    uint32_t clean[16];
    alignas(1024) Tiles tiles[2];
};
__device__ Scratch g_scratch;
#define STAMP(i) do {} while (0)
#define FST(i) do {} while (0)
#define TSARG
#define TSVAL

constexpr uint32_t SB = 1024;
constexpr int SM_SLOT = 16384;
__device__ __forceinline__ constexpr uint32_t slot_x(int kb) { return (kb ? 6 + kb : 0) * SM_SLOT; }
__device__ __forceinline__ constexpr uint32_t slot_kv(int kb) { return (kb < 5 ? 2 + kb : 6 - kb) * SM_SLOT; }
__device__ __forceinline__ constexpr uint32_t slot_wo(int kb) { return (kb < 6 ? 2 + kb : 12) * SM_SLOT; }
constexpr int SM_QO = 8 * SM_SLOT;
constexpr int SM_HALOK = SM_QO + 57344, SM_HALOV = 1 * SM_SLOT;
constexpr int NA_SLOTS = 6, NB_SLOTS = 8;
constexpr int SM_ARING = 0;
constexpr int SM_BRING = NA_SLOTS * 16384;
constexpr int SM_H = 212992;
constexpr int SM_TAG = SM_H + 8192 + 96;
constexpr int SM_HALOKIN = 229376;
constexpr int SM_BAR = 231424;
constexpr int SM_TOTAL = 232448;
constexpr int B_FULLX = 0;
constexpr int B_FULLKV = 7;
constexpr int B_FQ = 14;
constexpr int B_DONE1 = 16;
constexpr int B_DONEX = 23;
constexpr int B_DONEQ = 24;
constexpr int B_DONEO = 25;
constexpr int B_FULLO = 29;
constexpr int B_FULLWO = 33;
constexpr int B_END = 34;
constexpr int B_HALO = 35;
constexpr int B_FULLA = 39;
constexpr int B_FULLB = 55;
constexpr int B_DONE = 87;
constexpr int B_RAW = 119;
constexpr int B_CLR = 127;

constexpr long long WD_CLKS = 2000000000ll;

template<int N> struct Int { static constexpr int value = N; };
template<int A, int B, class F> __device__ __forceinline__ void static_for(F&& f) { if constexpr (A < B) { f(Int<A>()); static_for<A + 1, B>(f); } }

__device__ __forceinline__ uint32_t smem_u32(const void* p) { return (uint32_t)__cvta_generic_to_shared(p); }
__device__ __forceinline__ void mbar_init(uint32_t bar, uint32_t cnt) { asm volatile("mbarrier.init.shared::cta.b64 [%0], %1;" :: "r"(bar), "r"(cnt) : "memory"); }
__device__ __forceinline__ void mbar_expect(uint32_t bar, uint32_t bytes) { asm volatile("mbarrier.arrive.expect_tx.shared::cta.b64 _, [%0], %1;" :: "r"(bar), "r"(bytes) : "memory"); }
__device__ __forceinline__ void mbar_arrive(uint32_t bar) { asm volatile("mbarrier.arrive.shared::cta.b64 _, [%0];" :: "r"(bar) : "memory"); }
__device__ __forceinline__ bool mbar_try(uint32_t bar, uint32_t parity) {
    uint32_t ok;
    asm volatile("{\n.reg .pred p;\nmbarrier.try_wait.parity.shared::cta.b64 p, [%1], %2;\nselp.u32 %0, 1, 0, p;\n}" : "=r"(ok) : "r"(bar), "r"(parity) : "memory");
    return ok;
}
__device__ __forceinline__ bool mbar_test(uint32_t bar, uint32_t parity) {
    uint32_t ok;
    asm volatile("{\n.reg .pred p;\nmbarrier.test_wait.parity.shared::cta.b64 p, [%1], %2;\nselp.u32 %0, 1, 0, p;\n}" : "=r"(ok) : "r"(bar), "r"(parity) : "memory");
    return ok;
}
__device__ __forceinline__ void mbar_wait(uint32_t bar, uint32_t parity) {
    asm volatile("{\n.reg .pred p;\n"
                 "WAIT_LOOP:\n"
                 "mbarrier.try_wait.parity.shared::cta.b64 p, [%0], %1;\n"
                 "@!p bra WAIT_LOOP;\n}" :: "r"(bar), "r"(parity) : "memory");
}
__device__ __forceinline__ void mbar_wait_wd(uint32_t bar, uint32_t parity) {
    const long long t0 = clock64();
    while (!mbar_try(bar, parity)) { if (clock64() - t0 > WD_CLKS) __trap(); }
}
__device__ __forceinline__ bool elect() { uint32_t p; asm volatile("{\n.reg .pred P;\nelect.sync _|P, 0xffffffff;\nselp.u32 %0, 1, 0, P;\n}" : "=r"(p)); return p; }
__device__ __forceinline__ void tma2d(uint32_t dst, const CUtensorMap* tm, int c0, int c1, uint32_t bar) {
    asm volatile("cp.async.bulk.tensor.2d.shared::cluster.global.mbarrier::complete_tx::bytes [%0], [%1, {%3, %4}], [%2];" :: "r"(dst), "l"(tm), "r"(bar), "r"(c0), "r"(c1) : "memory");
}
__device__ __forceinline__ void tma3d(uint32_t dst, const CUtensorMap* tm, int c0, int c1, int c2, uint32_t bar) {
    asm volatile("cp.async.bulk.tensor.3d.shared::cluster.global.mbarrier::complete_tx::bytes [%0], [%1, {%3, %4, %5}], [%2];" :: "r"(dst), "l"(tm), "r"(bar), "r"(c0), "r"(c1), "r"(c2) : "memory");
}
__device__ __forceinline__ void tma5d(uint32_t dst, const CUtensorMap* tm, int c0, int c3, int c4, uint32_t bar) {
    asm volatile("cp.async.bulk.tensor.5d.shared::cluster.global.mbarrier::complete_tx::bytes [%0], [%1, {%3, 0, 0, %4, %5}], [%2];" :: "r"(dst), "l"(tm), "r"(bar), "r"(c0), "r"(c3), "r"(c4) : "memory");
}
__device__ __forceinline__ void tma2d_store(const CUtensorMap* tm, int c0, int c1, uint32_t src) {
    asm volatile("cp.async.bulk.tensor.2d.global.shared::cta.bulk_group [%0, {%2, %3}], [%1];" :: "l"(tm), "r"(src), "r"(c0), "r"(c1) : "memory");
}
__device__ __forceinline__ void bulk_ld(uint32_t dst, const void* src, uint32_t bytes, uint32_t bar) {
    asm volatile("cp.async.bulk.shared::cluster.global.mbarrier::complete_tx::bytes [%0], [%1], %2, [%3];" :: "r"(dst), "l"(src), "r"(bytes), "r"(bar) : "memory");
}
__device__ __forceinline__ void bulk_prefetch(const void* src, uint32_t bytes) { asm volatile("cp.async.bulk.prefetch.L2.global [%0], %1;" :: "l"(src), "r"(bytes) : "memory"); }
__device__ __forceinline__ void prefetch_map(const CUtensorMap* tm) { asm volatile("prefetch.tensormap [%0];" :: "l"(tm) : "memory"); }
__device__ __forceinline__ void st_global_if(uint32_t c, uint32_t* p, uint32_t v) {
    asm volatile("{\n.reg .pred p;\nsetp.ne.u32 p, %2, 0;\n@p st.global.u32 [%0], %1;\n}" :: "l"(p), "r"(v), "r"(c) : "memory");
}
__device__ __forceinline__ void st_relaxed4_if(bool c, uint4* p, uint32_t a, uint32_t b, uint32_t d) {
    asm volatile("{\n.reg .b128 t;\n.reg .b64 a, b;\n.reg .pred p;\nsetp.ne.u32 p, %4, 0;\nmov.b64 a, {%1, %2};\nmov.b64 b, {%3, %3};\nmov.b128 t, {a, b};\n@p st.relaxed.gpu.global.b128 [%0], t;\n}" :: "l"(p), "r"(a), "r"(b), "r"(d), "r"((uint32_t)c) : "memory");
}
__device__ __forceinline__ void pin_ptr(uint32_t never, const void* a) {
    asm volatile("{\n.reg .pred p;\nsetp.ne.u32 p, %1, 0;\n@p st.shared.u64 [%1], %0;\n}" :: "l"(a), "r"(never) : "memory");
}
__device__ __forceinline__ void pin4(uint32_t never, float a, float b, float c, float d) {
    asm volatile("{\n.reg .pred p;\nsetp.ne.u32 p, %4, 0;\n@p st.shared.v4.f32 [%4], {%0,%1,%2,%3};\n}" :: "f"(a), "f"(b), "f"(c), "f"(d), "r"(never) : "memory");
}
__device__ __forceinline__ void fence_async_smem() { asm volatile("fence.proxy.async.shared::cta;" ::: "memory"); }
__device__ __forceinline__ uint32_t ld_acquire(const void* p) { uint32_t v; asm volatile("ld.acquire.gpu.global.u32 %0, [%1];" : "=r"(v) : "l"(p) : "memory"); return v; }
__device__ __forceinline__ void st_release(void* p, uint32_t v) { asm volatile("st.release.gpu.global.u32 [%0], %1;" :: "l"(p), "r"(v) : "memory"); }
__device__ __forceinline__ uint32_t ld_relaxed(const void* p) { uint32_t v; asm volatile("ld.relaxed.gpu.global.u32 %0, [%1];" : "=r"(v) : "l"(p) : "memory"); return v; }
__device__ __forceinline__ uint2 ld_relaxed2(const void* p) {
    uint2 v; asm volatile("{\n.reg .b64 a;\nld.relaxed.gpu.global.b64 a, [%2];\nmov.b64 {%0, %1}, a;\n}" : "=r"(v.x), "=r"(v.y) : "l"(p) : "memory"); return v;
}
__device__ __forceinline__ uint4 ld_relaxed4(const uint4* p) {
    uint4 v;
    asm volatile("{\n.reg .b128 t;\n.reg .b64 a, b;\nld.relaxed.gpu.global.b128 t, [%4];\nmov.b128 {a, b}, t;\nmov.b64 {%0, %1}, a;\nmov.b64 {%2, %3}, b;\n}" : "=r"(v.x), "=r"(v.y), "=r"(v.z), "=r"(v.w) : "l"(p) : "memory");
    return v;
}
__device__ __forceinline__ void st_relaxed4(uint4* p, uint32_t a, uint32_t b, uint32_t c, uint32_t d) {
    asm volatile("{\n.reg .b128 t;\n.reg .b64 a, b;\nmov.b64 a, {%1, %2};\nmov.b64 b, {%3, %4};\nmov.b128 t, {a, b};\nst.relaxed.gpu.global.b128 [%0], t;\n}" :: "l"(p), "r"(a), "r"(b), "r"(c), "r"(d) : "memory");
}
__device__ __forceinline__ uint32_t ld_u16(const unsigned short* p) { uint32_t v; asm volatile("ld.volatile.global.u16 %0, [%1];" : "=r"(v) : "l"(p) : "memory"); return v; }
__device__ __forceinline__ uint32_t ld_volatile(const uint32_t* p) { uint32_t v; asm volatile("ld.volatile.global.u32 %0, [%1];" : "=r"(v) : "l"(p) : "memory"); return v; }
__device__ __forceinline__ void named_arrive(int id, int n) { asm volatile("bar.arrive %0, %1;" :: "r"(id), "r"(n) : "memory"); }
__device__ __forceinline__ void named_sync(int id, int n) { asm volatile("bar.sync %0, %1;" :: "r"(id), "r"(n) : "memory"); }
__device__ __forceinline__ void wg_fence() { asm volatile("wgmma.fence.sync.aligned;" ::: "memory"); }
__device__ __forceinline__ void wg_commit() { asm volatile("wgmma.commit_group.sync.aligned;" ::: "memory"); }
template<int N> __device__ __forceinline__ void wg_wait() { asm volatile("wgmma.wait_group.sync.aligned %0;" :: "n"(N) : "memory"); }
template<int N> __device__ __forceinline__ void reg_fence(float (&d)[N]) {
    #pragma unroll
    for (int i = 0; i < N; i++) asm volatile("" : "+f"(d[i]) :: "memory");
}
__device__ __forceinline__ constexpr uint64_t mkdesc(uint32_t addr, uint32_t lbo, uint32_t sbo, uint32_t sw) {
    return (uint64_t)((addr & 0x3FFFF) >> 4) | ((uint64_t)(lbo >> 4) << 16) | ((uint64_t)(sbo >> 4) << 32) | ((uint64_t)sw << 62);
}
__device__ __forceinline__ void ldsm4(uint32_t (&r)[4], uint32_t addr) {
    asm volatile("ldmatrix.sync.aligned.m8n8.x4.shared.b16 {%0,%1,%2,%3}, [%4];" : "=r"(r[0]), "=r"(r[1]), "=r"(r[2]), "=r"(r[3]) : "r"(addr) : "memory");
}
__device__ __forceinline__ void stsm4_if(uint32_t c, uint32_t addr, uint32_t r0, uint32_t r1, uint32_t r2, uint32_t r3) {
    asm volatile("{\n.reg .pred p;\nsetp.ne.u32 p, %5, 0;\n@p stmatrix.sync.aligned.m8n8.x4.shared.b16 [%0], {%1,%2,%3,%4};\n}" :: "r"(addr), "r"(r0), "r"(r1), "r"(r2), "r"(r3), "r"(c) : "memory");
}
__device__ __forceinline__ void sts4(uint32_t a, uint32_t x, uint32_t y, uint32_t z, uint32_t w) { asm volatile("st.shared.v4.u32 [%0], {%1,%2,%3,%4};" :: "r"(a), "r"(x), "r"(y), "r"(z), "r"(w) : "memory"); }
__device__ __forceinline__ uint4 lds4(uint32_t a) { uint4 v; asm volatile("ld.shared.v4.u32 {%0,%1,%2,%3}, [%4];" : "=r"(v.x), "=r"(v.y), "=r"(v.z), "=r"(v.w) : "r"(a) : "memory"); return v; }
__device__ __forceinline__ uint32_t movtrans(uint32_t a) { uint32_t d; asm volatile("movmatrix.sync.aligned.m8n8.trans.b16 %0, %1;" : "=r"(d) : "r"(a)); return d; }
__device__ __forceinline__ uint32_t pack_bf16(float lo, float hi) { uint32_t r; asm("cvt.rn.bf16x2.f32 %0, %1, %2;" : "=r"(r) : "f"(hi), "f"(lo)); return r; }
__device__ __forceinline__ void sub_bf16x2(uint32_t& a, uint32_t b) { asm volatile("sub.rn.bf16x2 %0, %0, %1;" : "+r"(a) : "r"(b)); }
__device__ __forceinline__ float bf_lo(uint32_t v) { return __uint_as_float(v << 16); }
__device__ __forceinline__ float bf_hi(uint32_t v) { return __uint_as_float(v & 0xffff0000u); }
__device__ __forceinline__ void mma16816(float (&c)[4], uint32_t a0, uint32_t a1, uint32_t a2, uint32_t a3, uint32_t b0, uint32_t b1) {
    asm volatile("mma.sync.aligned.m16n8k16.row.col.f32.bf16.bf16.f32 {%0,%1,%2,%3}, {%4,%5,%6,%7}, {%8,%9}, {%0,%1,%2,%3};"
        : "+f"(c[0]), "+f"(c[1]), "+f"(c[2]), "+f"(c[3]) : "r"(a0), "r"(a1), "r"(a2), "r"(a3), "r"(b0), "r"(b1));
}
__device__ __forceinline__ void mma1688(float (&c)[4], uint32_t a0, uint32_t a1, uint32_t b0) {
    asm volatile("mma.sync.aligned.m16n8k8.row.col.f32.bf16.bf16.f32 {%0,%1,%2,%3}, {%4,%5}, {%6}, {%0,%1,%2,%3};"
        : "+f"(c[0]), "+f"(c[1]), "+f"(c[2]), "+f"(c[3]) : "r"(a0), "r"(a1), "r"(b0));
}
__device__ __forceinline__ float quad_sum(float v) { v += __shfl_xor_sync(0xffffffffu, v, 1); v += __shfl_xor_sync(0xffffffffu, v, 2); return v; }
__device__ __forceinline__ float quad_max(float v) { v = fmaxf(v, __shfl_xor_sync(0xffffffffu, v, 1)); v = fmaxf(v, __shfl_xor_sync(0xffffffffu, v, 2)); return v; }
__device__ __forceinline__ float ex2(float x) { float y; asm("ex2.approx.ftz.f32 %0, %1;" : "=f"(y) : "f"(x)); return y; }
__device__ __forceinline__ float rsqrt_approx(float x) { float y; asm("rsqrt.approx.ftz.f32 %0, %1;" : "=f"(y) : "f"(x)); return y; }
__device__ __forceinline__ float rcp_approx(float x) { float y; asm("rcp.approx.ftz.f32 %0, %1;" : "=f"(y) : "f"(x)); return y; }
constexpr float GELU_K1 = 2.f * 0.7978845608028654f;
__device__ __forceinline__ float gelu_half(float hx, float k1) {
    const float z = hx * fmaf(hx * hx, 8.f * 0.044715f * 0.7978845608028654f, k1);
    float t; asm("tanh.approx.f32 %0, %1;" : "=f"(t) : "f"(z));
    return fmaf(hx, t, hx);
}
__device__ __forceinline__ uint32_t gtime32() { uint32_t t; asm volatile("mov.u32 %0, %%globaltimer_lo;" : "=r"(t)); return t; }
__device__ __forceinline__ uint32_t clock32() { uint32_t t; asm volatile("mov.u32 %0, %%clock;" : "=r"(t)); return t; }
#define PF_PACE 400

#define PF_AT 4000
#define NSQ 6
#define HALO_AT 3
#define PF_N 12
#define HINT_U 22
#define SP_AT 2000
#define SP_N 0
#define WO_HOLD 7
#define A_SCHED 0x322188
#define WO_ORD0 0x4321065
#define WO_ORD1 0x3465210
#define XR_HOLD 0
#define ROT 0
#define NPIPE 1
#define CL_AT 4000
#define WARM 1
#define WARM_AT 300
#define W2_AT 23
#define W2_HOLD 5
#define A3_END 20
#define A4_END 16
#define GO_H 1216
#define GO_U 1440
#define STAG 0
#define GO_O 1216
#define LATE_O 256
#define PP 0
#define DRY2 1
#define LATE_AT 0
#define HINT_H 1
#define SLACK 256
#define GDEP 4
template<int TB> __device__ __forceinline__ void wgmma_rs56(float (&d)[28], const uint32_t (&a)[4], uint64_t db, int sc) {
    asm volatile("{\n.reg .pred p;\nsetp.ne.b32 p, %33, 0;\n"
        "wgmma.mma_async.sync.aligned.m64n56k16.f32.bf16.bf16 {%0, %1, %2, %3, %4, %5, %6, %7, %8, %9, %10, %11, %12, %13, %14, %15, %16, %17, %18, %19, %20, %21, %22, %23, %24, %25, %26, %27}, {%28, %29, %30, %31}, %32, p, 1, 1, %34;\n}\n"
        : "+f"(d[0]), "+f"(d[1]), "+f"(d[2]), "+f"(d[3]), "+f"(d[4]), "+f"(d[5]), "+f"(d[6]), "+f"(d[7]), "+f"(d[8]), "+f"(d[9]), "+f"(d[10]), "+f"(d[11]), "+f"(d[12]), "+f"(d[13]), "+f"(d[14]), "+f"(d[15]), "+f"(d[16]), "+f"(d[17]), "+f"(d[18]), "+f"(d[19]), "+f"(d[20]), "+f"(d[21]), "+f"(d[22]), "+f"(d[23]), "+f"(d[24]), "+f"(d[25]), "+f"(d[26]), "+f"(d[27])
        : "r"(a[0]), "r"(a[1]), "r"(a[2]), "r"(a[3]), "l"(db), "r"(sc), "n"(TB));
}

template<int TA, int TB, int SC = 1> __device__ __forceinline__ void wgmma_ss112(float (&d)[56], uint64_t da, uint64_t db) {
    asm volatile("wgmma.mma_async.sync.aligned.m64n112k16.f32.bf16.bf16 {%0, %1, %2, %3, %4, %5, %6, %7, %8, %9, %10, %11, %12, %13, %14, %15, %16, %17, %18, %19, %20, %21, %22, %23, %24, %25, %26, %27, %28, %29, %30, %31, %32, %33, %34, %35, %36, %37, %38, %39, %40, %41, %42, %43, %44, %45, %46, %47, %48, %49, %50, %51, %52, %53, %54, %55}, %56, %57, %60, 1, 1, %58, %59;\n"
        : "+f"(d[0]), "+f"(d[1]), "+f"(d[2]), "+f"(d[3]), "+f"(d[4]), "+f"(d[5]), "+f"(d[6]), "+f"(d[7]), "+f"(d[8]), "+f"(d[9]), "+f"(d[10]), "+f"(d[11]), "+f"(d[12]), "+f"(d[13]), "+f"(d[14]), "+f"(d[15]), "+f"(d[16]), "+f"(d[17]), "+f"(d[18]), "+f"(d[19]), "+f"(d[20]), "+f"(d[21]), "+f"(d[22]), "+f"(d[23]), "+f"(d[24]), "+f"(d[25]), "+f"(d[26]), "+f"(d[27]), "+f"(d[28]), "+f"(d[29]), "+f"(d[30]), "+f"(d[31]), "+f"(d[32]), "+f"(d[33]), "+f"(d[34]), "+f"(d[35]), "+f"(d[36]), "+f"(d[37]), "+f"(d[38]), "+f"(d[39]), "+f"(d[40]), "+f"(d[41]), "+f"(d[42]), "+f"(d[43]), "+f"(d[44]), "+f"(d[45]), "+f"(d[46]), "+f"(d[47]), "+f"(d[48]), "+f"(d[49]), "+f"(d[50]), "+f"(d[51]), "+f"(d[52]), "+f"(d[53]), "+f"(d[54]), "+f"(d[55])
        : "l"(da), "l"(db), "n"(TA), "n"(TB), "n"(SC));
}

template<int TA, int TB, int SC = 1> __device__ __forceinline__ void wgmma_ss64(float (&d)[32], uint64_t da, uint64_t db) {
    asm volatile("wgmma.mma_async.sync.aligned.m64n64k16.f32.bf16.bf16 {%0, %1, %2, %3, %4, %5, %6, %7, %8, %9, %10, %11, %12, %13, %14, %15, %16, %17, %18, %19, %20, %21, %22, %23, %24, %25, %26, %27, %28, %29, %30, %31}, %32, %33, %36, 1, 1, %34, %35;\n"
        : "+f"(d[0]), "+f"(d[1]), "+f"(d[2]), "+f"(d[3]), "+f"(d[4]), "+f"(d[5]), "+f"(d[6]), "+f"(d[7]), "+f"(d[8]), "+f"(d[9]), "+f"(d[10]), "+f"(d[11]), "+f"(d[12]), "+f"(d[13]), "+f"(d[14]), "+f"(d[15]), "+f"(d[16]), "+f"(d[17]), "+f"(d[18]), "+f"(d[19]), "+f"(d[20]), "+f"(d[21]), "+f"(d[22]), "+f"(d[23]), "+f"(d[24]), "+f"(d[25]), "+f"(d[26]), "+f"(d[27]), "+f"(d[28]), "+f"(d[29]), "+f"(d[30]), "+f"(d[31])
        : "l"(da), "l"(db), "n"(TA), "n"(TB), "n"(SC));
}

template<int TA, int TB, int SC = 1> __device__ __forceinline__ void wgmma_ss48(float (&d)[24], uint64_t da, uint64_t db) {
    asm volatile("wgmma.mma_async.sync.aligned.m64n48k16.f32.bf16.bf16 {%0, %1, %2, %3, %4, %5, %6, %7, %8, %9, %10, %11, %12, %13, %14, %15, %16, %17, %18, %19, %20, %21, %22, %23}, %24, %25, %28, 1, 1, %26, %27;\n"
        : "+f"(d[0]), "+f"(d[1]), "+f"(d[2]), "+f"(d[3]), "+f"(d[4]), "+f"(d[5]), "+f"(d[6]), "+f"(d[7]), "+f"(d[8]), "+f"(d[9]), "+f"(d[10]), "+f"(d[11]), "+f"(d[12]), "+f"(d[13]), "+f"(d[14]), "+f"(d[15]), "+f"(d[16]), "+f"(d[17]), "+f"(d[18]), "+f"(d[19]), "+f"(d[20]), "+f"(d[21]), "+f"(d[22]), "+f"(d[23])
        : "l"(da), "l"(db), "n"(TA), "n"(TB), "n"(SC));
}

template<int NKB>
__device__ __forceinline__ void mix_mainloop(TSARG float (&acc)[56], uint32_t par, bool leader) {
    constexpr uint32_t sb = SB, bars = sb + SM_BAR;
    constexpr int A0 = NKB == 32 ? 0 : 16 % NA_SLOTS;
    int bslot = 0, aslot = A0;
    reg_fence(acc);
    #pragma unroll 1
    for (int i = 0; i < NKB / 2; i++) {
        mbar_wait(bars + 8 * (B_FULLA + i), par);
        const uint64_t adesc = mkdesc(sb + SM_ARING, 8192, 1024, 1) + (uint32_t)(aslot * 1024);
        aslot = aslot == NA_SLOTS - 1 ? 0 : aslot + 1;
        #pragma unroll
        for (int jj = 0; jj < 2; jj++) {
            const int j = 2 * i + jj;
            mbar_wait(bars + 8 * (B_FULLB + j), par);
            const uint64_t bdesc = mkdesc(sb + SM_BRING, 1792, 128, 0) + (uint32_t)(bslot * 896);
            bslot = bslot == NB_SLOTS - 1 ? 0 : bslot + 1;
            wg_fence();
            #pragma unroll
            for (int s = 0; s < 4; s++) wgmma_ss112<1, 1>(acc, adesc + jj * 512 + s * 128, bdesc + s * 224);
            wg_commit();
            wg_wait<1>();
            if (j > 0 && leader) mbar_arrive(bars + 8 * (B_DONE + j - 1));
        }
    }
    wg_wait<0>();
    reg_fence(acc);
    if (leader) mbar_arrive(bars + 8 * (B_DONE + NKB - 1));
}

constexpr uint32_t EMPTY = 0xFFFFFFFFu;
__device__ __forceinline__ void post_hint(uint4* p, uint32_t ep, int lane) { if (lane < 2) st_relaxed4(p + lane, ep, ep, ep, ep); }
__device__ __forceinline__ void post_time(uint4* p, uint32_t ep, int lane) { const uint32_t now = gtime32(); if (lane < 2) st_relaxed4(p + lane, ep, now, ep, now); }

__device__ __forceinline__ void wait_hints(TSARG const uint4* hint, uint32_t ep, uint32_t delay, int st) {
    uint2 v;
    do { v = ld_relaxed2(hint); } while (!__all_sync(0xffffffffu, v.x == ep));
    const uint32_t t1 = gtime32(), age = __reduce_min_sync(0xffffffffu, t1 + 256 - v.y);
    if (elect()) STAMP(st);
    while (gtime32() - t1 + age < delay + 256) {}
    __syncwarp();
}

template<int NKB>
__device__ __forceinline__ void mix_producer_b(TSARG uint32_t par, const uint4* hints, uint32_t ep, const uint32_t* src, int lane) {
    constexpr uint32_t sb = SB, bars = sb + SM_BAR;
    wait_hints(TSVAL hints, ep, NKB == 32 ? GO_H : GO_U, NKB == 32 ? 42 : 43);
    mbar_wait(bars + 8 * (par ? B_DONE + 31 : B_DONEO + 3), 0);
    #pragma unroll 1
    for (int j = 0; j < NKB; j++) {
        if (j >= NB_SLOTS) mbar_wait(bars + 8 * (B_DONE + j - NB_SLOTS), par);
        if (j == 0 && lane == 0) STAMP(NKB == 32 ? 29 : 30);
        if (j == 7 && lane == 0) STAMP(NKB == 32 ? 35 : 36);
        if (elect()) {
            mbar_expect(bars + 8 * (B_RAW + (j & 7)), 14336);
            bulk_ld(sb + SM_BRING + (j & 7) * 14336, src + j * 3584, 14336, bars + 8 * (B_RAW + (j & 7)));
        }
    }
}
__device__ __forceinline__ void check_tiles(TSARG int n, int w, int lane, uint32_t dst, const uint32_t* src, int full, const uint32_t (&late)[14], uint32_t* late_ptr) {
    constexpr uint32_t bars = SB + SM_BAR;
    uint32_t ph = 0;
    if (n > 4) asm volatile("ld.shared.u32 %0, [%1];" : "=r"(ph) : "r"(SB + SM_TAG + 4 + 4 * w) : "memory");
    #pragma unroll 1
    for (int j = w; j < n; j += 4) {
        const uint32_t raw = bars + 8 * (B_RAW + (j & 7)), d = dst + (j & 7) * 14336, a = d + lane * 128 + (lane & 3) * 32 + (lane >> 2) * 4;
        bool bad;
        do {
            mbar_wait(raw, (ph >> (j & 4)) & 1);
            ph ^= 1u << (j & 4);
            if (j == 0 && lane == 0) STAMP(n == 4 ? 6 : n == 32 ? 31 : 32);
            uint32_t v0, v1, v2, v3;
            asm volatile("ld.shared.u32 %0, [%4];\nld.shared.u32 %1, [%4+4096];\nld.shared.u32 %2, [%4+8192];\nld.shared.u32 %3, [%4+10240];"
                         : "=r"(v0), "=r"(v1), "=r"(v2), "=r"(v3) : "r"(a) : "memory");
            bad = __any_sync(0xffffffffu, max(max(v0, v1), max(v2, v3)) == EMPTY);
            if (elect() && bad) {
                mbar_expect(raw, 14336); bulk_ld(d, src + j * 3584, 14336, raw);
            }
        } while (bad);
        if (lane == 0) {
            asm volatile("st.shared.u32 [%0], %1;" :: "r"(SB + SM_TAG + 4 + 4 * w), "r"(ph) : "memory");
            mbar_arrive(bars + 8 * (full + j));
        }
        if ((j >> 2) == LATE_AT && late_ptr) {
            #pragma unroll
            for (int c = 0; c < 14; c++) st_global_if(1, late_ptr + c * 32, late[c]);
        }
    }
}

__device__ __forceinline__ uint32_t hcol(uint32_t a, int jp) { return (a ^ ((jp & 3) << 5)) + (jp >> 2) * 8192; }

__device__ __forceinline__ uint32_t get_tag() {
    mbar_wait(SB + SM_BAR + 8 * B_CLR, 0);
    uint32_t v; asm volatile("ld.shared.u32 %0, [%1];" : "=r"(v) : "r"(SB + SM_TAG) : "memory"); return v;
}

template<bool USE_SMID>
__global__ void __launch_bounds__(384, 1)
fused_kernel(Scratch* __restrict__ sc, const __nv_bfloat16* __restrict__ wo,
             const __nv_bfloat16* __restrict__ w1, const __nv_bfloat16* __restrict__ b1,
             const __nv_bfloat16* __restrict__ w2, const __nv_bfloat16* __restrict__ b2,
             const __grid_constant__ CUtensorMap tm_x, const __grid_constant__ CUtensorMap tm_wqkv,
             const __grid_constant__ CUtensorMap tm_wo64, const __grid_constant__ CUtensorMap tm_wo48,
             const __grid_constant__ CUtensorMap tm_w1, const __grid_constant__ CUtensorMap tm_w2,
             const __grid_constant__ CUtensorMap tm_xr64, const __grid_constant__ CUtensorMap tm_xr48,
             const __grid_constant__ CUtensorMap tm_out64, const __grid_constant__ CUtensorMap tm_out48) {
    extern __shared__ __align__(1024) uint8_t smem_raw[];
    constexpr uint32_t sb = SB;
    constexpr uint32_t bars = sb + SM_BAR;
    const int tid = threadIdx.x, lane = tid & 31;
    const int warp = __shfl_sync(0xffffffffu, tid >> 5, 0);
    int slot;
    if (USE_SMID) {
        asm("{\n.reg .u32 s, t, u, d, a, b, c;\n.reg .pred p, r;\n"
            "mov.u32 s, %%smid;\nshr.u32 t, s, 1;\nsub.u32 u, t, 32;\nmul.lo.u32 d, u, 37;\nshr.u32 d, d, 8;\n"
            "and.b32 a, t, 7;\nshl.b32 a, a, 3;\nshr.u32 c, t, 3;\nadd.u32 a, a, c;\n"
            "mad.lo.u32 b, d, -55, 12;\nshl.b32 c, u, 3;\nadd.u32 b, b, c;\n"
            "setp.lt.u32 p, t, 32;\nselp.u32 a, a, b, p;\n"
            "setp.lt.u32 r, t, 62;\nselp.s32 c, 4, -58, r;\nadd.u32 c, t, c;\nsetp.lt.u32 p, t, 60;\nselp.u32 a, a, c, p;\n"
            "and.b32 s, s, 1;\nshl.b32 a, a, 1;\nadd.u32 %0, a, s;\n}" : "=r"(slot));
    } else slot = blockIdx.x;
    const int G = slot >> 4, mi = slot & 15;
    const int tb = 4 * (G >> 1) + (mi >> 2), hp = 2 * (mi & 3) + (G & 1);
    const int wcol = (hp * 56) & ~15;
    if (slot >= 128) {
        const uint32_t ep = ld_volatile(&sc->epoch[slot]) + 1;
        if (warp == 1 && mi < 2) {
            post_hint(sc->go + 8 * mi, 0, lane);
            const uint4* hint = (mi ? sc->hint_u : sc->hint_h) + 2 * min(lane, mi ? 27 : 31);
            while (ld_relaxed(sc->hint_k) != ep) __nanosleep(200);
            uint2 v[4];
            do {
                #pragma unroll
                for (int i = 0; i < 4; i++) v[i] = ld_relaxed2(hint + 64 * i);
            } while (!__all_sync(0xffffffffu, v[0].x == ep && v[1].x == ep && v[2].x == ep && v[3].x == ep));
            const uint32_t t1 = gtime32() + 256;
            const uint32_t age = min(min(t1 - v[0].y, t1 - v[1].y), min(t1 - v[2].y, t1 - v[3].y)) + (lane < 16 ? 0 : SLACK);
            const uint32_t ts = t1 - __reduce_min_sync(0xffffffffu, age);
            if (lane < 2) st_relaxed4(sc->go + 8 * mi + lane, ep, ts, ep, ts);
        }
        if (tid == 0) {
            const long long t0 = clock64();
            while (clock64() - t0 < SP_AT) {}
            #pragma unroll 1
            for (int i = 0; i < 7; i++) bulk_prefetch((const char*)wo + (i * 4 + mi) * 14336, 14336);
            #pragma unroll 1
            for (int i = 0; i < SP_N; i++) bulk_prefetch((const char*)w1 + (i * 4 + mi) * 14336, 14336);
            while (ld_relaxed(sc->hint_u) != ep) { __nanosleep(500); if (clock64() - t0 > WD_CLKS) __trap(); }
            sc->epoch[slot] = ep;
        }
        return;
    }
    const int q = mi & 3, tt2 = 4 * G + (mi >> 2), ft = 4 * (G - 1) + (mi >> 2);
    const bool has_b1 = G > 0;
    const int c64 = 64 * q, c48 = 256 + 48 * q;

    if (warp < 8) {
        if (WARM) {
            const int w = warp & 3, wg = warp >> 2, g = lane >> 2, t = lane & 3;
            if (WARM_AT) { const uint32_t t0 = clock32(); while (clock32() - t0 < WARM_AT) {} __syncwarp(); }
            if (w > 0) post_hint(sc->hint_o + ((2 * tb + (w >> 1)) * 32 + hp * 4 + (w & 1) * 2 + wg) * 2, 0, lane);
            if (wg == 0) {
                if (t < 2) st_relaxed4(sc->stats + tt2 * 256 + q * 64 + 16 * w + g + 8 * t, 0, 0, 0, 0);
            }
        }
        named_sync(0, 384);
        asm volatile("setmaxnreg.inc.sync.aligned.u32 224;");
        int tid; asm volatile("mov.u32 %0, %%tid.x;" : "=r"(tid));
        const int lane = tid & 31, warp = __shfl_sync(0xffffffffu, tid >> 5, 0), wg = warp >> 2;
        uint32_t ep;
        Tiles* tl;
        const int w = warp & 3, g = lane >> 2, t = lane & 3;
        const bool leader = (tid & 127) == 0;
        const uint32_t never = gridDim.y - 1;
        {
            uint32_t a[28][4];
            float accK[28], accV[28], accQ[28];
            const int lrow = 16 * w + (lane & 7) + (lane & 8);
            const uint32_t lbase = sb + wg * 8192 + lrow * 128;
            const uint32_t lx = (lane >> 4) ^ (lane & 7);
            const uint32_t wofs = hp & 1;
            auto pin2 = [&](uint32_t x0, uint32_t x1) {
                asm volatile("{\n.reg .pred p;\nsetp.ne.u32 p, %2, 0;\n@p st.shared.v2.b32 [%0], {%0,%1};\n}" :: "r"(x0), "r"(x1), "r"(never) : "memory");
            };
            float cS[2][4] = {}, cA[2][4] = {}, cB[2][4] = {}, q0, q1, p0, p1;
            auto sq = [&](float& acc, uint32_t v) { const float lo = bf_lo(v), hi = bf_hi(v); acc = fmaf(hi, hi, fmaf(lo, lo, acc)); };
            #pragma unroll
            for (int kb = 0; kb < 8; kb++) {
                if (kb < 7) {
                    mbar_wait(bars + 8 * (B_FULLX + kb), 0);
                    if (kb == 0 && tid == 0) STAMP(0);
                    if (kb == 6 && tid == 0) STAMP(25);
                    if (kb == 0) FST(0); if (kb == 2) FST(1); if (kb == 4) FST(2); if (kb == 6) FST(3);
                    #pragma unroll
                    for (int s = 4 * kb; s < 4 * kb + 4; s++) ldsm4(a[s], lbase + slot_x(kb) + ((lx ^ (2 * (s & 3))) << 4));
                }
                if (kb == NPIPE) continue;
                const int kc = kb < NPIPE ? kb : kb - 1;
                if (kc == NSQ) { p0 = cS[0][0] + cS[1][0]; p1 = cS[0][2] + cS[1][2]; }
                #pragma unroll
                for (int s = 4 * kc; s < 4 * kc + 4; s++) {
                    mma16816(cS[s & 1], a[s][0], a[s][1], a[s][2], a[s][3], 0x3F803F80u, 0x3F803F80u);
                    if (kc < NSQ) {
                        mma1688(cA[0], a[s][0], a[s][1], a[s][0]); mma1688(cA[1], a[s][2], a[s][3], a[s][2]);
                        mma1688(cB[0], a[s][0], a[s][1], a[s][1]); mma1688(cB[1], a[s][2], a[s][3], a[s][3]);
                    }
                }
            }
            const float m0 = (cS[0][0] + cS[1][0]) * (1.f / D_), m1 = (cS[0][2] + cS[1][2]) * (1.f / D_);
            const uint32_t mm0 = pack_bf16(m0, m0), mm1 = pack_bf16(m1, m1);
            if (lane == 0) mbar_arrive(bars + 8 * B_DONEX);
            auto center = [&](int s) { sub_bf16x2(a[s][0], mm0); sub_bf16x2(a[s][1], mm1); sub_bf16x2(a[s][2], mm0); sub_bf16x2(a[s][3], mm1); };
            uint32_t Ka[8], Kb[8], Kc[8], Va[8], Vb[7], Vc[8];
            float r0, r1, ls0, ls1;
            uint32_t pm, zero;
            uint32_t* od;
            uint4* oh;
            auto kpack = [&](uint32_t (&k)[8], int j, int c, float r) {
                const uint32_t v = pack_bf16(accK[4 * j + c] * r, accK[4 * j + c + 1] * r);
                if (j == 3) { k[3] = t < 2 ? v : 0u; k[4] = t < 2 ? 0u : v; } else k[j + (j > 3)] = v;
            };
            auto batch = [&](auto c0, auto c1) {
                constexpr int n0 = c0.value, n1 = c1.value;
                if (PP && n0 < PP) named_sync(10 + wg, 256);
                wg_fence();
                static_for<n0, n1>([&](auto nc) {
                    constexpr int n = nc.value;
                    if (n == 4) { center(4); center(5); center(6); center(7); wg_fence(); }
                    const uint64_t desc = mkdesc(sb + (n < 56 ? slot_kv(n >> 3) + (n & 7) * 2048 : SM_QO + (n - 56) * 2048), 8192, 1024, 1) + wofs;
                    wgmma_rs56<1>(n < 28 ? accK : n < 56 ? accV : accQ, a[n % 28], desc, n % 28 != 0);
                });
                wg_commit();
                if (PP && n0 < PP && (n1 < PP || wg == 0)) named_arrive(11 - wg, 256);
                if (n0 > 0) wg_wait<1>();
            };
            const uint32_t hs = sb + tid * 16 + warp * 512;
            auto hand_over = [&](const uint32_t (&v)[8], int kv) {
                mbar_wait(bars + 8 * (kv ? B_DONE1 + 5 : B_DONEX), 0);
                sts4(hs + (kv ? SM_HALOV : SM_HALOK), v[0], v[1], v[2], v[3]); sts4(hs + (kv ? SM_HALOV : SM_HALOK) + 512, v[4], v[5], v[6], v[7]);
                if (w == 3) named_arrive(6 + kv, 96);
            };
            auto take_over = [&](uint32_t (&v)[8], int kv) {
                if (w == 0) mbar_wait(bars + 8 * (B_HALO + 2 * kv + wg), 0);
                const uint32_t ad = w ? hs + (kv ? SM_HALOV : SM_HALOK) - 1024 : sb + lane * 16 + wg * 1024 + (kv ? SM_HALOV + 8192 : SM_HALOKIN);
                const uint4 u0 = lds4(ad), u1 = lds4(ad + 512);
                v[0] = u0.x; v[1] = u0.y; v[2] = u0.z; v[3] = u0.w; v[4] = u1.x; v[5] = u1.y; v[6] = u1.z; v[7] = u1.w;
            };
            if (PP && wg == 1) { pin2(mm0, mm1); named_arrive(10, 256); }
            center(0); center(1); center(2); center(3);
            static_for<0, 7>([&](auto pc) {
                constexpr int p = pc.value;
                mbar_wait(bars + 8 * (B_FULLKV + p), 0);
                if (p == 0 && tid == 0) STAMP(26);
                if (p == 3 && tid == 0) STAMP(27);
                FST(4 + p);
                batch(Int<8 * p>(), Int<8 * p + 8>());
                if (p > 0 && leader) mbar_arrive(bars + 8 * (B_DONE1 + p - 1));
                #pragma unroll
                for (int s = 8 * p + 8; s < 8 * p + 16 && s < 28; s++) center(s);
                if (p == 1) {
                    const float c0 = bf_hi(mm0), c1 = bf_hi(mm1);
                    q0 = fmaf(c0, fmaf(c0, 64.f * NSQ, -2.f * p0), (g & 1) ? cA[0][1] + cA[1][1] : cA[0][0] + cA[1][0]) - D_ * (m0 - c0) * (m0 - c0);
                    q1 = fmaf(c1, fmaf(c1, 64.f * NSQ, -2.f * p1), (g & 1) ? cB[0][3] + cB[1][3] : cB[0][2] + cB[1][2]) - D_ * (m1 - c1) * (m1 - c1);
                    asm("" : "+f"(q0), "+f"(q1));
                    q0 = t == (g >> 1) ? q0 : 0.f; q1 = t == (g >> 1) ? q1 : 0.f;
                    pin2(__float_as_uint(q0), __float_as_uint(q1));
                }
                constexpr int PK = NSQ < 5 ? 5 : 4, NR = 28 - 4 * NSQ;
                if (p >= 2 && p < PK) {
                    #pragma unroll
                    for (int s = 4 * NSQ + NR * (p - 2) / (PK - 2); s < 4 * NSQ + NR * (p - 1) / (PK - 2); s++) { sq(q0, a[s][0]); sq(q1, a[s][1]); sq(q0, a[s][2]); sq(q1, a[s][3]); }
                    pin2(__float_as_uint(q0), __float_as_uint(q1));
                }
                if (p == PK - 1) { q0 = quad_sum(q0); q1 = quad_sum(q1); }
                if (p == PK) {
                    r0 = rsqrt_approx(fmaxf(q0 * (1.f / D_), 0.f) + LN_EPS); r1 = rsqrt_approx(fmaxf(q1 * (1.f / D_), 0.f) + LN_EPS);
                    reg_fence(accK);
                    #pragma unroll
                    for (int j = 0; j < 7; j++) kpack(Kc, j, 2, r1);
                    hand_over(Kc, 0);
                }
                if (p == PK + 1) {
                    #pragma unroll
                    for (int j = 0; j < 7; j++) kpack(Kb, j, 0, r0);
                    #pragma unroll
                    for (int j = 0; j < 8; j += 2) pin2(Kb[j], Kb[j + 1]);
                    ls0 = LOG2E_SCALE * r0; ls1 = LOG2E_SCALE * r1;
                    pm = (2 * t <= g ? 0xFFFFu : 0u) | (2 * t + 1 <= g ? 0xFFFF0000u : 0u);
                    zero = never; asm volatile("" : "+r"(zero));
                    pin2(__float_as_uint(ls0), __float_as_uint(ls1)); pin2(pm, zero);
                }
                if (p == 2) ep = get_tag();
                if (p == 6) {
                    tl = &sc->tiles[ep & 1];
                    const int tt = 2 * tb + (w >> 1);
                    od = tl->o + tt * 14336 + (7 * hp) * 256 + (2 * (2 * (w & 1) + wg)) * 32 + lane;
                    oh = sc->hint_o + (tt * 32 + hp * 4 + (w & 1) * 2 + wg) * 2 + (lane & 1);
                    pin2((uint32_t)(uint64_t)od, (uint32_t)((uint64_t)od >> 32));
                    pin2((uint32_t)(uint64_t)oh, (uint32_t)((uint64_t)oh >> 32));
                }
            });
            if (tid == 0) STAMP(1);
            FST(11);
            mbar_wait(bars + 8 * B_FQ, 0);
            batch(Int<56>(), Int<60>());
            reg_fence(accV);
            if (leader) mbar_arrive(bars + 8 * (B_DONE1 + 6));
            if (tid == 0) STAMP(2);
            FST(12);
            #pragma unroll
            for (int j = 0; j < 7; j++) Vc[j] = movtrans(pack_bf16(accV[4 * j + 2] * r1, accV[4 * j + 3] * r1));
            Vc[7] = Vc[6];
            hand_over(Vc, 1);
            batch(Int<60>(), Int<66>());
            #pragma unroll
            for (int j = 0; j < 7; j++) {
                Vb[j] = movtrans(pack_bf16(accV[4 * j] * r0, accV[4 * j + 1] * r0));
                Vc[j] |= zero;
            }
            batch(Int<66>(), Int<72>());
            #pragma unroll
            for (int j = 0; j < 7; j++) pin2(Vb[j], Vc[j]);
            mbar_wait(bars + 8 * (B_FQ + 1), 0);
            FST(13);
            if (w > 0 && lane < 2) { const uint32_t now = gtime32(); st_relaxed4(oh, ep, now, ep, now); }
            batch(Int<72>(), Int<84>());
            FST(14);
            named_sync(1 + wg, 128);
            take_over(Ka, 0);
            if (tid == 0) STAMP(3);
            wg_wait<0>();
            reg_fence(accQ);
            if (tid == 0) STAMP(4);
            FST(15);
            const bool first = (tb == 0 && w == 0);
            uint32_t pA[2], pB0[2], pB1[2], pC[2], z0[2], z1[2];
            #pragma unroll
            for (int h = 0; h < 2; h++) {
                float sA[4] = {0.f, 0.f, 0.f, 0.f}, sB[4] = {0.f, 0.f, 0.f, 0.f}, sC[4] = {0.f, 0.f, 0.f, 0.f};
                #pragma unroll
                for (int k = 0; k < 2; k++) {
                    const float* qq = accQ + 12 * h + 8 * k;
                    uint32_t a0 = pack_bf16(qq[0], qq[1]), a1 = pack_bf16(qq[2], qq[3]);
                    if (h == 1 && k == 0) { a0 |= zero; a1 |= zero; }
                    const uint32_t a2 = pack_bf16(qq[4], qq[5]), a3 = pack_bf16(qq[6], qq[7]);
                    mma16816(sB, a0, a1, a2, a3, Kb[4 * h + 2 * k], Kb[4 * h + 2 * k + 1]);
                    mma16816(sA, a0, a1, a2, a3, Ka[4 * h + 2 * k], Ka[4 * h + 2 * k + 1]);
                    mma16816(sC, a0, a1, a2, a3, Kc[4 * h + 2 * k], Kc[4 * h + 2 * k + 1]);
                }
                const bool n0 = pm & 1, n1 = (int)pm < 0;
                const float l00 = n0 ? sB[0] : (first ? -INFINITY : sA[0]), l01 = n1 ? sB[1] : (first ? -INFINITY : sA[1]);
                const float l10 = n0 ? sC[2] : sB[2], l11 = n1 ? sC[3] : sB[3];
                const float x0 = -ls0 * quad_max(fmaxf(l00, l01)), x1 = -ls1 * quad_max(fmaxf(l10, l11));
                const float e00 = ex2(fmaf(l00, ls0, x0)), e01 = ex2(fmaf(l01, ls0, x0)), e10 = ex2(fmaf(l10, ls1, x1)), e11 = ex2(fmaf(l11, ls1, x1));
                const float i0 = rcp_approx(quad_sum(e00 + e01)), i1 = rcp_approx(quad_sum(e10 + e11));
                const uint32_t P0 = pack_bf16(e00 * i0, e01 * i0), P1 = pack_bf16(e10 * i1, e11 * i1);
                pB0[h] = P0 & pm; pA[h] = P0 & ~pm; pC[h] = P1 & pm; pB1[h] = P1 & ~pm; z0[h] = P0 & zero; z1[h] = P1 & zero;
            }
            float o[8][4];
            #pragma unroll
            for (int j = 0; j < 8; j++) {
                o[j][0] = o[j][1] = o[j][2] = o[j][3] = 0.f;
                mma16816(o[j], pB0[j >> 2], pB1[j >> 2], z0[j >> 2], pC[j >> 2], Vb[j - (j >> 2)], Vc[j - (j >> 2)]);
            }
            if (tid == 0) STAMP(12);
            FST(16);
            take_over(Va, 1);
            if (lane == 0) mbar_arrive(bars + 8 * B_DONEQ);
            if (tid == 0) STAMP(16);
            #pragma unroll
            for (int j = 0; j < 8; j++) mma1688(o[j], pA[j >> 2], z1[j >> 2], Va[j - (j >> 2)]);
            #pragma unroll
            for (int j = 0; j < 7; j++) {
                float v[4];
                #pragma unroll
                for (int c = 0; c < 4; c++) v[c] = j < 3 ? o[j][c] : j > 3 ? o[j + 1][c] : (t < 2 ? o[3][c] : o[4][c]);
                od[j * 256] = pack_bf16(v[0], v[1]);
                od[j * 256 + 32] = pack_bf16(v[2], v[3]);
            }
            if (tid == 0) STAMP(5);
            FST(17);
        }
        const uint32_t live = wg ^ 1;
        uint32_t rb0, rb1, late[14];
        uint32_t* late_ptr = nullptr;
        const unsigned short* pb = (const unsigned short*)(live ? b2 + tt2 * 64 : b1 + max(ft, 0) * 64) + 16 * w + g;
        auto undef = [](float (&v)[56]) {
            #pragma unroll
            for (int i = 0; i < 56; i++) asm volatile("" : "=f"(v[i]));
        };
        {
            float acc[56];
            const int hrow = 32 * (w >> 1) + 2 * ((lane & 7) + (lane & 8)) + (w & 1);
            const uint32_t ha = sb + SM_H + hrow * 128 + (((lane >> 4) ^ (hrow & 7)) << 4);
            uint4* sp = sc->stats + tt2 * 256 + 16 * w + g + 8 * (t & 1);
            uint4* sp_out = sp + q * 64;
            const uint4* sp_in = sp + (t & 2) * 64;
            uint32_t* hd = tl->hn + (q * 64 + tt2) * 1792 + w * 448 + lane;
            pin_ptr(never, sp_out); pin_ptr(never, sp_in); pin_ptr(never, hd);
            float s0 = 0.f, s1 = 0.f, q0 = 0.f, q1 = 0.f, s2 = 0.f, s3 = 0.f, q2 = 0.f, q3 = 0.f;
            auto sums = [&](int j0, int j1) {
                #pragma unroll
                for (int j = j0; j < j1; j++) {
                    s0 += acc[4 * j]; s2 += acc[4 * j + 1]; q0 = fmaf(acc[4 * j], acc[4 * j], q0); q2 = fmaf(acc[4 * j + 1], acc[4 * j + 1], q2);
                    s1 += acc[4 * j + 2]; s3 += acc[4 * j + 3]; q1 = fmaf(acc[4 * j + 2], acc[4 * j + 2], q1); q3 = fmaf(acc[4 * j + 3], acc[4 * j + 3], q3);
                }
            };
            if (live) {
                mbar_wait(bars + 8 * B_FULLWO, 0);
                #pragma unroll
                for (int jp = 0; jp < 7; jp++) {
                    uint32_t xx[4];
                    ldsm4(xx, hcol(ha, jp));
                    #pragma unroll
                    for (int r = 0; r < 4; r++) { acc[8 * jp + 2 * r] = bf_lo(xx[r]); acc[8 * jp + 2 * r + 1] = bf_hi(xx[r]); }
                }
                reg_fence(acc);
                auto od_ = [&](int s) { return mkdesc(sb + SM_QO + s * 2048, 1024, 128, 0); };
                auto wd_ = [&](int s) { return mkdesc(sb + slot_wo(s >> 2) + (s & 3) * 2048, 8192, 1024, 1); };
                float accl[32], accr[24];
                #pragma unroll
                for (int i = 0; i < 5; i++) {
                    if (i < 4) mbar_wait(bars + 8 * (B_FULLO + i), 0);
                    if (i == 0 && tid == 0) STAMP(7);
                    if (i == 1) { rb0 = ld_u16(pb); rb1 = ld_u16(pb + 8); }
                    wg_fence();
                    #pragma unroll
                    for (int ss = 0; ss < 7; ss++) {
                        if (i < 3) wgmma_ss112<0, 1>(acc, od_(7 * i + ss), wd_(7 * i + ss));
                        else if (i == 4) wgmma_ss64<0, 1>(accl, od_(21 + ss), wd_(21 + ss));
                        else if (ss == 0) wgmma_ss48<0, 1, 0>(accr, od_(21), wd_(21) + 512);
                        else wgmma_ss48<0, 1>(accr, od_(21 + ss), wd_(21 + ss) + 512);
                    }
                    wg_commit();
                    if (i > 0) {
                        wg_wait<1>();
                        if (i == 3) {
                            reg_fence(acc);
                            #pragma unroll
                            for (int c = 0; c < 32; c++) accl[c] = __uint_as_float(__float_as_uint(acc[c]) | never);
                            reg_fence(accl);
                        }
                        if (i < 4 && leader) mbar_arrive(bars + 8 * (B_DONEO + i - 1));
                    }
                }
                reg_fence(accr);
                #pragma unroll
                for (int c = 0; c < 24; c++) acc[32 + c] += accr[c];
                sums(8, 14);
                pin4(never, s0, s1, s2, s3); pin4(never, q0, q1, q2, q3);
                wg_wait<0>();
                reg_fence(accl);
                #pragma unroll
                for (int c = 0; c < 32; c++) acc[c] = accl[c];
                if (leader) mbar_arrive(bars + 8 * (B_DONEO + 3));
                if (tid == 0) STAMP(8);
            } else undef(acc);
            if (live || (DRY2 && w == 3)) {
            sums(0, 8);
            s0 += s2; s1 += s3; q0 += q2; q1 += q3;
            float sr = ((t & 1) ? s1 : s0) + __shfl_xor_sync(0xffffffffu, (t & 1) ? s0 : s1, 1), qr = ((t & 1) ? q1 : q0) + __shfl_xor_sync(0xffffffffu, (t & 1) ? q0 : q1, 1);
            sr += __shfl_xor_sync(0xffffffffu, sr, 2); qr += __shfl_xor_sync(0xffffffffu, qr, 2);
            st_relaxed4_if(t < 2 * live, sp_out, __float_as_uint(sr), __float_as_uint(qr), ep);
            if (live) named_arrive(5, 256);
            if (tid == 0) STAMP(9);
            #pragma unroll
            for (int jp = 0; jp < 7; jp++)
                stsm4_if(live, hcol(ha, jp), pack_bf16(acc[8 * jp], acc[8 * jp + 1]), pack_bf16(acc[8 * jp + 2], acc[8 * jp + 3]),
                      pack_bf16(acc[8 * jp + 4], acc[8 * jp + 5]), pack_bf16(acc[8 * jp + 6], acc[8 * jp + 7]));
            uint4 v0, v1;
            do { v0 = ld_relaxed4(sp_in); v1 = ld_relaxed4(sp_in + 64); } while (live && __any_sync(0xffffffffu, v0.w != ep || v1.w != ep));
            if (tid == 0) STAMP(10);
            sr = __uint_as_float(v0.x) + __uint_as_float(v1.x); qr = __uint_as_float(v0.y) + __uint_as_float(v1.y);
            sr += __shfl_xor_sync(0xffffffffu, sr, 2); qr += __shfl_xor_sync(0xffffffffu, qr, 2);
            const float m = sr * (1.f / D_), v = fmaxf(qr * (1.f / D_) - m * m, 0.f);
            const float r = rsqrt_approx(fmaf(v, 4.f + 4.f * LN_EPS, 4.f * LN_EPS * LN_EPS)), c = -m * r;
            const float r0 = __shfl_sync(0xffffffffu, r, lane & ~1), c0 = __shfl_sync(0xffffffffu, c, lane & ~1);
            const float r1 = __shfl_sync(0xffffffffu, r, lane | 1), c1 = __shfl_sync(0xffffffffu, c, lane | 1);
            #pragma unroll
            for (int j = 0; j < 14; j++) st_global_if(live, hd + j * 32, pack_bf16(fmaf(acc[4 * j], r0, c0), fmaf(acc[4 * j + 1], r0, c0)));
            if (never) mbar_arrive(bars);
            #pragma unroll
            for (int j = 0; j < 14; j++) late[j] = pack_bf16(fmaf(acc[4 * j + 2], r1, c1), fmaf(acc[4 * j + 3], r1, c1));
            late_ptr = hd + 32 * 1792;
            if (tid == 0) STAMP(11);
            }
        }
        if (!live) {
            check_tiles(TSVAL 4, w, lane, sb + SM_QO, tl->o + tt2 * 14336, B_FULLO, late, nullptr);
            rb0 = ld_u16(pb); rb1 = ld_u16(pb + 8);
            late_ptr = nullptr;
            named_sync(5, 256);
            if (has_b1) {
                float acc[56];
                uint32_t* ud = tl->u + (q * 56 + ft) * 1792 + w * 448 + lane;
                #pragma unroll
                for (int j = 0; j < 56; j++) acc[j] = 0.5f * bf_lo((j & 2) ? rb1 : rb0);
                #pragma unroll 1
                for (uint32_t pass = never; pass < 2; pass++) {
                    if (pass) {
                        mix_mainloop<32>(TSVAL acc, 0, leader);
                        if (leader) STAMP(14);
                    }
                    uint32_t pk[14];
                    #pragma unroll
                    for (int j = 0; j < 14; j++) {
                        const float k = j < GDEP ? GELU_K1 : __uint_as_float(__float_as_uint(GELU_K1) | (pk[j - GDEP] & never));
                        pk[j] = pack_bf16(gelu_half(acc[4 * j], k), gelu_half(acc[4 * j + 1], k));
                        st_global_if(pass, ud + j * 32, pk[j]);
                    }
                }
                named_arrive(3, 256);
                if (leader) STAMP(15);
                #pragma unroll
                for (int j = 0; j < 14; j++) late[j] = pack_bf16(gelu_half(acc[4 * j + 2], GELU_K1), gelu_half(acc[4 * j + 3], GELU_K1));
                late_ptr = ud + 28 * 1792;
            }
            check_tiles(TSVAL 28, w, lane, sb + SM_BRING, tl->u + q * 28 * 3584, B_FULLB, late, late_ptr);
            return;
        }
        {
            float acc[56];
            const uint32_t ad = sb + SM_H + (16 * w + (lane & 15)) * 128 + (((lane >> 4) ^ (lane & 7)) << 4);
            const float bb0 = bf_lo(rb0), bb1 = bf_lo(rb1);
            named_sync(1, 128);
            #pragma unroll
            for (int jp = 0; jp < 7; jp++) {
                uint32_t hh[4];
                ldsm4(hh, hcol(ad, jp));
                #pragma unroll
                for (int r = 0; r < 4; r++) { acc[8 * jp + 2 * r] = bf_lo(hh[r]) + ((r & 1) ? bb1 : bb0); acc[8 * jp + 2 * r + 1] = bf_hi(hh[r]) + ((r & 1) ? bb1 : bb0); }
            }
            if (has_b1) {
                check_tiles(TSVAL 32, w, lane, sb + SM_BRING, tl->hn + q * 32 * 3584, B_FULLB, late, late_ptr);
                named_sync(3, 256);
            } else {
                #pragma unroll
                for (int c = 0; c < 14; c++) st_global_if(1, late_ptr + c * 32, late[c]);
            }
            #pragma unroll 1
            for (uint32_t pass = never; pass < 2; pass++) {
                if (pass) {
                    mix_mainloop<28>(TSVAL acc, has_b1, leader);
                    if (leader) mbar_arrive(bars + 8 * B_END);
                    if (tid == 0) STAMP(18);
                }
                #pragma unroll
                for (int jp = 0; jp < 7; jp++)
                    stsm4_if(1, hcol(ad, jp), pack_bf16(acc[8 * jp], acc[8 * jp + 1]), pack_bf16(acc[8 * jp + 2], acc[8 * jp + 3]),
                             pack_bf16(acc[8 * jp + 4], acc[8 * jp + 5]), pack_bf16(acc[8 * jp + 6], acc[8 * jp + 7]));
                fence_async_smem();
                __syncwarp();
            }
            if (elect()) {
                tma2d_store(&tm_out64, c64, tt2 * 64 + 16 * w, sb + SM_H + w * 2048);
                tma2d_store(&tm_out48, c48, tt2 * 64 + 16 * w, sb + SM_H + 8192 + w * 2048);
            }
            asm volatile("cp.async.bulk.commit_group;" ::: "memory");
            asm volatile("cp.async.bulk.wait_group.read 0;" ::: "memory");
            if (tid == 0) { sc->epoch[slot] = ep; STAMP(19); }
        }
    } else {
        asm volatile("setmaxnreg.dec.sync.aligned.u32 56;");
        int warp2; asm("mov.u32 %0, %1;" : "=r"(warp2) : "r"(warp));
        if (warp2 > 8) {
            uint32_t ep, cl;
            uint4* const oh = sc->hint_o + (2 * tb * 32 + hp * 4) * 2 + (lane & 3);
            if (warp == 10) {
                post_hint(sc->hint_h + (q * 32 + tt2) * 2, 0, lane);
                if (has_b1) post_hint(sc->hint_u + (q * 32 + ft) * 2, 0, lane);
            }
            if (warp == 11) {
                ep = ld_volatile(&sc->epoch[slot]) + 1; cl = ld_acquire(&sc->clean[lane & 15]);
                post_hint(sc->hint_k + (tb * 8 + hp) * 2, 0, lane);
                if (lane < (tb < 15 ? 4 : 0)) st_relaxed4(oh + 128, 0, 0, 0, 0);
                if (lane < (tb ? 0 : 4)) st_relaxed4(oh, 0, 0, 0, 0);
            }
            if (elect()) {
                if (warp == 9) {
                    #pragma unroll
                    for (int i = B_DONE1; i < B_DONEO; i++) mbar_init(bars + 8 * i, i < B_DONEX ? 2 : i == B_DONEX ? 8 : 9);
                    mbar_init(bars + 8 * B_CLR, 1);
                }
                #pragma unroll
                for (int i = 0; i < 34; i++) mbar_init(bars + 8 * (B_DONEO + i) + (warp - 9) * 272, 1);
                asm volatile("fence.mbarrier_init.release.cluster;" ::: "memory");
            }
            named_sync(0, 384);
            if (warp == 9) named_arrive(4, 64);
            if (warp < 11) {
                ep = get_tag();
                mbar_wait(bars + 8 * (B_DONE1 + HALO_AT), 0);
                #pragma unroll 1
                for (int kv = 0; kv < 2; kv++) {
                    uint4 v0 = {}, v1 = {}, v2 = {};
                    if (tb > 0) {
                        const uint4* hg = sc->halo + ((((tb - 1) * 8 + hp) * 2 + warp - 9) * 2 + kv) * 96 + lane;
                        if (kv == 0) while (ld_relaxed(sc->hint_k + ((tb - 1) * 8 + hp) * 2) != ep) {}
                        do { v0 = ld_relaxed4(hg); v1 = ld_relaxed4(hg + 32); v2 = ld_relaxed4(hg + 64); } while (!__all_sync(0xffffffffu, v0.w == ep && v1.w == ep && v2.w == ep));
                    }
                    if (kv) mbar_wait(bars + 8 * (B_DONE1 + 5), 0);
                    const uint32_t hs = sb + lane * 16 + (warp - 9) * 1024 + (kv ? SM_HALOV + 8192 : SM_HALOKIN);
                    sts4(hs, v0.x, v0.y, v0.z, v1.x); sts4(hs + 512, v1.y, v1.z, v2.x, v2.y);
                    __syncwarp();
                    if (lane == 0) mbar_arrive(bars + 8 * (B_HALO + 2 * kv + warp - 9));
                }
                if (tid == 288) STAMP(21);
            }
            if (warp == 10) {
                mbar_wait(bars + 8 * (B_FULLO + 3), 0);
                mbar_wait(bars + 8 * (B_DONEO + HINT_H), 0);
                post_time(sc->hint_h + (q * 32 + tt2) * 2, ep, lane);
                if (has_b1) {
                    mbar_wait(bars + 8 * (B_DONE + HINT_U), 0);
                    post_time(sc->hint_u + (q * 32 + ft) * 2, ep, lane);
                } else if (lane == 0) {
                    mbar_wait(bars + 8 * (B_DONEO + 3), 0);
                    uint32_t t = clock32() + PF_AT;
                    #pragma unroll 1
                    for (int i = 0; i < PF_N; i++) {
                        while ((int)(clock32() - t) < 0) __nanosleep(40);
                        const int c = i * 16 + mi;
                        bulk_prefetch((const char*)w2 + (c >> 1) * 65536 + (c & 1) * 16384, 16384);
                        t += PF_PACE;
                    }
                }
            } else if (warp == 11) {
                #pragma unroll 1
                for (uint32_t e = ep; e != ep + 2; e++) {
                    if (!has_b1 && __shfl_sync(0xffffffffu, cl, mi) != e) {
                        if (e != ep) { mbar_wait_wd(bars + 8 * (B_DONEO + 3), 0); const uint32_t t = clock32(); while (clock32() - t < CL_AT) __nanosleep(100); __syncwarp(); }
                        constexpr int NL = sizeof(Tiles) / 2048;
                        uint4* p = (uint4*)&sc->tiles[e & 1] + (mi * NL + (lane >> 1)) * 8 + (lane & 7);
                        #pragma unroll 7
                        for (int i = 0; i < NL / 16; i++) st_relaxed4(p + i * 128, EMPTY, EMPTY, EMPTY, EMPTY);
                        __syncwarp();
                        if (lane == 0) { st_release(&sc->clean[mi], e); STAMP(24); }
                        __syncwarp();
                    }
                    if (e == ep) {
                        const long long t0 = clock64();
                        while (__any_sync(0xffffffffu, (int)(cl - ep) < 0)) { cl = ld_acquire(&sc->clean[lane & 15]); if (clock64() - t0 > WD_CLKS) __trap(); }
                        if (lane == 0) { *(volatile uint32_t*)(smem_raw + SM_TAG) = ep; mbar_arrive(bars + 8 * B_CLR); }
                        uint4* hg = sc->halo + (tb * 8 + hp) * 384 + lane;
                        #pragma unroll 1
                        for (int kv = 0; kv < 2; kv++) {
                            const uint32_t hs = sb + lane * 16 + 3072 + (kv ? SM_HALOV : SM_HALOK);
                            named_sync(6 + kv, 96);
                            #pragma unroll
                            for (int p = 0; p < 2; p++) {
                                const uint4 u0 = lds4(hs + p * 4096), u1 = lds4(hs + p * 4096 + 512);
                                st_relaxed4(hg + p * 192, u0.x, u0.y, u0.z, ep); st_relaxed4(hg + p * 192 + 32, u0.w, u1.x, u1.y, ep); st_relaxed4(hg + p * 192 + 64, u1.z, u1.w, ep, ep);
                            }
                            hg += 96;
                            if (kv == 0) {
                                post_hint(sc->hint_k + (tb * 8 + hp) * 2, ep, lane);
                                #pragma unroll
                                for (int j = 0; j < 6; j++) st_relaxed4(hg + j * 32 + (j / 3) * 96, 0, 0, 0, 0);
                            }
                        }
                        const uint32_t now = gtime32() - LATE_O;
                        if (lane < (tb < 15 ? 4 : 0)) st_relaxed4(oh + 128, ep, now, ep, now);
                        if (lane < (tb ? 0 : 4)) st_relaxed4(oh, ep, now, ep, now);
                        if (lane == 0) STAMP(23);
                        if (lane == 0) mbar_arrive(bars + 8 * B_DONEQ);
                    }
                }
                if (lane == 0) {
                    mbar_wait_wd(bars + 8 * B_END, 0);
                }
            } else {
                int aslot = 0;
                if (lane == 0) { prefetch_map(&tm_out64); prefetch_map(&tm_out48); }
                if (has_b1) {
                    #pragma unroll 1
                    for (int i = 0; i < 16; i++) {
                        mbar_wait(bars + 8 * (i < NA_SLOTS ? B_DONEQ + ((A_SCHED >> (4 * i)) & 15) : B_DONE + 1 + ((i - NA_SLOTS) * A3_END) / (15 - NA_SLOTS)), 0);
                        if (elect()) {
                            const uint32_t bar = bars + 8 * (B_FULLA + i), dst = sb + SM_ARING + aslot * 16384;
                            mbar_expect(bar, 16384);
                            tma5d(dst, &tm_w1, ft * 64, (i & 7) * 8, i >> 3, bar);
                        }
                        aslot = aslot == NA_SLOTS - 1 ? 0 : aslot + 1;
                    }
                }
                aslot = 16 % NA_SLOTS;
                #pragma unroll 1
                for (int i = 0; i < 14; i++) {
                    if (i >= NA_SLOTS) mbar_wait(bars + 8 * (B_DONE + 1 + ((i - NA_SLOTS) * A4_END) / (13 - NA_SLOTS)), has_b1);
                    else if (has_b1) {
                        mbar_wait(bars + 8 * (B_DONE + max(33 - 2 * NA_SLOTS + 2 * i, W2_AT)), 0);
                        if (i >= W2_HOLD) mbar_wait(bars + 8 * B_FULLB, 1);
                    } else if (i == 0) { mbar_wait(bars + 8 * (B_DONEO + 3), 0); const uint32_t t = clock32() + PF_AT + 12 * PF_PACE; while ((int)(clock32() - t) < 0) __nanosleep(100); }
                    if (elect()) {
                        const uint32_t bar = bars + 8 * (B_FULLA + i);
                        mbar_expect(bar, 16384);
                        tma5d(sb + SM_ARING + aslot * 16384, &tm_w2, tt2 * 64, (i < 7 ? i : i - 7) * 8, i >= 7, bar);
                    }
                    aslot = aslot == NA_SLOTS - 1 ? 0 : aslot + 1;
                }
            }
        } else {
            auto krot = [&](int kb) { const int k = kb * 64 + (G & 1) * 64 * ROT; return k < 448 ? k : k - 448; };
            if (elect()) {
                #pragma unroll
                for (int i = 0; i < 7; i++) mbar_init(bars + 8 * i, 1);
                asm volatile("fence.mbarrier_init.release.cluster;" ::: "memory");
                if (STAG && G >= 2) { const uint32_t t0 = clock32(); while (clock32() - t0 < STAG) {} }
                #pragma unroll 1
                for (int kb = 0; kb < 7; kb++) {
                    const uint32_t st = sb + slot_x(kb), bar = bars + 8 * (B_FULLX + kb);
                    mbar_expect(bar, 16384);
                    tma3d(st, &tm_x, krot(kb), 0, tb * 64, bar); tma3d(st + 8192, &tm_x, krot(kb), 1, tb * 64, bar);
                }
                #pragma unroll
                for (int i = 7; i < B_DONE1; i++) mbar_init(bars + 8 * i, 1);
                asm volatile("fence.mbarrier_init.release.cluster;" ::: "memory");
            }
            named_arrive(0, 384);
            #pragma unroll 1
            for (int kb = 0; kb < 7; kb++) {
                if (kb == 6) { named_sync(4, 64); mbar_wait(bars + 8 * B_DONEX, 0); }
                if (elect()) {
                    const uint32_t st = sb + slot_kv(kb), bar = bars + 8 * (B_FULLKV + kb);
                    mbar_expect(bar, 16384);
                    #pragma unroll
                    for (int i = 0; i < 2; i++) {
                        const int n = 2 * kb + (ROT ? i : i ^ (G & 1));
                        tma2d(st + (n & 1) * 8192, &tm_wqkv, (n < 7 ? 448 : 896) + wcol, krot(n < 7 ? n : n - 7), bar);
                    }
                }
            }
            if (elect()) {
                mbar_expect(bars + 8 * B_FQ, 32768);
                mbar_expect(bars + 8 * (B_FQ + 1), 24576);
                #pragma unroll 1
                for (int i = 0; i < 7; i++) { const int j = ROT || i == 6 ? i : i ^ (G & 1); tma2d(sb + SM_QO + j * 8192, &tm_wqkv, wcol, krot(j), bars + 8 * (B_FQ + (i >> 2))); }
                mbar_expect(bars + 8 * B_FULLWO, 512 * 112 * 2);
            }
            #pragma unroll 1
            for (int i = 0; i < 7; i++) {
                const int kb = ((q & 1 ? WO_ORD1 : WO_ORD0) >> (4 * i)) & 7;
                if (kb < 5) mbar_wait(bars + 8 * (B_DONE1 + kb), 0);
                if (i == WO_HOLD) { mbar_wait(bars + 8 * (B_HALO + 2), 0); mbar_wait(bars + 8 * (B_HALO + 3), 0); }
                if (elect()) {
                    tma2d(sb + slot_wo(kb), &tm_wo64, c64, kb * 64, bars + 8 * B_FULLWO);
                    tma2d(sb + slot_wo(kb) + 8192, &tm_wo48, c48, kb * 64, bars + 8 * B_FULLWO);
                }
            }
            if (XR_HOLD) { mbar_wait(bars + 8 * (B_HALO + 2), 0); mbar_wait(bars + 8 * (B_HALO + 3), 0); }
            if (elect()) {
                tma2d(sb + SM_H, &tm_xr64, c64, tt2 * 64, bars + 8 * B_FULLWO);
                tma2d(sb + SM_H + 8192, &tm_xr48, c48, tt2 * 64, bars + 8 * B_FULLWO);
            }
            if (smem_u32(smem_raw) != SB) __trap();
            const uint32_t ep = get_tag();
            const Tiles* const tl = &sc->tiles[ep & 1];
            mbar_wait(bars + 8 * (B_DONE1 + 6), 0);
            wait_hints(TSVAL sc->hint_o + (tt2 * 32 + lane) * 2, ep, GO_O, 38);
            mbar_wait(bars + 8 * B_DONEQ, 0);
            if (elect()) {
                #pragma unroll
                for (int i = 0; i < 4; i++) {
                    mbar_expect(bars + 8 * (B_RAW + i), 14336);
                    bulk_ld(sb + SM_QO + i * 14336, tl->o + tt2 * 14336 + i * 3584, 14336, bars + 8 * (B_RAW + i));
                }
            }
            if (lane == 0) STAMP(20);
            mbar_wait(bars + 8 * (B_DONEO + 2), 0);
            if (has_b1) {
                mix_producer_b<32>(TSVAL 0, sc->go, ep, tl->hn + q * 32 * 3584, lane);
            }
            mix_producer_b<28>(TSVAL has_b1, sc->go + 8, ep, tl->u + q * 28 * 3584, lane);
        }
    }
}

typedef CUresult (*EncodeFn)(CUtensorMap*, CUtensorMapDataType, cuuint32_t, void*, const cuuint64_t*, const cuuint64_t*, const cuuint32_t*,
                             const cuuint32_t*, CUtensorMapInterleave, CUtensorMapSwizzle, CUtensorMapL2promotion, CUtensorMapFloatOOBfill);

void make_map(EncodeFn fn, CUtensorMap* tm, const void* ptr, int rank, const cuuint64_t* dims, const cuuint64_t* strides, const cuuint32_t* box, CUtensorMapSwizzle sw) {
    cuuint32_t es[5] = {1, 1, 1, 1, 1};
    fn(tm, CU_TENSOR_MAP_DATA_TYPE_BFLOAT16, rank, const_cast<void*>(ptr), dims, strides, box, es, CU_TENSOR_MAP_INTERLEAVE_NONE, sw,
       CU_TENSOR_MAP_L2_PROMOTION_NONE, CU_TENSOR_MAP_FLOAT_OOB_FILL_NONE);
}

}

extern "C" void kernel_launch(void* const* d_in, const int* in_sizes, int n_in, void* d_out, int out_size) {
    const __nv_bfloat16* x = (const __nv_bfloat16*)d_in[0];
    const __nv_bfloat16* wqkv = (const __nv_bfloat16*)d_in[1];
    const __nv_bfloat16* wo = (const __nv_bfloat16*)d_in[2];
    const __nv_bfloat16* w1 = (const __nv_bfloat16*)d_in[4];
    const __nv_bfloat16* b1 = (const __nv_bfloat16*)d_in[5];
    const __nv_bfloat16* w2 = (const __nv_bfloat16*)d_in[6];
    const __nv_bfloat16* b2 = (const __nv_bfloat16*)d_in[7];

    void* fnp = nullptr; cudaDriverEntryPointQueryResult qr;
    cudaGetDriverEntryPoint("cuTensorMapEncodeTiled", &fnp, cudaEnableDefault, &qr);
    EncodeFn fn = (EncodeFn)fnp;
    CUtensorMap tx, twqkv, two64, two48, tw1, tw2, txr64, txr48, tout64, tout48;
    { cuuint64_t d[3] = {448, 2, 1024}, s[2] = {896, 1792}; cuuint32_t b[3] = {64, 1, 64}; make_map(fn, &tx, x, 3, d, s, b, CU_TENSOR_MAP_SWIZZLE_128B); }
    { cuuint64_t d[2] = {1344, 448}, s[1] = {2688}; cuuint32_t b[2] = {64, 64}; make_map(fn, &twqkv, wqkv, 2, d, s, b, CU_TENSOR_MAP_SWIZZLE_128B); }
    { cuuint64_t d[2] = {448, 448}, s[1] = {896}; cuuint32_t b[2] = {64, 64}; make_map(fn, &two64, wo, 2, d, s, b, CU_TENSOR_MAP_SWIZZLE_128B); }
    { cuuint64_t d[2] = {448, 448}, s[1] = {896}; cuuint32_t b[2] = {48, 64}; make_map(fn, &two48, wo, 2, d, s, b, CU_TENSOR_MAP_SWIZZLE_128B); }
    { cuuint64_t d[5] = {1792, 8, 2, 64, 2}, s[4] = {2 * 3584, 3584, 32 * 3584, 16 * 3584}; cuuint32_t b[5] = {64, 8, 2, 8, 1}; make_map(fn, &tw1, w1, 5, d, s, b, CU_TENSOR_MAP_SWIZZLE_128B); }
    { cuuint64_t d[5] = {2048, 8, 2, 56, 2}, s[4] = {4096, 16 * 4096, 32 * 4096, 8 * 4096}; cuuint32_t b[5] = {64, 8, 2, 8, 1}; make_map(fn, &tw2, w2, 5, d, s, b, CU_TENSOR_MAP_SWIZZLE_128B); }
    { cuuint64_t d[2] = {448, 2048}, s[1] = {896}; cuuint32_t b[2] = {64, 64}; make_map(fn, &txr64, x, 2, d, s, b, CU_TENSOR_MAP_SWIZZLE_128B); }
    { cuuint64_t d[2] = {448, 2048}, s[1] = {896}; cuuint32_t b[2] = {48, 64}; make_map(fn, &txr48, x, 2, d, s, b, CU_TENSOR_MAP_SWIZZLE_128B); }
    { cuuint64_t d[2] = {448, 2048}, s[1] = {896}; cuuint32_t b[2] = {64, 16}; make_map(fn, &tout64, d_out, 2, d, s, b, CU_TENSOR_MAP_SWIZZLE_128B); }
    { cuuint64_t d[2] = {448, 2048}, s[1] = {896}; cuuint32_t b[2] = {48, 16}; make_map(fn, &tout48, d_out, 2, d, s, b, CU_TENSOR_MAP_SWIZZLE_128B); }

    void* scv = nullptr;
    cudaGetSymbolAddress(&scv, g_scratch);
    Scratch* scp = (Scratch*)scv;
    int dev = 0, sms = 0;
    cudaGetDevice(&dev);
    cudaDeviceGetAttribute(&sms, cudaDevAttrMultiProcessorCount, dev);
    if (sms == 132) {
        cudaFuncSetAttribute(fused_kernel<true>, cudaFuncAttributeMaxDynamicSharedMemorySize, SM_TOTAL);
        fused_kernel<true><<<132, 384, SM_TOTAL>>>(scp, wo, w1, b1, w2, b2, tx, twqkv, two64, two48, tw1, tw2, txr64, txr48, tout64, tout48);
    } else {
        cudaFuncSetAttribute(fused_kernel<false>, cudaFuncAttributeMaxDynamicSharedMemorySize, SM_TOTAL);
        fused_kernel<false><<<132, 384, SM_TOTAL>>>(scp, wo, w1, b1, w2, b2, tx, twqkv, two64, two48, tw1, tw2, txr64, txr48, tout64, tout48);
    }
}
```

```cpp
#include <cuda_runtime.h>
#include <cuda_bf16.h>
#include <cuda.h>
#include <stdint.h>

namespace {

constexpr int D_ = 448;
constexpr float LN_EPS = 1e-5f;
constexpr float LOG2E_SCALE = 0.1889822365046136f * 1.4426950408889634f;

struct Tiles {
    uint32_t o[32 * 57344 / 4];
    uint32_t hn[4 * 32 * 14336 / 4];
    uint32_t u[4 * 28 * 14336 / 4];
};
struct Scratch {
    uint4 halo[128 * 2 * 2 * 3 * 32];
    uint4 stats[32 * 4 * 64];
    uint4 hint_k[128 * 2];
    uint4 hint_o[32 * 32 * 2];
    uint4 hint_h[4 * 32 * 2];
    uint4 hint_u[4 * 32 * 2];
    uint4 go[16];
    uint32_t epoch[160];
    uint32_t clean[16];
    alignas(1024) Tiles tiles[2];
};
__device__ Scratch g_scratch;
#define STAMP(i) do {} while (0)
#define FST(i) do {} while (0)
#define TSARG
#define TSVAL

constexpr uint32_t SB = 1024;
constexpr int SM_SLOT = 16384;
__device__ __forceinline__ constexpr uint32_t slot_x(int kb) { return (kb ? 6 + kb : 0) * SM_SLOT; }
__device__ __forceinline__ constexpr uint32_t slot_kv(int kb) { return (kb < 5 ? 2 + kb : 6 - kb) * SM_SLOT; }
__device__ __forceinline__ constexpr uint32_t slot_wo(int kb) { return (kb < 6 ? 2 + kb : 12) * SM_SLOT; }
constexpr int SM_QO = 8 * SM_SLOT;
constexpr int SM_HALOK = SM_QO + 57344, SM_HALOV = 1 * SM_SLOT;
constexpr int NA_SLOTS = 6, NB_SLOTS = 8;
constexpr int SM_ARING = 0;
constexpr int SM_BRING = NA_SLOTS * 16384;
constexpr int SM_H = 212992;
constexpr int SM_TAG = SM_H + 8192 + 96;
constexpr int SM_HALOKIN = 229376;
constexpr int SM_BAR = 231424;
constexpr int SM_TOTAL = 232448;
constexpr int B_FULLX = 0;
constexpr int B_FULLKV = 7;
constexpr int B_FQ = 14;
constexpr int B_DONE1 = 16;
constexpr int B_DONEX = 23;
constexpr int B_DONEQ = 24;
constexpr int B_DONEO = 25;
constexpr int B_FULLO = 29;
constexpr int B_FULLWO = 33;
constexpr int B_END = 34;
constexpr int B_HALO = 35;
constexpr int B_FULLA = 39;
constexpr int B_FULLB = 55;
constexpr int B_DONE = 87;
constexpr int B_RAW = 119;
constexpr int B_CLR = 127;

constexpr long long WD_CLKS = 2000000000ll;

template<int N> struct Int { static constexpr int value = N; };
template<int A, int B, class F> __device__ __forceinline__ void static_for(F&& f) { if constexpr (A < B) { f(Int<A>()); static_for<A + 1, B>(f); } }

__device__ __forceinline__ uint32_t smem_u32(const void* p) { return (uint32_t)__cvta_generic_to_shared(p); }
__device__ __forceinline__ void mbar_init(uint32_t bar, uint32_t cnt) { asm volatile("mbarrier.init.shared::cta.b64 [%0], %1;" :: "r"(bar), "r"(cnt) : "memory"); }
__device__ __forceinline__ void mbar_expect(uint32_t bar, uint32_t bytes) { asm volatile("mbarrier.arrive.expect_tx.shared::cta.b64 _, [%0], %1;" :: "r"(bar), "r"(bytes) : "memory"); }
__device__ __forceinline__ void mbar_arrive(uint32_t bar) { asm volatile("mbarrier.arrive.shared::cta.b64 _, [%0];" :: "r"(bar) : "memory"); }
__device__ __forceinline__ bool mbar_try(uint32_t bar, uint32_t parity) {
    uint32_t ok;
    asm volatile("{\n.reg .pred p;\nmbarrier.try_wait.parity.shared::cta.b64 p, [%1], %2;\nselp.u32 %0, 1, 0, p;\n}" : "=r"(ok) : "r"(bar), "r"(parity) : "memory");
    return ok;
}
__device__ __forceinline__ bool mbar_test(uint32_t bar, uint32_t parity) {
    uint32_t ok;
    asm volatile("{\n.reg .pred p;\nmbarrier.test_wait.parity.shared::cta.b64 p, [%1], %2;\nselp.u32 %0, 1, 0, p;\n}" : "=r"(ok) : "r"(bar), "r"(parity) : "memory");
    return ok;
}
__device__ __forceinline__ void mbar_wait(uint32_t bar, uint32_t parity) {
    asm volatile("{\n.reg .pred p;\n"
                 "WAIT_LOOP:\n"
                 "mbarrier.try_wait.parity.shared::cta.b64 p, [%0], %1;\n"
                 "@!p bra WAIT_LOOP;\n}" :: "r"(bar), "r"(parity) : "memory");
}
__device__ __forceinline__ void mbar_wait_wd(uint32_t bar, uint32_t parity) {
    const long long t0 = clock64();
    while (!mbar_try(bar, parity)) { if (clock64() - t0 > WD_CLKS) __trap(); }
}
__device__ __forceinline__ bool elect() { uint32_t p; asm volatile("{\n.reg .pred P;\nelect.sync _|P, 0xffffffff;\nselp.u32 %0, 1, 0, P;\n}" : "=r"(p)); return p; }
__device__ __forceinline__ void tma2d(uint32_t dst, const CUtensorMap* tm, int c0, int c1, uint32_t bar) {
    asm volatile("cp.async.bulk.tensor.2d.shared::cluster.global.mbarrier::complete_tx::bytes [%0], [%1, {%3, %4}], [%2];" :: "r"(dst), "l"(tm), "r"(bar), "r"(c0), "r"(c1) : "memory");
}
__device__ __forceinline__ void tma3d(uint32_t dst, const CUtensorMap* tm, int c0, int c1, int c2, uint32_t bar) {
    asm volatile("cp.async.bulk.tensor.3d.shared::cluster.global.mbarrier::complete_tx::bytes [%0], [%1, {%3, %4, %5}], [%2];" :: "r"(dst), "l"(tm), "r"(bar), "r"(c0), "r"(c1), "r"(c2) : "memory");
}
__device__ __forceinline__ void tma5d(uint32_t dst, const CUtensorMap* tm, int c0, int c3, int c4, uint32_t bar) {
    asm volatile("cp.async.bulk.tensor.5d.shared::cluster.global.mbarrier::complete_tx::bytes [%0], [%1, {%3, 0, 0, %4, %5}], [%2];" :: "r"(dst), "l"(tm), "r"(bar), "r"(c0), "r"(c3), "r"(c4) : "memory");
}
__device__ __forceinline__ void tma2d_store(const CUtensorMap* tm, int c0, int c1, uint32_t src) {
    asm volatile("cp.async.bulk.tensor.2d.global.shared::cta.bulk_group [%0, {%2, %3}], [%1];" :: "l"(tm), "r"(src), "r"(c0), "r"(c1) : "memory");
}
__device__ __forceinline__ void bulk_ld(uint32_t dst, const void* src, uint32_t bytes, uint32_t bar) {
    asm volatile("cp.async.bulk.shared::cluster.global.mbarrier::complete_tx::bytes [%0], [%1], %2, [%3];" :: "r"(dst), "l"(src), "r"(bytes), "r"(bar) : "memory");
}
__device__ __forceinline__ void bulk_prefetch(const void* src, uint32_t bytes) { asm volatile("cp.async.bulk.prefetch.L2.global [%0], %1;" :: "l"(src), "r"(bytes) : "memory"); }
__device__ __forceinline__ void prefetch_map(const CUtensorMap* tm) { asm volatile("prefetch.tensormap [%0];" :: "l"(tm) : "memory"); }
__device__ __forceinline__ void st_global_if(uint32_t c, uint32_t* p, uint32_t v) {
    asm volatile("{\n.reg .pred p;\nsetp.ne.u32 p, %2, 0;\n@p st.global.u32 [%0], %1;\n}" :: "l"(p), "r"(v), "r"(c) : "memory");
}
__device__ __forceinline__ void st_relaxed4_if(bool c, uint4* p, uint32_t a, uint32_t b, uint32_t d) {
    asm volatile("{\n.reg .b128 t;\n.reg .b64 a, b;\n.reg .pred p;\nsetp.ne.u32 p, %4, 0;\nmov.b64 a, {%1, %2};\nmov.b64 b, {%3, %3};\nmov.b128 t, {a, b};\n@p st.relaxed.gpu.global.b128 [%0], t;\n}" :: "l"(p), "r"(a), "r"(b), "r"(d), "r"((uint32_t)c) : "memory");
}
__device__ __forceinline__ void pin_ptr(uint32_t never, const void* a) {
    asm volatile("{\n.reg .pred p;\nsetp.ne.u32 p, %1, 0;\n@p st.shared.u64 [%1], %0;\n}" :: "l"(a), "r"(never) : "memory");
}
__device__ __forceinline__ void pin4(uint32_t never, float a, float b, float c, float d) {
    asm volatile("{\n.reg .pred p;\nsetp.ne.u32 p, %4, 0;\n@p st.shared.v4.f32 [%4], {%0,%1,%2,%3};\n}" :: "f"(a), "f"(b), "f"(c), "f"(d), "r"(never) : "memory");
}
__device__ __forceinline__ void fence_async_smem() { asm volatile("fence.proxy.async.shared::cta;" ::: "memory"); }
__device__ __forceinline__ uint32_t ld_acquire(const void* p) { uint32_t v; asm volatile("ld.acquire.gpu.global.u32 %0, [%1];" : "=r"(v) : "l"(p) : "memory"); return v; }
__device__ __forceinline__ void st_release(void* p, uint32_t v) { asm volatile("st.release.gpu.global.u32 [%0], %1;" :: "l"(p), "r"(v) : "memory"); }
__device__ __forceinline__ uint32_t ld_relaxed(const void* p) { uint32_t v; asm volatile("ld.relaxed.gpu.global.u32 %0, [%1];" : "=r"(v) : "l"(p) : "memory"); return v; }
__device__ __forceinline__ uint2 ld_relaxed2(const void* p) {
    uint2 v; asm volatile("{\n.reg .b64 a;\nld.relaxed.gpu.global.b64 a, [%2];\nmov.b64 {%0, %1}, a;\n}" : "=r"(v.x), "=r"(v.y) : "l"(p) : "memory"); return v;
}
__device__ __forceinline__ uint4 ld_relaxed4(const uint4* p) {
    uint4 v;
    asm volatile("{\n.reg .b128 t;\n.reg .b64 a, b;\nld.relaxed.gpu.global.b128 t, [%4];\nmov.b128 {a, b}, t;\nmov.b64 {%0, %1}, a;\nmov.b64 {%2, %3}, b;\n}" : "=r"(v.x), "=r"(v.y), "=r"(v.z), "=r"(v.w) : "l"(p) : "memory");
    return v;
}
__device__ __forceinline__ void st_relaxed4(uint4* p, uint32_t a, uint32_t b, uint32_t c, uint32_t d) {
    asm volatile("{\n.reg .b128 t;\n.reg .b64 a, b;\nmov.b64 a, {%1, %2};\nmov.b64 b, {%3, %4};\nmov.b128 t, {a, b};\nst.relaxed.gpu.global.b128 [%0], t;\n}" :: "l"(p), "r"(a), "r"(b), "r"(c), "r"(d) : "memory");
}
__device__ __forceinline__ uint32_t ld_u16(const unsigned short* p) { uint32_t v; asm volatile("ld.volatile.global.u16 %0, [%1];" : "=r"(v) : "l"(p) : "memory"); return v; }
__device__ __forceinline__ uint32_t ld_volatile(const uint32_t* p) { uint32_t v; asm volatile("ld.volatile.global.u32 %0, [%1];" : "=r"(v) : "l"(p) : "memory"); return v; }
__device__ __forceinline__ void named_arrive(int id, int n) { asm volatile("bar.arrive %0, %1;" :: "r"(id), "r"(n) : "memory"); }
__device__ __forceinline__ void named_sync(int id, int n) { asm volatile("bar.sync %0, %1;" :: "r"(id), "r"(n) : "memory"); }
__device__ __forceinline__ void wg_fence() { asm volatile("wgmma.fence.sync.aligned;" ::: "memory"); }
__device__ __forceinline__ void wg_commit() { asm volatile("wgmma.commit_group.sync.aligned;" ::: "memory"); }
template<int N> __device__ __forceinline__ void wg_wait() { asm volatile("wgmma.wait_group.sync.aligned %0;" :: "n"(N) : "memory"); }
template<int N> __device__ __forceinline__ void reg_fence(float (&d)[N]) {
    #pragma unroll
    for (int i = 0; i < N; i++) asm volatile("" : "+f"(d[i]) :: "memory");
}
__device__ __forceinline__ constexpr uint64_t mkdesc(uint32_t addr, uint32_t lbo, uint32_t sbo, uint32_t sw) {
    return (uint64_t)((addr & 0x3FFFF) >> 4) | ((uint64_t)(lbo >> 4) << 16) | ((uint64_t)(sbo >> 4) << 32) | ((uint64_t)sw << 62);
}
__device__ __forceinline__ void ldsm4(uint32_t (&r)[4], uint32_t addr) {
    asm volatile("ldmatrix.sync.aligned.m8n8.x4.shared.b16 {%0,%1,%2,%3}, [%4];" : "=r"(r[0]), "=r"(r[1]), "=r"(r[2]), "=r"(r[3]) : "r"(addr) : "memory");
}
__device__ __forceinline__ void stsm4_if(uint32_t c, uint32_t addr, uint32_t r0, uint32_t r1, uint32_t r2, uint32_t r3) {
    asm volatile("{\n.reg .pred p;\nsetp.ne.u32 p, %5, 0;\n@p stmatrix.sync.aligned.m8n8.x4.shared.b16 [%0], {%1,%2,%3,%4};\n}" :: "r"(addr), "r"(r0), "r"(r1), "r"(r2), "r"(r3), "r"(c) : "memory");
}
__device__ __forceinline__ void sts4(uint32_t a, uint32_t x, uint32_t y, uint32_t z, uint32_t w) { asm volatile("st.shared.v4.u32 [%0], {%1,%2,%3,%4};" :: "r"(a), "r"(x), "r"(y), "r"(z), "r"(w) : "memory"); }
__device__ __forceinline__ uint4 lds4(uint32_t a) { uint4 v; asm volatile("ld.shared.v4.u32 {%0,%1,%2,%3}, [%4];" : "=r"(v.x), "=r"(v.y), "=r"(v.z), "=r"(v.w) : "r"(a) : "memory"); return v; }
__device__ __forceinline__ uint32_t movtrans(uint32_t a) { uint32_t d; asm volatile("movmatrix.sync.aligned.m8n8.trans.b16 %0, %1;" : "=r"(d) : "r"(a)); return d; }
__device__ __forceinline__ uint32_t pack_bf16(float lo, float hi) { uint32_t r; asm("cvt.rn.bf16x2.f32 %0, %1, %2;" : "=r"(r) : "f"(hi), "f"(lo)); return r; }
__device__ __forceinline__ void sub_bf16x2(uint32_t& a, uint32_t b) { asm volatile("sub.rn.bf16x2 %0, %0, %1;" : "+r"(a) : "r"(b)); }
__device__ __forceinline__ float bf_lo(uint32_t v) { return __uint_as_float(v << 16); }
__device__ __forceinline__ float bf_hi(uint32_t v) { return __uint_as_float(v & 0xffff0000u); }
__device__ __forceinline__ void mma16816(float (&c)[4], uint32_t a0, uint32_t a1, uint32_t a2, uint32_t a3, uint32_t b0, uint32_t b1) {
    asm volatile("mma.sync.aligned.m16n8k16.row.col.f32.bf16.bf16.f32 {%0,%1,%2,%3}, {%4,%5,%6,%7}, {%8,%9}, {%0,%1,%2,%3};"
        : "+f"(c[0]), "+f"(c[1]), "+f"(c[2]), "+f"(c[3]) : "r"(a0), "r"(a1), "r"(a2), "r"(a3), "r"(b0), "r"(b1));
}
__device__ __forceinline__ void mma1688(float (&c)[4], uint32_t a0, uint32_t a1, uint32_t b0) {
    asm volatile("mma.sync.aligned.m16n8k8.row.col.f32.bf16.bf16.f32 {%0,%1,%2,%3}, {%4,%5}, {%6}, {%0,%1,%2,%3};"
        : "+f"(c[0]), "+f"(c[1]), "+f"(c[2]), "+f"(c[3]) : "r"(a0), "r"(a1), "r"(b0));
}
__device__ __forceinline__ float quad_sum(float v) { v += __shfl_xor_sync(0xffffffffu, v, 1); v += __shfl_xor_sync(0xffffffffu, v, 2); return v; }
__device__ __forceinline__ float quad_max(float v) { v = fmaxf(v, __shfl_xor_sync(0xffffffffu, v, 1)); v = fmaxf(v, __shfl_xor_sync(0xffffffffu, v, 2)); return v; }
__device__ __forceinline__ float ex2(float x) { float y; asm("ex2.approx.ftz.f32 %0, %1;" : "=f"(y) : "f"(x)); return y; }
__device__ __forceinline__ float rsqrt_approx(float x) { float y; asm("rsqrt.approx.ftz.f32 %0, %1;" : "=f"(y) : "f"(x)); return y; }
__device__ __forceinline__ float rcp_approx(float x) { float y; asm("rcp.approx.ftz.f32 %0, %1;" : "=f"(y) : "f"(x)); return y; }
constexpr float GELU_K1 = 2.f * 0.7978845608028654f;
__device__ __forceinline__ float gelu_half(float hx, float k1) {
    const float z = hx * fmaf(hx * hx, 8.f * 0.044715f * 0.7978845608028654f, k1);
    float t; asm("tanh.approx.f32 %0, %1;" : "=f"(t) : "f"(z));
    return fmaf(hx, t, hx);
}
__device__ __forceinline__ uint32_t gtime32() { uint32_t t; asm volatile("mov.u32 %0, %%globaltimer_lo;" : "=r"(t)); return t; }
__device__ __forceinline__ uint32_t clock32() { uint32_t t; asm volatile("mov.u32 %0, %%clock;" : "=r"(t)); return t; }
#define PF_PACE 400

#define PF_AT 4000
#define NSQ 6
#define HALO_AT 3
#define PF_N 12
#define HINT_U 22
#define SP_AT 2000
#define SP_N 0
#define WO_HOLD 7
#define A_SCHED 0x322188
#define WO_ORD0 0x4321065
#define WO_ORD1 0x3465210
#define XR_HOLD 0
#define ROT 0
#define NPIPE 1
#define CL_AT 4000
#define WARM 1
#define WARM_AT 300
#define W2_AT 23
#define W2_HOLD 5
#define A3_END 20
#define A4_END 16
#define GO_H 1216
#define GO_U 1440
#define STAG 0
#define GO_O 1216
#define LATE_O 256
#define PP 0
#define DRY2 1
#define LATE_AT 0
#define HINT_H 1
#define SLACK 256
#define GDEP 4
#define LATE_GAP 0
template<int TB> __device__ __forceinline__ void wgmma_rs56(float (&d)[28], const uint32_t (&a)[4], uint64_t db, int sc) {
    asm volatile("{\n.reg .pred p;\nsetp.ne.b32 p, %33, 0;\n"
        "wgmma.mma_async.sync.aligned.m64n56k16.f32.bf16.bf16 {%0, %1, %2, %3, %4, %5, %6, %7, %8, %9, %10, %11, %12, %13, %14, %15, %16, %17, %18, %19, %20, %21, %22, %23, %24, %25, %26, %27}, {%28, %29, %30, %31}, %32, p, 1, 1, %34;\n}\n"
        : "+f"(d[0]), "+f"(d[1]), "+f"(d[2]), "+f"(d[3]), "+f"(d[4]), "+f"(d[5]), "+f"(d[6]), "+f"(d[7]), "+f"(d[8]), "+f"(d[9]), "+f"(d[10]), "+f"(d[11]), "+f"(d[12]), "+f"(d[13]), "+f"(d[14]), "+f"(d[15]), "+f"(d[16]), "+f"(d[17]), "+f"(d[18]), "+f"(d[19]), "+f"(d[20]), "+f"(d[21]), "+f"(d[22]), "+f"(d[23]), "+f"(d[24]), "+f"(d[25]), "+f"(d[26]), "+f"(d[27])
        : "r"(a[0]), "r"(a[1]), "r"(a[2]), "r"(a[3]), "l"(db), "r"(sc), "n"(TB));
}

template<int TA, int TB, int SC = 1> __device__ __forceinline__ void wgmma_ss112(float (&d)[56], uint64_t da, uint64_t db) {
    asm volatile("wgmma.mma_async.sync.aligned.m64n112k16.f32.bf16.bf16 {%0, %1, %2, %3, %4, %5, %6, %7, %8, %9, %10, %11, %12, %13, %14, %15, %16, %17, %18, %19, %20, %21, %22, %23, %24, %25, %26, %27, %28, %29, %30, %31, %32, %33, %34, %35, %36, %37, %38, %39, %40, %41, %42, %43, %44, %45, %46, %47, %48, %49, %50, %51, %52, %53, %54, %55}, %56, %57, %60, 1, 1, %58, %59;\n"
        : "+f"(d[0]), "+f"(d[1]), "+f"(d[2]), "+f"(d[3]), "+f"(d[4]), "+f"(d[5]), "+f"(d[6]), "+f"(d[7]), "+f"(d[8]), "+f"(d[9]), "+f"(d[10]), "+f"(d[11]), "+f"(d[12]), "+f"(d[13]), "+f"(d[14]), "+f"(d[15]), "+f"(d[16]), "+f"(d[17]), "+f"(d[18]), "+f"(d[19]), "+f"(d[20]), "+f"(d[21]), "+f"(d[22]), "+f"(d[23]), "+f"(d[24]), "+f"(d[25]), "+f"(d[26]), "+f"(d[27]), "+f"(d[28]), "+f"(d[29]), "+f"(d[30]), "+f"(d[31]), "+f"(d[32]), "+f"(d[33]), "+f"(d[34]), "+f"(d[35]), "+f"(d[36]), "+f"(d[37]), "+f"(d[38]), "+f"(d[39]), "+f"(d[40]), "+f"(d[41]), "+f"(d[42]), "+f"(d[43]), "+f"(d[44]), "+f"(d[45]), "+f"(d[46]), "+f"(d[47]), "+f"(d[48]), "+f"(d[49]), "+f"(d[50]), "+f"(d[51]), "+f"(d[52]), "+f"(d[53]), "+f"(d[54]), "+f"(d[55])
        : "l"(da), "l"(db), "n"(TA), "n"(TB), "n"(SC));
}

template<int TA, int TB, int SC = 1> __device__ __forceinline__ void wgmma_ss64(float (&d)[32], uint64_t da, uint64_t db) {
    asm volatile("wgmma.mma_async.sync.aligned.m64n64k16.f32.bf16.bf16 {%0, %1, %2, %3, %4, %5, %6, %7, %8, %9, %10, %11, %12, %13, %14, %15, %16, %17, %18, %19, %20, %21, %22, %23, %24, %25, %26, %27, %28, %29, %30, %31}, %32, %33, %36, 1, 1, %34, %35;\n"
        : "+f"(d[0]), "+f"(d[1]), "+f"(d[2]), "+f"(d[3]), "+f"(d[4]), "+f"(d[5]), "+f"(d[6]), "+f"(d[7]), "+f"(d[8]), "+f"(d[9]), "+f"(d[10]), "+f"(d[11]), "+f"(d[12]), "+f"(d[13]), "+f"(d[14]), "+f"(d[15]), "+f"(d[16]), "+f"(d[17]), "+f"(d[18]), "+f"(d[19]), "+f"(d[20]), "+f"(d[21]), "+f"(d[22]), "+f"(d[23]), "+f"(d[24]), "+f"(d[25]), "+f"(d[26]), "+f"(d[27]), "+f"(d[28]), "+f"(d[29]), "+f"(d[30]), "+f"(d[31])
        : "l"(da), "l"(db), "n"(TA), "n"(TB), "n"(SC));
}

template<int TA, int TB, int SC = 1> __device__ __forceinline__ void wgmma_ss48(float (&d)[24], uint64_t da, uint64_t db) {
    asm volatile("wgmma.mma_async.sync.aligned.m64n48k16.f32.bf16.bf16 {%0, %1, %2, %3, %4, %5, %6, %7, %8, %9, %10, %11, %12, %13, %14, %15, %16, %17, %18, %19, %20, %21, %22, %23}, %24, %25, %28, 1, 1, %26, %27;\n"
        : "+f"(d[0]), "+f"(d[1]), "+f"(d[2]), "+f"(d[3]), "+f"(d[4]), "+f"(d[5]), "+f"(d[6]), "+f"(d[7]), "+f"(d[8]), "+f"(d[9]), "+f"(d[10]), "+f"(d[11]), "+f"(d[12]), "+f"(d[13]), "+f"(d[14]), "+f"(d[15]), "+f"(d[16]), "+f"(d[17]), "+f"(d[18]), "+f"(d[19]), "+f"(d[20]), "+f"(d[21]), "+f"(d[22]), "+f"(d[23])
        : "l"(da), "l"(db), "n"(TA), "n"(TB), "n"(SC));
}

template<int NKB>
__device__ __forceinline__ void mix_mainloop(TSARG float (&acc)[56], uint32_t par, bool leader) {
    constexpr uint32_t sb = SB, bars = sb + SM_BAR;
    constexpr int A0 = NKB == 32 ? 0 : 16 % NA_SLOTS;
    int bslot = 0, aslot = A0;
    reg_fence(acc);
    #pragma unroll 1
    for (int i = 0; i < NKB / 2; i++) {
        mbar_wait(bars + 8 * (B_FULLA + i), par);
        const uint64_t adesc = mkdesc(sb + SM_ARING, 8192, 1024, 1) + (uint32_t)(aslot * 1024);
        aslot = aslot == NA_SLOTS - 1 ? 0 : aslot + 1;
        #pragma unroll
        for (int jj = 0; jj < 2; jj++) {
            const int j = 2 * i + jj;
            mbar_wait(bars + 8 * (B_FULLB + j), par);
            const uint64_t bdesc = mkdesc(sb + SM_BRING, 1792, 128, 0) + (uint32_t)(bslot * 896);
            bslot = bslot == NB_SLOTS - 1 ? 0 : bslot + 1;
            wg_fence();
            #pragma unroll
            for (int s = 0; s < 4; s++) wgmma_ss112<1, 1>(acc, adesc + jj * 512 + s * 128, bdesc + s * 224);
            wg_commit();
            wg_wait<1>();
            if (j > 0 && leader) mbar_arrive(bars + 8 * (B_DONE + j - 1));
        }
    }
    wg_wait<0>();
    reg_fence(acc);
    if (leader) mbar_arrive(bars + 8 * (B_DONE + NKB - 1));
}

constexpr uint32_t EMPTY = 0xFFFFFFFFu;
__device__ __forceinline__ void post_hint(uint4* p, uint32_t ep, int lane) { if (lane < 2) st_relaxed4(p + lane, ep, ep, ep, ep); }
__device__ __forceinline__ void post_time(uint4* p, uint32_t ep, int lane) { const uint32_t now = gtime32(); if (lane < 2) st_relaxed4(p + lane, ep, now, ep, now); }

__device__ __forceinline__ void wait_hints(TSARG const uint4* hint, uint32_t ep, uint32_t delay, int st) {
    uint2 v;
    do { v = ld_relaxed2(hint); } while (!__all_sync(0xffffffffu, v.x == ep));
    const uint32_t t1 = gtime32(), age = __reduce_min_sync(0xffffffffu, t1 + 256 - v.y);
    if (elect()) STAMP(st);
    while (gtime32() - t1 + age < delay + 256) {}
    __syncwarp();
}

template<int NKB>
__device__ __forceinline__ void mix_producer_b(TSARG uint32_t par, const uint4* hints, uint32_t ep, const uint32_t* src, int lane) {
    constexpr uint32_t sb = SB, bars = sb + SM_BAR;
    wait_hints(TSVAL hints, ep, NKB == 32 ? GO_H : GO_U, NKB == 32 ? 42 : 43);
    mbar_wait(bars + 8 * (par ? B_DONE + 31 : B_DONEO + 3), 0);
    #pragma unroll 1
    for (int j = 0; j < NKB; j++) {
        if (j >= NB_SLOTS) mbar_wait(bars + 8 * (B_DONE + j - NB_SLOTS), par);
        if (j == 0 && lane == 0) STAMP(NKB == 32 ? 29 : 30);
        if (j == 7 && lane == 0) STAMP(NKB == 32 ? 35 : 36);
        if (elect()) {
            mbar_expect(bars + 8 * (B_RAW + (j & 7)), 14336);
            bulk_ld(sb + SM_BRING + (j & 7) * 14336, src + j * 3584, 14336, bars + 8 * (B_RAW + (j & 7)));
        }
    }
}
__device__ __forceinline__ void check_tiles(TSARG int n, int w, int lane, uint32_t dst, const uint32_t* src, int full, const uint32_t (&late)[14], uint32_t* late_ptr) {
    constexpr uint32_t bars = SB + SM_BAR;
    uint32_t ph = 0;
    if (n > 4) asm volatile("ld.shared.u32 %0, [%1];" : "=r"(ph) : "r"(SB + SM_TAG + 4 + 4 * w) : "memory");
    #pragma unroll 1
    for (int j = w; j < n; j += 4) {
        const uint32_t raw = bars + 8 * (B_RAW + (j & 7)), d = dst + (j & 7) * 14336, a = d + lane * 128 + (lane & 3) * 32 + (lane >> 2) * 4;
        bool bad;
        do {
            mbar_wait(raw, (ph >> (j & 4)) & 1);
            ph ^= 1u << (j & 4);
            if (j == 0 && lane == 0) STAMP(n == 4 ? 6 : n == 32 ? 31 : 32);
            uint32_t v0, v1, v2, v3;
            asm volatile("ld.shared.u32 %0, [%4];\nld.shared.u32 %1, [%4+4096];\nld.shared.u32 %2, [%4+8192];\nld.shared.u32 %3, [%4+10240];"
                         : "=r"(v0), "=r"(v1), "=r"(v2), "=r"(v3) : "r"(a) : "memory");
            bad = __any_sync(0xffffffffu, max(max(v0, v1), max(v2, v3)) == EMPTY);
            if (elect() && bad) {
                mbar_expect(raw, 14336); bulk_ld(d, src + j * 3584, 14336, raw);
            }
        } while (bad);
        if (lane == 0) {
            asm volatile("st.shared.u32 [%0], %1;" :: "r"(SB + SM_TAG + 4 + 4 * w), "r"(ph) : "memory");
            mbar_arrive(bars + 8 * (full + j));
        }
        if ((j >> 2) == LATE_AT && late_ptr) {
            #pragma unroll
            for (int c = 0; c < 14; c++) {
                st_global_if(1, late_ptr + c * 32, late[c]);
                if (LATE_GAP) { const uint32_t t = clock32(); while (clock32() - t < LATE_GAP) {} }
            }
            __syncwarp();
        }
    }
}

__device__ __forceinline__ uint32_t hcol(uint32_t a, int jp) { return (a ^ ((jp & 3) << 5)) + (jp >> 2) * 8192; }

__device__ __forceinline__ uint32_t get_tag() {
    mbar_wait(SB + SM_BAR + 8 * B_CLR, 0);
    uint32_t v; asm volatile("ld.shared.u32 %0, [%1];" : "=r"(v) : "r"(SB + SM_TAG) : "memory"); return v;
}

template<bool USE_SMID>
__global__ void __launch_bounds__(384, 1)
fused_kernel(Scratch* __restrict__ sc, const __nv_bfloat16* __restrict__ wo,
             const __nv_bfloat16* __restrict__ w1, const __nv_bfloat16* __restrict__ b1,
             const __nv_bfloat16* __restrict__ w2, const __nv_bfloat16* __restrict__ b2,
             const __grid_constant__ CUtensorMap tm_x, const __grid_constant__ CUtensorMap tm_wqkv,
             const __grid_constant__ CUtensorMap tm_wo64, const __grid_constant__ CUtensorMap tm_wo48,
             const __grid_constant__ CUtensorMap tm_w1, const __grid_constant__ CUtensorMap tm_w2,
             const __grid_constant__ CUtensorMap tm_xr64, const __grid_constant__ CUtensorMap tm_xr48,
             const __grid_constant__ CUtensorMap tm_out64, const __grid_constant__ CUtensorMap tm_out48) {
    extern __shared__ __align__(1024) uint8_t smem_raw[];
    constexpr uint32_t sb = SB;
    constexpr uint32_t bars = sb + SM_BAR;
    const int tid = threadIdx.x, lane = tid & 31;
    const int warp = __shfl_sync(0xffffffffu, tid >> 5, 0);
    int slot;
    if (USE_SMID) {
        asm("{\n.reg .u32 s, t, u, d, a, b, c;\n.reg .pred p, r;\n"
            "mov.u32 s, %%smid;\nshr.u32 t, s, 1;\nsub.u32 u, t, 32;\nmul.lo.u32 d, u, 37;\nshr.u32 d, d, 8;\n"
            "and.b32 a, t, 7;\nshl.b32 a, a, 3;\nshr.u32 c, t, 3;\nadd.u32 a, a, c;\n"
            "mad.lo.u32 b, d, -55, 12;\nshl.b32 c, u, 3;\nadd.u32 b, b, c;\n"
            "setp.lt.u32 p, t, 32;\nselp.u32 a, a, b, p;\n"
            "setp.lt.u32 r, t, 62;\nselp.s32 c, 4, -58, r;\nadd.u32 c, t, c;\nsetp.lt.u32 p, t, 60;\nselp.u32 a, a, c, p;\n"
            "and.b32 s, s, 1;\nshl.b32 a, a, 1;\nadd.u32 %0, a, s;\n}" : "=r"(slot));
    } else slot = blockIdx.x;
    const int G = slot >> 4, mi = slot & 15;
    const int tb = 4 * (G >> 1) + (mi >> 2), hp = 2 * (mi & 3) + (G & 1);
    const int wcol = (hp * 56) & ~15;
    if (slot >= 128) {
        const uint32_t ep = ld_volatile(&sc->epoch[slot]) + 1;
        if (warp == 1 && mi < 2) {
            post_hint(sc->go + 8 * mi, 0, lane);
            const uint4* hint = (mi ? sc->hint_u : sc->hint_h) + 2 * min(lane, mi ? 27 : 31);
            while (ld_relaxed(sc->hint_k) != ep) __nanosleep(200);
            uint2 v[4];
            do {
                #pragma unroll
                for (int i = 0; i < 4; i++) v[i] = ld_relaxed2(hint + 64 * i);
            } while (!__all_sync(0xffffffffu, v[0].x == ep && v[1].x == ep && v[2].x == ep && v[3].x == ep));
            const uint32_t t1 = gtime32() + 256;
            const uint32_t age = min(min(t1 - v[0].y, t1 - v[1].y), min(t1 - v[2].y, t1 - v[3].y)) + (lane < 16 ? 0 : SLACK);
            const uint32_t ts = t1 - __reduce_min_sync(0xffffffffu, age);
            if (lane < 2) st_relaxed4(sc->go + 8 * mi + lane, ep, ts, ep, ts);
        }
        if (tid == 0) {
            const long long t0 = clock64();
            while (clock64() - t0 < SP_AT) {}
            #pragma unroll 1
            for (int i = 0; i < 7; i++) bulk_prefetch((const char*)wo + (i * 4 + mi) * 14336, 14336);
            #pragma unroll 1
            for (int i = 0; i < SP_N; i++) bulk_prefetch((const char*)w1 + (i * 4 + mi) * 14336, 14336);
            while (ld_relaxed(sc->hint_u) != ep) { __nanosleep(500); if (clock64() - t0 > WD_CLKS) __trap(); }
            sc->epoch[slot] = ep;
        }
        return;
    }
    const int q = mi & 3, tt2 = 4 * G + (mi >> 2), ft = 4 * (G - 1) + (mi >> 2);
    const bool has_b1 = G > 0;
    const int c64 = 64 * q, c48 = 256 + 48 * q;

    if (warp < 8) {
        if (WARM) {
            const int w = warp & 3, wg = warp >> 2, g = lane >> 2, t = lane & 3;
            if (WARM_AT) { const uint32_t t0 = clock32(); while (clock32() - t0 < WARM_AT) {} __syncwarp(); }
            if (w > 0) post_hint(sc->hint_o + ((2 * tb + (w >> 1)) * 32 + hp * 4 + (w & 1) * 2 + wg) * 2, 0, lane);
            if (wg == 0) {
                if (t < 2) st_relaxed4(sc->stats + tt2 * 256 + q * 64 + 16 * w + g + 8 * t, 0, 0, 0, 0);
            }
        }
        named_sync(0, 384);
        asm volatile("setmaxnreg.inc.sync.aligned.u32 224;");
        int tid; asm volatile("mov.u32 %0, %%tid.x;" : "=r"(tid));
        const int lane = tid & 31, warp = __shfl_sync(0xffffffffu, tid >> 5, 0), wg = warp >> 2;
        uint32_t ep;
        Tiles* tl;
        const int w = warp & 3, g = lane >> 2, t = lane & 3;
        const bool leader = (tid & 127) == 0;
        const uint32_t never = gridDim.y - 1;
        {
            uint32_t a[28][4];
            float accK[28], accV[28], accQ[28];
            const int lrow = 16 * w + (lane & 7) + (lane & 8);
            const uint32_t lbase = sb + wg * 8192 + lrow * 128;
            const uint32_t lx = (lane >> 4) ^ (lane & 7);
            const uint32_t wofs = hp & 1;
            auto pin2 = [&](uint32_t x0, uint32_t x1) {
                asm volatile("{\n.reg .pred p;\nsetp.ne.u32 p, %2, 0;\n@p st.shared.v2.b32 [%0], {%0,%1};\n}" :: "r"(x0), "r"(x1), "r"(never) : "memory");
            };
            float cS[2][4] = {}, cA[2][4] = {}, cB[2][4] = {}, q0, q1, p0, p1;
            auto sq = [&](float& acc, uint32_t v) { const float lo = bf_lo(v), hi = bf_hi(v); acc = fmaf(hi, hi, fmaf(lo, lo, acc)); };
            #pragma unroll
            for (int kb = 0; kb < 8; kb++) {
                if (kb < 7) {
                    mbar_wait(bars + 8 * (B_FULLX + kb), 0);
                    if (kb == 0 && tid == 0) STAMP(0);
                    if (kb == 6 && tid == 0) STAMP(25);
                    if (kb == 0) FST(0); if (kb == 2) FST(1); if (kb == 4) FST(2); if (kb == 6) FST(3);
                    #pragma unroll
                    for (int s = 4 * kb; s < 4 * kb + 4; s++) ldsm4(a[s], lbase + slot_x(kb) + ((lx ^ (2 * (s & 3))) << 4));
                }
                if (kb == NPIPE) continue;
                const int kc = kb < NPIPE ? kb : kb - 1;
                if (kc == NSQ) { p0 = cS[0][0] + cS[1][0]; p1 = cS[0][2] + cS[1][2]; }
                #pragma unroll
                for (int s = 4 * kc; s < 4 * kc + 4; s++) {
                    mma16816(cS[s & 1], a[s][0], a[s][1], a[s][2], a[s][3], 0x3F803F80u, 0x3F803F80u);
                    if (kc < NSQ) {
                        mma1688(cA[0], a[s][0], a[s][1], a[s][0]); mma1688(cA[1], a[s][2], a[s][3], a[s][2]);
                        mma1688(cB[0], a[s][0], a[s][1], a[s][1]); mma1688(cB[1], a[s][2], a[s][3], a[s][3]);
                    }
                }
            }
            const float m0 = (cS[0][0] + cS[1][0]) * (1.f / D_), m1 = (cS[0][2] + cS[1][2]) * (1.f / D_);
            const uint32_t mm0 = pack_bf16(m0, m0), mm1 = pack_bf16(m1, m1);
            if (lane == 0) mbar_arrive(bars + 8 * B_DONEX);
            auto center = [&](int s) { sub_bf16x2(a[s][0], mm0); sub_bf16x2(a[s][1], mm1); sub_bf16x2(a[s][2], mm0); sub_bf16x2(a[s][3], mm1); };
            uint32_t Ka[8], Kb[8], Kc[8], Va[8], Vb[7], Vc[8];
            float r0, r1, ls0, ls1;
            uint32_t pm, zero;
            uint32_t* od;
            uint4* oh;
            auto kpack = [&](uint32_t (&k)[8], int j, int c, float r) {
                const uint32_t v = pack_bf16(accK[4 * j + c] * r, accK[4 * j + c + 1] * r);
                if (j == 3) { k[3] = t < 2 ? v : 0u; k[4] = t < 2 ? 0u : v; } else k[j + (j > 3)] = v;
            };
            auto batch = [&](auto c0, auto c1) {
                constexpr int n0 = c0.value, n1 = c1.value;
                if (PP && n0 < PP) named_sync(10 + wg, 256);
                wg_fence();
                static_for<n0, n1>([&](auto nc) {
                    constexpr int n = nc.value;
                    if (n == 4) { center(4); center(5); center(6); center(7); wg_fence(); }
                    const uint64_t desc = mkdesc(sb + (n < 56 ? slot_kv(n >> 3) + (n & 7) * 2048 : SM_QO + (n - 56) * 2048), 8192, 1024, 1) + wofs;
                    wgmma_rs56<1>(n < 28 ? accK : n < 56 ? accV : accQ, a[n % 28], desc, n % 28 != 0);
                });
                wg_commit();
                if (PP && n0 < PP && (n1 < PP || wg == 0)) named_arrive(11 - wg, 256);
                if (n0 > 0) wg_wait<1>();
            };
            const uint32_t hs = sb + tid * 16 + warp * 512;
            auto hand_over = [&](const uint32_t (&v)[8], int kv) {
                mbar_wait(bars + 8 * (kv ? B_DONE1 + 5 : B_DONEX), 0);
                sts4(hs + (kv ? SM_HALOV : SM_HALOK), v[0], v[1], v[2], v[3]); sts4(hs + (kv ? SM_HALOV : SM_HALOK) + 512, v[4], v[5], v[6], v[7]);
                if (w == 3) named_arrive(6 + kv, 96);
            };
            auto take_over = [&](uint32_t (&v)[8], int kv) {
                if (w == 0) mbar_wait(bars + 8 * (B_HALO + 2 * kv + wg), 0);
                const uint32_t ad = w ? hs + (kv ? SM_HALOV : SM_HALOK) - 1024 : sb + lane * 16 + wg * 1024 + (kv ? SM_HALOV + 8192 : SM_HALOKIN);
                const uint4 u0 = lds4(ad), u1 = lds4(ad + 512);
                v[0] = u0.x; v[1] = u0.y; v[2] = u0.z; v[3] = u0.w; v[4] = u1.x; v[5] = u1.y; v[6] = u1.z; v[7] = u1.w;
            };
            if (PP && wg == 1) { pin2(mm0, mm1); named_arrive(10, 256); }
            center(0); center(1); center(2); center(3);
            static_for<0, 7>([&](auto pc) {
                constexpr int p = pc.value;
                mbar_wait(bars + 8 * (B_FULLKV + p), 0);
                if (p == 0 && tid == 0) STAMP(26);
                if (p == 3 && tid == 0) STAMP(27);
                FST(4 + p);
                batch(Int<8 * p>(), Int<8 * p + 8>());
                if (p > 0 && leader) mbar_arrive(bars + 8 * (B_DONE1 + p - 1));
                #pragma unroll
                for (int s = 8 * p + 8; s < 8 * p + 16 && s < 28; s++) center(s);
                if (p == 1) {
                    const float c0 = bf_hi(mm0), c1 = bf_hi(mm1);
                    q0 = fmaf(c0, fmaf(c0, 64.f * NSQ, -2.f * p0), (g & 1) ? cA[0][1] + cA[1][1] : cA[0][0] + cA[1][0]) - D_ * (m0 - c0) * (m0 - c0);
                    q1 = fmaf(c1, fmaf(c1, 64.f * NSQ, -2.f * p1), (g & 1) ? cB[0][3] + cB[1][3] : cB[0][2] + cB[1][2]) - D_ * (m1 - c1) * (m1 - c1);
                    asm("" : "+f"(q0), "+f"(q1));
                    q0 = t == (g >> 1) ? q0 : 0.f; q1 = t == (g >> 1) ? q1 : 0.f;
                    pin2(__float_as_uint(q0), __float_as_uint(q1));
                }
                constexpr int PK = NSQ < 5 ? 5 : 4, NR = 28 - 4 * NSQ;
                if (p >= 2 && p < PK) {
                    #pragma unroll
                    for (int s = 4 * NSQ + NR * (p - 2) / (PK - 2); s < 4 * NSQ + NR * (p - 1) / (PK - 2); s++) { sq(q0, a[s][0]); sq(q1, a[s][1]); sq(q0, a[s][2]); sq(q1, a[s][3]); }
                    pin2(__float_as_uint(q0), __float_as_uint(q1));
                }
                if (p == PK - 1) { q0 = quad_sum(q0); q1 = quad_sum(q1); }
                if (p == PK) {
                    r0 = rsqrt_approx(fmaxf(q0 * (1.f / D_), 0.f) + LN_EPS); r1 = rsqrt_approx(fmaxf(q1 * (1.f / D_), 0.f) + LN_EPS);
                    reg_fence(accK);
                    #pragma unroll
                    for (int j = 0; j < 7; j++) kpack(Kc, j, 2, r1);
                    hand_over(Kc, 0);
                }
                if (p == PK + 1) {
                    #pragma unroll
                    for (int j = 0; j < 7; j++) kpack(Kb, j, 0, r0);
                    #pragma unroll
                    for (int j = 0; j < 8; j += 2) pin2(Kb[j], Kb[j + 1]);
                    ls0 = LOG2E_SCALE * r0; ls1 = LOG2E_SCALE * r1;
                    pm = (2 * t <= g ? 0xFFFFu : 0u) | (2 * t + 1 <= g ? 0xFFFF0000u : 0u);
                    zero = never; asm volatile("" : "+r"(zero));
                    pin2(__float_as_uint(ls0), __float_as_uint(ls1)); pin2(pm, zero);
                }
                if (p == 2) ep = get_tag();
                if (p == 6) {
                    tl = &sc->tiles[ep & 1];
                    const int tt = 2 * tb + (w >> 1);
                    od = tl->o + tt * 14336 + (7 * hp) * 256 + (2 * (2 * (w & 1) + wg)) * 32 + lane;
                    oh = sc->hint_o + (tt * 32 + hp * 4 + (w & 1) * 2 + wg) * 2 + (lane & 1);
                    pin2((uint32_t)(uint64_t)od, (uint32_t)((uint64_t)od >> 32));
                    pin2((uint32_t)(uint64_t)oh, (uint32_t)((uint64_t)oh >> 32));
                }
            });
            if (tid == 0) STAMP(1);
            FST(11);
            mbar_wait(bars + 8 * B_FQ, 0);
            batch(Int<56>(), Int<60>());
            reg_fence(accV);
            if (leader) mbar_arrive(bars + 8 * (B_DONE1 + 6));
            if (tid == 0) STAMP(2);
            FST(12);
            #pragma unroll
            for (int j = 0; j < 7; j++) Vc[j] = movtrans(pack_bf16(accV[4 * j + 2] * r1, accV[4 * j + 3] * r1));
            Vc[7] = Vc[6];
            hand_over(Vc, 1);
            batch(Int<60>(), Int<66>());
            #pragma unroll
            for (int j = 0; j < 7; j++) {
                Vb[j] = movtrans(pack_bf16(accV[4 * j] * r0, accV[4 * j + 1] * r0));
                Vc[j] |= zero;
            }
            batch(Int<66>(), Int<72>());
            #pragma unroll
            for (int j = 0; j < 7; j++) pin2(Vb[j], Vc[j]);
            mbar_wait(bars + 8 * (B_FQ + 1), 0);
            FST(13);
            if (w > 0 && lane < 2) { const uint32_t now = gtime32(); st_relaxed4(oh, ep, now, ep, now); }
            batch(Int<72>(), Int<84>());
            FST(14);
            named_sync(1 + wg, 128);
            take_over(Ka, 0);
            if (tid == 0) STAMP(3);
            wg_wait<0>();
            reg_fence(accQ);
            if (tid == 0) STAMP(4);
            FST(15);
            const bool first = (tb == 0 && w == 0);
            uint32_t pA[2], pB0[2], pB1[2], pC[2], z0[2], z1[2];
            #pragma unroll
            for (int h = 0; h < 2; h++) {
                float sA[4] = {0.f, 0.f, 0.f, 0.f}, sB[4] = {0.f, 0.f, 0.f, 0.f}, sC[4] = {0.f, 0.f, 0.f, 0.f};
                #pragma unroll
                for (int k = 0; k < 2; k++) {
                    const float* qq = accQ + 12 * h + 8 * k;
                    uint32_t a0 = pack_bf16(qq[0], qq[1]), a1 = pack_bf16(qq[2], qq[3]);
                    if (h == 1 && k == 0) { a0 |= zero; a1 |= zero; }
                    const uint32_t a2 = pack_bf16(qq[4], qq[5]), a3 = pack_bf16(qq[6], qq[7]);
                    mma16816(sB, a0, a1, a2, a3, Kb[4 * h + 2 * k], Kb[4 * h + 2 * k + 1]);
                    mma16816(sA, a0, a1, a2, a3, Ka[4 * h + 2 * k], Ka[4 * h + 2 * k + 1]);
                    mma16816(sC, a0, a1, a2, a3, Kc[4 * h + 2 * k], Kc[4 * h + 2 * k + 1]);
                }
                const bool n0 = pm & 1, n1 = (int)pm < 0;
                const float l00 = n0 ? sB[0] : (first ? -INFINITY : sA[0]), l01 = n1 ? sB[1] : (first ? -INFINITY : sA[1]);
                const float l10 = n0 ? sC[2] : sB[2], l11 = n1 ? sC[3] : sB[3];
                const float x0 = -ls0 * quad_max(fmaxf(l00, l01)), x1 = -ls1 * quad_max(fmaxf(l10, l11));
                const float e00 = ex2(fmaf(l00, ls0, x0)), e01 = ex2(fmaf(l01, ls0, x0)), e10 = ex2(fmaf(l10, ls1, x1)), e11 = ex2(fmaf(l11, ls1, x1));
                const float i0 = rcp_approx(quad_sum(e00 + e01)), i1 = rcp_approx(quad_sum(e10 + e11));
                const uint32_t P0 = pack_bf16(e00 * i0, e01 * i0), P1 = pack_bf16(e10 * i1, e11 * i1);
                pB0[h] = P0 & pm; pA[h] = P0 & ~pm; pC[h] = P1 & pm; pB1[h] = P1 & ~pm; z0[h] = P0 & zero; z1[h] = P1 & zero;
            }
            float o[8][4];
            #pragma unroll
            for (int j = 0; j < 8; j++) {
                o[j][0] = o[j][1] = o[j][2] = o[j][3] = 0.f;
                mma16816(o[j], pB0[j >> 2], pB1[j >> 2], z0[j >> 2], pC[j >> 2], Vb[j - (j >> 2)], Vc[j - (j >> 2)]);
            }
            if (tid == 0) STAMP(12);
            FST(16);
            take_over(Va, 1);
            if (lane == 0) mbar_arrive(bars + 8 * B_DONEQ);
            if (tid == 0) STAMP(16);
            #pragma unroll
            for (int j = 0; j < 8; j++) mma1688(o[j], pA[j >> 2], z1[j >> 2], Va[j - (j >> 2)]);
            #pragma unroll
            for (int j = 0; j < 7; j++) {
                float v[4];
                #pragma unroll
                for (int c = 0; c < 4; c++) v[c] = j < 3 ? o[j][c] : j > 3 ? o[j + 1][c] : (t < 2 ? o[3][c] : o[4][c]);
                od[j * 256] = pack_bf16(v[0], v[1]);
                od[j * 256 + 32] = pack_bf16(v[2], v[3]);
            }
            if (tid == 0) STAMP(5);
            FST(17);
        }
        const uint32_t live = wg ^ 1;
        uint32_t rb0, rb1, late[14];
        uint32_t* late_ptr = nullptr;
        const unsigned short* pb = (const unsigned short*)(live ? b2 + tt2 * 64 : b1 + max(ft, 0) * 64) + 16 * w + g;
        auto undef = [](float (&v)[56]) {
            #pragma unroll
            for (int i = 0; i < 56; i++) asm volatile("" : "=f"(v[i]));
        };
        {
            float acc[56];
            const int hrow = 32 * (w >> 1) + 2 * ((lane & 7) + (lane & 8)) + (w & 1);
            const uint32_t ha = sb + SM_H + hrow * 128 + (((lane >> 4) ^ (hrow & 7)) << 4);
            uint4* sp = sc->stats + tt2 * 256 + 16 * w + g + 8 * (t & 1);
            uint4* sp_out = sp + q * 64;
            const uint4* sp_in = sp + (t & 2) * 64;
            uint32_t* hd = tl->hn + (q * 64 + tt2) * 1792 + w * 448 + lane;
            pin_ptr(never, sp_out); pin_ptr(never, sp_in); pin_ptr(never, hd);
            float s0 = 0.f, s1 = 0.f, q0 = 0.f, q1 = 0.f, s2 = 0.f, s3 = 0.f, q2 = 0.f, q3 = 0.f;
            auto sums = [&](int j0, int j1) {
                #pragma unroll
                for (int j = j0; j < j1; j++) {
                    s0 += acc[4 * j]; s2 += acc[4 * j + 1]; q0 = fmaf(acc[4 * j], acc[4 * j], q0); q2 = fmaf(acc[4 * j + 1], acc[4 * j + 1], q2);
                    s1 += acc[4 * j + 2]; s3 += acc[4 * j + 3]; q1 = fmaf(acc[4 * j + 2], acc[4 * j + 2], q1); q3 = fmaf(acc[4 * j + 3], acc[4 * j + 3], q3);
                }
            };
            if (live) {
                mbar_wait(bars + 8 * B_FULLWO, 0);
                #pragma unroll
                for (int jp = 0; jp < 7; jp++) {
                    uint32_t xx[4];
                    ldsm4(xx, hcol(ha, jp));
                    #pragma unroll
                    for (int r = 0; r < 4; r++) { acc[8 * jp + 2 * r] = bf_lo(xx[r]); acc[8 * jp + 2 * r + 1] = bf_hi(xx[r]); }
                }
                reg_fence(acc);
                auto od_ = [&](int s) { return mkdesc(sb + SM_QO + s * 2048, 1024, 128, 0); };
                auto wd_ = [&](int s) { return mkdesc(sb + slot_wo(s >> 2) + (s & 3) * 2048, 8192, 1024, 1); };
                float accl[32], accr[24];
                #pragma unroll
                for (int i = 0; i < 5; i++) {
                    if (i < 4) mbar_wait(bars + 8 * (B_FULLO + i), 0);
                    if (i == 0 && tid == 0) STAMP(7);
                    if (i == 1) { rb0 = ld_u16(pb); rb1 = ld_u16(pb + 8); }
                    wg_fence();
                    #pragma unroll
                    for (int ss = 0; ss < 7; ss++) {
                        if (i < 3) wgmma_ss112<0, 1>(acc, od_(7 * i + ss), wd_(7 * i + ss));
                        else if (i == 4) wgmma_ss64<0, 1>(accl, od_(21 + ss), wd_(21 + ss));
                        else if (ss == 0) wgmma_ss48<0, 1, 0>(accr, od_(21), wd_(21) + 512);
                        else wgmma_ss48<0, 1>(accr, od_(21 + ss), wd_(21 + ss) + 512);
                    }
                    wg_commit();
                    if (i > 0) {
                        wg_wait<1>();
                        if (i == 3) {
                            reg_fence(acc);
                            #pragma unroll
                            for (int c = 0; c < 32; c++) accl[c] = __uint_as_float(__float_as_uint(acc[c]) | never);
                            reg_fence(accl);
                        }
                        if (i < 4 && leader) mbar_arrive(bars + 8 * (B_DONEO + i - 1));
                    }
                }
                reg_fence(accr);
                #pragma unroll
                for (int c = 0; c < 24; c++) acc[32 + c] += accr[c];
                sums(8, 14);
                pin4(never, s0, s1, s2, s3); pin4(never, q0, q1, q2, q3);
                wg_wait<0>();
                reg_fence(accl);
                #pragma unroll
                for (int c = 0; c < 32; c++) acc[c] = accl[c];
                if (leader) mbar_arrive(bars + 8 * (B_DONEO + 3));
                if (tid == 0) STAMP(8);
            } else undef(acc);
            if (live || (DRY2 && w == 3)) {
            sums(0, 8);
            s0 += s2; s1 += s3; q0 += q2; q1 += q3;
            float sr = ((t & 1) ? s1 : s0) + __shfl_xor_sync(0xffffffffu, (t & 1) ? s0 : s1, 1), qr = ((t & 1) ? q1 : q0) + __shfl_xor_sync(0xffffffffu, (t & 1) ? q0 : q1, 1);
            sr += __shfl_xor_sync(0xffffffffu, sr, 2); qr += __shfl_xor_sync(0xffffffffu, qr, 2);
            st_relaxed4_if(t < 2 * live, sp_out, __float_as_uint(sr), __float_as_uint(qr), ep);
            if (live) named_arrive(5, 256);
            if (tid == 0) STAMP(9);
            #pragma unroll
            for (int jp = 0; jp < 7; jp++)
                stsm4_if(live, hcol(ha, jp), pack_bf16(acc[8 * jp], acc[8 * jp + 1]), pack_bf16(acc[8 * jp + 2], acc[8 * jp + 3]),
                      pack_bf16(acc[8 * jp + 4], acc[8 * jp + 5]), pack_bf16(acc[8 * jp + 6], acc[8 * jp + 7]));
            uint4 v0, v1;
            do { v0 = ld_relaxed4(sp_in); v1 = ld_relaxed4(sp_in + 64); } while (live && __any_sync(0xffffffffu, v0.w != ep || v1.w != ep));
            if (tid == 0) STAMP(10);
            sr = __uint_as_float(v0.x) + __uint_as_float(v1.x); qr = __uint_as_float(v0.y) + __uint_as_float(v1.y);
            sr += __shfl_xor_sync(0xffffffffu, sr, 2); qr += __shfl_xor_sync(0xffffffffu, qr, 2);
            const float m = sr * (1.f / D_), v = fmaxf(qr * (1.f / D_) - m * m, 0.f);
            const float r = rsqrt_approx(fmaf(v, 4.f + 4.f * LN_EPS, 4.f * LN_EPS * LN_EPS)), c = -m * r;
            const float r0 = __shfl_sync(0xffffffffu, r, lane & ~1), c0 = __shfl_sync(0xffffffffu, c, lane & ~1);
            const float r1 = __shfl_sync(0xffffffffu, r, lane | 1), c1 = __shfl_sync(0xffffffffu, c, lane | 1);
            #pragma unroll
            for (int j = 0; j < 14; j++) st_global_if(live, hd + j * 32, pack_bf16(fmaf(acc[4 * j], r0, c0), fmaf(acc[4 * j + 1], r0, c0)));
            if (never) mbar_arrive(bars);
            #pragma unroll
            for (int j = 0; j < 14; j++) late[j] = pack_bf16(fmaf(acc[4 * j + 2], r1, c1), fmaf(acc[4 * j + 3], r1, c1));
            late_ptr = hd + 32 * 1792;
            if (tid == 0) STAMP(11);
            }
        }
        if (!live) {
            check_tiles(TSVAL 4, w, lane, sb + SM_QO, tl->o + tt2 * 14336, B_FULLO, late, nullptr);
            rb0 = ld_u16(pb); rb1 = ld_u16(pb + 8);
            late_ptr = nullptr;
            named_sync(5, 256);
            if (has_b1) {
                float acc[56];
                uint32_t* ud = tl->u + (q * 56 + ft) * 1792 + w * 448 + lane;
                #pragma unroll
                for (int j = 0; j < 56; j++) acc[j] = 0.5f * bf_lo((j & 2) ? rb1 : rb0);
                #pragma unroll 1
                for (uint32_t pass = never; pass < 2; pass++) {
                    if (pass) {
                        mix_mainloop<32>(TSVAL acc, 0, leader);
                        if (leader) STAMP(14);
                    }
                    uint32_t pk[14];
                    #pragma unroll
                    for (int j = 0; j < 14; j++) {
                        const float k = j < GDEP ? GELU_K1 : __uint_as_float(__float_as_uint(GELU_K1) | (pk[j - GDEP] & never));
                        pk[j] = pack_bf16(gelu_half(acc[4 * j], k), gelu_half(acc[4 * j + 1], k));
                        st_global_if(pass, ud + j * 32, pk[j]);
                    }
                }
                named_arrive(3, 256);
                if (leader) STAMP(15);
                #pragma unroll
                for (int j = 0; j < 14; j++) late[j] = pack_bf16(gelu_half(acc[4 * j + 2], GELU_K1), gelu_half(acc[4 * j + 3], GELU_K1));
                late_ptr = ud + 28 * 1792;
            }
            check_tiles(TSVAL 28, w, lane, sb + SM_BRING, tl->u + q * 28 * 3584, B_FULLB, late, late_ptr);
            return;
        }
        {
            float acc[56];
            const uint32_t ad = sb + SM_H + (16 * w + (lane & 15)) * 128 + (((lane >> 4) ^ (lane & 7)) << 4);
            const float bb0 = bf_lo(rb0), bb1 = bf_lo(rb1);
            named_sync(1, 128);
            #pragma unroll
            for (int jp = 0; jp < 7; jp++) {
                uint32_t hh[4];
                ldsm4(hh, hcol(ad, jp));
                #pragma unroll
                for (int r = 0; r < 4; r++) { acc[8 * jp + 2 * r] = bf_lo(hh[r]) + ((r & 1) ? bb1 : bb0); acc[8 * jp + 2 * r + 1] = bf_hi(hh[r]) + ((r & 1) ? bb1 : bb0); }
            }
            if (has_b1) {
                check_tiles(TSVAL 32, w, lane, sb + SM_BRING, tl->hn + q * 32 * 3584, B_FULLB, late, late_ptr);
                named_sync(3, 256);
            } else {
                #pragma unroll
                for (int c = 0; c < 14; c++) st_global_if(1, late_ptr + c * 32, late[c]);
            }
            #pragma unroll 1
            for (uint32_t pass = never; pass < 2; pass++) {
                if (pass) {
                    mix_mainloop<28>(TSVAL acc, has_b1, leader);
                    if (leader) mbar_arrive(bars + 8 * B_END);
                    if (tid == 0) STAMP(18);
                }
                #pragma unroll
                for (int jp = 0; jp < 7; jp++)
                    stsm4_if(1, hcol(ad, jp), pack_bf16(acc[8 * jp], acc[8 * jp + 1]), pack_bf16(acc[8 * jp + 2], acc[8 * jp + 3]),
                             pack_bf16(acc[8 * jp + 4], acc[8 * jp + 5]), pack_bf16(acc[8 * jp + 6], acc[8 * jp + 7]));
                fence_async_smem();
                __syncwarp();
            }
            if (elect()) {
                tma2d_store(&tm_out64, c64, tt2 * 64 + 16 * w, sb + SM_H + w * 2048);
                tma2d_store(&tm_out48, c48, tt2 * 64 + 16 * w, sb + SM_H + 8192 + w * 2048);
            }
            asm volatile("cp.async.bulk.commit_group;" ::: "memory");
            asm volatile("cp.async.bulk.wait_group.read 0;" ::: "memory");
            if (tid == 0) { sc->epoch[slot] = ep; STAMP(19); }
        }
    } else {
        asm volatile("setmaxnreg.dec.sync.aligned.u32 56;");
        int warp2; asm("mov.u32 %0, %1;" : "=r"(warp2) : "r"(warp));
        if (warp2 > 8) {
            uint32_t ep, cl;
            uint4* const oh = sc->hint_o + (2 * tb * 32 + hp * 4) * 2 + (lane & 3);
            if (warp == 10) {
                post_hint(sc->hint_h + (q * 32 + tt2) * 2, 0, lane);
                if (has_b1) post_hint(sc->hint_u + (q * 32 + ft) * 2, 0, lane);
            }
            if (warp == 11) {
                ep = ld_volatile(&sc->epoch[slot]) + 1; cl = ld_acquire(&sc->clean[lane & 15]);
                post_hint(sc->hint_k + (tb * 8 + hp) * 2, 0, lane);
                if (lane < (tb < 15 ? 4 : 0)) st_relaxed4(oh + 128, 0, 0, 0, 0);
                if (lane < (tb ? 0 : 4)) st_relaxed4(oh, 0, 0, 0, 0);
            }
            if (elect()) {
                if (warp == 9) {
                    #pragma unroll
                    for (int i = B_DONE1; i < B_DONEO; i++) mbar_init(bars + 8 * i, i < B_DONEX ? 2 : i == B_DONEX ? 8 : 9);
                    mbar_init(bars + 8 * B_CLR, 1);
                }
                #pragma unroll
                for (int i = 0; i < 34; i++) mbar_init(bars + 8 * (B_DONEO + i) + (warp - 9) * 272, 1);
                asm volatile("fence.mbarrier_init.release.cluster;" ::: "memory");
            }
            named_sync(0, 384);
            if (warp == 9) named_arrive(4, 64);
            if (warp < 11) {
                ep = get_tag();
                mbar_wait(bars + 8 * (B_DONE1 + HALO_AT), 0);
                #pragma unroll 1
                for (int kv = 0; kv < 2; kv++) {
                    uint4 v0 = {}, v1 = {}, v2 = {};
                    if (tb > 0) {
                        const uint4* hg = sc->halo + ((((tb - 1) * 8 + hp) * 2 + warp - 9) * 2 + kv) * 96 + lane;
                        if (kv == 0) while (ld_relaxed(sc->hint_k + ((tb - 1) * 8 + hp) * 2) != ep) {}
                        do { v0 = ld_relaxed4(hg); v1 = ld_relaxed4(hg + 32); v2 = ld_relaxed4(hg + 64); } while (!__all_sync(0xffffffffu, v0.w == ep && v1.w == ep && v2.w == ep));
                    }
                    if (kv) mbar_wait(bars + 8 * (B_DONE1 + 5), 0);
                    const uint32_t hs = sb + lane * 16 + (warp - 9) * 1024 + (kv ? SM_HALOV + 8192 : SM_HALOKIN);
                    sts4(hs, v0.x, v0.y, v0.z, v1.x); sts4(hs + 512, v1.y, v1.z, v2.x, v2.y);
                    __syncwarp();
                    if (lane == 0) mbar_arrive(bars + 8 * (B_HALO + 2 * kv + warp - 9));
                }
                if (tid == 288) STAMP(21);
            }
            if (warp == 10) {
                mbar_wait(bars + 8 * (B_FULLO + 3), 0);
                mbar_wait(bars + 8 * (B_DONEO + HINT_H), 0);
                post_time(sc->hint_h + (q * 32 + tt2) * 2, ep, lane);
                if (has_b1) {
                    mbar_wait(bars + 8 * (B_DONE + HINT_U), 0);
                    post_time(sc->hint_u + (q * 32 + ft) * 2, ep, lane);
                } else if (lane == 0) {
                    mbar_wait(bars + 8 * (B_DONEO + 3), 0);
                    uint32_t t = clock32() + PF_AT;
                    #pragma unroll 1
                    for (int i = 0; i < PF_N; i++) {
                        while ((int)(clock32() - t) < 0) __nanosleep(40);
                        const int c = i * 16 + mi;
                        bulk_prefetch((const char*)w2 + (c >> 1) * 65536 + (c & 1) * 16384, 16384);
                        t += PF_PACE;
                    }
                }
            } else if (warp == 11) {
                #pragma unroll 1
                for (uint32_t e = ep; e != ep + 2; e++) {
                    if (!has_b1 && __shfl_sync(0xffffffffu, cl, mi) != e) {
                        if (e != ep) { mbar_wait_wd(bars + 8 * (B_DONEO + 3), 0); const uint32_t t = clock32(); while (clock32() - t < CL_AT) __nanosleep(100); __syncwarp(); }
                        constexpr int NL = sizeof(Tiles) / 2048;
                        uint4* p = (uint4*)&sc->tiles[e & 1] + (mi * NL + (lane >> 1)) * 8 + (lane & 7);
                        #pragma unroll 7
                        for (int i = 0; i < NL / 16; i++) st_relaxed4(p + i * 128, EMPTY, EMPTY, EMPTY, EMPTY);
                        __syncwarp();
                        if (lane == 0) { st_release(&sc->clean[mi], e); STAMP(24); }
                        __syncwarp();
                    }
                    if (e == ep) {
                        const long long t0 = clock64();
                        while (__any_sync(0xffffffffu, (int)(cl - ep) < 0)) { cl = ld_acquire(&sc->clean[lane & 15]); if (clock64() - t0 > WD_CLKS) __trap(); }
                        if (lane == 0) { *(volatile uint32_t*)(smem_raw + SM_TAG) = ep; mbar_arrive(bars + 8 * B_CLR); }
                        uint4* hg = sc->halo + (tb * 8 + hp) * 384 + lane;
                        #pragma unroll 1
                        for (int kv = 0; kv < 2; kv++) {
                            const uint32_t hs = sb + lane * 16 + 3072 + (kv ? SM_HALOV : SM_HALOK);
                            named_sync(6 + kv, 96);
                            #pragma unroll
                            for (int p = 0; p < 2; p++) {
                                const uint4 u0 = lds4(hs + p * 4096), u1 = lds4(hs + p * 4096 + 512);
                                st_relaxed4(hg + p * 192, u0.x, u0.y, u0.z, ep); st_relaxed4(hg + p * 192 + 32, u0.w, u1.x, u1.y, ep); st_relaxed4(hg + p * 192 + 64, u1.z, u1.w, ep, ep);
                            }
                            hg += 96;
                            if (kv == 0) {
                                post_hint(sc->hint_k + (tb * 8 + hp) * 2, ep, lane);
                                #pragma unroll
                                for (int j = 0; j < 6; j++) st_relaxed4(hg + j * 32 + (j / 3) * 96, 0, 0, 0, 0);
                            }
                        }
                        const uint32_t now = gtime32() - LATE_O;
                        if (lane < (tb < 15 ? 4 : 0)) st_relaxed4(oh + 128, ep, now, ep, now);
                        if (lane < (tb ? 0 : 4)) st_relaxed4(oh, ep, now, ep, now);
                        if (lane == 0) STAMP(23);
                        if (lane == 0) mbar_arrive(bars + 8 * B_DONEQ);
                    }
                }
                if (lane == 0) {
                    mbar_wait_wd(bars + 8 * B_END, 0);
                }
            } else {
                int aslot = 0;
                if (lane == 0) { prefetch_map(&tm_out64); prefetch_map(&tm_out48); }
                if (has_b1) {
                    #pragma unroll 1
                    for (int i = 0; i < 16; i++) {
                        mbar_wait(bars + 8 * (i < NA_SLOTS ? B_DONEQ + ((A_SCHED >> (4 * i)) & 15) : B_DONE + 1 + ((i - NA_SLOTS) * A3_END) / (15 - NA_SLOTS)), 0);
                        if (elect()) {
                            const uint32_t bar = bars + 8 * (B_FULLA + i), dst = sb + SM_ARING + aslot * 16384;
                            mbar_expect(bar, 16384);
                            tma5d(dst, &tm_w1, ft * 64, (i & 7) * 8, i >> 3, bar);
                        }
                        aslot = aslot == NA_SLOTS - 1 ? 0 : aslot + 1;
                    }
                }
                aslot = 16 % NA_SLOTS;
                #pragma unroll 1
                for (int i = 0; i < 14; i++) {
                    if (i >= NA_SLOTS) mbar_wait(bars + 8 * (B_DONE + 1 + ((i - NA_SLOTS) * A4_END) / (13 - NA_SLOTS)), has_b1);
                    else if (has_b1) {
                        mbar_wait(bars + 8 * (B_DONE + max(33 - 2 * NA_SLOTS + 2 * i, W2_AT)), 0);
                        if (i >= W2_HOLD) mbar_wait(bars + 8 * B_FULLB, 1);
                    } else if (i == 0) { mbar_wait(bars + 8 * (B_DONEO + 3), 0); const uint32_t t = clock32() + PF_AT + 12 * PF_PACE; while ((int)(clock32() - t) < 0) __nanosleep(100); }
                    if (elect()) {
                        const uint32_t bar = bars + 8 * (B_FULLA + i);
                        mbar_expect(bar, 16384);
                        tma5d(sb + SM_ARING + aslot * 16384, &tm_w2, tt2 * 64, (i < 7 ? i : i - 7) * 8, i >= 7, bar);
                    }
                    aslot = aslot == NA_SLOTS - 1 ? 0 : aslot + 1;
                }
            }
        } else {
            auto krot = [&](int kb) { const int k = kb * 64 + (G & 1) * 64 * ROT; return k < 448 ? k : k - 448; };
            if (elect()) {
                #pragma unroll
                for (int i = 0; i < 7; i++) mbar_init(bars + 8 * i, 1);
                asm volatile("fence.mbarrier_init.release.cluster;" ::: "memory");
                if (STAG && G >= 2) { const uint32_t t0 = clock32(); while (clock32() - t0 < STAG) {} }
                #pragma unroll 1
                for (int kb = 0; kb < 7; kb++) {
                    const uint32_t st = sb + slot_x(kb), bar = bars + 8 * (B_FULLX + kb);
                    mbar_expect(bar, 16384);
                    tma3d(st, &tm_x, krot(kb), 0, tb * 64, bar); tma3d(st + 8192, &tm_x, krot(kb), 1, tb * 64, bar);
                }
                #pragma unroll
                for (int i = 7; i < B_DONE1; i++) mbar_init(bars + 8 * i, 1);
                asm volatile("fence.mbarrier_init.release.cluster;" ::: "memory");
            }
            named_arrive(0, 384);
            #pragma unroll 1
            for (int kb = 0; kb < 7; kb++) {
                if (kb == 6) { named_sync(4, 64); mbar_wait(bars + 8 * B_DONEX, 0); }
                if (elect()) {
                    const uint32_t st = sb + slot_kv(kb), bar = bars + 8 * (B_FULLKV + kb);
                    mbar_expect(bar, 16384);
                    #pragma unroll
                    for (int i = 0; i < 2; i++) {
                        const int n = 2 * kb + (ROT ? i : i ^ (G & 1));
                        tma2d(st + (n & 1) * 8192, &tm_wqkv, (n < 7 ? 448 : 896) + wcol, krot(n < 7 ? n : n - 7), bar);
                    }
                }
            }
            if (elect()) {
                mbar_expect(bars + 8 * B_FQ, 32768);
                mbar_expect(bars + 8 * (B_FQ + 1), 24576);
                #pragma unroll 1
                for (int i = 0; i < 7; i++) { const int j = ROT || i == 6 ? i : i ^ (G & 1); tma2d(sb + SM_QO + j * 8192, &tm_wqkv, wcol, krot(j), bars + 8 * (B_FQ + (i >> 2))); }
                mbar_expect(bars + 8 * B_FULLWO, 512 * 112 * 2);
            }
            #pragma unroll 1
            for (int i = 0; i < 7; i++) {
                const int kb = ((q & 1 ? WO_ORD1 : WO_ORD0) >> (4 * i)) & 7;
                if (kb < 5) mbar_wait(bars + 8 * (B_DONE1 + kb), 0);
                if (i == WO_HOLD) { mbar_wait(bars + 8 * (B_HALO + 2), 0); mbar_wait(bars + 8 * (B_HALO + 3), 0); }
                if (elect()) {
                    tma2d(sb + slot_wo(kb), &tm_wo64, c64, kb * 64, bars + 8 * B_FULLWO);
                    tma2d(sb + slot_wo(kb) + 8192, &tm_wo48, c48, kb * 64, bars + 8 * B_FULLWO);
                }
            }
            if (XR_HOLD) { mbar_wait(bars + 8 * (B_HALO + 2), 0); mbar_wait(bars + 8 * (B_HALO + 3), 0); }
            if (elect()) {
                tma2d(sb + SM_H, &tm_xr64, c64, tt2 * 64, bars + 8 * B_FULLWO);
                tma2d(sb + SM_H + 8192, &tm_xr48, c48, tt2 * 64, bars + 8 * B_FULLWO);
            }
            if (smem_u32(smem_raw) != SB) __trap();
            const uint32_t ep = get_tag();
            const Tiles* const tl = &sc->tiles[ep & 1];
            mbar_wait(bars + 8 * (B_DONE1 + 6), 0);
            wait_hints(TSVAL sc->hint_o + (tt2 * 32 + lane) * 2, ep, GO_O, 38);
            mbar_wait(bars + 8 * B_DONEQ, 0);
            if (elect()) {
                #pragma unroll
                for (int i = 0; i < 4; i++) {
                    mbar_expect(bars + 8 * (B_RAW + i), 14336);
                    bulk_ld(sb + SM_QO + i * 14336, tl->o + tt2 * 14336 + i * 3584, 14336, bars + 8 * (B_RAW + i));
                }
            }
            if (lane == 0) STAMP(20);
            mbar_wait(bars + 8 * (B_DONEO + 2), 0);
            if (has_b1) {
                mix_producer_b<32>(TSVAL 0, sc->go, ep, tl->hn + q * 32 * 3584, lane);
            }
            mix_producer_b<28>(TSVAL has_b1, sc->go + 8, ep, tl->u + q * 28 * 3584, lane);
        }
    }
}

typedef CUresult (*EncodeFn)(CUtensorMap*, CUtensorMapDataType, cuuint32_t, void*, const cuuint64_t*, const cuuint64_t*, const cuuint32_t*,
                             const cuuint32_t*, CUtensorMapInterleave, CUtensorMapSwizzle, CUtensorMapL2promotion, CUtensorMapFloatOOBfill);

void make_map(EncodeFn fn, CUtensorMap* tm, const void* ptr, int rank, const cuuint64_t* dims, const cuuint64_t* strides, const cuuint32_t* box, CUtensorMapSwizzle sw) {
    cuuint32_t es[5] = {1, 1, 1, 1, 1};
    fn(tm, CU_TENSOR_MAP_DATA_TYPE_BFLOAT16, rank, const_cast<void*>(ptr), dims, strides, box, es, CU_TENSOR_MAP_INTERLEAVE_NONE, sw,
       CU_TENSOR_MAP_L2_PROMOTION_NONE, CU_TENSOR_MAP_FLOAT_OOB_FILL_NONE);
}

}

extern "C" void kernel_launch(void* const* d_in, const int* in_sizes, int n_in, void* d_out, int out_size) {
    const __nv_bfloat16* x = (const __nv_bfloat16*)d_in[0];
    const __nv_bfloat16* wqkv = (const __nv_bfloat16*)d_in[1];
    const __nv_bfloat16* wo = (const __nv_bfloat16*)d_in[2];
    const __nv_bfloat16* w1 = (const __nv_bfloat16*)d_in[4];
    const __nv_bfloat16* b1 = (const __nv_bfloat16*)d_in[5];
    const __nv_bfloat16* w2 = (const __nv_bfloat16*)d_in[6];
    const __nv_bfloat16* b2 = (const __nv_bfloat16*)d_in[7];

    void* fnp = nullptr; cudaDriverEntryPointQueryResult qr;
    cudaGetDriverEntryPoint("cuTensorMapEncodeTiled", &fnp, cudaEnableDefault, &qr);
    EncodeFn fn = (EncodeFn)fnp;
    CUtensorMap tx, twqkv, two64, two48, tw1, tw2, txr64, txr48, tout64, tout48;
    { cuuint64_t d[3] = {448, 2, 1024}, s[2] = {896, 1792}; cuuint32_t b[3] = {64, 1, 64}; make_map(fn, &tx, x, 3, d, s, b, CU_TENSOR_MAP_SWIZZLE_128B); }
    { cuuint64_t d[2] = {1344, 448}, s[1] = {2688}; cuuint32_t b[2] = {64, 64}; make_map(fn, &twqkv, wqkv, 2, d, s, b, CU_TENSOR_MAP_SWIZZLE_128B); }
    { cuuint64_t d[2] = {448, 448}, s[1] = {896}; cuuint32_t b[2] = {64, 64}; make_map(fn, &two64, wo, 2, d, s, b, CU_TENSOR_MAP_SWIZZLE_128B); }
    { cuuint64_t d[2] = {448, 448}, s[1] = {896}; cuuint32_t b[2] = {48, 64}; make_map(fn, &two48, wo, 2, d, s, b, CU_TENSOR_MAP_SWIZZLE_128B); }
    { cuuint64_t d[5] = {1792, 8, 2, 64, 2}, s[4] = {2 * 3584, 3584, 32 * 3584, 16 * 3584}; cuuint32_t b[5] = {64, 8, 2, 8, 1}; make_map(fn, &tw1, w1, 5, d, s, b, CU_TENSOR_MAP_SWIZZLE_128B); }
    { cuuint64_t d[5] = {2048, 8, 2, 56, 2}, s[4] = {4096, 16 * 4096, 32 * 4096, 8 * 4096}; cuuint32_t b[5] = {64, 8, 2, 8, 1}; make_map(fn, &tw2, w2, 5, d, s, b, CU_TENSOR_MAP_SWIZZLE_128B); }
    { cuuint64_t d[2] = {448, 2048}, s[1] = {896}; cuuint32_t b[2] = {64, 64}; make_map(fn, &txr64, x, 2, d, s, b, CU_TENSOR_MAP_SWIZZLE_128B); }
    { cuuint64_t d[2] = {448, 2048}, s[1] = {896}; cuuint32_t b[2] = {48, 64}; make_map(fn, &txr48, x, 2, d, s, b, CU_TENSOR_MAP_SWIZZLE_128B); }
    { cuuint64_t d[2] = {448, 2048}, s[1] = {896}; cuuint32_t b[2] = {64, 16}; make_map(fn, &tout64, d_out, 2, d, s, b, CU_TENSOR_MAP_SWIZZLE_128B); }
    { cuuint64_t d[2] = {448, 2048}, s[1] = {896}; cuuint32_t b[2] = {48, 16}; make_map(fn, &tout48, d_out, 2, d, s, b, CU_TENSOR_MAP_SWIZZLE_128B); }

    void* scv = nullptr;
    cudaGetSymbolAddress(&scv, g_scratch);
    Scratch* scp = (Scratch*)scv;
    int dev = 0, sms = 0;
    cudaGetDevice(&dev);
    cudaDeviceGetAttribute(&sms, cudaDevAttrMultiProcessorCount, dev);
    if (sms == 132) {
        cudaFuncSetAttribute(fused_kernel<true>, cudaFuncAttributeMaxDynamicSharedMemorySize, SM_TOTAL);
        fused_kernel<true><<<132, 384, SM_TOTAL>>>(scp, wo, w1, b1, w2, b2, tx, twqkv, two64, two48, tw1, tw2, txr64, txr48, tout64, tout48);
    } else {
        cudaFuncSetAttribute(fused_kernel<false>, cudaFuncAttributeMaxDynamicSharedMemorySize, SM_TOTAL);
        fused_kernel<false><<<132, 384, SM_TOTAL>>>(scp, wo, w1, b1, w2, b2, tx, twqkv, two64, two48, tw1, tw2, txr64, txr48, tout64, tout48);
    }
}
```

```cpp
#include <cuda_runtime.h>
#include <cuda_bf16.h>
#include <cuda.h>
#include <stdint.h>

namespace {

constexpr int D_ = 448;
constexpr float LN_EPS = 1e-5f;
constexpr float LOG2E_SCALE = 0.1889822365046136f * 1.4426950408889634f;

struct Tiles {
    uint32_t o[32 * 57344 / 4];
    uint32_t hn[4 * 32 * 14336 / 4];
    uint32_t u[4 * 28 * 14336 / 4];
};
struct Scratch {
    uint4 halo[128 * 2 * 2 * 3 * 32];
    uint4 stats[32 * 4 * 64];
    uint4 hint_k[128 * 2];
    uint4 hint_o[32 * 32 * 2];
    uint4 hint_h[4 * 32 * 2];
    uint4 hint_u[128 * 2];
    uint4 go[8];
    uint32_t epoch[160];
    uint32_t clean;
    alignas(1024) Tiles tiles[2];
};
__device__ Scratch g_scratch;
#define STAMP(i) do {} while (0)
#define FST(i) do {} while (0)
#define TSARG
#define TSVAL

constexpr uint32_t SB = 1024;
constexpr int SM_SLOT = 16384;
__device__ __forceinline__ constexpr uint32_t slot_x(int kb) { return (kb ? 6 + kb : 0) * SM_SLOT; }
__device__ __forceinline__ constexpr uint32_t slot_kv(int kb) { return (kb < 5 ? 2 + kb : 6 - kb) * SM_SLOT; }
__device__ __forceinline__ constexpr uint32_t slot_wo(int kb) { return (kb < 6 ? 2 + kb : 12) * SM_SLOT; }
constexpr int SM_QO = 8 * SM_SLOT;
constexpr int SM_HALOK = SM_QO + 57344, SM_HALOV = 1 * SM_SLOT;
constexpr int NA_SLOTS = 6, NB_SLOTS = 8;
constexpr int SM_ARING = 0;
constexpr int SM_BRING = NA_SLOTS * 16384;
constexpr int SM_H = 212992;
__device__ __forceinline__ uint32_t halo_kin(int par, int lane) { return SB + SM_H + 8192 + par * 4096 + lane * 128 + ((~lane & 6) << 4); }
constexpr int SM_BAR = 229376;
constexpr int SM_TAG = SM_BAR + 1536;
constexpr int SM_TIME = SM_TAG + 256;
constexpr int SM_TOTAL = SM_TIME + 256;
constexpr int B_FULLX = 0;
constexpr int B_FULLKV = 7;
constexpr int B_FQ = 14;
constexpr int B_DONE1 = 16;
constexpr int B_DONEX = 23;
constexpr int B_DONEQ = 24;
constexpr int B_DONEO = 25;
constexpr int B_FULLO = 29;
constexpr int B_FULLWO = 33;
constexpr int B_END = 34;
constexpr int B_HALO = 35;
constexpr int B_FULLA = 39;
constexpr int B_FULLB = 55;
constexpr int B_DONE = 87;
constexpr int B_GO = 119;
constexpr int B_CLR = 121;
constexpr int SM_RAW = SM_BAR + 8 * 122;

constexpr long long WD_CLKS = 2000000000ll;

template<int N> struct Int { static constexpr int value = N; };
template<int A, int B, class F> __device__ __forceinline__ void static_for(F&& f) { if constexpr (A < B) { f(Int<A>()); static_for<A + 1, B>(f); } }

__device__ __forceinline__ uint32_t smem_u32(const void* p) { return (uint32_t)__cvta_generic_to_shared(p); }
__device__ __forceinline__ void mbar_init(uint32_t bar, uint32_t cnt) { asm volatile("mbarrier.init.shared::cta.b64 [%0], %1;" :: "r"(bar), "r"(cnt) : "memory"); }
__device__ __forceinline__ void mbar_expect(uint32_t bar, uint32_t bytes) { asm volatile("mbarrier.arrive.expect_tx.shared::cta.b64 _, [%0], %1;" :: "r"(bar), "r"(bytes) : "memory"); }
__device__ __forceinline__ void mbar_arrive(uint32_t bar) { asm volatile("mbarrier.arrive.shared::cta.b64 _, [%0];" :: "r"(bar) : "memory"); }
__device__ __forceinline__ bool mbar_try(uint32_t bar, uint32_t parity) {
    uint32_t ok;
    asm volatile("{\n.reg .pred p;\nmbarrier.try_wait.parity.shared::cta.b64 p, [%1], %2;\nselp.u32 %0, 1, 0, p;\n}" : "=r"(ok) : "r"(bar), "r"(parity) : "memory");
    return ok;
}
__device__ __forceinline__ bool mbar_test(uint32_t bar, uint32_t parity) {
    uint32_t ok;
    asm volatile("{\n.reg .pred p;\nmbarrier.test_wait.parity.shared::cta.b64 p, [%1], %2;\nselp.u32 %0, 1, 0, p;\n}" : "=r"(ok) : "r"(bar), "r"(parity) : "memory");
    return ok;
}
__device__ __forceinline__ void mbar_wait(uint32_t bar, uint32_t parity) {
    asm volatile("{\n.reg .pred p;\n"
                 "WAIT_LOOP:\n"
                 "mbarrier.try_wait.parity.shared::cta.b64 p, [%0], %1;\n"
                 "@!p bra WAIT_LOOP;\n}" :: "r"(bar), "r"(parity) : "memory");
}
__device__ __forceinline__ void mbar_wait_wd(uint32_t bar, uint32_t parity) {
    asm volatile("{\n.reg .pred p, q;\n.reg .u32 s, t;\nmov.u32 s, %%clock;\n"
                 "WAIT_LOOP:\n"
                 "mbarrier.try_wait.parity.shared::cta.b64 p, [%0], %1;\nmov.u32 t, %%clock;\nsub.u32 t, t, s;\nsetp.lt.and.s32 q, t, 0, !p;\n@q trap;\n"
                 "@!p bra WAIT_LOOP;\n}" :: "r"(bar), "r"(parity) : "memory");
}
__device__ __forceinline__ bool elect() { uint32_t p; asm volatile("{\n.reg .pred P;\nelect.sync _|P, 0xffffffff;\nselp.u32 %0, 1, 0, P;\n}" : "=r"(p)); return p; }
__device__ __forceinline__ void tma2d(uint32_t dst, const CUtensorMap* tm, int c0, int c1, uint32_t bar) {
    asm volatile("cp.async.bulk.tensor.2d.shared::cluster.global.mbarrier::complete_tx::bytes [%0], [%1, {%3, %4}], [%2];" :: "r"(dst), "l"(tm), "r"(bar), "r"(c0), "r"(c1) : "memory");
}
__device__ __forceinline__ void tma3d(uint32_t dst, const CUtensorMap* tm, int c0, int c1, int c2, uint32_t bar) {
    asm volatile("cp.async.bulk.tensor.3d.shared::cluster.global.mbarrier::complete_tx::bytes [%0], [%1, {%3, %4, %5}], [%2];" :: "r"(dst), "l"(tm), "r"(bar), "r"(c0), "r"(c1), "r"(c2) : "memory");
}
__device__ __forceinline__ void tma5d(uint32_t dst, const CUtensorMap* tm, int c0, int c3, int c4, uint32_t bar) {
    asm volatile("cp.async.bulk.tensor.5d.shared::cluster.global.mbarrier::complete_tx::bytes [%0], [%1, {%3, 0, 0, %4, %5}], [%2];" :: "r"(dst), "l"(tm), "r"(bar), "r"(c0), "r"(c3), "r"(c4) : "memory");
}
__device__ __forceinline__ void tma5d_prefetch(const CUtensorMap* tm, int c0, int c3, int c4) {
    asm volatile("cp.async.bulk.prefetch.tensor.5d.L2.global [%0, {%1, 0, 0, %2, %3}];" :: "l"(tm), "r"(c0), "r"(c3), "r"(c4) : "memory");
}
__device__ __forceinline__ void tma2d_store(const CUtensorMap* tm, int c0, int c1, uint32_t src) {
    asm volatile("cp.async.bulk.tensor.2d.global.shared::cta.bulk_group [%0, {%2, %3}], [%1];" :: "l"(tm), "r"(src), "r"(c0), "r"(c1) : "memory");
}
__device__ __forceinline__ void bulk_ld(uint32_t dst, const void* src, uint32_t bytes, uint32_t bar) {
    asm volatile("cp.async.bulk.shared::cluster.global.mbarrier::complete_tx::bytes [%0], [%1], %2, [%3];" :: "r"(dst), "l"(src), "r"(bytes), "r"(bar) : "memory");
}
__device__ __forceinline__ void bulk_prefetch(const void* src, uint32_t bytes) { asm volatile("cp.async.bulk.prefetch.L2.global [%0], %1;" :: "l"(src), "r"(bytes) : "memory"); }
__device__ __forceinline__ void prefetch_map(const CUtensorMap* tm) { asm volatile("prefetch.tensormap [%0];" :: "l"(tm) : "memory"); }
__device__ __forceinline__ void st_global_if(uint32_t c, uint32_t* p, uint32_t v) {
    asm volatile("{\n.reg .pred p;\nsetp.ne.u32 p, %2, 0;\n@p st.global.u32 [%0], %1;\n}" :: "l"(p), "r"(v), "r"(c) : "memory");
}
__device__ __forceinline__ void st_relaxed4_if(bool c, uint4* p, uint32_t a, uint32_t b, uint32_t d) {
    asm volatile("{\n.reg .b128 t;\n.reg .b64 a, b;\n.reg .pred p;\nsetp.ne.u32 p, %4, 0;\nmov.b64 a, {%1, %2};\nmov.b64 b, {%3, %3};\nmov.b128 t, {a, b};\n@p st.relaxed.gpu.global.b128 [%0], t;\n}" :: "l"(p), "r"(a), "r"(b), "r"(d), "r"((uint32_t)c) : "memory");
}
__device__ __forceinline__ void pin_ptr(uint32_t never, const void* a) {
    asm volatile("{\n.reg .pred p;\nsetp.ne.u32 p, %1, 0;\n@p st.shared.u64 [%1], %0;\n}" :: "l"(a), "r"(never) : "memory");
}
__device__ __forceinline__ void pin4(uint32_t never, float a, float b, float c, float d) {
    asm volatile("{\n.reg .pred p;\nsetp.ne.u32 p, %4, 0;\n@p st.shared.v4.f32 [%4], {%0,%1,%2,%3};\n}" :: "f"(a), "f"(b), "f"(c), "f"(d), "r"(never) : "memory");
}
__device__ __forceinline__ void fence_async_smem() { asm volatile("fence.proxy.async.shared::cta;" ::: "memory"); }
__device__ __forceinline__ uint32_t ld_acquire(const void* p) { uint32_t v; asm volatile("ld.acquire.gpu.global.u32 %0, [%1];" : "=r"(v) : "l"(p) : "memory"); return v; }
__device__ __forceinline__ void st_release(void* p, uint32_t v) { asm volatile("st.release.gpu.global.u32 [%0], %1;" :: "l"(p), "r"(v) : "memory"); }
__device__ __forceinline__ uint32_t ld_relaxed(const void* p) { uint32_t v; asm volatile("ld.relaxed.gpu.global.u32 %0, [%1];" : "=r"(v) : "l"(p) : "memory"); return v; }
__device__ __forceinline__ uint2 ld_relaxed2(const void* p) {
    uint2 v; asm volatile("{\n.reg .b64 a;\nld.relaxed.gpu.global.b64 a, [%2];\nmov.b64 {%0, %1}, a;\n}" : "=r"(v.x), "=r"(v.y) : "l"(p) : "memory"); return v;
}
__device__ __forceinline__ uint4 ld_relaxed4(const uint4* p) {
    uint4 v;
    asm volatile("{\n.reg .b128 t;\n.reg .b64 a, b;\nld.relaxed.gpu.global.b128 t, [%4];\nmov.b128 {a, b}, t;\nmov.b64 {%0, %1}, a;\nmov.b64 {%2, %3}, b;\n}" : "=r"(v.x), "=r"(v.y), "=r"(v.z), "=r"(v.w) : "l"(p) : "memory");
    return v;
}
__device__ __forceinline__ void st_relaxed4(uint4* p, uint32_t a, uint32_t b, uint32_t c, uint32_t d) {
    asm volatile("{\n.reg .b128 t;\n.reg .b64 a, b;\nmov.b64 a, {%1, %2};\nmov.b64 b, {%3, %4};\nmov.b128 t, {a, b};\nst.relaxed.gpu.global.b128 [%0], t;\n}" :: "l"(p), "r"(a), "r"(b), "r"(c), "r"(d) : "memory");
}
__device__ __forceinline__ uint32_t ld_u16(const unsigned short* p) { uint32_t v; asm volatile("ld.volatile.global.u16 %0, [%1];" : "=r"(v) : "l"(p) : "memory"); return v; }
__device__ __forceinline__ uint32_t ld_volatile(const uint32_t* p) { uint32_t v; asm volatile("ld.volatile.global.u32 %0, [%1];" : "=r"(v) : "l"(p) : "memory"); return v; }
__device__ __forceinline__ void named_arrive(int id, int n) { asm volatile("bar.arrive %0, %1;" :: "r"(id), "r"(n) : "memory"); }
__device__ __forceinline__ void named_sync(int id, int n) { asm volatile("bar.sync %0, %1;" :: "r"(id), "r"(n) : "memory"); }
__device__ __forceinline__ void named_arrive_if(uint32_t c, int id, int n) { asm volatile("{\n.reg .pred p;\nsetp.ne.u32 p, %2, 0;\n@p bar.arrive %0, %1;\n}" :: "r"(id), "r"(n), "r"(c) : "memory"); }
__device__ __forceinline__ void wg_fence() { asm volatile("wgmma.fence.sync.aligned;" ::: "memory"); }
__device__ __forceinline__ void wg_commit() { asm volatile("wgmma.commit_group.sync.aligned;" ::: "memory"); }
template<int N> __device__ __forceinline__ void wg_wait() { asm volatile("wgmma.wait_group.sync.aligned %0;" :: "n"(N) : "memory"); }
template<int N> __device__ __forceinline__ void reg_fence(float (&d)[N]) {
    #pragma unroll
    for (int i = 0; i < N; i++) asm volatile("" : "+f"(d[i]) :: "memory");
}
__device__ __forceinline__ constexpr uint64_t mkdesc(uint32_t addr, uint32_t lbo, uint32_t sbo, uint32_t sw) {
    return (uint64_t)((addr & 0x3FFFF) >> 4) | ((uint64_t)(lbo >> 4) << 16) | ((uint64_t)(sbo >> 4) << 32) | ((uint64_t)sw << 62);
}
__device__ __forceinline__ void ldsm4(uint32_t (&r)[4], uint32_t addr) {
    asm volatile("ldmatrix.sync.aligned.m8n8.x4.shared.b16 {%0,%1,%2,%3}, [%4];" : "=r"(r[0]), "=r"(r[1]), "=r"(r[2]), "=r"(r[3]) : "r"(addr) : "memory");
}
__device__ __forceinline__ void stsm4_if(uint32_t c, uint32_t addr, uint32_t r0, uint32_t r1, uint32_t r2, uint32_t r3) {
    asm volatile("{\n.reg .pred p;\nsetp.ne.u32 p, %5, 0;\n@p stmatrix.sync.aligned.m8n8.x4.shared.b16 [%0], {%1,%2,%3,%4};\n}" :: "r"(addr), "r"(r0), "r"(r1), "r"(r2), "r"(r3), "r"(c) : "memory");
}
__device__ __forceinline__ void sts4(uint32_t a, uint32_t x, uint32_t y, uint32_t z, uint32_t w) { asm volatile("st.shared.v4.u32 [%0], {%1,%2,%3,%4};" :: "r"(a), "r"(x), "r"(y), "r"(z), "r"(w) : "memory"); }
__device__ __forceinline__ uint4 lds4(uint32_t a) { uint4 v; asm volatile("ld.shared.v4.u32 {%0,%1,%2,%3}, [%4];" : "=r"(v.x), "=r"(v.y), "=r"(v.z), "=r"(v.w) : "r"(a) : "memory"); return v; }
__device__ __forceinline__ uint32_t movtrans(uint32_t a) { uint32_t d; asm volatile("movmatrix.sync.aligned.m8n8.trans.b16 %0, %1;" : "=r"(d) : "r"(a)); return d; }
__device__ __forceinline__ uint32_t pack_bf16(float lo, float hi) { uint32_t r; asm("cvt.rn.bf16x2.f32 %0, %1, %2;" : "=r"(r) : "f"(hi), "f"(lo)); return r; }
__device__ __forceinline__ void sub_bf16x2(uint32_t& a, uint32_t b) { asm volatile("sub.rn.bf16x2 %0, %0, %1;" : "+r"(a) : "r"(b)); }
__device__ __forceinline__ float bf_lo(uint32_t v) { return __uint_as_float(v << 16); }
__device__ __forceinline__ float bf_hi(uint32_t v) { return __uint_as_float(v & 0xffff0000u); }
__device__ __forceinline__ void mma16816(float (&c)[4], uint32_t a0, uint32_t a1, uint32_t a2, uint32_t a3, uint32_t b0, uint32_t b1) {
    asm volatile("mma.sync.aligned.m16n8k16.row.col.f32.bf16.bf16.f32 {%0,%1,%2,%3}, {%4,%5,%6,%7}, {%8,%9}, {%0,%1,%2,%3};"
        : "+f"(c[0]), "+f"(c[1]), "+f"(c[2]), "+f"(c[3]) : "r"(a0), "r"(a1), "r"(a2), "r"(a3), "r"(b0), "r"(b1));
}
__device__ __forceinline__ void mma1688(float (&c)[4], uint32_t a0, uint32_t a1, uint32_t b0) {
    asm volatile("mma.sync.aligned.m16n8k8.row.col.f32.bf16.bf16.f32 {%0,%1,%2,%3}, {%4,%5}, {%6}, {%0,%1,%2,%3};"
        : "+f"(c[0]), "+f"(c[1]), "+f"(c[2]), "+f"(c[3]) : "r"(a0), "r"(a1), "r"(b0));
}
__device__ __forceinline__ float quad_sum(float v) { v += __shfl_xor_sync(0xffffffffu, v, 1); v += __shfl_xor_sync(0xffffffffu, v, 2); return v; }
__device__ __forceinline__ float quad_max(float v) { v = fmaxf(v, __shfl_xor_sync(0xffffffffu, v, 1)); v = fmaxf(v, __shfl_xor_sync(0xffffffffu, v, 2)); return v; }
__device__ __forceinline__ float ex2(float x) { float y; asm("ex2.approx.ftz.f32 %0, %1;" : "=f"(y) : "f"(x)); return y; }
__device__ __forceinline__ float rsqrt_approx(float x) { float y; asm("rsqrt.approx.ftz.f32 %0, %1;" : "=f"(y) : "f"(x)); return y; }
__device__ __forceinline__ float rcp_approx(float x) { float y; asm("rcp.approx.ftz.f32 %0, %1;" : "=f"(y) : "f"(x)); return y; }
constexpr float GELU_K1 = 2.f * 0.7978845608028654f;
__device__ __forceinline__ float gelu_half(float hx, float k1) {
    const float z = hx * fmaf(hx * hx, 8.f * 0.044715f * 0.7978845608028654f, k1);
    float t; asm("tanh.approx.f32 %0, %1;" : "=f"(t) : "f"(z));
    return fmaf(hx, t, hx);
}
__device__ __forceinline__ uint32_t gtime32() { uint32_t t; asm volatile("mov.u32 %0, %%globaltimer_lo;" : "=r"(t)); return t; }
__device__ __forceinline__ uint32_t clock32() { uint32_t t; asm volatile("mov.u32 %0, %%clock;" : "=r"(t)); return t; }
#define PF_PACE 160
#define PF_AT 16000
#define PF_N 128
#define NSQ 6
#define NPIPE 1
#define HALO_AT 3
#define HINT_U 24
#define HINT_E 18
#define SP_AT 2000
#define A_SCHED 0x322188
#define WO_ORD0 0x4321065
#define WO_ORD1 0x3465210
#define CL_AT 23
#define WARM_AT 300
#define A_HOLD 33
#define GO_H 1344
#define GO_E 1630
#define GO_U 1250
#define GO_O 1248
#define LATE_O 256
#define DRY2 1
#define LATE_AT 1
#define LATE_AT4 0
#define HINT_H 1
#define SLACK 256
#define SLACK_U 128
#define GDEP 4
#define START4 30
#define EMAP 1
#define DEPTH_N 1
#define DEPTH_E 2
#define PFE_AT 99
#define PFN_END 0
#define NE_SLOTS 11
#define POLL_E 22
#define POLL_U 22
#define CH_U 28
#define AE_END 20
#define AE_W2 27
#define PF1_AT 6000
#define PF1_N 80
#define PF1_PACE 160
#define HOLD 0
#define X0 1
#define GO_E2 150
#define GO_U2 400
#define POLL_I 21
#define POLL_N 17
template<int TB> __device__ __forceinline__ void wgmma_rs56(float (&d)[28], const uint32_t (&a)[4], uint64_t db, int sc) {
    asm volatile("{\n.reg .pred p;\nsetp.ne.b32 p, %33, 0;\n"
        "wgmma.mma_async.sync.aligned.m64n56k16.f32.bf16.bf16 {%0, %1, %2, %3, %4, %5, %6, %7, %8, %9, %10, %11, %12, %13, %14, %15, %16, %17, %18, %19, %20, %21, %22, %23, %24, %25, %26, %27}, {%28, %29, %30, %31}, %32, p, 1, 1, %34;\n}\n"
        : "+f"(d[0]), "+f"(d[1]), "+f"(d[2]), "+f"(d[3]), "+f"(d[4]), "+f"(d[5]), "+f"(d[6]), "+f"(d[7]), "+f"(d[8]), "+f"(d[9]), "+f"(d[10]), "+f"(d[11]), "+f"(d[12]), "+f"(d[13]), "+f"(d[14]), "+f"(d[15]), "+f"(d[16]), "+f"(d[17]), "+f"(d[18]), "+f"(d[19]), "+f"(d[20]), "+f"(d[21]), "+f"(d[22]), "+f"(d[23]), "+f"(d[24]), "+f"(d[25]), "+f"(d[26]), "+f"(d[27])
        : "r"(a[0]), "r"(a[1]), "r"(a[2]), "r"(a[3]), "l"(db), "r"(sc), "n"(TB));
}

template<int TA, int TB, int SC = 1> __device__ __forceinline__ void wgmma_ss112(float (&d)[56], uint64_t da, uint64_t db) {
    asm volatile("wgmma.mma_async.sync.aligned.m64n112k16.f32.bf16.bf16 {%0, %1, %2, %3, %4, %5, %6, %7, %8, %9, %10, %11, %12, %13, %14, %15, %16, %17, %18, %19, %20, %21, %22, %23, %24, %25, %26, %27, %28, %29, %30, %31, %32, %33, %34, %35, %36, %37, %38, %39, %40, %41, %42, %43, %44, %45, %46, %47, %48, %49, %50, %51, %52, %53, %54, %55}, %56, %57, %60, 1, 1, %58, %59;\n"
        : "+f"(d[0]), "+f"(d[1]), "+f"(d[2]), "+f"(d[3]), "+f"(d[4]), "+f"(d[5]), "+f"(d[6]), "+f"(d[7]), "+f"(d[8]), "+f"(d[9]), "+f"(d[10]), "+f"(d[11]), "+f"(d[12]), "+f"(d[13]), "+f"(d[14]), "+f"(d[15]), "+f"(d[16]), "+f"(d[17]), "+f"(d[18]), "+f"(d[19]), "+f"(d[20]), "+f"(d[21]), "+f"(d[22]), "+f"(d[23]), "+f"(d[24]), "+f"(d[25]), "+f"(d[26]), "+f"(d[27]), "+f"(d[28]), "+f"(d[29]), "+f"(d[30]), "+f"(d[31]), "+f"(d[32]), "+f"(d[33]), "+f"(d[34]), "+f"(d[35]), "+f"(d[36]), "+f"(d[37]), "+f"(d[38]), "+f"(d[39]), "+f"(d[40]), "+f"(d[41]), "+f"(d[42]), "+f"(d[43]), "+f"(d[44]), "+f"(d[45]), "+f"(d[46]), "+f"(d[47]), "+f"(d[48]), "+f"(d[49]), "+f"(d[50]), "+f"(d[51]), "+f"(d[52]), "+f"(d[53]), "+f"(d[54]), "+f"(d[55])
        : "l"(da), "l"(db), "n"(TA), "n"(TB), "n"(SC));
}

template<int TA, int TB, int SC = 1> __device__ __forceinline__ void wgmma_ss80(float (&d)[40], uint64_t da, uint64_t db) {
    asm volatile("wgmma.mma_async.sync.aligned.m64n80k16.f32.bf16.bf16 {%0, %1, %2, %3, %4, %5, %6, %7, %8, %9, %10, %11, %12, %13, %14, %15, %16, %17, %18, %19, %20, %21, %22, %23, %24, %25, %26, %27, %28, %29, %30, %31, %32, %33, %34, %35, %36, %37, %38, %39}, %40, %41, %44, 1, 1, %42, %43;\n"
        : "+f"(d[0]), "+f"(d[1]), "+f"(d[2]), "+f"(d[3]), "+f"(d[4]), "+f"(d[5]), "+f"(d[6]), "+f"(d[7]), "+f"(d[8]), "+f"(d[9]), "+f"(d[10]), "+f"(d[11]), "+f"(d[12]), "+f"(d[13]), "+f"(d[14]), "+f"(d[15]), "+f"(d[16]), "+f"(d[17]), "+f"(d[18]), "+f"(d[19]), "+f"(d[20]), "+f"(d[21]), "+f"(d[22]), "+f"(d[23]), "+f"(d[24]), "+f"(d[25]), "+f"(d[26]), "+f"(d[27]), "+f"(d[28]), "+f"(d[29]), "+f"(d[30]), "+f"(d[31]), "+f"(d[32]), "+f"(d[33]), "+f"(d[34]), "+f"(d[35]), "+f"(d[36]), "+f"(d[37]), "+f"(d[38]), "+f"(d[39])
        : "l"(da), "l"(db), "n"(TA), "n"(TB), "n"(SC));
}

template<int TA, int TB, int SC = 1> __device__ __forceinline__ void wgmma_ss64(float (&d)[32], uint64_t da, uint64_t db) {
    asm volatile("wgmma.mma_async.sync.aligned.m64n64k16.f32.bf16.bf16 {%0, %1, %2, %3, %4, %5, %6, %7, %8, %9, %10, %11, %12, %13, %14, %15, %16, %17, %18, %19, %20, %21, %22, %23, %24, %25, %26, %27, %28, %29, %30, %31}, %32, %33, %36, 1, 1, %34, %35;\n"
        : "+f"(d[0]), "+f"(d[1]), "+f"(d[2]), "+f"(d[3]), "+f"(d[4]), "+f"(d[5]), "+f"(d[6]), "+f"(d[7]), "+f"(d[8]), "+f"(d[9]), "+f"(d[10]), "+f"(d[11]), "+f"(d[12]), "+f"(d[13]), "+f"(d[14]), "+f"(d[15]), "+f"(d[16]), "+f"(d[17]), "+f"(d[18]), "+f"(d[19]), "+f"(d[20]), "+f"(d[21]), "+f"(d[22]), "+f"(d[23]), "+f"(d[24]), "+f"(d[25]), "+f"(d[26]), "+f"(d[27]), "+f"(d[28]), "+f"(d[29]), "+f"(d[30]), "+f"(d[31])
        : "l"(da), "l"(db), "n"(TA), "n"(TB), "n"(SC));
}

template<int TA, int TB, int SC = 1> __device__ __forceinline__ void wgmma_ss48(float (&d)[24], uint64_t da, uint64_t db) {
    asm volatile("wgmma.mma_async.sync.aligned.m64n48k16.f32.bf16.bf16 {%0, %1, %2, %3, %4, %5, %6, %7, %8, %9, %10, %11, %12, %13, %14, %15, %16, %17, %18, %19, %20, %21, %22, %23}, %24, %25, %28, 1, 1, %26, %27;\n"
        : "+f"(d[0]), "+f"(d[1]), "+f"(d[2]), "+f"(d[3]), "+f"(d[4]), "+f"(d[5]), "+f"(d[6]), "+f"(d[7]), "+f"(d[8]), "+f"(d[9]), "+f"(d[10]), "+f"(d[11]), "+f"(d[12]), "+f"(d[13]), "+f"(d[14]), "+f"(d[15]), "+f"(d[16]), "+f"(d[17]), "+f"(d[18]), "+f"(d[19]), "+f"(d[20]), "+f"(d[21]), "+f"(d[22]), "+f"(d[23])
        : "l"(da), "l"(db), "n"(TA), "n"(TB), "n"(SC));
}

template<int NKB, int NR>
__device__ __forceinline__ void mix_mainloop(TSARG float (&acc)[NR], bool leader) {
    constexpr uint32_t sb = SB, bars = sb + SM_BAR, par = NKB == 28;
    constexpr int A0 = NKB == 32 ? 0 : 16 % NA_SLOTS;
    constexpr int DEPTH = NR == 56 ? DEPTH_N : DEPTH_E;
    int bslot = 0, aslot = A0;
    reg_fence(acc);
    #pragma unroll 1
    for (int i = 0; i < NKB / 2; i++) {
        mbar_wait(bars + 8 * (B_FULLA + i), par);
        const uint64_t adesc = mkdesc(sb + SM_ARING, 8192, 1024, 1) + (uint32_t)(aslot * 1024);
        aslot = aslot == NA_SLOTS - 1 ? 0 : aslot + 1;
        #pragma unroll
        for (int jj = 0; jj < 2; jj++) {
            const int j = 2 * i + jj;
            mbar_wait(bars + 8 * (B_FULLB + j), par);
            const uint64_t bdesc = mkdesc(sb + SM_BRING, 128, 1024, 0) + (uint32_t)(bslot * NR * 16);
            bslot = bslot == (NR == 56 ? NB_SLOTS : NE_SLOTS) - 1 ? 0 : bslot + 1;
            wg_fence();
            #pragma unroll
            for (int s = 0; s < 4; s++) {
                if constexpr (NR == 56) wgmma_ss112<1, 1>(acc, adesc + jj * 512 + s * 128, bdesc + s * 16);
                else wgmma_ss80<1, 1>(acc, adesc + jj * 512 + s * 128, bdesc + s * 16);
            }
            wg_commit();
            wg_wait<DEPTH>();
            if (j >= DEPTH && leader) mbar_arrive(bars + 8 * (B_DONE + j - DEPTH));
        }
    }
    if (DEPTH == 2) { wg_wait<1>(); if (leader) mbar_arrive(bars + 8 * (B_DONE + NKB - 2)); }
    wg_wait<0>();
    reg_fence(acc);
    if (leader) mbar_arrive(bars + 8 * (B_DONE + NKB - 1));
}

constexpr uint32_t EMPTY = 0xFFFFFFFFu;
__device__ __forceinline__ void post_hint(uint4* p, uint32_t ep, int lane) { if (lane < 2) st_relaxed4(p + lane, ep, ep, ep, ep); }
__device__ __forceinline__ void post_time(uint4* p, uint32_t ep, int lane) { const uint32_t now = gtime32(); if (lane < 2) st_relaxed4(p + lane, ep, now, ep, now); }

__device__ __forceinline__ uint32_t last_hint(TSARG const uint4* hint, uint32_t ep, int st) {
    uint2 v;
    do { v = ld_relaxed2(hint); } while (!__all_sync(0xffffffffu, v.x == ep));
    const uint32_t t1 = gtime32() + 256;
    if (elect()) STAMP(st);
    return t1 - __reduce_min_sync(0xffffffffu, t1 - v.y);
}
__device__ __forceinline__ void fetch_times(TSARG const uint4* hint_u, int k, int q, uint32_t ep, int lane) {
    const uint4* hint = hint_u + (k ? 48 + q * 20 + min(lane, 19) : (q + (q >> 1)) * 8 + (lane & 15)) * 2;
    uint2 v;
    do { v = ld_relaxed2(hint); } while (!__all_sync(0xffffffffu, v.x == ep));
    v.y += max((int)(__shfl_xor_sync(0xffffffffu, v.y, 1) - v.y), 0);
    if (!k) v.y += max((int)(__shfl_xor_sync(0xffffffffu, v.y, 8) - v.y), 0);
    asm volatile("st.shared.u32 [%0], %1;" :: "r"(SB + SM_TIME + 128 * k + 4 * lane), "r"(v.y) : "memory");
    __syncwarp();
    if (lane == 0) { mbar_arrive(SB + SM_BAR + 8 * (B_GO + k)); STAMP(k ? 43 : 24); }
    __syncwarp();
}
__device__ __forceinline__ void wait_until(uint32_t t) { while ((int)(gtime32() - t) < 0) {} __syncwarp(); }

__device__ __forceinline__ uint32_t check_tile(uint32_t raw, uint32_t full, uint32_t dst, uint32_t lofs, const uint32_t* src, uint32_t bytes, int lane) {
    uint32_t cnt;
    asm volatile("{\n.reg .pred p, e;\n.reg .u32 a, b, c, d;\nmov.u32 %0, 0;\n"
                 "AGAIN:\nand.b32 a, %0, 1;\n"
                 "WAIT:\nmbarrier.try_wait.parity.shared::cta.b64 p, [%1], a;\n@!p bra.uni WAIT;\n"
                 "ld.shared.u32 a, [%4];\nld.shared.u32 b, [%4+4096];\nld.shared.u32 c, [%5+-8192];\nld.shared.u32 d, [%5+-4096];\n"
                 "add.u32 %0, %0, 1;\nmax.u32 a, a, b;\nmax.u32 c, c, d;\nmax.u32 a, a, c;\nsetp.lt.u32 e, %8, 32;\nsetp.eq.and.u32 p, a, 0xFFFFFFFF, e;\n"
                 "vote.sync.any.pred p, p, 0xffffffff;\nsetp.eq.and.u32 e, %8, 0, !p;\n@e mbarrier.arrive.shared::cta.b64 _, [%2];\n"
                 "elect.sync _|e, 0xffffffff;\nand.pred e, e, p;\n"
                 "@e mbarrier.arrive.expect_tx.shared::cta.b64 _, [%1], %7;\n"
                 "@e cp.async.bulk.shared::cluster.global.mbarrier::complete_tx::bytes [%3], [%6], %7, [%1];\n"
                 "@p bra.uni AGAIN;\n}"
                 : "=&r"(cnt) : "r"(raw), "r"(full), "r"(dst), "r"(dst + lofs), "r"(dst + lofs + bytes), "l"(src), "r"(bytes), "r"(lane) : "memory");
    return cnt;
}

template<int ST>
__device__ __forceinline__ void check_tiles(int j, int step, int n, const uint32_t* src, bool small, int lane, bool dry) {
    const uint32_t bytes = small ? 10240 : 14336, nb = small ? NE_SLOTS : NB_SLOTS, lofs = lane * 128 + (lane & 3) * 32 + (lane >> 2) * 4;
    uint32_t sl = j % nb;
    #pragma unroll 1
    for (int inc = dry ? 0 : step; j < n; j += inc, inc = step) {
        const uint32_t c = check_tile(inc ? SB + SM_RAW + 8 * (j + (ST ? 32 * ST - 28 : 0)) : SB + SM_BAR + 8 * B_CLR, SB + SM_BAR + 8 * (j + (ST ? B_FULLB : B_FULLO)),
                                      SB + (ST ? SM_BRING : SM_QO) + sl * bytes, lofs, src + j * (ST ? 7168 : 3584), bytes, inc ? lane : 32);
        sl += inc;
        if (sl >= nb) sl -= nb;
    }
}

__device__ __forceinline__ uint32_t hcol(uint32_t a, int jp) { return (a ^ ((jp & 3) << 5)) + (jp >> 2) * 8192; }

__device__ __forceinline__ uint32_t get_tag() {
    mbar_wait(SB + SM_BAR + 8 * B_CLR, 0);
    uint32_t v; asm volatile("ld.shared.u32 %0, [%1];" : "=r"(v) : "r"(SB + SM_TAG) : "memory"); return v;
}

template<bool USE_SMID>
__global__ void __launch_bounds__(384, 1)
fused_kernel(Scratch* __restrict__ sc, const __nv_bfloat16* __restrict__ wo,
             const __nv_bfloat16* __restrict__ w1, const __nv_bfloat16* __restrict__ b1,
             const __nv_bfloat16* __restrict__ w2, const __nv_bfloat16* __restrict__ b2,
             const __grid_constant__ CUtensorMap tm_x, const __grid_constant__ CUtensorMap tm_wqkv,
             const __grid_constant__ CUtensorMap tm_wo64, const __grid_constant__ CUtensorMap tm_wo48,
             const __grid_constant__ CUtensorMap tm_w1, const __grid_constant__ CUtensorMap tm_w2,
             const __grid_constant__ CUtensorMap tm_xr64, const __grid_constant__ CUtensorMap tm_xr48,
             const __grid_constant__ CUtensorMap tm_out64, const __grid_constant__ CUtensorMap tm_out48) {
    extern __shared__ __align__(1024) uint8_t smem_raw[];
    constexpr uint32_t sb = SB;
    constexpr uint32_t bars = sb + SM_BAR;
    const int tid = threadIdx.x, lane = tid & 31;
    auto get_slot = [&]() {
        int slot;
    if (USE_SMID) {
        asm volatile("{\n.reg .u32 s, t, u, d, a, b, c;\n.reg .pred p, r;\n"
            "mov.u32 s, %%smid;\nshr.u32 t, s, 1;\nsub.u32 u, t, 32;\nmul.lo.u32 d, u, 37;\nshr.u32 d, d, 8;\n"
            "and.b32 a, t, 7;\nshl.b32 a, a, 3;\nshr.u32 c, t, 3;\nadd.u32 a, a, c;\n"
            "mad.lo.u32 b, d, -55, 12;\nshl.b32 c, u, 3;\nadd.u32 b, b, c;\n"
            "setp.lt.u32 p, t, 32;\nselp.u32 a, a, b, p;\n"
            "setp.lt.u32 r, t, 62;\nselp.s32 c, 4, -58, r;\nadd.u32 c, t, c;\nsetp.lt.u32 p, t, 60;\nselp.u32 a, a, c, p;\n"
            "and.b32 s, s, 1;\nshl.b32 a, a, 1;\nadd.u32 %0, a, s;\n}" : "=r"(slot));
    } else slot = blockIdx.x;
        return slot;
    };
    auto load_x = [&](int kb, int row) {
        const uint32_t st = sb + slot_x(kb), bar = bars + 8 * (B_FULLX + kb);
        mbar_expect(bar, 16384);
        tma3d(st, &tm_x, kb * 64, 0, row, bar); tma3d(st + 8192, &tm_x, kb * 64, 1, row, bar);
    };
    const int warp = __shfl_sync(0xffffffffu, tid >> 5, 0);
#define ASSIGN_WORK(s) \
    const int slot = (s), G = slot >> 4, mi = slot & 15; \
    const int tb = 4 * (G >> 1) + (mi >> 2), hp = 2 * (mi & 3) + (G & 1), wcol = (hp * 56) & ~15; \
    const int q = mi & 3, tt2 = 4 * G + (mi >> 2), c64 = 64 * q, c48 = 256 + 48 * q; \
    const bool early = G < 3; \
    const int ech = G < 2 ? q : 4 + (mi & 1), ft = !early ? tt2 - 4 : G == 2 ? mi >> 1 : tt2; \
    const int pr3 = early ? ech >= 3 : q >> 1, col3 = early ? (ech - 3 * pr3) * 9 : (q & 1) * 14;

    if (warp < 8) {
        ASSIGN_WORK(get_slot())
        if (slot >= 128) {
            const uint32_t ep = ld_volatile(&sc->epoch[slot]) + 1;
            if (mi == 0 && warp == 1) {
                post_hint(sc->go, 0, lane);
                while (ld_relaxed(sc->hint_k) != ep) __nanosleep(200);
                uint2 v[4];
                do {
                    #pragma unroll
                    for (int i = 0; i < 4; i++) v[i] = ld_relaxed2(sc->hint_h + 64 * i + 2 * lane);
                } while (!__all_sync(0xffffffffu, v[0].x == ep && v[1].x == ep && v[2].x == ep && v[3].x == ep));
                const uint32_t t1 = gtime32() + 256;
                const uint32_t age = min(min(t1 - v[0].y, t1 - v[1].y), min(t1 - v[2].y, t1 - v[3].y)) + (lane < 16 ? 0 : SLACK);
                const uint32_t ts = t1 - __reduce_min_sync(0xffffffffu, age);
                if (lane < 2) st_relaxed4(sc->go + lane, ep, ts, ep, ts);
            }
            if (mi == 1 && warp >= 4 && ld_volatile(&sc->clean) != ep) {
                for (int l = (tid - 128) / 2; l < sizeof(Tiles) / 128; l += 64) st_relaxed4((uint4*)&sc->tiles[ep & 1] + l * 8 + (lane & 7), EMPTY, EMPTY, EMPTY, EMPTY);
                named_sync(1, 128);
                if (tid == 128) st_release(&sc->clean, ep);
            }
            if (tid == 0) {
                const long long t0 = clock64();
                while (clock64() - t0 < SP_AT) {}
                #pragma unroll 1
                for (int i = 0; i < 7; i++) bulk_prefetch((const char*)wo + (i * 4 + mi) * 14336, 14336);
                if (mi) {
                    uint32_t t = (uint32_t)t0 + PF1_AT;
                    #pragma unroll 1
                    for (int i = mi - 1; i < PF1_N; i += 3) {
                        while ((int)(clock32() - t) < 0) {}
                        tma5d_prefetch(&tm_w1, (i & 7) * 64, (i + 48) & 56, (i + 48) >> 6);
                        t += PF1_PACE;
                    }
                    t = (uint32_t)t0 + PF_AT;
                    #pragma unroll 1
                    for (int i = mi - 1; i < PF_N; i += 3) {
                        while ((int)(clock32() - t) < 0) {}
                        bulk_prefetch((const char*)w2 + (i < 128 ? i * 16384 : (i - 64 >> 1) * 65536 + (i & 1) * 16384), 16384);
                        t += PF_PACE;
                    }
                }
                while (ld_relaxed(sc->hint_u + 254) != ep) { __nanosleep(500); if (clock64() - t0 > WD_CLKS) __trap(); }
                sc->epoch[slot] = ep;
                if (mi == 1) sc->clean = ep + 1;
            }
            return;
        }
        {
            const int w = warp & 3, wg = warp >> 2, g = lane >> 2, t = lane & 3;
            if (WARM_AT) { const uint32_t t0 = clock32(); while (clock32() - t0 < WARM_AT) {} __syncwarp(); }
            if (w > 0) post_hint(sc->hint_o + ((2 * tb + (w >> 1)) * 32 + hp * 4 + (w & 1) * 2 + wg) * 2, 0, lane);
            if (wg == 0) {
                if (t < 2) st_relaxed4(sc->stats + tt2 * 256 + q * 64 + 16 * w + g + 8 * t, 0, 0, 0, 0);
            }
        }
        named_sync(0, 288);
        asm volatile("setmaxnreg.inc.sync.aligned.u32 224;");
        int tid; asm volatile("mov.u32 %0, %%tid.x;" : "=r"(tid));
        const int lane = tid & 31, warp = __shfl_sync(0xffffffffu, tid >> 5, 0), wg = warp >> 2;
        uint32_t ep;
        Tiles* tl;
        const int w = warp & 3, g = lane >> 2, t = lane & 3;
        const bool leader = (tid & 127) == 0;
        const uint32_t never = gridDim.y - 1;
        {
            uint32_t a[28][4];
            float accK[28], accV[28], accQ[28];
            const int lrow = 16 * w + (lane & 7) + (lane & 8);
            const uint32_t lbase = sb + wg * 8192 + lrow * 128;
            const uint32_t lx = (lane >> 4) ^ (lane & 7);
            const uint32_t wofs = hp & 1;
            auto pin2 = [&](uint32_t x0, uint32_t x1) {
                asm volatile("{\n.reg .pred p;\nsetp.ne.u32 p, %2, 0;\n@p st.shared.v2.b32 [%0], {%0,%1};\n}" :: "r"(x0), "r"(x1), "r"(never) : "memory");
            };
            float cS[2][4] = {}, cA[2][4] = {}, cB[2][4] = {}, q0, q1, p0, p1;
            auto sq = [&](float& acc, uint32_t v) { const float lo = bf_lo(v), hi = bf_hi(v); acc = fmaf(hi, hi, fmaf(lo, lo, acc)); };
            #pragma unroll
            for (int kb = 0; kb < 8; kb++) {
                if (kb < 7) {
                    mbar_wait(bars + 8 * (B_FULLX + kb), 0);
                    if (kb == 0 && tid == 0) STAMP(0);
                    if (kb == 6 && tid == 0) STAMP(25);
                    if (kb == 0) FST(0); if (kb == 2) FST(1); if (kb == 4) FST(2); if (kb == 6) FST(3);
                    #pragma unroll
                    for (int s = 4 * kb; s < 4 * kb + 4; s++) ldsm4(a[s], lbase + slot_x(kb) + ((lx ^ (2 * (s & 3))) << 4));
                }
                if (kb == 5) named_sync(9 + wg, 160);
                if (kb == NPIPE) continue;
                const int kc = kb < NPIPE ? kb : kb - 1;
                if (kc == NSQ) { p0 = cS[0][0] + cS[1][0]; p1 = cS[0][2] + cS[1][2]; }
                #pragma unroll
                for (int s = 4 * kc; s < 4 * kc + 4; s++) {
                    mma16816(cS[s & 1], a[s][0], a[s][1], a[s][2], a[s][3], 0x3F803F80u, 0x3F803F80u);
                    if (kc < NSQ) {
                        mma1688(cA[0], a[s][0], a[s][1], a[s][0]); mma1688(cA[1], a[s][2], a[s][3], a[s][2]);
                        mma1688(cB[0], a[s][0], a[s][1], a[s][1]); mma1688(cB[1], a[s][2], a[s][3], a[s][3]);
                    }
                }
            }
            const float m0 = (cS[0][0] + cS[1][0]) * (1.f / D_), m1 = (cS[0][2] + cS[1][2]) * (1.f / D_);
            const uint32_t mm0 = pack_bf16(m0, m0), mm1 = pack_bf16(m1, m1);
            if (lane == 0) mbar_arrive(bars + 8 * B_DONEX);
            auto center = [&](int s) { sub_bf16x2(a[s][0], mm0); sub_bf16x2(a[s][1], mm1); sub_bf16x2(a[s][2], mm0); sub_bf16x2(a[s][3], mm1); };
            uint32_t Ka[8], Kb[8], Kc[8], Va[8], Vb[7], Vc[8];
            float r0, r1, ls0, ls1;
            uint32_t pm, zero;
            uint32_t* od;
            uint4* oh;
            auto kpack = [&](uint32_t (&k)[8], int j, int c, float r) {
                const uint32_t v = pack_bf16(accK[4 * j + c] * r, accK[4 * j + c + 1] * r);
                if (j == 3) { k[3] = t < 2 ? v : 0u; k[4] = t < 2 ? 0u : v; } else k[j + (j > 3)] = v;
            };
            auto batch = [&](auto c0, auto c1) {
                constexpr int n0 = c0.value, n1 = c1.value;
                wg_fence();
                static_for<n0, n1>([&](auto nc) {
                    constexpr int n = nc.value;
                    if (n == 4) { center(4); center(5); center(6); center(7); wg_fence(); }
                    const uint64_t desc = mkdesc(sb + (n < 56 ? slot_kv(n >> 3) + (n & 7) * 2048 : SM_QO + (n - 56) * 2048), 8192, 1024, 1) + wofs;
                    wgmma_rs56<1>(n < 28 ? accK : n < 56 ? accV : accQ, a[n % 28], desc, n % 28 != 0);
                });
                wg_commit();
                if (n0 > 0) wg_wait<1>();
            };
            const uint32_t hs = sb + tid * 16 + warp * 512;
            auto hand_over = [&](const uint32_t (&v)[8], int kv) {
                mbar_wait(bars + 8 * (kv ? B_DONE1 + 5 : B_DONEX), 0);
                sts4(hs + (kv ? SM_HALOV : SM_HALOK), v[0], v[1], v[2], v[3]); sts4(hs + (kv ? SM_HALOV : SM_HALOK) + 512, v[4], v[5], v[6], v[7]);
                if (w == 3) named_arrive(6 + kv, 96);
            };
            auto take_over = [&](uint32_t (&v)[8], int kv) {
                if (w == 0) mbar_wait(bars + 8 * (B_HALO + 2 * kv + wg), 0);
                const uint32_t ad = w ? hs + (kv ? SM_HALOV : SM_HALOK) - 1024 : kv ? sb + lane * 16 + wg * 1024 + SM_HALOV + 8192 : halo_kin(wg, lane);
                const uint4 u0 = lds4(ad), u1 = lds4(ad + (w || kv ? 512 : 16));
                v[0] = u0.x; v[1] = u0.y; v[2] = u0.z; v[3] = u0.w; v[4] = u1.x; v[5] = u1.y; v[6] = u1.z; v[7] = u1.w;
            };
            center(0); center(1); center(2); center(3);
            static_for<0, 7>([&](auto pc) {
                constexpr int p = pc.value;
                mbar_wait(bars + 8 * (B_FULLKV + p), 0);
                if (p == 0 && tid == 0) STAMP(26);
                if (p == 3 && tid == 0) STAMP(27);
                FST(4 + p);
                batch(Int<8 * p>(), Int<8 * p + 8>());
                if (p > 0 && leader) mbar_arrive(bars + 8 * (B_DONE1 + p - 1));
                #pragma unroll
                for (int s = 8 * p + 8; s < 8 * p + 16 && s < 28; s++) center(s);
                if (p == 1) {
                    const float c0 = bf_hi(mm0), c1 = bf_hi(mm1);
                    q0 = fmaf(c0, fmaf(c0, 64.f * NSQ, -2.f * p0), (g & 1) ? cA[0][1] + cA[1][1] : cA[0][0] + cA[1][0]) - D_ * (m0 - c0) * (m0 - c0);
                    q1 = fmaf(c1, fmaf(c1, 64.f * NSQ, -2.f * p1), (g & 1) ? cB[0][3] + cB[1][3] : cB[0][2] + cB[1][2]) - D_ * (m1 - c1) * (m1 - c1);
                    asm("" : "+f"(q0), "+f"(q1));
                    q0 = t == (g >> 1) ? q0 : 0.f; q1 = t == (g >> 1) ? q1 : 0.f;
                    pin2(__float_as_uint(q0), __float_as_uint(q1));
                }
                constexpr int PK = NSQ < 5 ? 5 : 4, NR = 28 - 4 * NSQ;
                if (p >= 2 && p < PK) {
                    #pragma unroll
                    for (int s = 4 * NSQ + NR * (p - 2) / (PK - 2); s < 4 * NSQ + NR * (p - 1) / (PK - 2); s++) { sq(q0, a[s][0]); sq(q1, a[s][1]); sq(q0, a[s][2]); sq(q1, a[s][3]); }
                    pin2(__float_as_uint(q0), __float_as_uint(q1));
                }
                if (p == PK - 1) { q0 = quad_sum(q0); q1 = quad_sum(q1); }
                if (p == PK) {
                    r0 = rsqrt_approx(fmaxf(q0 * (1.f / D_), 0.f) + LN_EPS); r1 = rsqrt_approx(fmaxf(q1 * (1.f / D_), 0.f) + LN_EPS);
                    reg_fence(accK);
                    #pragma unroll
                    for (int j = 0; j < 7; j++) kpack(Kc, j, 2, r1);
                    hand_over(Kc, 0);
                }
                if (p == PK + 1) {
                    #pragma unroll
                    for (int j = 0; j < 7; j++) kpack(Kb, j, 0, r0);
                    #pragma unroll
                    for (int j = 0; j < 8; j += 2) pin2(Kb[j], Kb[j + 1]);
                    ls0 = LOG2E_SCALE * r0; ls1 = LOG2E_SCALE * r1;
                    pm = (2 * t <= g ? 0xFFFFu : 0u) | (2 * t + 1 <= g ? 0xFFFF0000u : 0u);
                    zero = never; asm volatile("" : "+r"(zero));
                    pin2(__float_as_uint(ls0), __float_as_uint(ls1)); pin2(pm, zero);
                }
                if (p == 2) ep = get_tag();
                if (p == 6) {
                    tl = &sc->tiles[ep & 1];
                    const int tt = 2 * tb + (w >> 1);
                    od = tl->o + tt * 14336 + (7 * hp) * 256 + (2 * (2 * (w & 1) + wg)) * 32 + lane;
                    oh = sc->hint_o + (tt * 32 + hp * 4 + (w & 1) * 2 + wg) * 2 + (lane & 1);
                    pin2((uint32_t)(uint64_t)od, (uint32_t)((uint64_t)od >> 32));
                    pin2((uint32_t)(uint64_t)oh, (uint32_t)((uint64_t)oh >> 32));
                }
            });
            if (tid == 0) STAMP(1);
            FST(11);
            mbar_wait(bars + 8 * B_FQ, 0);
            batch(Int<56>(), Int<60>());
            reg_fence(accV);
            if (leader) mbar_arrive(bars + 8 * (B_DONE1 + 6));
            if (tid == 0) STAMP(2);
            FST(12);
            #pragma unroll
            for (int j = 0; j < 7; j++) Vc[j] = movtrans(pack_bf16(accV[4 * j + 2] * r1, accV[4 * j + 3] * r1));
            Vc[7] = Vc[6];
            hand_over(Vc, 1);
            batch(Int<60>(), Int<66>());
            #pragma unroll
            for (int j = 0; j < 7; j++) {
                Vb[j] = movtrans(pack_bf16(accV[4 * j] * r0, accV[4 * j + 1] * r0));
                Vc[j] |= zero;
            }
            batch(Int<66>(), Int<72>());
            #pragma unroll
            for (int j = 0; j < 7; j++) pin2(Vb[j], Vc[j]);
            mbar_wait(bars + 8 * (B_FQ + 1), 0);
            FST(13);
            if (w > 0 && lane < 2) { const uint32_t now = gtime32(); st_relaxed4(oh, ep, now, ep, now); }
            batch(Int<72>(), Int<84>());
            FST(14);
            named_sync(1 + wg, 128);
            take_over(Ka, 0);
            if (tid == 0) STAMP(3);
            wg_wait<0>();
            reg_fence(accQ);
            if (tid == 0) STAMP(4);
            FST(15);
            const bool first = (tb == 0 && w == 0);
            uint32_t pA[2], pB0[2], pB1[2], pC[2], z0[2], z1[2];
            #pragma unroll
            for (int h = 0; h < 2; h++) {
                float sA[4] = {0.f, 0.f, 0.f, 0.f}, sB[4] = {0.f, 0.f, 0.f, 0.f}, sC[4] = {0.f, 0.f, 0.f, 0.f};
                #pragma unroll
                for (int k = 0; k < 2; k++) {
                    const float* qq = accQ + 12 * h + 8 * k;
                    uint32_t a0 = pack_bf16(qq[0], qq[1]), a1 = pack_bf16(qq[2], qq[3]);
                    if (h == 1 && k == 0) { a0 |= zero; a1 |= zero; }
                    const uint32_t a2 = pack_bf16(qq[4], qq[5]), a3 = pack_bf16(qq[6], qq[7]);
                    mma16816(sB, a0, a1, a2, a3, Kb[4 * h + 2 * k], Kb[4 * h + 2 * k + 1]);
                    mma16816(sA, a0, a1, a2, a3, Ka[4 * h + 2 * k], Ka[4 * h + 2 * k + 1]);
                    mma16816(sC, a0, a1, a2, a3, Kc[4 * h + 2 * k], Kc[4 * h + 2 * k + 1]);
                }
                const bool n0 = pm & 1, n1 = (int)pm < 0;
                const float l00 = n0 ? sB[0] : (first ? -INFINITY : sA[0]), l01 = n1 ? sB[1] : (first ? -INFINITY : sA[1]);
                const float l10 = n0 ? sC[2] : sB[2], l11 = n1 ? sC[3] : sB[3];
                const float x0 = -ls0 * quad_max(fmaxf(l00, l01)), x1 = -ls1 * quad_max(fmaxf(l10, l11));
                const float e00 = ex2(fmaf(l00, ls0, x0)), e01 = ex2(fmaf(l01, ls0, x0)), e10 = ex2(fmaf(l10, ls1, x1)), e11 = ex2(fmaf(l11, ls1, x1));
                const float i0 = rcp_approx(quad_sum(e00 + e01)), i1 = rcp_approx(quad_sum(e10 + e11));
                const uint32_t P0 = pack_bf16(e00 * i0, e01 * i0), P1 = pack_bf16(e10 * i1, e11 * i1);
                pB0[h] = P0 & pm; pA[h] = P0 & ~pm; pC[h] = P1 & pm; pB1[h] = P1 & ~pm; z0[h] = P0 & zero; z1[h] = P1 & zero;
            }
            float o[8][4];
            #pragma unroll
            for (int j = 0; j < 8; j++) {
                o[j][0] = o[j][1] = o[j][2] = o[j][3] = 0.f;
                mma16816(o[j], pB0[j >> 2], pB1[j >> 2], z0[j >> 2], pC[j >> 2], Vb[j - (j >> 2)], Vc[j - (j >> 2)]);
            }
            if (tid == 0) STAMP(12);
            FST(16);
            take_over(Va, 1);
            if (lane == 0) mbar_arrive(bars + 8 * B_DONEQ);
            if (tid == 0) STAMP(16);
            #pragma unroll
            for (int j = 0; j < 8; j++) mma1688(o[j], pA[j >> 2], z1[j >> 2], Va[j - (j >> 2)]);
            #pragma unroll
            for (int j = 0; j < 7; j++) {
                float v[4];
                #pragma unroll
                for (int c = 0; c < 4; c++) v[c] = j < 3 ? o[j][c] : j > 3 ? o[j + 1][c] : (t < 2 ? o[3][c] : o[4][c]);
                od[j * 256] = pack_bf16(v[0], v[1]);
                od[j * 256 + 32] = pack_bf16(v[2], v[3]);
            }
            if (tid == 0) STAMP(5);
            FST(17);
        }
        const int z = get_tag() - ep, slot1 = slot + z, tid1 = tid + z, warp1 = warp + z;
        ep += z;
        {
        ASSIGN_WORK(slot1)
        const int tid = tid1, lane = tid & 31, wg = warp1 >> 2, w = warp1 & 3, g = lane >> 2, t = lane & 3;
        tl = &sc->tiles[ep & 1];
        const uint32_t live = wg ^ 1;
        uint32_t rb0, rb1, late[14];
        uint32_t* late_ptr;
        const unsigned short* pb = (const unsigned short*)(live ? b2 + tt2 * 64 : b1 + ft * 64) + 16 * w + g;
        auto undef = [](float (&v)[56]) {
            #pragma unroll
            for (int i = 0; i < 56; i++) asm volatile("" : "=f"(v[i]));
        };
        {
            float acc[56];
            const int hrow = 32 * (w >> 1) + 2 * ((lane & 7) + (lane & 8)) + (w & 1);
            const uint32_t ha = sb + SM_H + hrow * 128 + (((lane >> 4) ^ (hrow & 7)) << 4);
            uint4* sp = sc->stats + tt2 * 256 + 16 * w + g + 8 * (t & 1);
            uint4* sp_out = sp + q * 64;
            const uint4* sp_in = sp + (t & 2) * 64;
            uint32_t* hd = tl->hn + ((q >> 1) * 32 + (tt2 >> 1)) * 7168 + (q & 1) * 3584 + (tt2 & 1) * 128 + w * 32 + lane;
            pin_ptr(never, sp_out); pin_ptr(never, sp_in); pin_ptr(never, hd);
            float s0 = 0.f, s1 = 0.f, q0 = 0.f, q1 = 0.f, s2 = 0.f, s3 = 0.f, q2 = 0.f, q3 = 0.f;
            auto sums = [&](int j0, int j1) {
                #pragma unroll
                for (int j = j0; j < j1; j++) {
                    s0 += acc[4 * j]; s2 += acc[4 * j + 1]; q0 = fmaf(acc[4 * j], acc[4 * j], q0); q2 = fmaf(acc[4 * j + 1], acc[4 * j + 1], q2);
                    s1 += acc[4 * j + 2]; s3 += acc[4 * j + 3]; q1 = fmaf(acc[4 * j + 2], acc[4 * j + 2], q1); q3 = fmaf(acc[4 * j + 3], acc[4 * j + 3], q3);
                }
            };
            if (live) {
                mbar_wait(bars + 8 * B_FULLWO, 0);
                #pragma unroll
                for (int jp = 0; jp < 7; jp++) {
                    uint32_t xx[4];
                    ldsm4(xx, hcol(ha, jp));
                    #pragma unroll
                    for (int r = 0; r < 4; r++) { acc[8 * jp + 2 * r] = bf_lo(xx[r]); acc[8 * jp + 2 * r + 1] = bf_hi(xx[r]); }
                }
                reg_fence(acc);
                auto od_ = [&](int s) { return mkdesc(sb + SM_QO + s * 2048, 1024, 128, 0); };
                auto wd_ = [&](int s) { return mkdesc(sb + slot_wo(s >> 2) + (s & 3) * 2048, 8192, 1024, 1); };
                float accl[32], accr[24];
                #pragma unroll
                for (int i = 0; i < 5; i++) {
                    if (i < 4) mbar_wait(bars + 8 * (B_FULLO + i), 0);
                    if (i == 0 && tid == 0) STAMP(7);
                    if (i == 1) { rb0 = ld_u16(pb); rb1 = ld_u16(pb + 8); }
                    wg_fence();
                    #pragma unroll
                    for (int ss = 0; ss < 7; ss++) {
                        if (i < 3) wgmma_ss112<0, 1>(acc, od_(7 * i + ss), wd_(7 * i + ss));
                        else if (i == 4) wgmma_ss64<0, 1>(accl, od_(21 + ss), wd_(21 + ss));
                        else if (ss == 0) wgmma_ss48<0, 1, 0>(accr, od_(21), wd_(21) + 512);
                        else wgmma_ss48<0, 1>(accr, od_(21 + ss), wd_(21 + ss) + 512);
                    }
                    wg_commit();
                    if (i > 0) {
                        wg_wait<1>();
                        if (i == 3) {
                            reg_fence(acc);
                            #pragma unroll
                            for (int c = 0; c < 32; c++) accl[c] = __uint_as_float(__float_as_uint(acc[c]) | never);
                            reg_fence(accl);
                        }
                        if (i < 4 && leader) mbar_arrive(bars + 8 * (B_DONEO + i - 1));
                    }
                }
                reg_fence(accr);
                #pragma unroll
                for (int c = 0; c < 24; c++) acc[32 + c] += accr[c];
                sums(8, 14);
                pin4(never, s0, s1, s2, s3); pin4(never, q0, q1, q2, q3);
                wg_wait<0>();
                reg_fence(accl);
                #pragma unroll
                for (int c = 0; c < 32; c++) acc[c] = accl[c];
                if (leader) mbar_arrive(bars + 8 * (B_DONEO + 3));
                if (tid == 0) STAMP(8);
            } else undef(acc);
            if (live || (DRY2 && w == 3)) {
            sums(0, 8);
            s0 += s2; s1 += s3; q0 += q2; q1 += q3;
            float sr = ((t & 1) ? s1 : s0) + __shfl_xor_sync(0xffffffffu, (t & 1) ? s0 : s1, 1), qr = ((t & 1) ? q1 : q0) + __shfl_xor_sync(0xffffffffu, (t & 1) ? q0 : q1, 1);
            sr += __shfl_xor_sync(0xffffffffu, sr, 2); qr += __shfl_xor_sync(0xffffffffu, qr, 2);
            st_relaxed4_if(t < 2 * live, sp_out, __float_as_uint(sr), __float_as_uint(qr), ep);
            if (live) named_arrive(5, 256);
            if (tid == 0) STAMP(9);
            #pragma unroll
            for (int jp = 0; jp < 7; jp++)
                stsm4_if(live, hcol(ha, jp), pack_bf16(acc[8 * jp], acc[8 * jp + 1]), pack_bf16(acc[8 * jp + 2], acc[8 * jp + 3]),
                      pack_bf16(acc[8 * jp + 4], acc[8 * jp + 5]), pack_bf16(acc[8 * jp + 6], acc[8 * jp + 7]));
            uint4 v0, v1;
            do { v0 = ld_relaxed4(sp_in); v1 = ld_relaxed4(sp_in + 64); } while (live && __any_sync(0xffffffffu, v0.w != ep || v1.w != ep));
            if (tid == 0) STAMP(10);
            sr = __uint_as_float(v0.x) + __uint_as_float(v1.x); qr = __uint_as_float(v0.y) + __uint_as_float(v1.y);
            sr += __shfl_xor_sync(0xffffffffu, sr, 2); qr += __shfl_xor_sync(0xffffffffu, qr, 2);
            const float m = sr * (1.f / D_), v = fmaxf(qr * (1.f / D_) - m * m, 0.f);
            const float r = rsqrt_approx(fmaf(v, 4.f + 4.f * LN_EPS, 4.f * LN_EPS * LN_EPS)), c = -m * r;
            const float r0 = __shfl_sync(0xffffffffu, r, lane & ~1), c0 = __shfl_sync(0xffffffffu, c, lane & ~1);
            const float r1 = __shfl_sync(0xffffffffu, r, lane | 1), c1 = __shfl_sync(0xffffffffu, c, lane | 1);
            #pragma unroll
            for (int j = 0; j < 14; j++) st_global_if(live, hd + j * 256, pack_bf16(fmaf(acc[4 * j], r0, c0), fmaf(acc[4 * j + 1], r0, c0)));
            if (never) mbar_arrive(bars);
            #pragma unroll
            for (int j = 0; j < 14; j++) late[j] = pack_bf16(fmaf(acc[4 * j + 2], r1, c1), fmaf(acc[4 * j + 3], r1, c1));
            late_ptr = hd + 16 * 7168;
            if (tid == 0) STAMP(11);
            }
        }
        if (!live) {
            check_tiles<0>(w, 4, 4, tl->o + tt2 * 14336, false, lane, true);
            rb0 = ld_u16(pb); rb1 = ld_u16(pb + 8);
            named_sync(5, 256);
            auto phase3 = [&](auto nc) {
                constexpr int NC = nc.value;
                float acc[4 * NC];
                uint32_t* ud = tl->u + (pr3 * 28 + (ft >> 1) + (NC == 14 ? 4 : 0)) * 7168 + col3 * 256 + (ft & 1) * 128 + w * 32 + lane;
                #pragma unroll
                for (int j = 0; j < 4 * NC; j++) acc[j] = 0.5f * bf_lo((j & 2) ? rb1 : rb0);
                #pragma unroll 1
                for (uint32_t pass = never; pass < 2; pass++) {
                    if (pass) {
                        mix_mainloop<32>(TSVAL acc, leader);
                        if (leader) STAMP(14);
                    }
                    uint32_t pk[NC];
                    #pragma unroll
                    for (int j = 0; j < NC; j++) {
                        const float k = j < GDEP ? GELU_K1 : __uint_as_float(__float_as_uint(GELU_K1) | (pk[j - GDEP] & never));
                        pk[j] = pack_bf16(gelu_half(acc[4 * j], k), gelu_half(acc[4 * j + 1], k));
                        st_global_if(pass, ud + j * 256, pk[j]);
                    }
                }
                if (leader) STAMP(15);
                #pragma unroll
                for (int j = 0; j < NC; j++) late[j] = pack_bf16(gelu_half(acc[4 * j + 2], GELU_K1), gelu_half(acc[4 * j + 3], GELU_K1));
                if (NC == 14) mbar_wait(bars + 8 * (B_FULLB + LATE_AT4), 1);
                #pragma unroll
                for (int c = 0; c < NC; c++) st_global_if(1, ud + (NC == 14 ? 10 : 4) * 7168 + c * 256, late[c]);
            };
            if (early) phase3(Int<10>()); else phase3(Int<14>());
            if (w) {
                if (early && w == 1) fetch_times(TSVAL sc->hint_u, 1, q, ep, lane);
                check_tiles<2>(CH_U - 1 + w, 3, 28, tl->u + (q >> 1) * 28 * 7168 + (q & 1) * 3584, false, lane, false);
                mbar_wait(bars + 8 * (B_DONE + CL_AT), 1);
                const int l = slot * 48 + (tid - 160) / 2;
                #pragma unroll
                for (int i = 0; i < 7; i++)
                    st_relaxed4_if(i < 6 || l < sizeof(Tiles) / 128 - 6 * 6144, (uint4*)&sc->tiles[~ep & 1] + (i * 6144 + l) * 8 + (lane & 7), EMPTY, EMPTY, EMPTY);
            }
            if (leader) mbar_wait_wd(bars + 8 * B_END, 0);
            return;
        }
        {
            float acc[56];
            const uint32_t ad = sb + SM_H + (16 * w + (lane & 15)) * 128 + (((lane >> 4) ^ (lane & 7)) << 4);
            const float bb0 = bf_lo(rb0), bb1 = bf_lo(rb1);
            named_sync(1, 128);
            #pragma unroll
            for (int jp = 0; jp < 7; jp++) {
                uint32_t hh[4];
                ldsm4(hh, hcol(ad, jp));
                #pragma unroll
                for (int r = 0; r < 4; r++) { acc[8 * jp + 2 * r] = bf_lo(hh[r]) + ((r & 1) ? bb1 : bb0); acc[8 * jp + 2 * r + 1] = bf_hi(hh[r]) + ((r & 1) ? bb1 : bb0); }
            }
            #pragma unroll 1
            for (uint32_t pass = never; pass < 2; pass++) {
                if (pass) {
                    #pragma unroll 1
                    for (int k = 0; k < 2; k++) {
                        check_tiles<1>(w + 4 * LATE_AT * k, 4, k ? 32 : 4 * LATE_AT, tl->hn + pr3 * 32 * 7168 + col3 * 256, early, lane, k == 0);
                        #pragma unroll
                        for (int c = 0; c < 14; c++) st_global_if(k ^ 1, late_ptr + c * 256, late[c]);
                    }
                    mbar_wait(bars + 8 * (B_DONE + START4), 0);
                    mix_mainloop<28>(TSVAL acc, leader);
                    if (leader) mbar_arrive(bars + 8 * B_END);
                    if (tid == 0) STAMP(18);
                }
                #pragma unroll
                for (int jp = 0; jp < 7; jp++)
                    stsm4_if(1, hcol(ad, jp), pack_bf16(acc[8 * jp], acc[8 * jp + 1]), pack_bf16(acc[8 * jp + 2], acc[8 * jp + 3]),
                             pack_bf16(acc[8 * jp + 4], acc[8 * jp + 5]), pack_bf16(acc[8 * jp + 6], acc[8 * jp + 7]));
                fence_async_smem();
                __syncwarp();
            }
            if (elect()) {
                tma2d_store(&tm_out64, c64, tt2 * 64 + 16 * w, sb + SM_H + w * 2048);
                tma2d_store(&tm_out48, c48, tt2 * 64 + 16 * w, sb + SM_H + 8192 + w * 2048);
            }
            asm volatile("cp.async.bulk.commit_group;" ::: "memory");
            asm volatile("cp.async.bulk.wait_group.read 0;" ::: "memory");
            if (tid == 0) { sc->epoch[slot] = ep; STAMP(19); }
        }
        }
    } else {
        asm volatile("setmaxnreg.dec.sync.aligned.u32 56;");
        int warp2; asm("mov.u32 %0, %1;" : "=r"(warp2) : "r"(warp));
        if (warp2 > 8) {
            ASSIGN_WORK(get_slot())
            if (slot >= 128) return;
            uint32_t ep, cl;
            uint4* const oh = sc->hint_o + (2 * tb * 32 + hp * 4) * 2 + (lane & 3);
            uint4* const hu = sc->hint_u + (early ? ech * 8 + ft : 40 + q * 20 + ft) * 2;
            if (warp == 10) {
                post_hint(sc->hint_h + (q * 32 + tt2) * 2, 0, lane);
                post_hint(hu, 0, lane);
            }
            if (warp == 11) {
                ep = ld_volatile(&sc->epoch[slot]) + 1; cl = ld_acquire(&sc->clean);
                post_hint(sc->hint_k + (tb * 8 + hp) * 2, 0, lane);
                if (lane < (tb < 15 ? 4 : 0)) st_relaxed4(oh + 128, 0, 0, 0, 0);
                if (lane < (tb ? 0 : 4)) st_relaxed4(oh, 0, 0, 0, 0);
            }
            if (elect()) {
                if (warp == 9) {
                    #pragma unroll
                    for (int i = B_DONE1; i < B_DONEO; i++) mbar_init(bars + 8 * i, i < B_DONEX ? 2 : i == B_DONEX ? 8 : 9);
                }
                #pragma unroll
                for (int i = 0; i < 54; i++) mbar_init(bars + 8 * (B_DONEO + i) + (warp - 9) * 432, 1);
                asm volatile("fence.mbarrier_init.release.cluster;" ::: "memory");
            }
            named_sync(8, 128);
            if (warp < 11) mbar_expect(sb + SM_RAW + 8 * (tid - 288), early && tid >= 292 && tid < 324 ? 10240 : 14336);
            if (warp == 9) { named_arrive(4, 64); named_arrive(9, 160); named_arrive(10, 160); }
            if (warp < 11) {
                ep = get_tag();
                mbar_wait(bars + 8 * (B_DONE1 + HALO_AT), 0);
                #pragma unroll 1
                for (int kv = 0; kv < 2; kv++) {
                    uint4 v0 = {}, v1 = {}, v2 = {};
                    if (tb > 0) {
                        const uint4* hg = sc->halo + ((((tb - 1) * 8 + hp) * 2 + warp - 9) * 2 + kv) * 96 + lane;
                        if (kv == 0) while (ld_relaxed(sc->hint_k + ((tb - 1) * 8 + hp) * 2) != ep) {}
                        do { v0 = ld_relaxed4(hg); v1 = ld_relaxed4(hg + 32); v2 = ld_relaxed4(hg + 64); } while (!__all_sync(0xffffffffu, v0.w == ep && v1.w == ep && v2.w == ep));
                    }
                    if (kv) mbar_wait(bars + 8 * (B_DONE1 + 5), 0);
                    const uint32_t hs = kv ? sb + lane * 16 + (warp - 9) * 1024 + SM_HALOV + 8192 : halo_kin(warp - 9, lane);
                    sts4(hs, v0.x, v0.y, v0.z, v1.x); sts4(hs + (kv ? 512 : 16), v1.y, v1.z, v2.x, v2.y);
                    __syncwarp();
                    if (lane == 0) mbar_arrive(bars + 8 * (B_HALO + 2 * kv + warp - 9));
                }
                if (tid == 288) STAMP(21);
            } else {
                const long long t0 = clock64();
                while (__any_sync(0xffffffffu, (int)(cl - ep) < 0)) { cl = ld_acquire(&sc->clean); if (clock64() - t0 > WD_CLKS) __trap(); }
                if (lane == 0) { *(volatile uint32_t*)(smem_raw + SM_TAG) = ep; mbar_arrive(bars + 8 * B_CLR); }
                uint4* hg = sc->halo + (tb * 8 + hp) * 384 + lane;
                #pragma unroll 1
                for (int kv = 0; kv < 2; kv++) {
                    const uint32_t hs = sb + lane * 16 + 3072 + (kv ? SM_HALOV : SM_HALOK);
                    named_sync(6 + kv, 96);
                    #pragma unroll
                    for (int p = 0; p < 2; p++) {
                        const uint4 u0 = lds4(hs + p * 4096), u1 = lds4(hs + p * 4096 + 512);
                        st_relaxed4(hg + p * 192, u0.x, u0.y, u0.z, ep); st_relaxed4(hg + p * 192 + 32, u0.w, u1.x, u1.y, ep); st_relaxed4(hg + p * 192 + 64, u1.z, u1.w, ep, ep);
                    }
                    hg += 96;
                    if (kv == 0) {
                        post_hint(sc->hint_k + (tb * 8 + hp) * 2, ep, lane);
                        #pragma unroll
                        for (int j = 0; j < 6; j++) st_relaxed4(hg + j * 32 + (j / 3) * 96, 0, 0, 0, 0);
                    }
                }
                const uint32_t now = gtime32() - LATE_O;
                if (lane < (tb < 15 ? 4 : 0)) st_relaxed4(oh + 128, ep, now, ep, now);
                if (lane < (tb ? 0 : 4)) st_relaxed4(oh, ep, now, ep, now);
                if (lane == 0) STAMP(23);
                if (lane == 0) mbar_arrive(bars + 8 * B_DONEQ);
            }
            if (warp > 9) {
                const Tiles* const tl = &sc->tiles[ep & 1];
                if (warp == 10) {
                    mbar_wait(bars + 8 * (B_FULLO + 3), 0);
                    mbar_wait(bars + 8 * (B_DONEO + HINT_H), 0);
                    post_time(sc->hint_h + (q * 32 + tt2) * 2, ep, lane);
                    mbar_wait(bars + 8 * (B_DONE + (early ? HINT_E : HINT_U)), 0);
                    post_time(hu, ep, lane);
                }
                if (warp == 11) {
                    mbar_wait(bars + 8 * (B_DONE + (early ? POLL_E : POLL_N)), 0);
                    fetch_times(TSVAL sc->hint_u, 0, q, ep, lane);
                }
                check_tiles<2>(11 - warp, 2, CH_U, tl->u + (q >> 1) * 28 * 7168 + (q & 1) * 3584, false, lane, true);
            } else {
                int aslot = 0;
                if (lane == 0) { prefetch_map(&tm_out64); prefetch_map(&tm_out48); }
                auto prefetch_w1 = [&]() {
                    if (elect()) {
                        #pragma unroll 1
                        for (int i = NA_SLOTS + (early ? ech : q); i < (early ? 16 : PFN_END); i += early ? 6 : 4) tma5d_prefetch(&tm_w1, ft * 64, (i & 7) * 8, i >> 3);
                    }
                };
                if (PFE_AT < 0) prefetch_w1();
                #pragma unroll 1
                for (int i = 0; i < 30; i++) {
                    if (i == POLL_I && !early) fetch_times(TSVAL sc->hint_u, 1, q, ep, lane);
                    int d = i == 21 && !early ? A_HOLD : 2 * i - 11;
                    if (early) d = i < 16 ? 1 + (i - NA_SLOTS) * AE_END / 9 : max(d, AE_W2);
                    mbar_wait(bars + 8 * (i < NA_SLOTS ? B_DONEQ + ((A_SCHED >> (4 * i)) & 15) : B_DONE + (d & 31)), d >= 32);
                    if (elect()) {
                        const uint32_t bar = bars + 8 * (B_FULLA + (i & 15)), dst = sb + SM_ARING + aslot * 16384;
                        mbar_expect(bar, 16384);
                        if (i < 16) tma5d(dst, &tm_w1, ft * 64, (i & 7) * 8, i >> 3, bar);
                        else tma5d(dst, &tm_w2, tt2 * 64, 8 * (i < 20 ? i & 1 : i < 25 ? i - 18 : i - 23), i < 20 ? (i >> 1) & 1 : i >= 25, bar);
                    }
                    aslot = aslot == NA_SLOTS - 1 ? 0 : aslot + 1;
                    if (i == PFE_AT) prefetch_w1();
                }
            }
        } else {
            const int slot0 = get_slot(), row0 = (slot0 >> 5) * 256 + (slot0 & 12) * 16;
            if (elect()) {
                prefetch_map(&tm_x);
                #pragma unroll
                for (int i = 0; i < 7; i++) mbar_init(bars + 8 * i, 1);
                asm volatile("fence.mbarrier_init.release.cluster;" ::: "memory");
            }
            named_arrive(0, 288);
            if (elect()) {
                #pragma unroll 1
                for (int kb = 0; kb < 7; kb++) {
                    load_x(kb, row0);
                    if (kb == 0) STAMP(22);
                }
                #pragma unroll
                for (int i = 7; i < B_DONE1; i++) mbar_init(bars + 8 * i, 1);
                asm volatile("fence.mbarrier_init.release.cluster;" ::: "memory");
            }
            named_arrive(8, 128);
            ASSIGN_WORK(get_slot())
            if (slot >= 128) return;
            #pragma unroll 1
            for (int kb = 0; kb < 7; kb++) {
                if (kb == 6) { named_sync(4, 64); mbar_wait(bars + 8 * B_DONEX, 0); }
                if (elect()) {
                    const uint32_t st = sb + slot_kv(kb), bar = bars + 8 * (B_FULLKV + kb);
                    mbar_expect(bar, 16384);
                    #pragma unroll
                    for (int i = 0; i < 2; i++) {
                        const int n = 2 * kb + (i ^ (G & 1));
                        tma2d(st + (n & 1) * 8192, &tm_wqkv, (n < 7 ? 448 : 896) + wcol, (n < 7 ? n : n - 7) * 64, bar);
                    }
                }
            }
            if (elect()) {
                mbar_expect(bars + 8 * B_FQ, 32768);
                mbar_expect(bars + 8 * (B_FQ + 1), 24576);
                #pragma unroll 1
                for (int i = 0; i < 7; i++) { const int j = i == 6 ? i : i ^ (G & 1); tma2d(sb + SM_QO + j * 8192, &tm_wqkv, wcol, j * 64, bars + 8 * (B_FQ + (i >> 2))); }
                mbar_expect(bars + 8 * B_FULLWO, 512 * 112 * 2);
            }
            #pragma unroll 1
            for (int i = 0; i < 7; i++) {
                const int kb = ((q & 1 ? WO_ORD1 : WO_ORD0) >> (4 * i)) & 7;
                if (kb < 5) mbar_wait(bars + 8 * (B_DONE1 + kb), 0);
                if (elect()) {
                    tma2d(sb + slot_wo(kb), &tm_wo64, c64, kb * 64, bars + 8 * B_FULLWO);
                    tma2d(sb + slot_wo(kb) + 8192, &tm_wo48, c48, kb * 64, bars + 8 * B_FULLWO);
                }
            }
            if (elect()) {
                tma2d(sb + SM_H, &tm_xr64, c64, tt2 * 64, bars + 8 * B_FULLWO);
                tma2d(sb + SM_H + 8192, &tm_xr48, c48, tt2 * 64, bars + 8 * B_FULLWO);
            }
            if (smem_u32(smem_raw) != SB) __trap();
            const uint32_t ep = get_tag();
            const Tiles* const tl = &sc->tiles[ep & 1];
            mbar_wait(bars + 8 * (B_DONE1 + 6), 0);
            const uint32_t t_o = last_hint(TSVAL sc->hint_o + (tt2 * 32 + lane) * 2, ep, 38);
            mbar_wait(bars + 8 * B_DONEQ, 0);
            wait_until(t_o + GO_O);
            if (elect()) {
                #pragma unroll
                for (int i = 0; i < 4; i++) {
                    bulk_ld(sb + SM_QO + i * 14336, tl->o + tt2 * 14336 + i * 3584, 14336, sb + SM_RAW + 8 * i);
                }
            }
            if (lane == 0) STAMP(20);
            mbar_wait(bars + 8 * (B_DONEO + 2), 0);
            const uint32_t* src = tl->hn + pr3 * 32 * 7168 + col3 * 256;
            uint32_t bytes = early ? 10240 : 14336, dst = sb + SM_BRING, top = dst + (early ? NE_SLOTS * 10240 : NB_SLOTS * 14336), raw = sb + SM_RAW + 32;
            auto issue = [&]() {
                if (elect()) bulk_ld(dst, src, bytes, raw);
                src += 7168; raw += 8; dst += bytes;
                if (dst == top) dst = sb + SM_BRING;
            };
            wait_until(last_hint(TSVAL sc->go, ep, 42) + GO_H);
            mbar_wait(bars + 8 * (B_DONEO + 3), 0);
            STAMP(29);
            #pragma unroll 1
            do issue(); while (dst != sb + SM_BRING);
            uint32_t done = bars + 8 * B_DONE;
            #pragma unroll 1
            do { mbar_wait(done, 0); done += 8; issue(); } while (raw != sb + SM_RAW + 288);
            if (early) mbar_wait(bars + 8 * (B_DONE + 31), 0);
            src = tl->u + (q >> 1) * 28 * 7168 + (q & 1) * 3584; bytes = 14336; dst = sb + SM_BRING; top = dst + NB_SLOTS * 14336;
            done = bars + 8 * (B_DONE + 24);
            #pragma unroll 1
            for (uint32_t par = 0; par < 2; par++) {
                mbar_wait(bars + 8 * (B_GO + par), 0);
                const uint32_t ts = *(volatile uint32_t*)(smem_raw + SM_TIME + (par ? 128 + 8 * (lane % 10) : 8 * (lane & 3)))
                                    + (par ? (lane < 10 ? GO_U : GO_U + GO_U2) : (lane < 4 ? GO_E : GO_E + GO_E2));
                if (par) done = bars + 8 * B_DONE;
                uint32_t bit = 1, wait = ~0u;
                #pragma unroll 1
                do {
                    while (wait & bit) wait = __ballot_sync(0xffffffffu, (int)(gtime32() - ts) < 0);
                    if (bit == 1) STAMP(par ? 36 : 30);
                    mbar_wait(done, par); done += 8;
                    issue();
                    bit *= 2;
                } while (bit != (par ? 1 << 20 : 1 << 8));
            }
        }
    }
}

typedef CUresult (*EncodeFn)(CUtensorMap*, CUtensorMapDataType, cuuint32_t, void*, const cuuint64_t*, const cuuint64_t*, const cuuint32_t*,
                             const cuuint32_t*, CUtensorMapInterleave, CUtensorMapSwizzle, CUtensorMapL2promotion, CUtensorMapFloatOOBfill);

void make_map(EncodeFn fn, CUtensorMap* tm, const void* ptr, int rank, const cuuint64_t* dims, const cuuint64_t* strides, const cuuint32_t* box, CUtensorMapSwizzle sw) {
    cuuint32_t es[5] = {1, 1, 1, 1, 1};
    fn(tm, CU_TENSOR_MAP_DATA_TYPE_BFLOAT16, rank, const_cast<void*>(ptr), dims, strides, box, es, CU_TENSOR_MAP_INTERLEAVE_NONE, sw,
       CU_TENSOR_MAP_L2_PROMOTION_NONE, CU_TENSOR_MAP_FLOAT_OOB_FILL_NONE);
}

}

extern "C" void kernel_launch(void* const* d_in, const int* in_sizes, int n_in, void* d_out, int out_size) {
    const __nv_bfloat16* x = (const __nv_bfloat16*)d_in[0];
    const __nv_bfloat16* wqkv = (const __nv_bfloat16*)d_in[1];
    const __nv_bfloat16* wo = (const __nv_bfloat16*)d_in[2];
    const __nv_bfloat16* w1 = (const __nv_bfloat16*)d_in[4];
    const __nv_bfloat16* b1 = (const __nv_bfloat16*)d_in[5];
    const __nv_bfloat16* w2 = (const __nv_bfloat16*)d_in[6];
    const __nv_bfloat16* b2 = (const __nv_bfloat16*)d_in[7];

    void* fnp = nullptr; cudaDriverEntryPointQueryResult qr;
    cudaGetDriverEntryPoint("cuTensorMapEncodeTiled", &fnp, cudaEnableDefault, &qr);
    EncodeFn fn = (EncodeFn)fnp;
    CUtensorMap tx, twqkv, two64, two48, tw1, tw2, txr64, txr48, tout64, tout48;
    { cuuint64_t d[3] = {448, 2, 1024}, s[2] = {896, 1792}; cuuint32_t b[3] = {64, 1, 64}; make_map(fn, &tx, x, 3, d, s, b, CU_TENSOR_MAP_SWIZZLE_128B); }
    { cuuint64_t d[2] = {1344, 448}, s[1] = {2688}; cuuint32_t b[2] = {64, 64}; make_map(fn, &twqkv, wqkv, 2, d, s, b, CU_TENSOR_MAP_SWIZZLE_128B); }
    { cuuint64_t d[2] = {448, 448}, s[1] = {896}; cuuint32_t b[2] = {64, 64}; make_map(fn, &two64, wo, 2, d, s, b, CU_TENSOR_MAP_SWIZZLE_128B); }
    { cuuint64_t d[2] = {448, 448}, s[1] = {896}; cuuint32_t b[2] = {48, 64}; make_map(fn, &two48, wo, 2, d, s, b, CU_TENSOR_MAP_SWIZZLE_128B); }
    { cuuint64_t d[5] = {1792, 8, 2, 64, 2}, s[4] = {2 * 3584, 3584, 32 * 3584, 16 * 3584}; cuuint32_t b[5] = {64, 8, 2, 8, 1}; make_map(fn, &tw1, w1, 5, d, s, b, CU_TENSOR_MAP_SWIZZLE_128B); }
    { cuuint64_t d[5] = {2048, 8, 2, 56, 2}, s[4] = {4096, 16 * 4096, 32 * 4096, 8 * 4096}; cuuint32_t b[5] = {64, 8, 2, 8, 1}; make_map(fn, &tw2, w2, 5, d, s, b, CU_TENSOR_MAP_SWIZZLE_128B); }
    { cuuint64_t d[2] = {448, 2048}, s[1] = {896}; cuuint32_t b[2] = {64, 64}; make_map(fn, &txr64, x, 2, d, s, b, CU_TENSOR_MAP_SWIZZLE_128B); }
    { cuuint64_t d[2] = {448, 2048}, s[1] = {896}; cuuint32_t b[2] = {48, 64}; make_map(fn, &txr48, x, 2, d, s, b, CU_TENSOR_MAP_SWIZZLE_128B); }
    { cuuint64_t d[2] = {448, 2048}, s[1] = {896}; cuuint32_t b[2] = {64, 16}; make_map(fn, &tout64, d_out, 2, d, s, b, CU_TENSOR_MAP_SWIZZLE_128B); }
    { cuuint64_t d[2] = {448, 2048}, s[1] = {896}; cuuint32_t b[2] = {48, 16}; make_map(fn, &tout48, d_out, 2, d, s, b, CU_TENSOR_MAP_SWIZZLE_128B); }

    void* scv = nullptr;
    cudaGetSymbolAddress(&scv, g_scratch);
    Scratch* scp = (Scratch*)scv;
    int dev = 0, sms = 0;
    cudaGetDevice(&dev);
    cudaDeviceGetAttribute(&sms, cudaDevAttrMultiProcessorCount, dev);
    if (sms == 132) {
        cudaFuncSetAttribute(fused_kernel<true>, cudaFuncAttributeMaxDynamicSharedMemorySize, SM_TOTAL);
        fused_kernel<true><<<132, 384, SM_TOTAL>>>(scp, wo, w1, b1, w2, b2, tx, twqkv, two64, two48, tw1, tw2, txr64, txr48, tout64, tout48);
    } else {
        cudaFuncSetAttribute(fused_kernel<false>, cudaFuncAttributeMaxDynamicSharedMemorySize, SM_TOTAL);
        fused_kernel<false><<<132, 384, SM_TOTAL>>>(scp, wo, w1, b1, w2, b2, tx, twqkv, two64, two48, tw1, tw2, txr64, txr48, tout64, tout48);
    }
}
```

```cpp
#include <cuda_runtime.h>
#include <cuda_bf16.h>
#include <cuda.h>
#include <stdint.h>

namespace {

constexpr int D_ = 448;
constexpr float LN_EPS = 1e-5f;
constexpr float LOG2E_SCALE = 0.1889822365046136f * 1.4426950408889634f;

struct Tiles {
    uint32_t o[32 * 57344 / 4];
    uint32_t hn[4 * 32 * 14336 / 4];
    uint32_t u[4 * 28 * 14336 / 4];
};
struct Scratch {
    uint4 halo[128 * 2 * 2 * 3 * 32];
    uint4 stats[32 * 4 * 64];
    uint4 hint_k[128 * 2];
    uint4 hint_o[32 * 32 * 2];
    uint4 hint_h[4 * 32 * 2];
    uint4 hint_u[128 * 2];
    uint4 go[24];
    uint32_t epoch[160];
    uint32_t clean;
    alignas(1024) Tiles tiles[2];
};
__device__ Scratch g_scratch;
#define STAMP(i) do {} while (0)
#define FST(i) do {} while (0)
#define TSARG
#define TSVAL

constexpr uint32_t SB = 1024;
constexpr int SM_SLOT = 16384;
__device__ __forceinline__ constexpr uint32_t slot_x(int kb) { return (kb ? 6 + kb : 0) * SM_SLOT; }
__device__ __forceinline__ constexpr uint32_t slot_kv(int kb) { return (kb < 5 ? 2 + kb : 6 - kb) * SM_SLOT; }
__device__ __forceinline__ constexpr uint32_t slot_wo(int kb) { return (kb < 6 ? 2 + kb : 12) * SM_SLOT; }
constexpr int SM_QO = 8 * SM_SLOT;
constexpr int SM_HALOK = SM_QO + 57344, SM_HALOV = 1 * SM_SLOT;
constexpr int NA_SLOTS = 6, NB_SLOTS = 8;
constexpr int SM_ARING = 0;
constexpr int SM_BRING = NA_SLOTS * 16384;
constexpr int SM_H = 212992;
__device__ __forceinline__ uint32_t halo_kin(int par, int lane) { return SB + SM_H + 8192 + par * 4096 + lane * 128 + ((~lane & 6) << 4); }
constexpr int SM_BAR = 229376;
constexpr int SM_TAG = SM_BAR + 1536;
constexpr int SM_TIME = SM_TAG + 256;
constexpr int SM_TOTAL = SM_TIME + 256;
constexpr int B_FULLX = 0;
constexpr int B_FULLKV = 7;
constexpr int B_FQ = 14;
constexpr int B_DONE1 = 16;
constexpr int B_DONEX = 23;
constexpr int B_DONEQ = 24;
constexpr int B_DONEO = 25;
constexpr int B_FULLO = 29;
constexpr int B_FULLWO = 33;
constexpr int B_END = 34;
constexpr int B_HALO = 35;
constexpr int B_FULLA = 39;
constexpr int B_FULLB = 55;
constexpr int B_DONE = 87;
constexpr int B_GO = 119;
constexpr int B_CLR = 121;
constexpr int SM_RAW = SM_BAR + 8 * 122;

constexpr long long WD_CLKS = 2000000000ll;

template<int N> struct Int { static constexpr int value = N; };
template<int A, int B, class F> __device__ __forceinline__ void static_for(F&& f) { if constexpr (A < B) { f(Int<A>()); static_for<A + 1, B>(f); } }

__device__ __forceinline__ uint32_t smem_u32(const void* p) { return (uint32_t)__cvta_generic_to_shared(p); }
__device__ __forceinline__ void mbar_init(uint32_t bar, uint32_t cnt) { asm volatile("mbarrier.init.shared::cta.b64 [%0], %1;" :: "r"(bar), "r"(cnt) : "memory"); }
__device__ __forceinline__ void mbar_expect(uint32_t bar, uint32_t bytes) { asm volatile("mbarrier.arrive.expect_tx.shared::cta.b64 _, [%0], %1;" :: "r"(bar), "r"(bytes) : "memory"); }
__device__ __forceinline__ void mbar_arrive(uint32_t bar) { asm volatile("mbarrier.arrive.shared::cta.b64 _, [%0];" :: "r"(bar) : "memory"); }
__device__ __forceinline__ bool mbar_try(uint32_t bar, uint32_t parity) {
    uint32_t ok;
    asm volatile("{\n.reg .pred p;\nmbarrier.try_wait.parity.shared::cta.b64 p, [%1], %2;\nselp.u32 %0, 1, 0, p;\n}" : "=r"(ok) : "r"(bar), "r"(parity) : "memory");
    return ok;
}
__device__ __forceinline__ bool mbar_test(uint32_t bar, uint32_t parity) {
    uint32_t ok;
    asm volatile("{\n.reg .pred p;\nmbarrier.test_wait.parity.shared::cta.b64 p, [%1], %2;\nselp.u32 %0, 1, 0, p;\n}" : "=r"(ok) : "r"(bar), "r"(parity) : "memory");
    return ok;
}
__device__ __forceinline__ void mbar_wait(uint32_t bar, uint32_t parity) {
    asm volatile("{\n.reg .pred p;\n"
                 "WAIT_LOOP:\n"
                 "mbarrier.try_wait.parity.shared::cta.b64 p, [%0], %1;\n"
                 "@!p bra WAIT_LOOP;\n}" :: "r"(bar), "r"(parity) : "memory");
}
__device__ __forceinline__ void mbar_wait_wd(uint32_t bar, uint32_t parity) {
    asm volatile("{\n.reg .pred p, q;\n.reg .u32 s, t;\nmov.u32 s, %%clock;\n"
                 "WAIT_LOOP:\n"
                 "mbarrier.try_wait.parity.shared::cta.b64 p, [%0], %1;\nmov.u32 t, %%clock;\nsub.u32 t, t, s;\nsetp.lt.and.s32 q, t, 0, !p;\n@q trap;\n"
                 "@!p bra WAIT_LOOP;\n}" :: "r"(bar), "r"(parity) : "memory");
}
__device__ __forceinline__ bool elect() { uint32_t p; asm volatile("{\n.reg .pred P;\nelect.sync _|P, 0xffffffff;\nselp.u32 %0, 1, 0, P;\n}" : "=r"(p)); return p; }
__device__ __forceinline__ void tma2d(uint32_t dst, const CUtensorMap* tm, int c0, int c1, uint32_t bar) {
    asm volatile("cp.async.bulk.tensor.2d.shared::cluster.global.mbarrier::complete_tx::bytes [%0], [%1, {%3, %4}], [%2];" :: "r"(dst), "l"(tm), "r"(bar), "r"(c0), "r"(c1) : "memory");
}
__device__ __forceinline__ void tma3d(uint32_t dst, const CUtensorMap* tm, int c0, int c1, int c2, uint32_t bar) {
    asm volatile("cp.async.bulk.tensor.3d.shared::cluster.global.mbarrier::complete_tx::bytes [%0], [%1, {%3, %4, %5}], [%2];" :: "r"(dst), "l"(tm), "r"(bar), "r"(c0), "r"(c1), "r"(c2) : "memory");
}
__device__ __forceinline__ void tma5d(uint32_t dst, const CUtensorMap* tm, int c0, int c3, int c4, uint32_t bar) {
    asm volatile("cp.async.bulk.tensor.5d.shared::cluster.global.mbarrier::complete_tx::bytes [%0], [%1, {%3, 0, 0, %4, %5}], [%2];" :: "r"(dst), "l"(tm), "r"(bar), "r"(c0), "r"(c3), "r"(c4) : "memory");
}
__device__ __forceinline__ void tma5d_prefetch(const CUtensorMap* tm, int c0, int c3, int c4) {
    asm volatile("cp.async.bulk.prefetch.tensor.5d.L2.global [%0, {%1, 0, 0, %2, %3}];" :: "l"(tm), "r"(c0), "r"(c3), "r"(c4) : "memory");
}
__device__ __forceinline__ void tma2d_store(const CUtensorMap* tm, int c0, int c1, uint32_t src) {
    asm volatile("cp.async.bulk.tensor.2d.global.shared::cta.bulk_group [%0, {%2, %3}], [%1];" :: "l"(tm), "r"(src), "r"(c0), "r"(c1) : "memory");
}
__device__ __forceinline__ void bulk_st(void* dst, uint32_t src, uint32_t bytes) {
    asm volatile("cp.async.bulk.global.shared::cta.bulk_group [%0], [%1], %2;" :: "l"(dst), "r"(src), "r"(bytes) : "memory");
}
__device__ __forceinline__ void bulk_ld(uint32_t dst, const void* src, uint32_t bytes, uint32_t bar) {
    asm volatile("cp.async.bulk.shared::cluster.global.mbarrier::complete_tx::bytes [%0], [%1], %2, [%3];" :: "r"(dst), "l"(src), "r"(bytes), "r"(bar) : "memory");
}
__device__ __forceinline__ void bulk_prefetch(const void* src, uint32_t bytes) { asm volatile("cp.async.bulk.prefetch.L2.global [%0], %1;" :: "l"(src), "r"(bytes) : "memory"); }
__device__ __forceinline__ void prefetch_map(const CUtensorMap* tm) { asm volatile("prefetch.tensormap [%0];" :: "l"(tm) : "memory"); }
__device__ __forceinline__ void st_global_if(uint32_t c, uint32_t* p, uint32_t v) {
    asm volatile("{\n.reg .pred p;\nsetp.ne.u32 p, %2, 0;\n@p st.global.u32 [%0], %1;\n}" :: "l"(p), "r"(v), "r"(c) : "memory");
}
__device__ __forceinline__ void st_relaxed4_if(bool c, uint4* p, uint32_t a, uint32_t b, uint32_t d) {
    asm volatile("{\n.reg .b128 t;\n.reg .b64 a, b;\n.reg .pred p;\nsetp.ne.u32 p, %4, 0;\nmov.b64 a, {%1, %2};\nmov.b64 b, {%3, %3};\nmov.b128 t, {a, b};\n@p st.relaxed.gpu.global.b128 [%0], t;\n}" :: "l"(p), "r"(a), "r"(b), "r"(d), "r"((uint32_t)c) : "memory");
}
__device__ __forceinline__ void pin_ptr(uint32_t never, const void* a) {
    asm volatile("{\n.reg .pred p;\nsetp.ne.u32 p, %1, 0;\n@p st.shared.u64 [%1], %0;\n}" :: "l"(a), "r"(never) : "memory");
}
__device__ __forceinline__ void pin4(uint32_t never, float a, float b, float c, float d) {
    asm volatile("{\n.reg .pred p;\nsetp.ne.u32 p, %4, 0;\n@p st.shared.v4.f32 [%4], {%0,%1,%2,%3};\n}" :: "f"(a), "f"(b), "f"(c), "f"(d), "r"(never) : "memory");
}
__device__ __forceinline__ void fence_async_smem() { asm volatile("fence.proxy.async.shared::cta;" ::: "memory"); }
__device__ __forceinline__ uint32_t ld_acquire(const void* p) { uint32_t v; asm volatile("ld.acquire.gpu.global.u32 %0, [%1];" : "=r"(v) : "l"(p) : "memory"); return v; }
__device__ __forceinline__ void st_release(void* p, uint32_t v) { asm volatile("st.release.gpu.global.u32 [%0], %1;" :: "l"(p), "r"(v) : "memory"); }
__device__ __forceinline__ uint32_t ld_relaxed(const void* p) { uint32_t v; asm volatile("ld.relaxed.gpu.global.u32 %0, [%1];" : "=r"(v) : "l"(p) : "memory"); return v; }
__device__ __forceinline__ uint2 ld_relaxed2(const void* p) {
    uint2 v; asm volatile("{\n.reg .b64 a;\nld.relaxed.gpu.global.b64 a, [%2];\nmov.b64 {%0, %1}, a;\n}" : "=r"(v.x), "=r"(v.y) : "l"(p) : "memory"); return v;
}
__device__ __forceinline__ void st_relaxed2(void* p, uint32_t a, uint32_t b) {
    asm volatile("{\n.reg .b64 a;\nmov.b64 a, {%1, %2};\nst.relaxed.gpu.global.b64 [%0], a;\n}" :: "l"(p), "r"(a), "r"(b) : "memory");
}
__device__ __forceinline__ uint4 ld_relaxed4(const uint4* p) {
    uint4 v;
    asm volatile("{\n.reg .b128 t;\n.reg .b64 a, b;\nld.relaxed.gpu.global.b128 t, [%4];\nmov.b128 {a, b}, t;\nmov.b64 {%0, %1}, a;\nmov.b64 {%2, %3}, b;\n}" : "=r"(v.x), "=r"(v.y), "=r"(v.z), "=r"(v.w) : "l"(p) : "memory");
    return v;
}
__device__ __forceinline__ void st_relaxed4(uint4* p, uint32_t a, uint32_t b, uint32_t c, uint32_t d) {
    asm volatile("{\n.reg .b128 t;\n.reg .b64 a, b;\nmov.b64 a, {%1, %2};\nmov.b64 b, {%3, %4};\nmov.b128 t, {a, b};\nst.relaxed.gpu.global.b128 [%0], t;\n}" :: "l"(p), "r"(a), "r"(b), "r"(c), "r"(d) : "memory");
}
__device__ __forceinline__ uint32_t ld_u16(const unsigned short* p) { uint32_t v; asm volatile("ld.volatile.global.u16 %0, [%1];" : "=r"(v) : "l"(p) : "memory"); return v; }
__device__ __forceinline__ uint32_t ld_volatile(const uint32_t* p) { uint32_t v; asm volatile("ld.volatile.global.u32 %0, [%1];" : "=r"(v) : "l"(p) : "memory"); return v; }
__device__ __forceinline__ void named_arrive(int id, int n) { asm volatile("bar.arrive %0, %1;" :: "r"(id), "r"(n) : "memory"); }
__device__ __forceinline__ void named_sync(int id, int n) { asm volatile("bar.sync %0, %1;" :: "r"(id), "r"(n) : "memory"); }
__device__ __forceinline__ void named_arrive_if(uint32_t c, int id, int n) { asm volatile("{\n.reg .pred p;\nsetp.ne.u32 p, %2, 0;\n@p bar.arrive %0, %1;\n}" :: "r"(id), "r"(n), "r"(c) : "memory"); }
__device__ __forceinline__ void wg_fence() { asm volatile("wgmma.fence.sync.aligned;" ::: "memory"); }
__device__ __forceinline__ void wg_commit() { asm volatile("wgmma.commit_group.sync.aligned;" ::: "memory"); }
template<int N> __device__ __forceinline__ void wg_wait() { asm volatile("wgmma.wait_group.sync.aligned %0;" :: "n"(N) : "memory"); }
template<int N> __device__ __forceinline__ void reg_fence(float (&d)[N]) {
    #pragma unroll
    for (int i = 0; i < N; i++) asm volatile("" : "+f"(d[i]) :: "memory");
}
__device__ __forceinline__ constexpr uint64_t mkdesc(uint32_t addr, uint32_t lbo, uint32_t sbo, uint32_t sw) {
    return (uint64_t)((addr & 0x3FFFF) >> 4) | ((uint64_t)(lbo >> 4) << 16) | ((uint64_t)(sbo >> 4) << 32) | ((uint64_t)sw << 62);
}
__device__ __forceinline__ void ldsm4(uint32_t (&r)[4], uint32_t addr) {
    asm volatile("ldmatrix.sync.aligned.m8n8.x4.shared.b16 {%0,%1,%2,%3}, [%4];" : "=r"(r[0]), "=r"(r[1]), "=r"(r[2]), "=r"(r[3]) : "r"(addr) : "memory");
}
__device__ __forceinline__ void stsm4_if(uint32_t c, uint32_t addr, uint32_t r0, uint32_t r1, uint32_t r2, uint32_t r3) {
    asm volatile("{\n.reg .pred p;\nsetp.ne.u32 p, %5, 0;\n@p stmatrix.sync.aligned.m8n8.x4.shared.b16 [%0], {%1,%2,%3,%4};\n}" :: "r"(addr), "r"(r0), "r"(r1), "r"(r2), "r"(r3), "r"(c) : "memory");
}
__device__ __forceinline__ void sts4(uint32_t a, uint32_t x, uint32_t y, uint32_t z, uint32_t w) { asm volatile("st.shared.v4.u32 [%0], {%1,%2,%3,%4};" :: "r"(a), "r"(x), "r"(y), "r"(z), "r"(w) : "memory"); }
__device__ __forceinline__ uint4 lds4(uint32_t a) { uint4 v; asm volatile("ld.shared.v4.u32 {%0,%1,%2,%3}, [%4];" : "=r"(v.x), "=r"(v.y), "=r"(v.z), "=r"(v.w) : "r"(a) : "memory"); return v; }
__device__ __forceinline__ uint32_t movtrans(uint32_t a) { uint32_t d; asm volatile("movmatrix.sync.aligned.m8n8.trans.b16 %0, %1;" : "=r"(d) : "r"(a)); return d; }
__device__ __forceinline__ uint32_t pack_bf16(float lo, float hi) { uint32_t r; asm("cvt.rn.bf16x2.f32 %0, %1, %2;" : "=r"(r) : "f"(hi), "f"(lo)); return r; }
__device__ __forceinline__ void sub_bf16x2(uint32_t& a, uint32_t b) { asm volatile("sub.rn.bf16x2 %0, %0, %1;" : "+r"(a) : "r"(b)); }
__device__ __forceinline__ float bf_lo(uint32_t v) { return __uint_as_float(v << 16); }
__device__ __forceinline__ float bf_hi(uint32_t v) { return __uint_as_float(v & 0xffff0000u); }
__device__ __forceinline__ void mma16816(float (&c)[4], uint32_t a0, uint32_t a1, uint32_t a2, uint32_t a3, uint32_t b0, uint32_t b1) {
    asm volatile("mma.sync.aligned.m16n8k16.row.col.f32.bf16.bf16.f32 {%0,%1,%2,%3}, {%4,%5,%6,%7}, {%8,%9}, {%0,%1,%2,%3};"
        : "+f"(c[0]), "+f"(c[1]), "+f"(c[2]), "+f"(c[3]) : "r"(a0), "r"(a1), "r"(a2), "r"(a3), "r"(b0), "r"(b1));
}
__device__ __forceinline__ void mma1688(float (&c)[4], uint32_t a0, uint32_t a1, uint32_t b0) {
    asm volatile("mma.sync.aligned.m16n8k8.row.col.f32.bf16.bf16.f32 {%0,%1,%2,%3}, {%4,%5}, {%6}, {%0,%1,%2,%3};"
        : "+f"(c[0]), "+f"(c[1]), "+f"(c[2]), "+f"(c[3]) : "r"(a0), "r"(a1), "r"(b0));
}
__device__ __forceinline__ float quad_sum(float v) { v += __shfl_xor_sync(0xffffffffu, v, 1); v += __shfl_xor_sync(0xffffffffu, v, 2); return v; }
__device__ __forceinline__ float quad_max(float v) { v = fmaxf(v, __shfl_xor_sync(0xffffffffu, v, 1)); v = fmaxf(v, __shfl_xor_sync(0xffffffffu, v, 2)); return v; }
__device__ __forceinline__ float ex2(float x) { float y; asm("ex2.approx.ftz.f32 %0, %1;" : "=f"(y) : "f"(x)); return y; }
__device__ __forceinline__ float rsqrt_approx(float x) { float y; asm("rsqrt.approx.ftz.f32 %0, %1;" : "=f"(y) : "f"(x)); return y; }
__device__ __forceinline__ float rcp_approx(float x) { float y; asm("rcp.approx.ftz.f32 %0, %1;" : "=f"(y) : "f"(x)); return y; }
constexpr float GELU_K1 = 2.f * 0.7978845608028654f;
__device__ __forceinline__ float gelu_half(float hx, float k1) {
    const float z = hx * fmaf(hx * hx, 8.f * 0.044715f * 0.7978845608028654f, k1);
    float t; asm("tanh.approx.f32 %0, %1;" : "=f"(t) : "f"(z));
    return fmaf(hx, t, hx);
}
__device__ __forceinline__ uint32_t gtime32() { uint32_t t; asm volatile("mov.u32 %0, %%globaltimer_lo;" : "=r"(t)); return t; }
__device__ __forceinline__ uint32_t clock32() { uint32_t t; asm volatile("mov.u32 %0, %%clock;" : "=r"(t)); return t; }
#define PF_PACE 160
#define PF_AT 13000
#define PF_N 256
#define NSQ 6
#define NPIPE 1
#define HALO_AT 3
#define HINT_U 18
#define HINT_E 16
#define SP_AT 2000
#define A_SCHED 0x322188
#define WO_ORD0 0x4321065
#define WO_ORD1 0x3465210
#define CL_AT 23
#define WARM_AT 300
#define A_HOLD 31
#define GO_H 1408
#define GO_E 1830
#define GO_U 2200
#define GO_O 1280
#define LATE_O 256
#define DRY2 1
#define LATE_AT 1
#define LATE_AT4 0
#define HINT_H 1
#define SLACK 0
#define SLACK_U 128
#define GDEP 4
#define START4 30
#define EMAP 1
#define DEPTH_N 1
#define DEPTH_E 2
#define PFE_AT 99
#define PFN_END 0
#define NE_SLOTS 11
#define POLL_E 26
#define POLL_U 22
#define CH_U 28
#define AE_END 18
#define AE_W2 27
#define PF1_AT 6000
#define PF1_N 80
#define PF1_PACE 160
#define HOLD 0
#define X0 1
#define GO_E2 300
#define GO_U2 400
#define POLL_I 20
#define POLL_N 19
#define LATES 0x11111111u
#define GATE_J 22
#define GATE_D 16
#define ROLES 0x65432107u
#define LATE_E 1
#define LATE_N 1
#define CL_I0 0
#define CL_SP 1000
#define POLL0 250
template<int TB> __device__ __forceinline__ void wgmma_rs56(float (&d)[28], const uint32_t (&a)[4], uint64_t db, int sc) {
    asm volatile("{\n.reg .pred p;\nsetp.ne.b32 p, %33, 0;\n"
        "wgmma.mma_async.sync.aligned.m64n56k16.f32.bf16.bf16 {%0, %1, %2, %3, %4, %5, %6, %7, %8, %9, %10, %11, %12, %13, %14, %15, %16, %17, %18, %19, %20, %21, %22, %23, %24, %25, %26, %27}, {%28, %29, %30, %31}, %32, p, 1, 1, %34;\n}\n"
        : "+f"(d[0]), "+f"(d[1]), "+f"(d[2]), "+f"(d[3]), "+f"(d[4]), "+f"(d[5]), "+f"(d[6]), "+f"(d[7]), "+f"(d[8]), "+f"(d[9]), "+f"(d[10]), "+f"(d[11]), "+f"(d[12]), "+f"(d[13]), "+f"(d[14]), "+f"(d[15]), "+f"(d[16]), "+f"(d[17]), "+f"(d[18]), "+f"(d[19]), "+f"(d[20]), "+f"(d[21]), "+f"(d[22]), "+f"(d[23]), "+f"(d[24]), "+f"(d[25]), "+f"(d[26]), "+f"(d[27])
        : "r"(a[0]), "r"(a[1]), "r"(a[2]), "r"(a[3]), "l"(db), "r"(sc), "n"(TB));
}

template<int TA, int TB, int SC = 1> __device__ __forceinline__ void wgmma_ss112(float (&d)[56], uint64_t da, uint64_t db) {
    asm volatile("wgmma.mma_async.sync.aligned.m64n112k16.f32.bf16.bf16 {%0, %1, %2, %3, %4, %5, %6, %7, %8, %9, %10, %11, %12, %13, %14, %15, %16, %17, %18, %19, %20, %21, %22, %23, %24, %25, %26, %27, %28, %29, %30, %31, %32, %33, %34, %35, %36, %37, %38, %39, %40, %41, %42, %43, %44, %45, %46, %47, %48, %49, %50, %51, %52, %53, %54, %55}, %56, %57, %60, 1, 1, %58, %59;\n"
        : "+f"(d[0]), "+f"(d[1]), "+f"(d[2]), "+f"(d[3]), "+f"(d[4]), "+f"(d[5]), "+f"(d[6]), "+f"(d[7]), "+f"(d[8]), "+f"(d[9]), "+f"(d[10]), "+f"(d[11]), "+f"(d[12]), "+f"(d[13]), "+f"(d[14]), "+f"(d[15]), "+f"(d[16]), "+f"(d[17]), "+f"(d[18]), "+f"(d[19]), "+f"(d[20]), "+f"(d[21]), "+f"(d[22]), "+f"(d[23]), "+f"(d[24]), "+f"(d[25]), "+f"(d[26]), "+f"(d[27]), "+f"(d[28]), "+f"(d[29]), "+f"(d[30]), "+f"(d[31]), "+f"(d[32]), "+f"(d[33]), "+f"(d[34]), "+f"(d[35]), "+f"(d[36]), "+f"(d[37]), "+f"(d[38]), "+f"(d[39]), "+f"(d[40]), "+f"(d[41]), "+f"(d[42]), "+f"(d[43]), "+f"(d[44]), "+f"(d[45]), "+f"(d[46]), "+f"(d[47]), "+f"(d[48]), "+f"(d[49]), "+f"(d[50]), "+f"(d[51]), "+f"(d[52]), "+f"(d[53]), "+f"(d[54]), "+f"(d[55])
        : "l"(da), "l"(db), "n"(TA), "n"(TB), "n"(SC));
}

template<int TA, int TB, int SC = 1> __device__ __forceinline__ void wgmma_ss80(float (&d)[40], uint64_t da, uint64_t db) {
    asm volatile("wgmma.mma_async.sync.aligned.m64n80k16.f32.bf16.bf16 {%0, %1, %2, %3, %4, %5, %6, %7, %8, %9, %10, %11, %12, %13, %14, %15, %16, %17, %18, %19, %20, %21, %22, %23, %24, %25, %26, %27, %28, %29, %30, %31, %32, %33, %34, %35, %36, %37, %38, %39}, %40, %41, %44, 1, 1, %42, %43;\n"
        : "+f"(d[0]), "+f"(d[1]), "+f"(d[2]), "+f"(d[3]), "+f"(d[4]), "+f"(d[5]), "+f"(d[6]), "+f"(d[7]), "+f"(d[8]), "+f"(d[9]), "+f"(d[10]), "+f"(d[11]), "+f"(d[12]), "+f"(d[13]), "+f"(d[14]), "+f"(d[15]), "+f"(d[16]), "+f"(d[17]), "+f"(d[18]), "+f"(d[19]), "+f"(d[20]), "+f"(d[21]), "+f"(d[22]), "+f"(d[23]), "+f"(d[24]), "+f"(d[25]), "+f"(d[26]), "+f"(d[27]), "+f"(d[28]), "+f"(d[29]), "+f"(d[30]), "+f"(d[31]), "+f"(d[32]), "+f"(d[33]), "+f"(d[34]), "+f"(d[35]), "+f"(d[36]), "+f"(d[37]), "+f"(d[38]), "+f"(d[39])
        : "l"(da), "l"(db), "n"(TA), "n"(TB), "n"(SC));
}

template<int TA, int TB, int SC = 1> __device__ __forceinline__ void wgmma_ss64(float (&d)[32], uint64_t da, uint64_t db) {
    asm volatile("wgmma.mma_async.sync.aligned.m64n64k16.f32.bf16.bf16 {%0, %1, %2, %3, %4, %5, %6, %7, %8, %9, %10, %11, %12, %13, %14, %15, %16, %17, %18, %19, %20, %21, %22, %23, %24, %25, %26, %27, %28, %29, %30, %31}, %32, %33, %36, 1, 1, %34, %35;\n"
        : "+f"(d[0]), "+f"(d[1]), "+f"(d[2]), "+f"(d[3]), "+f"(d[4]), "+f"(d[5]), "+f"(d[6]), "+f"(d[7]), "+f"(d[8]), "+f"(d[9]), "+f"(d[10]), "+f"(d[11]), "+f"(d[12]), "+f"(d[13]), "+f"(d[14]), "+f"(d[15]), "+f"(d[16]), "+f"(d[17]), "+f"(d[18]), "+f"(d[19]), "+f"(d[20]), "+f"(d[21]), "+f"(d[22]), "+f"(d[23]), "+f"(d[24]), "+f"(d[25]), "+f"(d[26]), "+f"(d[27]), "+f"(d[28]), "+f"(d[29]), "+f"(d[30]), "+f"(d[31])
        : "l"(da), "l"(db), "n"(TA), "n"(TB), "n"(SC));
}

template<int TA, int TB, int SC = 1> __device__ __forceinline__ void wgmma_ss48(float (&d)[24], uint64_t da, uint64_t db) {
    asm volatile("wgmma.mma_async.sync.aligned.m64n48k16.f32.bf16.bf16 {%0, %1, %2, %3, %4, %5, %6, %7, %8, %9, %10, %11, %12, %13, %14, %15, %16, %17, %18, %19, %20, %21, %22, %23}, %24, %25, %28, 1, 1, %26, %27;\n"
        : "+f"(d[0]), "+f"(d[1]), "+f"(d[2]), "+f"(d[3]), "+f"(d[4]), "+f"(d[5]), "+f"(d[6]), "+f"(d[7]), "+f"(d[8]), "+f"(d[9]), "+f"(d[10]), "+f"(d[11]), "+f"(d[12]), "+f"(d[13]), "+f"(d[14]), "+f"(d[15]), "+f"(d[16]), "+f"(d[17]), "+f"(d[18]), "+f"(d[19]), "+f"(d[20]), "+f"(d[21]), "+f"(d[22]), "+f"(d[23])
        : "l"(da), "l"(db), "n"(TA), "n"(TB), "n"(SC));
}

template<int NKB, int NR>
__device__ __forceinline__ void mix_mainloop(TSARG float (&acc)[NR], bool leader) {
    constexpr uint32_t sb = SB, bars = sb + SM_BAR, par = NKB == 28;
    constexpr int A0 = NKB == 32 ? 0 : 16 % NA_SLOTS;
    constexpr int DEPTH = NR == 56 ? DEPTH_N : DEPTH_E;
    int bslot = 0, aslot = A0;
    reg_fence(acc);
    #pragma unroll 1
    for (int i = 0; i < NKB / 2; i++) {
        mbar_wait(bars + 8 * (B_FULLA + i), par);
        const uint64_t adesc = mkdesc(sb + SM_ARING, 8192, 1024, 1) + (uint32_t)(aslot * 1024);
        aslot = aslot == NA_SLOTS - 1 ? 0 : aslot + 1;
        #pragma unroll
        for (int jj = 0; jj < 2; jj++) {
            const int j = 2 * i + jj;
            mbar_wait(bars + 8 * (B_FULLB + j), par);
            const uint64_t bdesc = mkdesc(sb + SM_BRING, 128, 1024, 0) + (uint32_t)(bslot * NR * 16);
            bslot = bslot == (NR == 56 ? NB_SLOTS : NE_SLOTS) - 1 ? 0 : bslot + 1;
            wg_fence();
            #pragma unroll
            for (int s = 0; s < 4; s++) {
                if constexpr (NR == 56) wgmma_ss112<1, 1>(acc, adesc + jj * 512 + s * 128, bdesc + s * 16);
                else wgmma_ss80<1, 1>(acc, adesc + jj * 512 + s * 128, bdesc + s * 16);
            }
            wg_commit();
            wg_wait<DEPTH>();
            if (j >= DEPTH && leader) mbar_arrive(bars + 8 * (B_DONE + j - DEPTH));
        }
    }
    if (DEPTH == 2) { wg_wait<1>(); if (leader) mbar_arrive(bars + 8 * (B_DONE + NKB - 2)); }
    wg_wait<0>();
    reg_fence(acc);
    if (leader) mbar_arrive(bars + 8 * (B_DONE + NKB - 1));
}

constexpr uint32_t EMPTY = 0xFFFFFFFFu;
__device__ __forceinline__ void post_hint(uint4* p, uint32_t ep, int lane) { if (lane < 2) st_relaxed4(p + lane, ep, ep, ep, ep); }
__device__ __forceinline__ void post_time(uint4* p, uint32_t ep, int lane) { const uint32_t now = gtime32(); if (lane < 2) st_relaxed4(p + lane, ep, now, ep, now); }

__device__ __forceinline__ uint32_t last_hint(TSARG const uint4* hint, uint32_t ep, int st) {
    uint2 v;
    do { v = ld_relaxed2(hint); } while (!__all_sync(0xffffffffu, v.x == ep));
    const uint32_t t1 = gtime32() + 256;
    if (elect()) STAMP(st);
    return t1 - __reduce_min_sync(0xffffffffu, t1 - v.y);
}
__device__ __forceinline__ uint32_t later(uint32_t a, uint32_t b) { return a + max((int)(b - a), 0); }
__device__ __forceinline__ void fetch_times(TSARG const uint4* go, int k, uint32_t ep, int lane) {
    const uint2* p = (const uint2*)(go + 8 + 8 * k) + (k ? lane % 10 : lane & 3);
    uint2 v;
    do { v = ld_relaxed2(p); } while (!__all_sync(0xffffffffu, v.x == ep));
    v.y += k ? (lane < 10 ? GO_U : GO_U + GO_U2) : (lane < 4 ? GO_E : GO_E + GO_E2);
    asm volatile("st.shared.u32 [%0], %1;" :: "r"(SB + SM_TIME + 128 * k + 4 * lane), "r"(v.y) : "memory");
    __syncwarp();
    if (lane == 0) { mbar_arrive(SB + SM_BAR + 8 * (B_GO + k)); STAMP(k ? 43 : 24); }
    __syncwarp();
}
__device__ __forceinline__ void wait_until(uint32_t t) { while ((int)(gtime32() - t) < 0) {} __syncwarp(); }

__device__ __forceinline__ uint32_t check_tile(uint32_t raw, uint32_t full, uint32_t dst, uint32_t lofs, const uint32_t* src, uint32_t bytes, int lane) {
    uint32_t cnt;
    asm volatile("{\n.reg .pred p, e;\n.reg .u32 a, b, c, d;\nmov.u32 %0, 0;\n"
                 "AGAIN:\nand.b32 a, %0, 1;\n"
                 "WAIT:\nmbarrier.try_wait.parity.shared::cta.b64 p, [%1], a;\n@!p bra.uni WAIT;\n"
                 "ld.shared.u32 a, [%4];\nld.shared.u32 b, [%4+4096];\nld.shared.u32 c, [%5+-8192];\nld.shared.u32 d, [%5+-4096];\n"
                 "add.u32 %0, %0, 1;\nmax.u32 a, a, b;\nmax.u32 c, c, d;\nmax.u32 a, a, c;\nsetp.lt.u32 e, %8, 32;\nsetp.eq.and.u32 p, a, 0xFFFFFFFF, e;\n"
                 "vote.sync.any.pred p, p, 0xffffffff;\nsetp.eq.and.u32 e, %8, 0, !p;\n@e mbarrier.arrive.shared::cta.b64 _, [%2];\n"
                 "elect.sync _|e, 0xffffffff;\nand.pred e, e, p;\n"
                 "@e mbarrier.arrive.expect_tx.shared::cta.b64 _, [%1], %7;\n"
                 "@e cp.async.bulk.shared::cluster.global.mbarrier::complete_tx::bytes [%3], [%6], %7, [%1];\n"
                 "@p bra.uni AGAIN;\n}"
                 : "=&r"(cnt) : "r"(raw), "r"(full), "r"(dst), "r"(dst + lofs), "r"(dst + lofs + bytes), "l"(src), "r"(bytes), "r"(lane) : "memory");
    return cnt;
}

template<int ST>
__device__ __forceinline__ void check_tiles(int j, int step, int n, const uint32_t* src, bool small, int lane, bool dry) {
    const uint32_t bytes = small ? 10240 : 14336, nb = small ? NE_SLOTS : NB_SLOTS, lofs = lane * 128 + (lane & 3) * 32 + (lane >> 2) * 4;
    uint32_t sl = j % nb;
    #pragma unroll 1
    for (int inc = dry ? 0 : step; j < n; j += inc, inc = step) {
        const uint32_t c = check_tile(inc ? SB + SM_RAW + 8 * (j + (ST ? 32 * ST - 28 : 0)) : SB + SM_BAR + 8 * B_CLR, SB + SM_BAR + 8 * (j + (ST ? B_FULLB : B_FULLO)),
                                      SB + (ST ? SM_BRING : SM_QO) + sl * bytes, lofs, src + j * (ST ? 7168 : 3584), bytes, inc ? lane : 32);
        sl += inc;
        if (sl >= nb) sl -= nb;
    }
}

__device__ __forceinline__ uint32_t hcol(uint32_t a, int jp) { return (a ^ ((jp & 3) << 5)) + (jp >> 2) * 8192; }

__device__ __forceinline__ uint32_t get_tag() {
    mbar_wait(SB + SM_BAR + 8 * B_CLR, 0);
    uint32_t v; asm volatile("ld.shared.u32 %0, [%1];" : "=r"(v) : "r"(SB + SM_TAG) : "memory"); return v;
}

template<bool USE_SMID>
__global__ void __launch_bounds__(384, 1)
fused_kernel(Scratch* __restrict__ sc, const __nv_bfloat16* __restrict__ wo,
             const __nv_bfloat16* __restrict__ w1, const __nv_bfloat16* __restrict__ b1,
             const __nv_bfloat16* __restrict__ w2, const __nv_bfloat16* __restrict__ b2,
             const __grid_constant__ CUtensorMap tm_x, const __grid_constant__ CUtensorMap tm_wqkv,
             const __grid_constant__ CUtensorMap tm_wo64, const __grid_constant__ CUtensorMap tm_wo48,
             const __grid_constant__ CUtensorMap tm_w1, const __grid_constant__ CUtensorMap tm_w2,
             const __grid_constant__ CUtensorMap tm_xr64, const __grid_constant__ CUtensorMap tm_xr48,
             const __grid_constant__ CUtensorMap tm_out64, const __grid_constant__ CUtensorMap tm_out48) {
    extern __shared__ __align__(1024) uint8_t smem_raw[];
    constexpr uint32_t sb = SB;
    constexpr uint32_t bars = sb + SM_BAR;
    const int tid = threadIdx.x, lane = tid & 31;
    auto get_slot = [&]() {
        int slot;
    if (USE_SMID) {
        asm volatile("{\n.reg .u32 s, t, u, d, a, b, c;\n.reg .pred p, r;\n"
            "mov.u32 s, %%smid;\nshr.u32 t, s, 1;\nsub.u32 u, t, 32;\nmul.lo.u32 d, u, 37;\nshr.u32 d, d, 8;\n"
            "and.b32 a, t, 7;\nshl.b32 a, a, 3;\nshr.u32 c, t, 3;\nadd.u32 a, a, c;\n"
            "mad.lo.u32 b, d, -55, 12;\nshl.b32 c, u, 3;\nadd.u32 b, b, c;\n"
            "setp.lt.u32 p, t, 32;\nselp.u32 a, a, b, p;\n"
            "setp.lt.u32 r, t, 62;\nselp.s32 c, 4, -58, r;\nadd.u32 c, t, c;\nsetp.lt.u32 p, t, 60;\nselp.u32 a, a, c, p;\n"
            "and.b32 s, s, 1;\nshl.b32 a, a, 1;\nadd.u32 %0, a, s;\n}" : "=r"(slot));
    } else slot = blockIdx.x;
        return slot;
    };
    auto load_x = [&](int kb, int row) {
        const uint32_t st = sb + slot_x(kb), bar = bars + 8 * (B_FULLX + kb);
        mbar_expect(bar, 16384);
        tma3d(st, &tm_x, kb * 64, 0, row, bar); tma3d(st + 8192, &tm_x, kb * 64, 1, row, bar);
    };
    const int warp = __shfl_sync(0xffffffffu, tid >> 5, 0);
#define ASSIGN_WORK(s) \
    const int slot = (s), G = slot >> 4, mi = slot & 15; \
    const int tb = 4 * (G >> 1) + (mi >> 2), hp = 2 * (mi & 3) + (G & 1), wcol = (hp * 56) & ~15; \
    const int q = mi & 3, tt2 = 4 * G + (mi >> 2), c64 = 64 * q, c48 = 256 + 48 * q; \
    const int R = (ROLES >> (4 * G)) & 7; \
    const bool early = R < 3; \
    const int ech = R < 2 ? q : 4 + (mi & 1), ft = R == 2 ? mi >> 1 : 4 * (R - !early) + (mi >> 2); \
    const int pr3 = early ? ech >= 3 : q >> 1, col3 = early ? (ech - 3 * pr3) * 9 : (q & 1) * 14;

    if (warp < 8) {
        ASSIGN_WORK(get_slot())
        if (slot >= 128) {
            const uint32_t ep = ld_volatile(&sc->epoch[slot]) + 1;
            if (mi == 0 && warp == 1) {
                post_hint(sc->go, 0, lane);
                while (ld_relaxed(sc->hint_k) != ep) __nanosleep(200);
                uint2 v[4];
                do {
                    #pragma unroll
                    for (int i = 0; i < 4; i++) v[i] = ld_relaxed2(sc->hint_h + 64 * i + 2 * lane);
                } while (!__all_sync(0xffffffffu, v[0].x == ep && v[1].x == ep && v[2].x == ep && v[3].x == ep));
                const uint32_t t1 = gtime32() + 256;
                const uint32_t age = min(min(t1 - v[0].y, t1 - v[1].y), min(t1 - v[2].y, t1 - v[3].y)) + (lane < 16 ? 0 : SLACK);
                const uint32_t ts = t1 - __reduce_min_sync(0xffffffffu, age);
                if (lane < 2) st_relaxed4(sc->go + lane, ep, ts, ep, ts);
            }
            if (mi == 0 && warp >= 2) {
                const int k = warp & 1;
                uint2* go = (uint2*)(sc->go + 8 + 8 * k) + lane;
                if (warp < 4 && lane < 16) st_relaxed2(go, 0, 0);
                while (ld_relaxed(sc->go) != ep) __nanosleep(200);
                __nanosleep(warp * 60);
                const uint4* hint = sc->hint_u + (k ? 48 + min(lane, 19) : lane) * 2;
                uint2 v[4];
                do {
                    #pragma unroll
                    for (int i = 0; i < 4; i++) v[i] = ld_relaxed2(hint + (k ? 40 * i : 32 * (i & 1)));
                } while (!__all_sync(0xffffffffu, v[0].x == ep && v[1].x == ep && v[2].x == ep && v[3].x == ep));
                uint32_t t = later(later(v[0].y, v[1].y), later(v[2].y, v[3].y));
                t = later(t, __shfl_xor_sync(0xffffffffu, t, 1));
                if (!k) { t = later(t, __shfl_xor_sync(0xffffffffu, t, 8)); t = later(t, __shfl_xor_sync(0xffffffffu, t, 16)); }
                t = __shfl_sync(0xffffffffu, t, 2 * lane);
                if (lane < 16) st_relaxed2(go, ep, t);
            }
            if (mi == 1 && warp >= 4 && ld_volatile(&sc->clean) != ep) {
                for (int l = (tid - 128) / 2; l < sizeof(Tiles) / 128; l += 64) st_relaxed4((uint4*)&sc->tiles[ep & 1] + l * 8 + (lane & 7), EMPTY, EMPTY, EMPTY, EMPTY);
                named_sync(1, 128);
                if (tid == 128) st_release(&sc->clean, ep);
            }
            if (tid == 0) {
                const long long t0 = clock64();
                while (clock64() - t0 < SP_AT) {}
                #pragma unroll 1
                for (int i = 0; i < 7; i++) bulk_prefetch((const char*)wo + (i * 4 + mi) * 14336, 14336);
                if (mi) {
                    uint32_t t = (uint32_t)t0 + PF1_AT;
                    #pragma unroll 1
                    for (int i = mi - 1; i < PF1_N; i += 3) {
                        while ((int)(clock32() - t) < 0) {}
                        tma5d_prefetch(&tm_w1, (i & 7) * 64, (i + 48) & 56, (i + 48) >> 6);
                        t += PF1_PACE;
                    }
                    t = (uint32_t)t0 + PF_AT;
                    #pragma unroll 1
                    for (int i = mi - 1; i < PF_N; i += 3) {
                        while ((int)(clock32() - t) < 0) {}
                        bulk_prefetch((const char*)w2 + (i < 128 ? i * 16384 : (i - 64 >> 1) * 65536 + (i & 1) * 16384), 16384);
                        t += PF_PACE;
                    }
                }
                while (ld_relaxed(sc->hint_u + 254) != ep) { __nanosleep(500); if (clock64() - t0 > WD_CLKS) __trap(); }
                sc->epoch[slot] = ep;
                if (mi == 1) sc->clean = ep + 1;
            }
            return;
        }
        {
            const int w = warp & 3, wg = warp >> 2, g = lane >> 2, t = lane & 3;
            if (WARM_AT) { const uint32_t t0 = clock32(); while (clock32() - t0 < WARM_AT) {} __syncwarp(); }
            if (w > 0) post_hint(sc->hint_o + ((2 * tb + (w >> 1)) * 32 + hp * 4 + (w & 1) * 2 + wg) * 2, 0, lane);
            if (wg == 0) {
                if (t < 2) st_relaxed4(sc->stats + tt2 * 256 + q * 64 + 16 * w + g + 8 * t, 0, 0, 0, 0);
            }
        }
        named_sync(0, 288);
        asm volatile("setmaxnreg.inc.sync.aligned.u32 224;");
        int tid; asm volatile("mov.u32 %0, %%tid.x;" : "=r"(tid));
        const int lane = tid & 31, warp = __shfl_sync(0xffffffffu, tid >> 5, 0), wg = warp >> 2;
        uint32_t ep;
        Tiles* tl;
        const int w = warp & 3, g = lane >> 2, t = lane & 3;
        const bool leader = (tid & 127) == 0;
        const uint32_t never = gridDim.y - 1;
        {
            uint32_t a[28][4];
            float accK[28], accV[28], accQ[28];
            const int lrow = 16 * w + (lane & 7) + (lane & 8);
            const uint32_t lbase = sb + wg * 8192 + lrow * 128;
            const uint32_t lx = (lane >> 4) ^ (lane & 7);
            const uint32_t wofs = hp & 1;
            auto pin2 = [&](uint32_t x0, uint32_t x1) {
                asm volatile("{\n.reg .pred p;\nsetp.ne.u32 p, %2, 0;\n@p st.shared.v2.b32 [%0], {%0,%1};\n}" :: "r"(x0), "r"(x1), "r"(never) : "memory");
            };
            float cS[2][4] = {}, cA[2][4] = {}, cB[2][4] = {}, q0, q1, p0, p1;
            auto sq = [&](float& acc, uint32_t v) { const float lo = bf_lo(v), hi = bf_hi(v); acc = fmaf(hi, hi, fmaf(lo, lo, acc)); };
            #pragma unroll
            for (int kb = 0; kb < 8; kb++) {
                if (kb < 7) {
                    mbar_wait(bars + 8 * (B_FULLX + kb), 0);
                    if (kb == 0 && tid == 0) STAMP(0);
                    if (kb == 6 && tid == 0) STAMP(25);
                    if (kb == 0) FST(0); if (kb == 2) FST(1); if (kb == 4) FST(2); if (kb == 6) FST(3);
                    #pragma unroll
                    for (int s = 4 * kb; s < 4 * kb + 4; s++) ldsm4(a[s], lbase + slot_x(kb) + ((lx ^ (2 * (s & 3))) << 4));
                }
                if (kb == 5) named_sync(9 + wg, 160);
                if (kb == NPIPE) continue;
                const int kc = kb < NPIPE ? kb : kb - 1;
                if (kc == NSQ) { p0 = cS[0][0] + cS[1][0]; p1 = cS[0][2] + cS[1][2]; }
                #pragma unroll
                for (int s = 4 * kc; s < 4 * kc + 4; s++) {
                    mma16816(cS[s & 1], a[s][0], a[s][1], a[s][2], a[s][3], 0x3F803F80u, 0x3F803F80u);
                    if (kc < NSQ) {
                        mma1688(cA[0], a[s][0], a[s][1], a[s][0]); mma1688(cA[1], a[s][2], a[s][3], a[s][2]);
                        mma1688(cB[0], a[s][0], a[s][1], a[s][1]); mma1688(cB[1], a[s][2], a[s][3], a[s][3]);
                    }
                }
            }
            const float m0 = (cS[0][0] + cS[1][0]) * (1.f / D_), m1 = (cS[0][2] + cS[1][2]) * (1.f / D_);
            const uint32_t mm0 = pack_bf16(m0, m0), mm1 = pack_bf16(m1, m1);
            if (lane == 0) mbar_arrive(bars + 8 * B_DONEX);
            auto center = [&](int s) { sub_bf16x2(a[s][0], mm0); sub_bf16x2(a[s][1], mm1); sub_bf16x2(a[s][2], mm0); sub_bf16x2(a[s][3], mm1); };
            uint32_t Ka[8], Kb[8], Kc[8], Va[8], Vb[7], Vc[8];
            float r0, r1, ls0, ls1;
            uint32_t pm, zero;
            uint32_t* od;
            uint4* oh;
            auto kpack = [&](uint32_t (&k)[8], int j, int c, float r) {
                const uint32_t v = pack_bf16(accK[4 * j + c] * r, accK[4 * j + c + 1] * r);
                if (j == 3) { k[3] = t < 2 ? v : 0u; k[4] = t < 2 ? 0u : v; } else k[j + (j > 3)] = v;
            };
            auto batch = [&](auto c0, auto c1) {
                constexpr int n0 = c0.value, n1 = c1.value;
                wg_fence();
                static_for<n0, n1>([&](auto nc) {
                    constexpr int n = nc.value;
                    if (n == 4) { center(4); center(5); center(6); center(7); wg_fence(); }
                    const uint64_t desc = mkdesc(sb + (n < 56 ? slot_kv(n >> 3) + (n & 7) * 2048 : SM_QO + (n - 56) * 2048), 8192, 1024, 1) + wofs;
                    wgmma_rs56<1>(n < 28 ? accK : n < 56 ? accV : accQ, a[n % 28], desc, n % 28 != 0);
                });
                wg_commit();
                if (n0 > 0) wg_wait<1>();
            };
            const uint32_t hs = sb + tid * 16 + warp * 512;
            auto hand_over = [&](const uint32_t (&v)[8], int kv) {
                mbar_wait(bars + 8 * (kv ? B_DONE1 + 5 : B_DONEX), 0);
                sts4(hs + (kv ? SM_HALOV : SM_HALOK), v[0], v[1], v[2], v[3]); sts4(hs + (kv ? SM_HALOV : SM_HALOK) + 512, v[4], v[5], v[6], v[7]);
                if (w == 3) named_arrive(6 + kv, 96);
            };
            auto take_over = [&](uint32_t (&v)[8], int kv) {
                if (w == 0) mbar_wait(bars + 8 * (B_HALO + 2 * kv + wg), 0);
                const uint32_t ad = w ? hs + (kv ? SM_HALOV : SM_HALOK) - 1024 : kv ? sb + lane * 16 + wg * 1024 + SM_HALOV + 8192 : halo_kin(wg, lane);
                const uint4 u0 = lds4(ad), u1 = lds4(ad + (w || kv ? 512 : 16));
                v[0] = u0.x; v[1] = u0.y; v[2] = u0.z; v[3] = u0.w; v[4] = u1.x; v[5] = u1.y; v[6] = u1.z; v[7] = u1.w;
            };
            center(0); center(1); center(2); center(3);
            static_for<0, 7>([&](auto pc) {
                constexpr int p = pc.value;
                mbar_wait(bars + 8 * (B_FULLKV + p), 0);
                if (p == 0 && tid == 0) STAMP(26);
                if (p == 3 && tid == 0) STAMP(27);
                FST(4 + p);
                batch(Int<8 * p>(), Int<8 * p + 8>());
                if (p > 0 && leader) mbar_arrive(bars + 8 * (B_DONE1 + p - 1));
                #pragma unroll
                for (int s = 8 * p + 8; s < 8 * p + 16 && s < 28; s++) center(s);
                if (p == 1) {
                    const float c0 = bf_hi(mm0), c1 = bf_hi(mm1);
                    q0 = fmaf(c0, fmaf(c0, 64.f * NSQ, -2.f * p0), (g & 1) ? cA[0][1] + cA[1][1] : cA[0][0] + cA[1][0]) - D_ * (m0 - c0) * (m0 - c0);
                    q1 = fmaf(c1, fmaf(c1, 64.f * NSQ, -2.f * p1), (g & 1) ? cB[0][3] + cB[1][3] : cB[0][2] + cB[1][2]) - D_ * (m1 - c1) * (m1 - c1);
                    asm("" : "+f"(q0), "+f"(q1));
                    q0 = t == (g >> 1) ? q0 : 0.f; q1 = t == (g >> 1) ? q1 : 0.f;
                    pin2(__float_as_uint(q0), __float_as_uint(q1));
                }
                constexpr int PK = NSQ < 5 ? 5 : 4, NR = 28 - 4 * NSQ;
                if (p >= 2 && p < PK) {
                    #pragma unroll
                    for (int s = 4 * NSQ + NR * (p - 2) / (PK - 2); s < 4 * NSQ + NR * (p - 1) / (PK - 2); s++) { sq(q0, a[s][0]); sq(q1, a[s][1]); sq(q0, a[s][2]); sq(q1, a[s][3]); }
                    pin2(__float_as_uint(q0), __float_as_uint(q1));
                }
                if (p == PK - 1) { q0 = quad_sum(q0); q1 = quad_sum(q1); }
                if (p == PK) {
                    r0 = rsqrt_approx(fmaxf(q0 * (1.f / D_), 0.f) + LN_EPS); r1 = rsqrt_approx(fmaxf(q1 * (1.f / D_), 0.f) + LN_EPS);
                    reg_fence(accK);
                    #pragma unroll
                    for (int j = 0; j < 7; j++) kpack(Kc, j, 2, r1);
                    hand_over(Kc, 0);
                }
                if (p == PK + 1) {
                    #pragma unroll
                    for (int j = 0; j < 7; j++) kpack(Kb, j, 0, r0);
                    #pragma unroll
                    for (int j = 0; j < 8; j += 2) pin2(Kb[j], Kb[j + 1]);
                    ls0 = LOG2E_SCALE * r0; ls1 = LOG2E_SCALE * r1;
                    pm = (2 * t <= g ? 0xFFFFu : 0u) | (2 * t + 1 <= g ? 0xFFFF0000u : 0u);
                    zero = never; asm volatile("" : "+r"(zero));
                    pin2(__float_as_uint(ls0), __float_as_uint(ls1)); pin2(pm, zero);
                }
                if (p == 2) ep = get_tag();
                if (p == 6) {
                    tl = &sc->tiles[ep & 1];
                    const int tt = 2 * tb + (w >> 1);
                    od = tl->o + tt * 14336 + (7 * hp) * 256 + (2 * (2 * (w & 1) + wg)) * 32 + lane;
                    oh = sc->hint_o + (tt * 32 + hp * 4 + (w & 1) * 2 + wg) * 2 + (lane & 1);
                    pin2((uint32_t)(uint64_t)od, (uint32_t)((uint64_t)od >> 32));
                    pin2((uint32_t)(uint64_t)oh, (uint32_t)((uint64_t)oh >> 32));
                }
            });
            if (tid == 0) STAMP(1);
            FST(11);
            mbar_wait(bars + 8 * B_FQ, 0);
            batch(Int<56>(), Int<60>());
            reg_fence(accV);
            if (leader) mbar_arrive(bars + 8 * (B_DONE1 + 6));
            if (tid == 0) STAMP(2);
            FST(12);
            #pragma unroll
            for (int j = 0; j < 7; j++) Vc[j] = movtrans(pack_bf16(accV[4 * j + 2] * r1, accV[4 * j + 3] * r1));
            Vc[7] = Vc[6];
            hand_over(Vc, 1);
            batch(Int<60>(), Int<66>());
            #pragma unroll
            for (int j = 0; j < 7; j++) {
                Vb[j] = movtrans(pack_bf16(accV[4 * j] * r0, accV[4 * j + 1] * r0));
                Vc[j] |= zero;
            }
            batch(Int<66>(), Int<72>());
            #pragma unroll
            for (int j = 0; j < 7; j++) pin2(Vb[j], Vc[j]);
            mbar_wait(bars + 8 * (B_FQ + 1), 0);
            FST(13);
            if (w > 0 && lane < 2) { const uint32_t now = gtime32(); st_relaxed4(oh, ep, now, ep, now); }
            batch(Int<72>(), Int<84>());
            FST(14);
            named_sync(1 + wg, 128);
            take_over(Ka, 0);
            if (tid == 0) STAMP(3);
            wg_wait<0>();
            reg_fence(accQ);
            if (tid == 0) STAMP(4);
            FST(15);
            const bool first = (tb == 0 && w == 0);
            uint32_t pA[2], pB0[2], pB1[2], pC[2], z0[2], z1[2];
            #pragma unroll
            for (int h = 0; h < 2; h++) {
                float sA[4] = {0.f, 0.f, 0.f, 0.f}, sB[4] = {0.f, 0.f, 0.f, 0.f}, sC[4] = {0.f, 0.f, 0.f, 0.f};
                #pragma unroll
                for (int k = 0; k < 2; k++) {
                    const float* qq = accQ + 12 * h + 8 * k;
                    uint32_t a0 = pack_bf16(qq[0], qq[1]), a1 = pack_bf16(qq[2], qq[3]);
                    if (h == 1 && k == 0) { a0 |= zero; a1 |= zero; }
                    const uint32_t a2 = pack_bf16(qq[4], qq[5]), a3 = pack_bf16(qq[6], qq[7]);
                    mma16816(sB, a0, a1, a2, a3, Kb[4 * h + 2 * k], Kb[4 * h + 2 * k + 1]);
                    mma16816(sA, a0, a1, a2, a3, Ka[4 * h + 2 * k], Ka[4 * h + 2 * k + 1]);
                    mma16816(sC, a0, a1, a2, a3, Kc[4 * h + 2 * k], Kc[4 * h + 2 * k + 1]);
                }
                const bool n0 = pm & 1, n1 = (int)pm < 0;
                const float l00 = n0 ? sB[0] : (first ? -INFINITY : sA[0]), l01 = n1 ? sB[1] : (first ? -INFINITY : sA[1]);
                const float l10 = n0 ? sC[2] : sB[2], l11 = n1 ? sC[3] : sB[3];
                const float x0 = -ls0 * quad_max(fmaxf(l00, l01)), x1 = -ls1 * quad_max(fmaxf(l10, l11));
                const float e00 = ex2(fmaf(l00, ls0, x0)), e01 = ex2(fmaf(l01, ls0, x0)), e10 = ex2(fmaf(l10, ls1, x1)), e11 = ex2(fmaf(l11, ls1, x1));
                const float i0 = rcp_approx(quad_sum(e00 + e01)), i1 = rcp_approx(quad_sum(e10 + e11));
                const uint32_t P0 = pack_bf16(e00 * i0, e01 * i0), P1 = pack_bf16(e10 * i1, e11 * i1);
                pB0[h] = P0 & pm; pA[h] = P0 & ~pm; pC[h] = P1 & pm; pB1[h] = P1 & ~pm; z0[h] = P0 & zero; z1[h] = P1 & zero;
            }
            float o[8][4];
            #pragma unroll
            for (int j = 0; j < 8; j++) {
                o[j][0] = o[j][1] = o[j][2] = o[j][3] = 0.f;
                mma16816(o[j], pB0[j >> 2], pB1[j >> 2], z0[j >> 2], pC[j >> 2], Vb[j - (j >> 2)], Vc[j - (j >> 2)]);
            }
            if (tid == 0) STAMP(12);
            FST(16);
            take_over(Va, 1);
            if (lane == 0) mbar_arrive(bars + 8 * B_DONEQ);
            if (tid == 0) STAMP(16);
            #pragma unroll
            for (int j = 0; j < 8; j++) mma1688(o[j], pA[j >> 2], z1[j >> 2], Va[j - (j >> 2)]);
            #pragma unroll
            for (int j = 0; j < 7; j++) {
                float v[4];
                #pragma unroll
                for (int c = 0; c < 4; c++) v[c] = j < 3 ? o[j][c] : j > 3 ? o[j + 1][c] : (t < 2 ? o[3][c] : o[4][c]);
                od[j * 256] = pack_bf16(v[0], v[1]);
                od[j * 256 + 32] = pack_bf16(v[2], v[3]);
            }
            if (tid == 0) STAMP(5);
            FST(17);
        }
        const int z = get_tag() - ep, slot1 = slot + z, tid1 = tid + z, warp1 = warp + z;
        ep += z;
        {
        ASSIGN_WORK(slot1)
        const int tid = tid1, lane = tid & 31, wg = warp1 >> 2, w = warp1 & 3, g = lane >> 2, t = lane & 3;
        tl = &sc->tiles[ep & 1];
        const uint32_t live = wg ^ 1;
        uint32_t rb0, rb1, late[14];
        const unsigned short* pb = (const unsigned short*)(live ? b2 + tt2 * 64 : b1 + ft * 64) + 16 * w + g;
        auto stage_late = [&]() {
            #pragma unroll
            for (int c = 0; c < 14; c++) asm volatile("st.shared.u32 [%0], %1;" :: "r"(sb + SM_H + wg * 8192 + (tid & 127) * 4 + c * 512), "r"(late[c]) : "memory");
            fence_async_smem();
            named_sync(1 + wg, 128);
        };
        auto store_late = [&](bool on, uint32_t* p) {
            #pragma unroll
            for (int c = 0; c < 4; c++)
                if (elect() && on && (c < 3 || w < 2)) bulk_st(p + (4 * c + w) * 256, sb + SM_H + wg * 8192 + (4 * c + w) * 512, 512);
            asm volatile("cp.async.bulk.commit_group;" ::: "memory");
        };
        auto undef = [](float (&v)[56]) {
            #pragma unroll
            for (int i = 0; i < 56; i++) asm volatile("" : "=f"(v[i]));
        };
        {
            float acc[56];
            const int hrow = 32 * (w >> 1) + 2 * ((lane & 7) + (lane & 8)) + (w & 1);
            const uint32_t ha = sb + SM_H + hrow * 128 + (((lane >> 4) ^ (hrow & 7)) << 4);
            uint4* sp = sc->stats + tt2 * 256 + 16 * w + g + 8 * (t & 1);
            uint4* sp_out = sp + q * 64;
            const uint4* sp_in = sp + (t & 2) * 64;
            uint32_t* hd = tl->hn + ((q >> 1) * 32 + (tt2 >> 1)) * 7168 + (q & 1) * 3584 + (tt2 & 1) * 128 + w * 32 + lane;
            pin_ptr(never, sp_out); pin_ptr(never, sp_in); pin_ptr(never, hd);
            float s0 = 0.f, s1 = 0.f, q0 = 0.f, q1 = 0.f, s2 = 0.f, s3 = 0.f, q2 = 0.f, q3 = 0.f;
            auto sums = [&](int j0, int j1) {
                #pragma unroll
                for (int j = j0; j < j1; j++) {
                    s0 += acc[4 * j]; s2 += acc[4 * j + 1]; q0 = fmaf(acc[4 * j], acc[4 * j], q0); q2 = fmaf(acc[4 * j + 1], acc[4 * j + 1], q2);
                    s1 += acc[4 * j + 2]; s3 += acc[4 * j + 3]; q1 = fmaf(acc[4 * j + 2], acc[4 * j + 2], q1); q3 = fmaf(acc[4 * j + 3], acc[4 * j + 3], q3);
                }
            };
            if (live) {
                mbar_wait(bars + 8 * B_FULLWO, 0);
                #pragma unroll
                for (int jp = 0; jp < 7; jp++) {
                    uint32_t xx[4];
                    ldsm4(xx, hcol(ha, jp));
                    #pragma unroll
                    for (int r = 0; r < 4; r++) { acc[8 * jp + 2 * r] = bf_lo(xx[r]); acc[8 * jp + 2 * r + 1] = bf_hi(xx[r]); }
                }
                reg_fence(acc);
                auto od_ = [&](int s) { return mkdesc(sb + SM_QO + s * 2048, 1024, 128, 0); };
                auto wd_ = [&](int s) { return mkdesc(sb + slot_wo(s >> 2) + (s & 3) * 2048, 8192, 1024, 1); };
                float accl[32], accr[24];
                #pragma unroll
                for (int i = 0; i < 5; i++) {
                    if (i < 4) mbar_wait(bars + 8 * (B_FULLO + i), 0);
                    if (i == 0 && tid == 0) STAMP(7);
                    if (i == 1) { rb0 = ld_u16(pb); rb1 = ld_u16(pb + 8); }
                    wg_fence();
                    #pragma unroll
                    for (int ss = 0; ss < 7; ss++) {
                        if (i < 3) wgmma_ss112<0, 1>(acc, od_(7 * i + ss), wd_(7 * i + ss));
                        else if (i == 4) wgmma_ss64<0, 1>(accl, od_(21 + ss), wd_(21 + ss));
                        else if (ss == 0) wgmma_ss48<0, 1, 0>(accr, od_(21), wd_(21) + 512);
                        else wgmma_ss48<0, 1>(accr, od_(21 + ss), wd_(21 + ss) + 512);
                    }
                    wg_commit();
                    if (i > 0) {
                        wg_wait<1>();
                        if (i == 3) {
                            reg_fence(acc);
                            #pragma unroll
                            for (int c = 0; c < 32; c++) accl[c] = __uint_as_float(__float_as_uint(acc[c]) | never);
                            reg_fence(accl);
                        }
                        if (i < 4 && leader) mbar_arrive(bars + 8 * (B_DONEO + i - 1));
                    }
                }
                reg_fence(accr);
                #pragma unroll
                for (int c = 0; c < 24; c++) acc[32 + c] += accr[c];
                sums(8, 14);
                pin4(never, s0, s1, s2, s3); pin4(never, q0, q1, q2, q3);
                wg_wait<0>();
                reg_fence(accl);
                #pragma unroll
                for (int c = 0; c < 32; c++) acc[c] = accl[c];
                if (leader) mbar_arrive(bars + 8 * (B_DONEO + 3));
                if (tid == 0) STAMP(8);
            } else undef(acc);
            if (live || (DRY2 && w == 3)) {
            sums(0, 8);
            s0 += s2; s1 += s3; q0 += q2; q1 += q3;
            float sr = ((t & 1) ? s1 : s0) + __shfl_xor_sync(0xffffffffu, (t & 1) ? s0 : s1, 1), qr = ((t & 1) ? q1 : q0) + __shfl_xor_sync(0xffffffffu, (t & 1) ? q0 : q1, 1);
            sr += __shfl_xor_sync(0xffffffffu, sr, 2); qr += __shfl_xor_sync(0xffffffffu, qr, 2);
            st_relaxed4_if(t < 2 * live, sp_out, __float_as_uint(sr), __float_as_uint(qr), ep);
            const uint32_t tp = clock32();
            if (live) named_arrive(5, 256);
            if (tid == 0) STAMP(9);
            #pragma unroll
            for (int jp = 0; jp < 7; jp++)
                stsm4_if(live, hcol(ha, jp), pack_bf16(acc[8 * jp], acc[8 * jp + 1]), pack_bf16(acc[8 * jp + 2], acc[8 * jp + 3]),
                      pack_bf16(acc[8 * jp + 4], acc[8 * jp + 5]), pack_bf16(acc[8 * jp + 6], acc[8 * jp + 7]));
            uint4 v0, v1;
            if (POLL0) { while (clock32() - tp < POLL0) {} __syncwarp(); }
            do { v0 = ld_relaxed4(sp_in); v1 = ld_relaxed4(sp_in + 64); } while (live && __any_sync(0xffffffffu, v0.w != ep || v1.w != ep));
            if (tid == 0) STAMP(10);
            sr = __uint_as_float(v0.x) + __uint_as_float(v1.x); qr = __uint_as_float(v0.y) + __uint_as_float(v1.y);
            sr += __shfl_xor_sync(0xffffffffu, sr, 2); qr += __shfl_xor_sync(0xffffffffu, qr, 2);
            const float m = sr * (1.f / D_), var = fmaxf(qr * (1.f / D_) - m * m, 0.f);
            const float r = rsqrt_approx(fmaf(var, 4.f + 4.f * LN_EPS, 4.f * LN_EPS * LN_EPS)), c = -m * r;
            const float r0 = __shfl_sync(0xffffffffu, r, lane & ~1), c0 = __shfl_sync(0xffffffffu, c, lane & ~1);
            const float r1 = __shfl_sync(0xffffffffu, r, lane | 1), c1 = __shfl_sync(0xffffffffu, c, lane | 1);
            #pragma unroll
            for (int j = 0; j < 14; j++) st_global_if(live, hd + j * 256, pack_bf16(fmaf(acc[4 * j], r0, c0), fmaf(acc[4 * j + 1], r0, c0)));
            if (never) mbar_arrive(bars);
            #pragma unroll
            for (int j = 0; j < 14; j++) late[j] = pack_bf16(fmaf(acc[4 * j + 2], r1, c1), fmaf(acc[4 * j + 3], r1, c1));
            if (tid == 0) STAMP(11);
            }
        }
        if (!live) {
            check_tiles<0>(w, 4, 4, tl->o + tt2 * 14336, false, lane, true);
            rb0 = ld_u16(pb); rb1 = ld_u16(pb + 8);
            named_sync(5, 256);
            auto phase3 = [&](auto nc) {
                constexpr int NC = nc.value;
                float acc[4 * NC];
                uint32_t* ud = tl->u + (pr3 * 28 + (ft >> 1) + (NC == 14 ? 4 : 0)) * 7168 + col3 * 256 + (ft & 1) * 128 + w * 32 + lane;
                #pragma unroll
                for (int j = 0; j < 4 * NC; j++) acc[j] = 0.5f * bf_lo((j & 2) ? rb1 : rb0);
                #pragma unroll 1
                for (uint32_t pass = never; pass < 2; pass++) {
                    if (pass) {
                        mix_mainloop<32>(TSVAL acc, leader);
                        if (leader) STAMP(14);
                    }
                    uint32_t pk[NC];
                    #pragma unroll
                    for (int j = 0; j < NC; j++) {
                        const float k = j < GDEP ? GELU_K1 : __uint_as_float(__float_as_uint(GELU_K1) | (pk[j - GDEP] & never));
                        pk[j] = pack_bf16(gelu_half(acc[4 * j], k), gelu_half(acc[4 * j + 1], k));
                        st_global_if(pass, ud + j * 256, pk[j]);
                    }
                }
                if (leader) STAMP(15);
                #pragma unroll
                for (int j = 0; j < NC; j++) late[j] = pack_bf16(gelu_half(acc[4 * j + 2], GELU_K1), gelu_half(acc[4 * j + 3], GELU_K1));
                if (NC == 14) {
                    stage_late();
                    mbar_wait(bars + 8 * (B_FULLB + LATE_AT4), 1);
                    store_late(true, tl->u + (pr3 * 28 + (ft >> 1) + 14) * 7168 + col3 * 256 + (ft & 1) * 128);
                } else {
                    #pragma unroll
                    for (int c = 0; c < NC; c++) st_global_if(1, ud + 4 * 7168 + c * 256, late[c]);
                }
            };
            if (early) phase3(Int<10>()); else phase3(Int<14>());
            if (w) {
                if (early && w == 1) fetch_times(TSVAL sc->go, 1, ep, lane);
                check_tiles<2>(CH_U - 1 + w, 3, 28, tl->u + (q >> 1) * 28 * 7168 + (q & 1) * 3584, false, lane, false);
                mbar_wait(bars + 8 * (B_DONE + CL_AT), 1);
                const int l = slot * 48 + (tid - 160) / 2;
                #pragma unroll
                for (int i = 0; i < 7; i++)
                    st_relaxed4_if(i < 6 || l < sizeof(Tiles) / 128 - 6 * 6144, (uint4*)&sc->tiles[~ep & 1] + (i * 6144 + l) * 8 + (lane & 7), EMPTY, EMPTY, EMPTY);
            }
            if (leader) mbar_wait_wd(bars + 8 * B_END, 0);
            return;
        }
        {
            float acc[56];
            const uint32_t ad = sb + SM_H + (16 * w + (lane & 15)) * 128 + (((lane >> 4) ^ (lane & 7)) << 4);
            const float bb0 = bf_lo(rb0), bb1 = bf_lo(rb1);
            named_sync(1, 128);
            #pragma unroll
            for (int jp = 0; jp < 7; jp++) {
                uint32_t hh[4];
                ldsm4(hh, hcol(ad, jp));
                #pragma unroll
                for (int r = 0; r < 4; r++) { acc[8 * jp + 2 * r] = bf_lo(hh[r]) + ((r & 1) ? bb1 : bb0); acc[8 * jp + 2 * r + 1] = bf_hi(hh[r]) + ((r & 1) ? bb1 : bb0); }
            }
            #pragma unroll 1
            for (uint32_t pass = never; pass < 2; pass++) {
                if (pass) {
                    const int nl = (early ? LATE_E : LATE_N) * 4;
                    named_sync(1, 128);
                    stage_late();
                    #pragma unroll 1
                    for (int k = 0; k < 2; k++) {
                        check_tiles<1>(w + nl * k, 4, k ? 32 : nl, tl->hn + pr3 * 32 * 7168 + col3 * 256, early, lane, k == 0);
                        store_late(k == 0, tl->hn + ((q >> 1) * 32 + 16 + (tt2 >> 1)) * 7168 + (q & 1) * 3584 + (tt2 & 1) * 128);
                    }
                    mbar_wait(bars + 8 * (B_DONE + START4), 0);
                    mix_mainloop<28>(TSVAL acc, leader);
                    if (leader) mbar_arrive(bars + 8 * B_END);
                    if (tid == 0) STAMP(18);
                }
                #pragma unroll
                for (int jp = 0; jp < 7; jp++)
                    stsm4_if(1, hcol(ad, jp), pack_bf16(acc[8 * jp], acc[8 * jp + 1]), pack_bf16(acc[8 * jp + 2], acc[8 * jp + 3]),
                             pack_bf16(acc[8 * jp + 4], acc[8 * jp + 5]), pack_bf16(acc[8 * jp + 6], acc[8 * jp + 7]));
                fence_async_smem();
                __syncwarp();
            }
            if (elect()) {
                tma2d_store(&tm_out64, c64, tt2 * 64 + 16 * w, sb + SM_H + w * 2048);
                tma2d_store(&tm_out48, c48, tt2 * 64 + 16 * w, sb + SM_H + 8192 + w * 2048);
            }
            asm volatile("cp.async.bulk.commit_group;" ::: "memory");
            asm volatile("cp.async.bulk.wait_group.read 0;" ::: "memory");
            if (tid == 0) { sc->epoch[slot] = ep; STAMP(19); }
        }
        }
    } else {
        asm volatile("setmaxnreg.dec.sync.aligned.u32 56;");
        int warp2; asm("mov.u32 %0, %1;" : "=r"(warp2) : "r"(warp));
        if (warp2 > 8) {
            ASSIGN_WORK(get_slot())
            if (slot >= 128) return;
            uint32_t ep, cl;
            uint4* const oh = sc->hint_o + (2 * tb * 32 + hp * 4) * 2 + (lane & 3);
            uint4* const hu = sc->hint_u + (early ? ech * 8 + ft : 40 + q * 20 + ft) * 2;
            if (warp == 10) {
                post_hint(sc->hint_h + (q * 32 + tt2) * 2, 0, lane);
                post_hint(hu, 0, lane);
            }
            if (warp == 11) {
                ep = ld_volatile(&sc->epoch[slot]) + 1; cl = ld_acquire(&sc->clean);
                post_hint(sc->hint_k + (tb * 8 + hp) * 2, 0, lane);
                if (lane < (tb < 15 ? 4 : 0)) st_relaxed4(oh + 128, 0, 0, 0, 0);
                if (lane < (tb ? 0 : 4)) st_relaxed4(oh, 0, 0, 0, 0);
            }
            if (elect()) {
                if (warp == 9) {
                    #pragma unroll
                    for (int i = B_DONE1; i < B_DONEO; i++) mbar_init(bars + 8 * i, i < B_DONEX ? 2 : i == B_DONEX ? 8 : 9);
                }
                #pragma unroll
                for (int i = 0; i < 54; i++) mbar_init(bars + 8 * (B_DONEO + i) + (warp - 9) * 432, 1);
                asm volatile("fence.mbarrier_init.release.cluster;" ::: "memory");
            }
            named_sync(8, 128);
            if (warp < 11) mbar_expect(sb + SM_RAW + 8 * (tid - 288), early && tid >= 292 && tid < 324 ? 10240 : 14336);
            if (warp == 9) { named_arrive(4, 64); named_arrive(9, 160); named_arrive(10, 160); }
            if (warp < 11) {
                ep = get_tag();
                mbar_wait(bars + 8 * (B_DONE1 + HALO_AT), 0);
                #pragma unroll 1
                for (int kv = 0; kv < 2; kv++) {
                    uint4 v0 = {}, v1 = {}, v2 = {};
                    if (tb > 0) {
                        const uint4* hg = sc->halo + ((((tb - 1) * 8 + hp) * 2 + warp - 9) * 2 + kv) * 96 + lane;
                        if (kv == 0) while (ld_relaxed(sc->hint_k + ((tb - 1) * 8 + hp) * 2) != ep) {}
                        do { v0 = ld_relaxed4(hg); v1 = ld_relaxed4(hg + 32); v2 = ld_relaxed4(hg + 64); } while (!__all_sync(0xffffffffu, v0.w == ep && v1.w == ep && v2.w == ep));
                    }
                    if (kv) mbar_wait(bars + 8 * (B_DONE1 + 5), 0);
                    const uint32_t hs = kv ? sb + lane * 16 + (warp - 9) * 1024 + SM_HALOV + 8192 : halo_kin(warp - 9, lane);
                    sts4(hs, v0.x, v0.y, v0.z, v1.x); sts4(hs + (kv ? 512 : 16), v1.y, v1.z, v2.x, v2.y);
                    __syncwarp();
                    if (lane == 0) mbar_arrive(bars + 8 * (B_HALO + 2 * kv + warp - 9));
                }
                if (tid == 288) STAMP(21);
            } else {
                const long long t0 = clock64();
                while (__any_sync(0xffffffffu, (int)(cl - ep) < 0)) { cl = ld_acquire(&sc->clean); if (clock64() - t0 > WD_CLKS) __trap(); }
                if (lane == 0) { *(volatile uint32_t*)(smem_raw + SM_TAG) = ep; mbar_arrive(bars + 8 * B_CLR); }
                uint4* hg = sc->halo + (tb * 8 + hp) * 384 + lane;
                #pragma unroll 1
                for (int kv = 0; kv < 2; kv++) {
                    const uint32_t hs = sb + lane * 16 + 3072 + (kv ? SM_HALOV : SM_HALOK);
                    named_sync(6 + kv, 96);
                    #pragma unroll
                    for (int p = 0; p < 2; p++) {
                        const uint4 u0 = lds4(hs + p * 4096), u1 = lds4(hs + p * 4096 + 512);
                        st_relaxed4(hg + p * 192, u0.x, u0.y, u0.z, ep); st_relaxed4(hg + p * 192 + 32, u0.w, u1.x, u1.y, ep); st_relaxed4(hg + p * 192 + 64, u1.z, u1.w, ep, ep);
                    }
                    hg += 96;
                    if (kv == 0) {
                        post_hint(sc->hint_k + (tb * 8 + hp) * 2, ep, lane);
                        #pragma unroll
                        for (int j = 0; j < 6; j++) st_relaxed4(hg + j * 32 + (j / 3) * 96, 0, 0, 0, 0);
                    }
                }
                const uint32_t now = gtime32() - LATE_O;
                if (lane < (tb < 15 ? 4 : 0)) st_relaxed4(oh + 128, ep, now, ep, now);
                if (lane < (tb ? 0 : 4)) st_relaxed4(oh, ep, now, ep, now);
                if (lane == 0) STAMP(23);
                if (lane == 0) mbar_arrive(bars + 8 * B_DONEQ);
            }
            if (warp > 9) {
                const Tiles* const tl = &sc->tiles[ep & 1];
                if (warp == 10) {
                    mbar_wait(bars + 8 * (B_FULLO + 3), 0);
                    mbar_wait(bars + 8 * (B_DONEO + HINT_H), 0);
                    post_time(sc->hint_h + (q * 32 + tt2) * 2, ep, lane);
                    mbar_wait(bars + 8 * (B_DONE + (early ? HINT_E : HINT_U)), 0);
                    post_time(hu, ep, lane);
                }
                if (warp == 11) {
                    mbar_wait(bars + 8 * (B_DONE + (early ? POLL_E : POLL_N)), 0);
                    fetch_times(TSVAL sc->go, 0, ep, lane);
                }
                check_tiles<2>(11 - warp, 2, CH_U, tl->u + (q >> 1) * 28 * 7168 + (q & 1) * 3584, false, lane, true);
            } else {
                int aslot = 0;
                if (lane == 0) { prefetch_map(&tm_out64); prefetch_map(&tm_out48); }
                auto prefetch_w1 = [&]() {
                    if (elect()) {
                        #pragma unroll 1
                        for (int i = NA_SLOTS + (early ? ech : q); i < (early ? 16 : PFN_END); i += early ? 6 : 4) tma5d_prefetch(&tm_w1, ft * 64, (i & 7) * 8, i >> 3);
                    }
                };
                if (PFE_AT < 0) prefetch_w1();
                #pragma unroll 1
                for (int i = 0; i < 30; i++) {
                    if (i == POLL_I && !early) fetch_times(TSVAL sc->go, 1, ep, lane);
                    int d = i == 21 && !early ? A_HOLD : 2 * i - 11;
                    if (early) d = i < 16 ? 1 + (i - NA_SLOTS) * AE_END / 9 : max(d, AE_W2);
                    mbar_wait(bars + 8 * (i < NA_SLOTS ? B_DONEQ + ((A_SCHED >> (4 * i)) & 15) : B_DONE + (d & 31)), d >= 32);
                    if (elect()) {
                        const uint32_t bar = bars + 8 * (B_FULLA + (i & 15)), dst = sb + SM_ARING + aslot * 16384;
                        mbar_expect(bar, 16384);
                        if (i < 16) tma5d(dst, &tm_w1, ft * 64, (i & 7) * 8, i >> 3, bar);
                        else tma5d(dst, &tm_w2, tt2 * 64, 8 * (i < 20 ? i & 1 : i < 25 ? i - 18 : i - 23), i < 20 ? (i >> 1) & 1 : i >= 25, bar);
                    }
                    aslot = aslot == NA_SLOTS - 1 ? 0 : aslot + 1;
                    if (i == PFE_AT) prefetch_w1();
                }
            }
        } else {
            const int slot0 = get_slot(), row0 = (slot0 >> 5) * 256 + (slot0 & 12) * 16;
            if (elect()) {
                prefetch_map(&tm_x);
                #pragma unroll
                for (int i = 0; i < 7; i++) mbar_init(bars + 8 * i, 1);
                asm volatile("fence.mbarrier_init.release.cluster;" ::: "memory");
            }
            named_arrive(0, 288);
            if (elect()) {
                #pragma unroll 1
                for (int kb = 0; kb < 7; kb++) {
                    load_x(kb, row0);
                    if (kb == 0) STAMP(22);
                }
                #pragma unroll
                for (int i = 7; i < B_DONE1; i++) mbar_init(bars + 8 * i, 1);
                asm volatile("fence.mbarrier_init.release.cluster;" ::: "memory");
            }
            named_arrive(8, 128);
            ASSIGN_WORK(get_slot())
            if (slot >= 128) return;
            #pragma unroll 1
            for (int kb = 0; kb < 7; kb++) {
                if (kb == 6) { named_sync(4, 64); mbar_wait(bars + 8 * B_DONEX, 0); }
                if (elect()) {
                    const uint32_t st = sb + slot_kv(kb), bar = bars + 8 * (B_FULLKV + kb);
                    mbar_expect(bar, 16384);
                    #pragma unroll
                    for (int i = 0; i < 2; i++) {
                        const int n = 2 * kb + (i ^ (G & 1));
                        tma2d(st + (n & 1) * 8192, &tm_wqkv, (n < 7 ? 448 : 896) + wcol, (n < 7 ? n : n - 7) * 64, bar);
                    }
                }
            }
            if (elect()) {
                mbar_expect(bars + 8 * B_FQ, 32768);
                mbar_expect(bars + 8 * (B_FQ + 1), 24576);
                #pragma unroll 1
                for (int i = 0; i < 7; i++) { const int j = i == 6 ? i : i ^ (G & 1); tma2d(sb + SM_QO + j * 8192, &tm_wqkv, wcol, j * 64, bars + 8 * (B_FQ + (i >> 2))); }
                mbar_expect(bars + 8 * B_FULLWO, 512 * 112 * 2);
            }
            #pragma unroll 1
            for (int i = 0; i < 7; i++) {
                const int kb = ((q & 1 ? WO_ORD1 : WO_ORD0) >> (4 * i)) & 7;
                if (kb < 5) mbar_wait(bars + 8 * (B_DONE1 + kb), 0);
                if (elect()) {
                    tma2d(sb + slot_wo(kb), &tm_wo64, c64, kb * 64, bars + 8 * B_FULLWO);
                    tma2d(sb + slot_wo(kb) + 8192, &tm_wo48, c48, kb * 64, bars + 8 * B_FULLWO);
                }
            }
            if (elect()) {
                tma2d(sb + SM_H, &tm_xr64, c64, tt2 * 64, bars + 8 * B_FULLWO);
                tma2d(sb + SM_H + 8192, &tm_xr48, c48, tt2 * 64, bars + 8 * B_FULLWO);
            }
            if (smem_u32(smem_raw) != SB) __trap();
            const uint32_t ep = get_tag();
            const Tiles* const tl = &sc->tiles[ep & 1];
            mbar_wait(bars + 8 * (B_DONE1 + 6), 0);
            const uint32_t t_o = last_hint(TSVAL sc->hint_o + (tt2 * 32 + lane) * 2, ep, 38);
            mbar_wait(bars + 8 * B_DONEQ, 0);
            wait_until(t_o + GO_O);
            if (elect()) {
                #pragma unroll
                for (int i = 0; i < 4; i++) {
                    bulk_ld(sb + SM_QO + i * 14336, tl->o + tt2 * 14336 + i * 3584, 14336, sb + SM_RAW + 8 * i);
                }
            }
            if (lane == 0) STAMP(20);
            mbar_wait(bars + 8 * (B_DONEO + 2), 0);
            const uint32_t* src = tl->hn + pr3 * 32 * 7168 + col3 * 256;
            uint32_t bytes = early ? 10240 : 14336, dst = sb + SM_BRING, top = dst + (early ? NE_SLOTS * 10240 : NB_SLOTS * 14336), raw = sb + SM_RAW + 32;
            auto issue = [&]() {
                if (elect()) bulk_ld(dst, src, bytes, raw);
                src += 7168; raw += 8; dst += bytes;
                if (dst == top) dst = sb + SM_BRING;
            };
            wait_until(last_hint(TSVAL sc->go, ep, 42) + GO_H);
            mbar_wait(bars + 8 * (B_DONEO + 3), 0);
            STAMP(29);
            #pragma unroll 1
            do issue(); while (dst != sb + SM_BRING);
            uint32_t done = bars + 8 * B_DONE;
            #pragma unroll 1
            do { mbar_wait(done, 0); done += 8; issue(); } while (raw != sb + SM_RAW + 288);
            if (early) mbar_wait(bars + 8 * (B_DONE + 31), 0);
            src = tl->u + (q >> 1) * 28 * 7168 + (q & 1) * 3584; bytes = 14336; dst = sb + SM_BRING; top = dst + NB_SLOTS * 14336;
            done = bars + 8 * (B_DONE + 24);
            #pragma unroll 1
            for (uint32_t par = 0; par < 2; par++) {
                mbar_wait(bars + 8 * (B_GO + par), 0);
                const uint32_t ts = *(volatile uint32_t*)(smem_raw + SM_TIME + 128 * par + 4 * lane);
                if (par) done = bars + 8 * B_DONE;
                uint32_t bit = 1, wait = ~0u;
                #pragma unroll 1
                do {
                    while (wait & bit) wait = __ballot_sync(0xffffffffu, (int)(gtime32() - ts) < 0);
                    if (bit == 1) STAMP(par ? 36 : 30);
                    mbar_wait(done, par); done += 8;
                    issue();
                    bit *= 2;
                } while (bit != (par ? 1 << 20 : 1 << 8));
            }
        }
    }
}

typedef CUresult (*EncodeFn)(CUtensorMap*, CUtensorMapDataType, cuuint32_t, void*, const cuuint64_t*, const cuuint64_t*, const cuuint32_t*,
                             const cuuint32_t*, CUtensorMapInterleave, CUtensorMapSwizzle, CUtensorMapL2promotion, CUtensorMapFloatOOBfill);

void make_map(EncodeFn fn, CUtensorMap* tm, const void* ptr, int rank, const cuuint64_t* dims, const cuuint64_t* strides, const cuuint32_t* box, CUtensorMapSwizzle sw) {
    cuuint32_t es[5] = {1, 1, 1, 1, 1};
    fn(tm, CU_TENSOR_MAP_DATA_TYPE_BFLOAT16, rank, const_cast<void*>(ptr), dims, strides, box, es, CU_TENSOR_MAP_INTERLEAVE_NONE, sw,
       CU_TENSOR_MAP_L2_PROMOTION_NONE, CU_TENSOR_MAP_FLOAT_OOB_FILL_NONE);
}

}

extern "C" void kernel_launch(void* const* d_in, const int* in_sizes, int n_in, void* d_out, int out_size) {
    const __nv_bfloat16* x = (const __nv_bfloat16*)d_in[0];
    const __nv_bfloat16* wqkv = (const __nv_bfloat16*)d_in[1];
    const __nv_bfloat16* wo = (const __nv_bfloat16*)d_in[2];
    const __nv_bfloat16* w1 = (const __nv_bfloat16*)d_in[4];
    const __nv_bfloat16* b1 = (const __nv_bfloat16*)d_in[5];
    const __nv_bfloat16* w2 = (const __nv_bfloat16*)d_in[6];
    const __nv_bfloat16* b2 = (const __nv_bfloat16*)d_in[7];

    void* fnp = nullptr; cudaDriverEntryPointQueryResult qr;
    cudaGetDriverEntryPoint("cuTensorMapEncodeTiled", &fnp, cudaEnableDefault, &qr);
    EncodeFn fn = (EncodeFn)fnp;
    CUtensorMap tx, twqkv, two64, two48, tw1, tw2, txr64, txr48, tout64, tout48;
    { cuuint64_t d[3] = {448, 2, 1024}, s[2] = {896, 1792}; cuuint32_t b[3] = {64, 1, 64}; make_map(fn, &tx, x, 3, d, s, b, CU_TENSOR_MAP_SWIZZLE_128B); }
    { cuuint64_t d[2] = {1344, 448}, s[1] = {2688}; cuuint32_t b[2] = {64, 64}; make_map(fn, &twqkv, wqkv, 2, d, s, b, CU_TENSOR_MAP_SWIZZLE_128B); }
    { cuuint64_t d[2] = {448, 448}, s[1] = {896}; cuuint32_t b[2] = {64, 64}; make_map(fn, &two64, wo, 2, d, s, b, CU_TENSOR_MAP_SWIZZLE_128B); }
    { cuuint64_t d[2] = {448, 448}, s[1] = {896}; cuuint32_t b[2] = {48, 64}; make_map(fn, &two48, wo, 2, d, s, b, CU_TENSOR_MAP_SWIZZLE_128B); }
    { cuuint64_t d[5] = {1792, 8, 2, 64, 2}, s[4] = {2 * 3584, 3584, 32 * 3584, 16 * 3584}; cuuint32_t b[5] = {64, 8, 2, 8, 1}; make_map(fn, &tw1, w1, 5, d, s, b, CU_TENSOR_MAP_SWIZZLE_128B); }
    { cuuint64_t d[5] = {2048, 8, 2, 56, 2}, s[4] = {4096, 16 * 4096, 32 * 4096, 8 * 4096}; cuuint32_t b[5] = {64, 8, 2, 8, 1}; make_map(fn, &tw2, w2, 5, d, s, b, CU_TENSOR_MAP_SWIZZLE_128B); }
    { cuuint64_t d[2] = {448, 2048}, s[1] = {896}; cuuint32_t b[2] = {64, 64}; make_map(fn, &txr64, x, 2, d, s, b, CU_TENSOR_MAP_SWIZZLE_128B); }
    { cuuint64_t d[2] = {448, 2048}, s[1] = {896}; cuuint32_t b[2] = {48, 64}; make_map(fn, &txr48, x, 2, d, s, b, CU_TENSOR_MAP_SWIZZLE_128B); }
    { cuuint64_t d[2] = {448, 2048}, s[1] = {896}; cuuint32_t b[2] = {64, 16}; make_map(fn, &tout64, d_out, 2, d, s, b, CU_TENSOR_MAP_SWIZZLE_128B); }
    { cuuint64_t d[2] = {448, 2048}, s[1] = {896}; cuuint32_t b[2] = {48, 16}; make_map(fn, &tout48, d_out, 2, d, s, b, CU_TENSOR_MAP_SWIZZLE_128B); }

    void* scv = nullptr;
    cudaGetSymbolAddress(&scv, g_scratch);
    Scratch* scp = (Scratch*)scv;
    int dev = 0, sms = 0;
    cudaGetDevice(&dev);
    cudaDeviceGetAttribute(&sms, cudaDevAttrMultiProcessorCount, dev);
    if (sms == 132) {
        cudaFuncSetAttribute(fused_kernel<true>, cudaFuncAttributeMaxDynamicSharedMemorySize, SM_TOTAL);
        fused_kernel<true><<<132, 384, SM_TOTAL>>>(scp, wo, w1, b1, w2, b2, tx, twqkv, two64, two48, tw1, tw2, txr64, txr48, tout64, tout48);
    } else {
        cudaFuncSetAttribute(fused_kernel<false>, cudaFuncAttributeMaxDynamicSharedMemorySize, SM_TOTAL);
        fused_kernel<false><<<132, 384, SM_TOTAL>>>(scp, wo, w1, b1, w2, b2, tx, twqkv, two64, two48, tw1, tw2, txr64, txr48, tout64, tout48);
    }
}
```

```cpp
#include <cuda_runtime.h>
#include <cuda_bf16.h>
#include <cuda.h>
#include <stdint.h>

namespace {

constexpr int D_ = 448;
constexpr float LN_EPS = 1e-5f;
constexpr float LOG2E_SCALE = 0.1889822365046136f * 1.4426950408889634f;

struct Tiles {
    uint32_t o[32 * 57344 / 4];
    uint32_t hn[4 * 32 * 14336 / 4];
    uint32_t u[4 * 28 * 14336 / 4];
};
struct Scratch {
    uint4 halo[128 * 2 * 2 * 3 * 32];
    uint4 stats[32 * 4 * 64];
    uint4 hint_k[128 * 2];
    uint4 hint_o[32 * 32 * 2];
    uint4 hint_h[4 * 32 * 2];
    uint4 hint_u[128 * 2];
    uint4 go[24];
    uint32_t epoch[160];
    uint32_t clean;
    alignas(1024) Tiles tiles[2];
};
__device__ Scratch g_scratch;
#define STAMP(i) do {} while (0)
#define FST(i) do {} while (0)
#define TSARG
#define TSVAL

constexpr uint32_t SB = 1024;
constexpr int SM_SLOT = 16384;
__device__ __forceinline__ constexpr uint32_t slot_x(int kb) { return (kb ? 6 + kb : 0) * SM_SLOT; }
__device__ __forceinline__ constexpr uint32_t slot_kv(int kb) { return (kb < 5 ? 2 + kb : 6 - kb) * SM_SLOT; }
__device__ __forceinline__ constexpr uint32_t slot_wo(int kb) { return (kb < 6 ? 2 + kb : 12) * SM_SLOT; }
constexpr int SM_QO = 8 * SM_SLOT;
constexpr int SM_HALOK = SM_QO + 57344, SM_HALOV = 1 * SM_SLOT;
constexpr int NA_SLOTS = 6, NB_SLOTS = 8;
constexpr int SM_ARING = 0;
constexpr int SM_BRING = NA_SLOTS * 16384;
constexpr int SM_H = 212992;
__device__ __forceinline__ uint32_t halo_kin(int par, int lane) { return SB + SM_H + 8192 + par * 4096 + lane * 128 + ((~lane & 6) << 4); }
constexpr int SM_BAR = 229376;
constexpr int SM_TAG = SM_BAR + 1536;
constexpr int SM_TIME = SM_TAG + 256;
constexpr int SM_TOTAL = SM_TIME + 256;
constexpr int B_FULLX = 0;
constexpr int B_FULLKV = 7;
constexpr int B_FQ = 14;
constexpr int B_DONE1 = 16;
constexpr int B_DONEX = 23;
constexpr int B_DONEQ = 24;
constexpr int B_DONEO = 25;
constexpr int B_FULLO = 29;
constexpr int B_FULLWO = 33;
constexpr int B_END = 34;
constexpr int B_HALO = 35;
constexpr int B_FULLA = 39;
constexpr int B_FULLB = 55;
constexpr int B_DONE = 87;
constexpr int B_GO = 119;
constexpr int B_CLR = 121;
constexpr int SM_RAW = SM_BAR + 8 * 122;

constexpr long long WD_CLKS = 2000000000ll;

template<int N> struct Int { static constexpr int value = N; };
template<int A, int B, class F> __device__ __forceinline__ void static_for(F&& f) { if constexpr (A < B) { f(Int<A>()); static_for<A + 1, B>(f); } }

__device__ __forceinline__ uint32_t smem_u32(const void* p) { return (uint32_t)__cvta_generic_to_shared(p); }
__device__ __forceinline__ void mbar_init(uint32_t bar, uint32_t cnt) { asm volatile("mbarrier.init.shared::cta.b64 [%0], %1;" :: "r"(bar), "r"(cnt) : "memory"); }
__device__ __forceinline__ void mbar_expect(uint32_t bar, uint32_t bytes) { asm volatile("mbarrier.arrive.expect_tx.shared::cta.b64 _, [%0], %1;" :: "r"(bar), "r"(bytes) : "memory"); }
__device__ __forceinline__ void mbar_arrive(uint32_t bar) { asm volatile("mbarrier.arrive.shared::cta.b64 _, [%0];" :: "r"(bar) : "memory"); }
__device__ __forceinline__ bool mbar_try(uint32_t bar, uint32_t parity) {
    uint32_t ok;
    asm volatile("{\n.reg .pred p;\nmbarrier.try_wait.parity.shared::cta.b64 p, [%1], %2;\nselp.u32 %0, 1, 0, p;\n}" : "=r"(ok) : "r"(bar), "r"(parity) : "memory");
    return ok;
}
__device__ __forceinline__ bool mbar_test(uint32_t bar, uint32_t parity) {
    uint32_t ok;
    asm volatile("{\n.reg .pred p;\nmbarrier.test_wait.parity.shared::cta.b64 p, [%1], %2;\nselp.u32 %0, 1, 0, p;\n}" : "=r"(ok) : "r"(bar), "r"(parity) : "memory");
    return ok;
}
__device__ __forceinline__ void mbar_wait(uint32_t bar, uint32_t parity) {
    asm volatile("{\n.reg .pred p;\n"
                 "WAIT_LOOP:\n"
                 "mbarrier.try_wait.parity.shared::cta.b64 p, [%0], %1;\n"
                 "@!p bra WAIT_LOOP;\n}" :: "r"(bar), "r"(parity) : "memory");
}
__device__ __forceinline__ void mbar_wait_wd(uint32_t bar, uint32_t parity) {
    asm volatile("{\n.reg .pred p, q;\n.reg .u32 s, t;\nmov.u32 s, %%clock;\n"
                 "WAIT_LOOP:\n"
                 "mbarrier.try_wait.parity.shared::cta.b64 p, [%0], %1;\nmov.u32 t, %%clock;\nsub.u32 t, t, s;\nsetp.lt.and.s32 q, t, 0, !p;\n@q trap;\n"
                 "@!p bra WAIT_LOOP;\n}" :: "r"(bar), "r"(parity) : "memory");
}
__device__ __forceinline__ bool elect() { uint32_t p; asm volatile("{\n.reg .pred P;\nelect.sync _|P, 0xffffffff;\nselp.u32 %0, 1, 0, P;\n}" : "=r"(p)); return p; }
__device__ __forceinline__ void tma2d(uint32_t dst, const CUtensorMap* tm, int c0, int c1, uint32_t bar) {
    asm volatile("cp.async.bulk.tensor.2d.shared::cluster.global.mbarrier::complete_tx::bytes [%0], [%1, {%3, %4}], [%2];" :: "r"(dst), "l"(tm), "r"(bar), "r"(c0), "r"(c1) : "memory");
}
__device__ __forceinline__ void tma3d(uint32_t dst, const CUtensorMap* tm, int c0, int c1, int c2, uint32_t bar) {
    asm volatile("cp.async.bulk.tensor.3d.shared::cluster.global.mbarrier::complete_tx::bytes [%0], [%1, {%3, %4, %5}], [%2];" :: "r"(dst), "l"(tm), "r"(bar), "r"(c0), "r"(c1), "r"(c2) : "memory");
}
__device__ __forceinline__ void tma5d(uint32_t dst, const CUtensorMap* tm, int c0, int c3, int c4, uint32_t bar) {
    asm volatile("cp.async.bulk.tensor.5d.shared::cluster.global.mbarrier::complete_tx::bytes [%0], [%1, {%3, 0, 0, %4, %5}], [%2];" :: "r"(dst), "l"(tm), "r"(bar), "r"(c0), "r"(c3), "r"(c4) : "memory");
}
__device__ __forceinline__ void tma5d_prefetch(const CUtensorMap* tm, int c0, int c3, int c4) {
    asm volatile("cp.async.bulk.prefetch.tensor.5d.L2.global [%0, {%1, 0, 0, %2, %3}];" :: "l"(tm), "r"(c0), "r"(c3), "r"(c4) : "memory");
}
__device__ __forceinline__ void tma2d_store(const CUtensorMap* tm, int c0, int c1, uint32_t src) {
    asm volatile("cp.async.bulk.tensor.2d.global.shared::cta.bulk_group [%0, {%2, %3}], [%1];" :: "l"(tm), "r"(src), "r"(c0), "r"(c1) : "memory");
}
__device__ __forceinline__ void bulk_st(void* dst, uint32_t src, uint32_t bytes) {
    asm volatile("cp.async.bulk.global.shared::cta.bulk_group [%0], [%1], %2;" :: "l"(dst), "r"(src), "r"(bytes) : "memory");
}
__device__ __forceinline__ void bulk_ld(uint32_t dst, const void* src, uint32_t bytes, uint32_t bar) {
    asm volatile("cp.async.bulk.shared::cluster.global.mbarrier::complete_tx::bytes [%0], [%1], %2, [%3];" :: "r"(dst), "l"(src), "r"(bytes), "r"(bar) : "memory");
}
__device__ __forceinline__ void bulk_prefetch(const void* src, uint32_t bytes) { asm volatile("cp.async.bulk.prefetch.L2.global [%0], %1;" :: "l"(src), "r"(bytes) : "memory"); }
__device__ __forceinline__ void prefetch_map(const CUtensorMap* tm) { asm volatile("prefetch.tensormap [%0];" :: "l"(tm) : "memory"); }
__device__ __forceinline__ void st_global_if(uint32_t c, uint32_t* p, uint32_t v) {
    asm volatile("{\n.reg .pred p;\nsetp.ne.u32 p, %2, 0;\n@p st.global.u32 [%0], %1;\n}" :: "l"(p), "r"(v), "r"(c) : "memory");
}
__device__ __forceinline__ void st_relaxed4_if(bool c, uint4* p, uint32_t a, uint32_t b, uint32_t d) {
    asm volatile("{\n.reg .b128 t;\n.reg .b64 a, b;\n.reg .pred p;\nsetp.ne.u32 p, %4, 0;\nmov.b64 a, {%1, %2};\nmov.b64 b, {%3, %3};\nmov.b128 t, {a, b};\n@p st.relaxed.gpu.global.b128 [%0], t;\n}" :: "l"(p), "r"(a), "r"(b), "r"(d), "r"((uint32_t)c) : "memory");
}
__device__ __forceinline__ void pin_ptr(uint32_t never, const void* a) {
    asm volatile("{\n.reg .pred p;\nsetp.ne.u32 p, %1, 0;\n@p st.shared.u64 [%1], %0;\n}" :: "l"(a), "r"(never) : "memory");
}
__device__ __forceinline__ void pin4(uint32_t never, float a, float b, float c, float d) {
    asm volatile("{\n.reg .pred p;\nsetp.ne.u32 p, %4, 0;\n@p st.shared.v4.f32 [%4], {%0,%1,%2,%3};\n}" :: "f"(a), "f"(b), "f"(c), "f"(d), "r"(never) : "memory");
}
__device__ __forceinline__ void fence_async_smem() { asm volatile("fence.proxy.async.shared::cta;" ::: "memory"); }
__device__ __forceinline__ uint32_t ld_acquire(const void* p) { uint32_t v; asm volatile("ld.acquire.gpu.global.u32 %0, [%1];" : "=r"(v) : "l"(p) : "memory"); return v; }
__device__ __forceinline__ void st_release(void* p, uint32_t v) { asm volatile("st.release.gpu.global.u32 [%0], %1;" :: "l"(p), "r"(v) : "memory"); }
__device__ __forceinline__ uint32_t ld_relaxed(const void* p) { uint32_t v; asm volatile("ld.relaxed.gpu.global.u32 %0, [%1];" : "=r"(v) : "l"(p) : "memory"); return v; }
__device__ __forceinline__ uint2 ld_relaxed2(const void* p) {
    uint2 v; asm volatile("{\n.reg .b64 a;\nld.relaxed.gpu.global.b64 a, [%2];\nmov.b64 {%0, %1}, a;\n}" : "=r"(v.x), "=r"(v.y) : "l"(p) : "memory"); return v;
}
__device__ __forceinline__ void st_relaxed2(void* p, uint32_t a, uint32_t b) {
    asm volatile("{\n.reg .b64 a;\nmov.b64 a, {%1, %2};\nst.relaxed.gpu.global.b64 [%0], a;\n}" :: "l"(p), "r"(a), "r"(b) : "memory");
}
__device__ __forceinline__ uint4 ld_relaxed4(const uint4* p) {
    uint4 v;
    asm volatile("{\n.reg .b128 t;\n.reg .b64 a, b;\nld.relaxed.gpu.global.b128 t, [%4];\nmov.b128 {a, b}, t;\nmov.b64 {%0, %1}, a;\nmov.b64 {%2, %3}, b;\n}" : "=r"(v.x), "=r"(v.y), "=r"(v.z), "=r"(v.w) : "l"(p) : "memory");
    return v;
}
__device__ __forceinline__ void st_relaxed4(uint4* p, uint32_t a, uint32_t b, uint32_t c, uint32_t d) {
    asm volatile("{\n.reg .b128 t;\n.reg .b64 a, b;\nmov.b64 a, {%1, %2};\nmov.b64 b, {%3, %4};\nmov.b128 t, {a, b};\nst.relaxed.gpu.global.b128 [%0], t;\n}" :: "l"(p), "r"(a), "r"(b), "r"(c), "r"(d) : "memory");
}
__device__ __forceinline__ uint32_t ld_u16(const unsigned short* p) { uint32_t v; asm volatile("ld.volatile.global.u16 %0, [%1];" : "=r"(v) : "l"(p) : "memory"); return v; }
__device__ __forceinline__ uint32_t ld_volatile(const uint32_t* p) { uint32_t v; asm volatile("ld.volatile.global.u32 %0, [%1];" : "=r"(v) : "l"(p) : "memory"); return v; }
__device__ __forceinline__ void named_arrive(int id, int n) { asm volatile("bar.arrive %0, %1;" :: "r"(id), "r"(n) : "memory"); }
__device__ __forceinline__ void named_sync(int id, int n) { asm volatile("bar.sync %0, %1;" :: "r"(id), "r"(n) : "memory"); }
__device__ __forceinline__ void named_arrive_if(uint32_t c, int id, int n) { asm volatile("{\n.reg .pred p;\nsetp.ne.u32 p, %2, 0;\n@p bar.arrive %0, %1;\n}" :: "r"(id), "r"(n), "r"(c) : "memory"); }
__device__ __forceinline__ bool named_any(int id, int n, bool v) {
    uint32_t r; asm volatile("{\n.reg .pred p, q;\nsetp.ne.u32 p, %3, 0;\nbar.red.or.pred q, %1, %2, p;\nselp.u32 %0, 1, 0, q;\n}" : "=r"(r) : "r"(id), "r"(n), "r"((uint32_t)v) : "memory"); return r;
}
__device__ __forceinline__ void wg_fence() { asm volatile("wgmma.fence.sync.aligned;" ::: "memory"); }
__device__ __forceinline__ void wg_commit() { asm volatile("wgmma.commit_group.sync.aligned;" ::: "memory"); }
template<int N> __device__ __forceinline__ void wg_wait() { asm volatile("wgmma.wait_group.sync.aligned %0;" :: "n"(N) : "memory"); }
template<int N> __device__ __forceinline__ void reg_fence(float (&d)[N]) {
    #pragma unroll
    for (int i = 0; i < N; i++) asm volatile("" : "+f"(d[i]) :: "memory");
}
__device__ __forceinline__ constexpr uint64_t mkdesc(uint32_t addr, uint32_t lbo, uint32_t sbo, uint32_t sw) {
    return (uint64_t)((addr & 0x3FFFF) >> 4) | ((uint64_t)(lbo >> 4) << 16) | ((uint64_t)(sbo >> 4) << 32) | ((uint64_t)sw << 62);
}
__device__ __forceinline__ void ldsm4(uint32_t (&r)[4], uint32_t addr) {
    asm volatile("ldmatrix.sync.aligned.m8n8.x4.shared.b16 {%0,%1,%2,%3}, [%4];" : "=r"(r[0]), "=r"(r[1]), "=r"(r[2]), "=r"(r[3]) : "r"(addr) : "memory");
}
__device__ __forceinline__ void stsm4_if(uint32_t c, uint32_t addr, uint32_t r0, uint32_t r1, uint32_t r2, uint32_t r3) {
    asm volatile("{\n.reg .pred p;\nsetp.ne.u32 p, %5, 0;\n@p stmatrix.sync.aligned.m8n8.x4.shared.b16 [%0], {%1,%2,%3,%4};\n}" :: "r"(addr), "r"(r0), "r"(r1), "r"(r2), "r"(r3), "r"(c) : "memory");
}
__device__ __forceinline__ void sts4(uint32_t a, uint32_t x, uint32_t y, uint32_t z, uint32_t w) { asm volatile("st.shared.v4.u32 [%0], {%1,%2,%3,%4};" :: "r"(a), "r"(x), "r"(y), "r"(z), "r"(w) : "memory"); }
__device__ __forceinline__ uint4 lds4(uint32_t a) { uint4 v; asm volatile("ld.shared.v4.u32 {%0,%1,%2,%3}, [%4];" : "=r"(v.x), "=r"(v.y), "=r"(v.z), "=r"(v.w) : "r"(a) : "memory"); return v; }
__device__ __forceinline__ uint32_t movtrans(uint32_t a) { uint32_t d; asm volatile("movmatrix.sync.aligned.m8n8.trans.b16 %0, %1;" : "=r"(d) : "r"(a)); return d; }
__device__ __forceinline__ uint32_t pack_bf16(float lo, float hi) { uint32_t r; asm("cvt.rn.bf16x2.f32 %0, %1, %2;" : "=r"(r) : "f"(hi), "f"(lo)); return r; }
__device__ __forceinline__ void sub_bf16x2(uint32_t& a, uint32_t b) { asm volatile("sub.rn.bf16x2 %0, %0, %1;" : "+r"(a) : "r"(b)); }
__device__ __forceinline__ float bf_lo(uint32_t v) { return __uint_as_float(v << 16); }
__device__ __forceinline__ float bf_hi(uint32_t v) { return __uint_as_float(v & 0xffff0000u); }
__device__ __forceinline__ void mma16816(float (&c)[4], uint32_t a0, uint32_t a1, uint32_t a2, uint32_t a3, uint32_t b0, uint32_t b1) {
    asm volatile("mma.sync.aligned.m16n8k16.row.col.f32.bf16.bf16.f32 {%0,%1,%2,%3}, {%4,%5,%6,%7}, {%8,%9}, {%0,%1,%2,%3};"
        : "+f"(c[0]), "+f"(c[1]), "+f"(c[2]), "+f"(c[3]) : "r"(a0), "r"(a1), "r"(a2), "r"(a3), "r"(b0), "r"(b1));
}
__device__ __forceinline__ void mma1688(float (&c)[4], uint32_t a0, uint32_t a1, uint32_t b0) {
    asm volatile("mma.sync.aligned.m16n8k8.row.col.f32.bf16.bf16.f32 {%0,%1,%2,%3}, {%4,%5}, {%6}, {%0,%1,%2,%3};"
        : "+f"(c[0]), "+f"(c[1]), "+f"(c[2]), "+f"(c[3]) : "r"(a0), "r"(a1), "r"(b0));
}
__device__ __forceinline__ float quad_sum(float v) { v += __shfl_xor_sync(0xffffffffu, v, 1); v += __shfl_xor_sync(0xffffffffu, v, 2); return v; }
__device__ __forceinline__ float quad_max(float v) { v = fmaxf(v, __shfl_xor_sync(0xffffffffu, v, 1)); v = fmaxf(v, __shfl_xor_sync(0xffffffffu, v, 2)); return v; }
__device__ __forceinline__ float ex2(float x) { float y; asm("ex2.approx.ftz.f32 %0, %1;" : "=f"(y) : "f"(x)); return y; }
__device__ __forceinline__ float rsqrt_approx(float x) { float y; asm("rsqrt.approx.ftz.f32 %0, %1;" : "=f"(y) : "f"(x)); return y; }
__device__ __forceinline__ float rcp_approx(float x) { float y; asm("rcp.approx.ftz.f32 %0, %1;" : "=f"(y) : "f"(x)); return y; }
constexpr float GELU_K1 = 2.f * 0.7978845608028654f;
__device__ __forceinline__ float gelu_half(float hx, float k1) {
    const float z = hx * fmaf(hx * hx, 8.f * 0.044715f * 0.7978845608028654f, k1);
    float t; asm("tanh.approx.f32 %0, %1;" : "=f"(t) : "f"(z));
    return fmaf(hx, t, hx);
}
__device__ __forceinline__ uint32_t gtime32() { uint32_t t; asm volatile("mov.u32 %0, %%globaltimer_lo;" : "=r"(t)); return t; }
__device__ __forceinline__ uint32_t clock32() { uint32_t t; asm volatile("mov.u32 %0, %%clock;" : "=r"(t)); return t; }
#define PF_PACE 160
#define PF_AT 16500
#define PF_N 256
#define NSQ 6
#define NPIPE 1
#define HALO_AT 3
#define HINT_U 18
#define HINT_E 16
#define SP_AT 2000
#define A_SCHED 0x322188
#define WO_ORD0 0x4321065
#define WO_ORD1 0x3465210
#define CL_AT 23
#define WARM_AT 300
#define A_HOLD 31
#define GO_H 1430
#define GO_E 1830
#define GO_U 2200
#define GO_O 1280
#define LATE_O 256
#define DRY2 1
#define LATE_AT 1
#define LATE_AT4 0
#define HINT_H 0
#define SLACK 0
#define SLACK_U 128
#define GDEP 4
#define START4 30
#define EMAP 1
#define DEPTH_N 1
#define DEPTH_E 2
#define PFE_AT 99
#define PFN_END 0
#define NE_SLOTS 11
#define POLL_E 26
#define POLL_U 22
#define CH_U 28
#define AE_END 18
#define AE_W2 27
#define PF1_AT 12000
#define PF1_N 80
#define PF1_PACE 160
#define HOLD 0
#define X0 1
#define GO_E2 300
#define GO_U2 400
#define POLL_I 20
#define POLL_N 19
#define LATES 0x11111111u
#define GATE_J 22
#define GATE_D 16
#define ROLES 0x65432107u
#define LATE_E 1
#define LATE_N 1
#define CL_I0 0
#define CL_SP 1000
#define POLL0 250
#define A4_FROM 23
#define A4_DLY 2
#define SPIN2 1
#define SPIN3 1
#define SPIN4 0
#define SPIN_N 2
#define STOP2 200
#define STOP3 3
#define PF0_AT 5000
#define PF0_N 48
#define PF0_PACE 140
template<int TB> __device__ __forceinline__ void wgmma_rs56(float (&d)[28], const uint32_t (&a)[4], uint64_t db, int sc) {
    asm volatile("{\n.reg .pred p;\nsetp.ne.b32 p, %33, 0;\n"
        "wgmma.mma_async.sync.aligned.m64n56k16.f32.bf16.bf16 {%0, %1, %2, %3, %4, %5, %6, %7, %8, %9, %10, %11, %12, %13, %14, %15, %16, %17, %18, %19, %20, %21, %22, %23, %24, %25, %26, %27}, {%28, %29, %30, %31}, %32, p, 1, 1, %34;\n}\n"
        : "+f"(d[0]), "+f"(d[1]), "+f"(d[2]), "+f"(d[3]), "+f"(d[4]), "+f"(d[5]), "+f"(d[6]), "+f"(d[7]), "+f"(d[8]), "+f"(d[9]), "+f"(d[10]), "+f"(d[11]), "+f"(d[12]), "+f"(d[13]), "+f"(d[14]), "+f"(d[15]), "+f"(d[16]), "+f"(d[17]), "+f"(d[18]), "+f"(d[19]), "+f"(d[20]), "+f"(d[21]), "+f"(d[22]), "+f"(d[23]), "+f"(d[24]), "+f"(d[25]), "+f"(d[26]), "+f"(d[27])
        : "r"(a[0]), "r"(a[1]), "r"(a[2]), "r"(a[3]), "l"(db), "r"(sc), "n"(TB));
}

template<int TA, int TB, int SC = 1> __device__ __forceinline__ void wgmma_ss112(float (&d)[56], uint64_t da, uint64_t db) {
    asm volatile("wgmma.mma_async.sync.aligned.m64n112k16.f32.bf16.bf16 {%0, %1, %2, %3, %4, %5, %6, %7, %8, %9, %10, %11, %12, %13, %14, %15, %16, %17, %18, %19, %20, %21, %22, %23, %24, %25, %26, %27, %28, %29, %30, %31, %32, %33, %34, %35, %36, %37, %38, %39, %40, %41, %42, %43, %44, %45, %46, %47, %48, %49, %50, %51, %52, %53, %54, %55}, %56, %57, %60, 1, 1, %58, %59;\n"
        : "+f"(d[0]), "+f"(d[1]), "+f"(d[2]), "+f"(d[3]), "+f"(d[4]), "+f"(d[5]), "+f"(d[6]), "+f"(d[7]), "+f"(d[8]), "+f"(d[9]), "+f"(d[10]), "+f"(d[11]), "+f"(d[12]), "+f"(d[13]), "+f"(d[14]), "+f"(d[15]), "+f"(d[16]), "+f"(d[17]), "+f"(d[18]), "+f"(d[19]), "+f"(d[20]), "+f"(d[21]), "+f"(d[22]), "+f"(d[23]), "+f"(d[24]), "+f"(d[25]), "+f"(d[26]), "+f"(d[27]), "+f"(d[28]), "+f"(d[29]), "+f"(d[30]), "+f"(d[31]), "+f"(d[32]), "+f"(d[33]), "+f"(d[34]), "+f"(d[35]), "+f"(d[36]), "+f"(d[37]), "+f"(d[38]), "+f"(d[39]), "+f"(d[40]), "+f"(d[41]), "+f"(d[42]), "+f"(d[43]), "+f"(d[44]), "+f"(d[45]), "+f"(d[46]), "+f"(d[47]), "+f"(d[48]), "+f"(d[49]), "+f"(d[50]), "+f"(d[51]), "+f"(d[52]), "+f"(d[53]), "+f"(d[54]), "+f"(d[55])
        : "l"(da), "l"(db), "n"(TA), "n"(TB), "n"(SC));
}

template<int TA, int TB, int SC = 1> __device__ __forceinline__ void wgmma_ss80(float (&d)[40], uint64_t da, uint64_t db) {
    asm volatile("wgmma.mma_async.sync.aligned.m64n80k16.f32.bf16.bf16 {%0, %1, %2, %3, %4, %5, %6, %7, %8, %9, %10, %11, %12, %13, %14, %15, %16, %17, %18, %19, %20, %21, %22, %23, %24, %25, %26, %27, %28, %29, %30, %31, %32, %33, %34, %35, %36, %37, %38, %39}, %40, %41, %44, 1, 1, %42, %43;\n"
        : "+f"(d[0]), "+f"(d[1]), "+f"(d[2]), "+f"(d[3]), "+f"(d[4]), "+f"(d[5]), "+f"(d[6]), "+f"(d[7]), "+f"(d[8]), "+f"(d[9]), "+f"(d[10]), "+f"(d[11]), "+f"(d[12]), "+f"(d[13]), "+f"(d[14]), "+f"(d[15]), "+f"(d[16]), "+f"(d[17]), "+f"(d[18]), "+f"(d[19]), "+f"(d[20]), "+f"(d[21]), "+f"(d[22]), "+f"(d[23]), "+f"(d[24]), "+f"(d[25]), "+f"(d[26]), "+f"(d[27]), "+f"(d[28]), "+f"(d[29]), "+f"(d[30]), "+f"(d[31]), "+f"(d[32]), "+f"(d[33]), "+f"(d[34]), "+f"(d[35]), "+f"(d[36]), "+f"(d[37]), "+f"(d[38]), "+f"(d[39])
        : "l"(da), "l"(db), "n"(TA), "n"(TB), "n"(SC));
}

template<int TA, int TB, int SC = 1> __device__ __forceinline__ void wgmma_ss64(float (&d)[32], uint64_t da, uint64_t db) {
    asm volatile("wgmma.mma_async.sync.aligned.m64n64k16.f32.bf16.bf16 {%0, %1, %2, %3, %4, %5, %6, %7, %8, %9, %10, %11, %12, %13, %14, %15, %16, %17, %18, %19, %20, %21, %22, %23, %24, %25, %26, %27, %28, %29, %30, %31}, %32, %33, %36, 1, 1, %34, %35;\n"
        : "+f"(d[0]), "+f"(d[1]), "+f"(d[2]), "+f"(d[3]), "+f"(d[4]), "+f"(d[5]), "+f"(d[6]), "+f"(d[7]), "+f"(d[8]), "+f"(d[9]), "+f"(d[10]), "+f"(d[11]), "+f"(d[12]), "+f"(d[13]), "+f"(d[14]), "+f"(d[15]), "+f"(d[16]), "+f"(d[17]), "+f"(d[18]), "+f"(d[19]), "+f"(d[20]), "+f"(d[21]), "+f"(d[22]), "+f"(d[23]), "+f"(d[24]), "+f"(d[25]), "+f"(d[26]), "+f"(d[27]), "+f"(d[28]), "+f"(d[29]), "+f"(d[30]), "+f"(d[31])
        : "l"(da), "l"(db), "n"(TA), "n"(TB), "n"(SC));
}

template<int TA, int TB, int SC = 1> __device__ __forceinline__ void wgmma_ss48(float (&d)[24], uint64_t da, uint64_t db) {
    asm volatile("wgmma.mma_async.sync.aligned.m64n48k16.f32.bf16.bf16 {%0, %1, %2, %3, %4, %5, %6, %7, %8, %9, %10, %11, %12, %13, %14, %15, %16, %17, %18, %19, %20, %21, %22, %23}, %24, %25, %28, 1, 1, %26, %27;\n"
        : "+f"(d[0]), "+f"(d[1]), "+f"(d[2]), "+f"(d[3]), "+f"(d[4]), "+f"(d[5]), "+f"(d[6]), "+f"(d[7]), "+f"(d[8]), "+f"(d[9]), "+f"(d[10]), "+f"(d[11]), "+f"(d[12]), "+f"(d[13]), "+f"(d[14]), "+f"(d[15]), "+f"(d[16]), "+f"(d[17]), "+f"(d[18]), "+f"(d[19]), "+f"(d[20]), "+f"(d[21]), "+f"(d[22]), "+f"(d[23])
        : "l"(da), "l"(db), "n"(TA), "n"(TB), "n"(SC));
}

template<int NKB, int NR>
__device__ __forceinline__ void mix_mainloop(TSARG float (&acc)[NR], bool leader) {
    constexpr uint32_t sb = SB, bars = sb + SM_BAR, par = NKB == 28;
    constexpr int A0 = NKB == 32 ? 0 : 16 % NA_SLOTS;
    constexpr int DEPTH = NR == 56 ? DEPTH_N : DEPTH_E;
    int bslot = 0, aslot = A0;
    reg_fence(acc);
    #pragma unroll 1
    for (int i = 0; i < NKB / 2; i++) {
        mbar_wait(bars + 8 * (B_FULLA + i), par);
        const uint64_t adesc = mkdesc(sb + SM_ARING, 8192, 1024, 1) + (uint32_t)(aslot * 1024);
        aslot = aslot == NA_SLOTS - 1 ? 0 : aslot + 1;
        #pragma unroll
        for (int jj = 0; jj < 2; jj++) {
            const int j = 2 * i + jj;
            mbar_wait(bars + 8 * (B_FULLB + j), par);
            const uint64_t bdesc = mkdesc(sb + SM_BRING, 128, 1024, 0) + (uint32_t)(bslot * NR * 16);
            bslot = bslot == (NR == 56 ? NB_SLOTS : NE_SLOTS) - 1 ? 0 : bslot + 1;
            wg_fence();
            #pragma unroll
            for (int s = 0; s < 4; s++) {
                if constexpr (NR == 56) wgmma_ss112<1, 1>(acc, adesc + jj * 512 + s * 128, bdesc + s * 16);
                else wgmma_ss80<1, 1>(acc, adesc + jj * 512 + s * 128, bdesc + s * 16);
            }
            wg_commit();
            wg_wait<DEPTH>();
            if (j >= DEPTH && leader) mbar_arrive(bars + 8 * (B_DONE + j - DEPTH));
        }
    }
    if (DEPTH == 2) { wg_wait<1>(); if (leader) mbar_arrive(bars + 8 * (B_DONE + NKB - 2)); }
    wg_wait<0>();
    reg_fence(acc);
    if (leader) mbar_arrive(bars + 8 * (B_DONE + NKB - 1));
}

__device__ __forceinline__ void spin_mma(uint32_t bar, uint32_t never) {
    float d[56];
    #pragma unroll
    for (int i = 0; i < 56; i++) d[i] = 0.f;
    reg_fence(d);
    #pragma unroll 1
    do {
        wg_fence();
        #pragma unroll
        for (int s = 0; s < SPIN_N; s++) wgmma_ss112<1, 1>(d, mkdesc(SB + 2 * SM_SLOT + s * 2048, 8192, 1024, 1), mkdesc(SB + 3 * SM_SLOT + s * 256, 128, 1024, 0));
        wg_commit();
        wg_wait<1>();
    } while (!named_any(11, 128, mbar_test(bar, 1)));
    wg_wait<0>();
    reg_fence(d);
    pin4(never, d[0], d[1], d[2], d[3]);
}

constexpr uint32_t EMPTY = 0xFFFFFFFFu;
__device__ __forceinline__ void post_hint(uint4* p, uint32_t ep, int lane) { if (lane < 2) st_relaxed4(p + lane, ep, ep, ep, ep); }
__device__ __forceinline__ void post_time(uint4* p, uint32_t ep, int lane) { const uint32_t now = gtime32(); if (lane < 2) st_relaxed4(p + lane, ep, now, ep, now); }

__device__ __forceinline__ uint32_t last_hint(TSARG const uint4* hint, uint32_t ep, int st) {
    uint2 v;
    do { v = ld_relaxed2(hint); } while (!__all_sync(0xffffffffu, v.x == ep));
    const uint32_t t1 = gtime32() + 256;
    if (elect()) STAMP(st);
    return t1 - __reduce_min_sync(0xffffffffu, t1 - v.y);
}
__device__ __forceinline__ uint32_t later(uint32_t a, uint32_t b) { return a + max((int)(b - a), 0); }
__device__ __forceinline__ void fetch_times(TSARG const uint4* go, int k, uint32_t ep, int lane) {
    const uint2* p = (const uint2*)(go + 8 + 8 * k) + (k ? lane % 10 : lane & 3);
    uint2 v;
    do { v = ld_relaxed2(p); } while (!__all_sync(0xffffffffu, v.x == ep));
    v.y += k ? (lane < 10 ? GO_U : GO_U + GO_U2) : (lane < 4 ? GO_E : GO_E + GO_E2);
    asm volatile("st.shared.u32 [%0], %1;" :: "r"(SB + SM_TIME + 128 * k + 4 * lane), "r"(v.y) : "memory");
    __syncwarp();
    if (lane == 0) { mbar_arrive(SB + SM_BAR + 8 * (B_GO + k)); STAMP(k ? 43 : 24); }
    __syncwarp();
}
__device__ __forceinline__ void wait_until(uint32_t t) { while ((int)(gtime32() - t) < 0) {} __syncwarp(); }

__device__ __forceinline__ uint32_t check_tile(uint32_t raw, uint32_t full, uint32_t dst, uint32_t lofs, const uint32_t* src, uint32_t bytes, int lane) {
    uint32_t cnt;
    asm volatile("{\n.reg .pred p, e;\n.reg .u32 a, b, c, d;\nmov.u32 %0, 0;\n"
                 "AGAIN:\nand.b32 a, %0, 1;\n"
                 "WAIT:\nmbarrier.try_wait.parity.shared::cta.b64 p, [%1], a;\n@!p bra.uni WAIT;\n"
                 "ld.shared.u32 a, [%4];\nld.shared.u32 b, [%4+4096];\nld.shared.u32 c, [%5+-8192];\nld.shared.u32 d, [%5+-4096];\n"
                 "add.u32 %0, %0, 1;\nmax.u32 a, a, b;\nmax.u32 c, c, d;\nmax.u32 a, a, c;\nsetp.lt.u32 e, %8, 32;\nsetp.eq.and.u32 p, a, 0xFFFFFFFF, e;\n"
                 "vote.sync.any.pred p, p, 0xffffffff;\nsetp.eq.and.u32 e, %8, 0, !p;\n@e mbarrier.arrive.shared::cta.b64 _, [%2];\n"
                 "elect.sync _|e, 0xffffffff;\nand.pred e, e, p;\n"
                 "@e mbarrier.arrive.expect_tx.shared::cta.b64 _, [%1], %7;\n"
                 "@e cp.async.bulk.shared::cluster.global.mbarrier::complete_tx::bytes [%3], [%6], %7, [%1];\n"
                 "@p bra.uni AGAIN;\n}"
                 : "=&r"(cnt) : "r"(raw), "r"(full), "r"(dst), "r"(dst + lofs), "r"(dst + lofs + bytes), "l"(src), "r"(bytes), "r"(lane) : "memory");
    return cnt;
}

template<int ST>
__device__ __forceinline__ void check_tiles(int j, int step, int n, const uint32_t* src, bool small, int lane, bool dry) {
    const uint32_t bytes = small ? 10240 : 14336, nb = small ? NE_SLOTS : NB_SLOTS, lofs = lane * 128 + (lane & 3) * 32 + (lane >> 2) * 4;
    uint32_t sl = j % nb;
    #pragma unroll 1
    for (int inc = dry ? 0 : step; j < n; j += inc, inc = step) {
        const uint32_t c = check_tile(inc ? SB + SM_RAW + 8 * (j + (ST ? 32 * ST - 28 : 0)) : SB + SM_BAR + 8 * B_CLR, SB + SM_BAR + 8 * (j + (ST ? B_FULLB : B_FULLO)),
                                      SB + (ST ? SM_BRING : SM_QO) + sl * bytes, lofs, src + j * (ST ? 7168 : 3584), bytes, inc ? lane : 32);
        sl += inc;
        if (sl >= nb) sl -= nb;
    }
}

__device__ __forceinline__ uint32_t hcol(uint32_t a, int jp) { return (a ^ ((jp & 3) << 5)) + (jp >> 2) * 8192; }

__device__ __forceinline__ uint32_t get_tag() {
    mbar_wait(SB + SM_BAR + 8 * B_CLR, 0);
    uint32_t v; asm volatile("ld.shared.u32 %0, [%1];" : "=r"(v) : "r"(SB + SM_TAG) : "memory"); return v;
}

template<bool USE_SMID>
__global__ void __launch_bounds__(384, 1)
fused_kernel(Scratch* __restrict__ sc, const __nv_bfloat16* __restrict__ wo,
             const __nv_bfloat16* __restrict__ w1, const __nv_bfloat16* __restrict__ b1,
             const __nv_bfloat16* __restrict__ w2, const __nv_bfloat16* __restrict__ b2,
             const __grid_constant__ CUtensorMap tm_x, const __grid_constant__ CUtensorMap tm_wqkv,
             const __grid_constant__ CUtensorMap tm_wo64, const __grid_constant__ CUtensorMap tm_wo48,
             const __grid_constant__ CUtensorMap tm_w1, const __grid_constant__ CUtensorMap tm_w2,
             const __grid_constant__ CUtensorMap tm_xr64, const __grid_constant__ CUtensorMap tm_xr48,
             const __grid_constant__ CUtensorMap tm_out64, const __grid_constant__ CUtensorMap tm_out48) {
    extern __shared__ __align__(1024) uint8_t smem_raw[];
    constexpr uint32_t sb = SB;
    constexpr uint32_t bars = sb + SM_BAR;
    const int tid = threadIdx.x, lane = tid & 31;
    auto get_slot = [&]() {
        int slot;
    if (USE_SMID) {
        asm volatile("{\n.reg .u32 s, t, u, d, a, b, c;\n.reg .pred p, r;\n"
            "mov.u32 s, %%smid;\nshr.u32 t, s, 1;\nsub.u32 u, t, 32;\nmul.lo.u32 d, u, 37;\nshr.u32 d, d, 8;\n"
            "and.b32 a, t, 7;\nshl.b32 a, a, 3;\nshr.u32 c, t, 3;\nadd.u32 a, a, c;\n"
            "mad.lo.u32 b, d, -55, 12;\nshl.b32 c, u, 3;\nadd.u32 b, b, c;\n"
            "setp.lt.u32 p, t, 32;\nselp.u32 a, a, b, p;\n"
            "setp.lt.u32 r, t, 62;\nselp.s32 c, 4, -58, r;\nadd.u32 c, t, c;\nsetp.lt.u32 p, t, 60;\nselp.u32 a, a, c, p;\n"
            "and.b32 s, s, 1;\nshl.b32 a, a, 1;\nadd.u32 %0, a, s;\n}" : "=r"(slot));
    } else slot = blockIdx.x;
        return slot;
    };
    auto load_x = [&](int kb, int row) {
        const uint32_t st = sb + slot_x(kb), bar = bars + 8 * (B_FULLX + kb);
        mbar_expect(bar, 16384);
        tma3d(st, &tm_x, kb * 64, 0, row, bar); tma3d(st + 8192, &tm_x, kb * 64, 1, row, bar);
    };
    const int warp = __shfl_sync(0xffffffffu, tid >> 5, 0);
#define ASSIGN_WORK(s) \
    const int slot = (s), G = slot >> 4, mi = slot & 15; \
    const int tb = 4 * (G >> 1) + (mi >> 2), hp = 2 * (mi & 3) + (G & 1), wcol = (hp * 56) & ~15; \
    const int q = mi & 3, tt2 = 4 * G + (mi >> 2), c64 = 64 * q, c48 = 256 + 48 * q; \
    const int R = (ROLES >> (4 * G)) & 7; \
    const bool early = R < 3; \
    const int ech = R < 2 ? q : 4 + (mi & 1), ft = R == 2 ? mi >> 1 : 4 * (R - !early) + (mi >> 2); \
    const int pr3 = early ? ech >= 3 : q >> 1, col3 = early ? (ech - 3 * pr3) * 9 : (q & 1) * 14;

    if (warp < 8) {
        ASSIGN_WORK(get_slot())
        if (slot >= 128) {
            const uint32_t ep = ld_volatile(&sc->epoch[slot]) + 1;
            if (mi == 0 && warp > 0) {
                const int k = warp == 1 ? 0 : 1 + (warp & 1);
                uint2* go = (uint2*)(sc->go + 8 * k) + lane;
                if (warp < 4 && lane < 16) st_relaxed2(go, 0, 0);
                while (ld_relaxed(k ? sc->go : sc->hint_k) != ep) __nanosleep(200);
                __nanosleep(warp * 60);
                const uint4* hint = (k ? sc->hint_u : sc->hint_h) + (k == 2 ? 48 + min(lane, 19) : lane) * 2;
                uint2 v[4];
                do {
                    #pragma unroll
                    for (int i = 0; i < 4; i++) v[i] = ld_relaxed2(hint + (k == 0 ? 64 * i : k == 2 ? 40 * i : 32 * (i & 1)));
                } while (!__all_sync(0xffffffffu, v[0].x == ep && v[1].x == ep && v[2].x == ep && v[3].x == ep));
                uint32_t t = later(later(v[0].y, v[1].y), later(v[2].y, v[3].y));
                t = later(t, __shfl_xor_sync(0xffffffffu, t, 1));
                if (k == 1) { t = later(t, __shfl_xor_sync(0xffffffffu, t, 8)); t = later(t, __shfl_xor_sync(0xffffffffu, t, 16)); }
                if (k == 0) {
                    const uint32_t now = gtime32() + 256;
                    t = later(t, now - __reduce_min_sync(0xffffffffu, now - t) - SLACK);
                }
                t = __shfl_sync(0xffffffffu, t, 2 * lane);
                if (lane < 16) st_relaxed2(go, ep, t);
            }
            if (mi == 1 && warp >= 4 && ld_volatile(&sc->clean) != ep) {
                for (int l = (tid - 128) / 2; l < sizeof(Tiles) / 128; l += 64) st_relaxed4((uint4*)&sc->tiles[ep & 1] + l * 8 + (lane & 7), EMPTY, EMPTY, EMPTY, EMPTY);
                named_sync(1, 128);
                if (tid == 128) st_release(&sc->clean, ep);
            }
            if (tid == 0) {
                const long long t0 = clock64();
                while (clock64() - t0 < SP_AT) {}
                #pragma unroll 1
                for (int i = 0; i < 7; i++) bulk_prefetch((const char*)wo + (i * 4 + mi) * 14336, 14336);
                uint32_t t = (uint32_t)t0 + PF0_AT;
                #pragma unroll 1
                for (int i = 0; i < PF0_N; i++) {
                    while ((int)(clock32() - t) < 0) {}
                    bulk_prefetch((const char*)w1 + i * 114688 + mi * 14336, 14336);
                    t += PF0_PACE;
                }
                if (mi) {
                    t = (uint32_t)t0 + PF1_AT;
                    #pragma unroll 1
                    for (int i = mi - 1; i < PF1_N; i += 3) {
                        while ((int)(clock32() - t) < 0) {}
                        tma5d_prefetch(&tm_w1, (i & 7) * 64, (i + 48) & 56, (i + 48) >> 6);
                        t += PF1_PACE;
                    }
                    t = (uint32_t)t0 + PF_AT;
                    #pragma unroll 1
                    for (int i = mi - 1; i < PF_N; i += 3) {
                        while ((int)(clock32() - t) < 0) {}
                        bulk_prefetch((const char*)w2 + (i < 128 ? i * 16384 : (i - 64 >> 1) * 65536 + (i & 1) * 16384), 16384);
                        t += PF_PACE;
                    }
                }
                while (ld_relaxed(sc->hint_u + 254) != ep) { __nanosleep(500); if (clock64() - t0 > WD_CLKS) __trap(); }
                sc->epoch[slot] = ep;
                if (mi == 1) sc->clean = ep + 1;
            }
            return;
        }
        {
            const int w = warp & 3, wg = warp >> 2, g = lane >> 2, t = lane & 3;
            if (WARM_AT) { const uint32_t t0 = clock32(); while (clock32() - t0 < WARM_AT) {} __syncwarp(); }
            if (w > 0) post_hint(sc->hint_o + ((2 * tb + (w >> 1)) * 32 + hp * 4 + (w & 1) * 2 + wg) * 2, 0, lane);
            if (wg == 0) {
                if (t < 2) st_relaxed4(sc->stats + tt2 * 256 + q * 64 + 16 * w + g + 8 * t, 0, 0, 0, 0);
            }
        }
        named_sync(0, 288);
        asm volatile("setmaxnreg.inc.sync.aligned.u32 224;");
        int tid; asm volatile("mov.u32 %0, %%tid.x;" : "=r"(tid));
        const int lane = tid & 31, warp = __shfl_sync(0xffffffffu, tid >> 5, 0), wg = warp >> 2;
        uint32_t ep;
        Tiles* tl;
        const int w = warp & 3, g = lane >> 2, t = lane & 3;
        const bool leader = (tid & 127) == 0;
        const uint32_t never = gridDim.y - 1;
        {
            uint32_t a[28][4];
            float accK[28], accV[28], accQ[28];
            const int lrow = 16 * w + (lane & 7) + (lane & 8);
            const uint32_t lbase = sb + wg * 8192 + lrow * 128;
            const uint32_t lx = (lane >> 4) ^ (lane & 7);
            const uint32_t wofs = hp & 1;
            auto pin2 = [&](uint32_t x0, uint32_t x1) {
                asm volatile("{\n.reg .pred p;\nsetp.ne.u32 p, %2, 0;\n@p st.shared.v2.b32 [%0], {%0,%1};\n}" :: "r"(x0), "r"(x1), "r"(never) : "memory");
            };
            float cS[2][4] = {}, cA[2][4] = {}, cB[2][4] = {}, q0, q1, p0, p1;
            auto sq = [&](float& acc, uint32_t v) { const float lo = bf_lo(v), hi = bf_hi(v); acc = fmaf(hi, hi, fmaf(lo, lo, acc)); };
            #pragma unroll
            for (int kb = 0; kb < 8; kb++) {
                if (kb < 7) {
                    mbar_wait(bars + 8 * (B_FULLX + kb), 0);
                    if (kb == 0 && tid == 0) STAMP(0);
                    if (kb == 6 && tid == 0) STAMP(25);
                    if (kb == 0) FST(0); if (kb == 2) FST(1); if (kb == 4) FST(2); if (kb == 6) FST(3);
                    #pragma unroll
                    for (int s = 4 * kb; s < 4 * kb + 4; s++) ldsm4(a[s], lbase + slot_x(kb) + ((lx ^ (2 * (s & 3))) << 4));
                }
                if (kb == 5) named_sync(9 + wg, 160);
                if (kb == NPIPE) continue;
                const int kc = kb < NPIPE ? kb : kb - 1;
                if (kc == NSQ) { p0 = cS[0][0] + cS[1][0]; p1 = cS[0][2] + cS[1][2]; }
                #pragma unroll
                for (int s = 4 * kc; s < 4 * kc + 4; s++) {
                    mma16816(cS[s & 1], a[s][0], a[s][1], a[s][2], a[s][3], 0x3F803F80u, 0x3F803F80u);
                    if (kc < NSQ) {
                        mma1688(cA[0], a[s][0], a[s][1], a[s][0]); mma1688(cA[1], a[s][2], a[s][3], a[s][2]);
                        mma1688(cB[0], a[s][0], a[s][1], a[s][1]); mma1688(cB[1], a[s][2], a[s][3], a[s][3]);
                    }
                }
            }
            const float m0 = (cS[0][0] + cS[1][0]) * (1.f / D_), m1 = (cS[0][2] + cS[1][2]) * (1.f / D_);
            const uint32_t mm0 = pack_bf16(m0, m0), mm1 = pack_bf16(m1, m1);
            if (lane == 0) mbar_arrive(bars + 8 * B_DONEX);
            auto center = [&](int s) { sub_bf16x2(a[s][0], mm0); sub_bf16x2(a[s][1], mm1); sub_bf16x2(a[s][2], mm0); sub_bf16x2(a[s][3], mm1); };
            uint32_t Ka[8], Kb[8], Kc[8], Va[8], Vb[7], Vc[8];
            float r0, r1, ls0, ls1;
            uint32_t pm, zero;
            uint32_t* od;
            uint4* oh;
            auto kpack = [&](uint32_t (&k)[8], int j, int c, float r) {
                const uint32_t v = pack_bf16(accK[4 * j + c] * r, accK[4 * j + c + 1] * r);
                if (j == 3) { k[3] = t < 2 ? v : 0u; k[4] = t < 2 ? 0u : v; } else k[j + (j > 3)] = v;
            };
            auto batch = [&](auto c0, auto c1) {
                constexpr int n0 = c0.value, n1 = c1.value;
                wg_fence();
                static_for<n0, n1>([&](auto nc) {
                    constexpr int n = nc.value;
                    if (n == 4) { center(4); center(5); center(6); center(7); wg_fence(); }
                    const uint64_t desc = mkdesc(sb + (n < 56 ? slot_kv(n >> 3) + (n & 7) * 2048 : SM_QO + (n - 56) * 2048), 8192, 1024, 1) + wofs;
                    wgmma_rs56<1>(n < 28 ? accK : n < 56 ? accV : accQ, a[n % 28], desc, n % 28 != 0);
                });
                wg_commit();
                if (n0 > 0) wg_wait<1>();
            };
            const uint32_t hs = sb + tid * 16 + warp * 512;
            auto hand_over = [&](const uint32_t (&v)[8], int kv) {
                mbar_wait(bars + 8 * (kv ? B_DONE1 + 5 : B_DONEX), 0);
                sts4(hs + (kv ? SM_HALOV : SM_HALOK), v[0], v[1], v[2], v[3]); sts4(hs + (kv ? SM_HALOV : SM_HALOK) + 512, v[4], v[5], v[6], v[7]);
                if (w == 3) named_arrive(6 + kv, 96);
            };
            auto take_over = [&](uint32_t (&v)[8], int kv) {
                if (w == 0) mbar_wait(bars + 8 * (B_HALO + 2 * kv + wg), 0);
                const uint32_t ad = w ? hs + (kv ? SM_HALOV : SM_HALOK) - 1024 : kv ? sb + lane * 16 + wg * 1024 + SM_HALOV + 8192 : halo_kin(wg, lane);
                const uint4 u0 = lds4(ad), u1 = lds4(ad + (w || kv ? 512 : 16));
                v[0] = u0.x; v[1] = u0.y; v[2] = u0.z; v[3] = u0.w; v[4] = u1.x; v[5] = u1.y; v[6] = u1.z; v[7] = u1.w;
            };
            center(0); center(1); center(2); center(3);
            static_for<0, 7>([&](auto pc) {
                constexpr int p = pc.value;
                mbar_wait(bars + 8 * (B_FULLKV + p), 0);
                if (p == 0 && tid == 0) STAMP(26);
                if (p == 3 && tid == 0) STAMP(27);
                FST(4 + p);
                batch(Int<8 * p>(), Int<8 * p + 8>());
                if (p > 0 && leader) mbar_arrive(bars + 8 * (B_DONE1 + p - 1));
                #pragma unroll
                for (int s = 8 * p + 8; s < 8 * p + 16 && s < 28; s++) center(s);
                if (p == 1) {
                    const float c0 = bf_hi(mm0), c1 = bf_hi(mm1);
                    q0 = fmaf(c0, fmaf(c0, 64.f * NSQ, -2.f * p0), (g & 1) ? cA[0][1] + cA[1][1] : cA[0][0] + cA[1][0]) - D_ * (m0 - c0) * (m0 - c0);
                    q1 = fmaf(c1, fmaf(c1, 64.f * NSQ, -2.f * p1), (g & 1) ? cB[0][3] + cB[1][3] : cB[0][2] + cB[1][2]) - D_ * (m1 - c1) * (m1 - c1);
                    asm("" : "+f"(q0), "+f"(q1));
                    q0 = t == (g >> 1) ? q0 : 0.f; q1 = t == (g >> 1) ? q1 : 0.f;
                    pin2(__float_as_uint(q0), __float_as_uint(q1));
                }
                constexpr int PK = NSQ < 5 ? 5 : 4, NR = 28 - 4 * NSQ;
                if (p >= 2 && p < PK) {
                    #pragma unroll
                    for (int s = 4 * NSQ + NR * (p - 2) / (PK - 2); s < 4 * NSQ + NR * (p - 1) / (PK - 2); s++) { sq(q0, a[s][0]); sq(q1, a[s][1]); sq(q0, a[s][2]); sq(q1, a[s][3]); }
                    pin2(__float_as_uint(q0), __float_as_uint(q1));
                }
                if (p == PK - 1) { q0 = quad_sum(q0); q1 = quad_sum(q1); }
                if (p == PK) {
                    r0 = rsqrt_approx(fmaxf(q0 * (1.f / D_), 0.f) + LN_EPS); r1 = rsqrt_approx(fmaxf(q1 * (1.f / D_), 0.f) + LN_EPS);
                    reg_fence(accK);
                    #pragma unroll
                    for (int j = 0; j < 7; j++) kpack(Kc, j, 2, r1);
                    hand_over(Kc, 0);
                }
                if (p == PK + 1) {
                    #pragma unroll
                    for (int j = 0; j < 7; j++) kpack(Kb, j, 0, r0);
                    #pragma unroll
                    for (int j = 0; j < 8; j += 2) pin2(Kb[j], Kb[j + 1]);
                    ls0 = LOG2E_SCALE * r0; ls1 = LOG2E_SCALE * r1;
                    pm = (2 * t <= g ? 0xFFFFu : 0u) | (2 * t + 1 <= g ? 0xFFFF0000u : 0u);
                    zero = never; asm volatile("" : "+r"(zero));
                    pin2(__float_as_uint(ls0), __float_as_uint(ls1)); pin2(pm, zero);
                }
                if (p == 2) ep = get_tag();
                if (p == 6) {
                    tl = &sc->tiles[ep & 1];
                    const int tt = 2 * tb + (w >> 1);
                    od = tl->o + tt * 14336 + (7 * hp) * 256 + (2 * (2 * (w & 1) + wg)) * 32 + lane;
                    oh = sc->hint_o + (tt * 32 + hp * 4 + (w & 1) * 2 + wg) * 2 + (lane & 1);
                    pin2((uint32_t)(uint64_t)od, (uint32_t)((uint64_t)od >> 32));
                    pin2((uint32_t)(uint64_t)oh, (uint32_t)((uint64_t)oh >> 32));
                }
            });
            if (tid == 0) STAMP(1);
            FST(11);
            mbar_wait(bars + 8 * B_FQ, 0);
            batch(Int<56>(), Int<60>());
            reg_fence(accV);
            if (leader) mbar_arrive(bars + 8 * (B_DONE1 + 6));
            if (tid == 0) STAMP(2);
            FST(12);
            #pragma unroll
            for (int j = 0; j < 7; j++) Vc[j] = movtrans(pack_bf16(accV[4 * j + 2] * r1, accV[4 * j + 3] * r1));
            Vc[7] = Vc[6];
            hand_over(Vc, 1);
            batch(Int<60>(), Int<66>());
            #pragma unroll
            for (int j = 0; j < 7; j++) {
                Vb[j] = movtrans(pack_bf16(accV[4 * j] * r0, accV[4 * j + 1] * r0));
                Vc[j] |= zero;
            }
            batch(Int<66>(), Int<72>());
            #pragma unroll
            for (int j = 0; j < 7; j++) pin2(Vb[j], Vc[j]);
            mbar_wait(bars + 8 * (B_FQ + 1), 0);
            FST(13);
            if (w > 0 && lane < 2) { const uint32_t now = gtime32(); st_relaxed4(oh, ep, now, ep, now); }
            batch(Int<72>(), Int<84>());
            FST(14);
            named_sync(1 + wg, 128);
            take_over(Ka, 0);
            if (tid == 0) STAMP(3);
            wg_wait<0>();
            reg_fence(accQ);
            if (tid == 0) STAMP(4);
            FST(15);
            const bool first = (tb == 0 && w == 0);
            uint32_t pA[2], pB0[2], pB1[2], pC[2], z0[2], z1[2];
            #pragma unroll
            for (int h = 0; h < 2; h++) {
                float sA[4] = {0.f, 0.f, 0.f, 0.f}, sB[4] = {0.f, 0.f, 0.f, 0.f}, sC[4] = {0.f, 0.f, 0.f, 0.f};
                #pragma unroll
                for (int k = 0; k < 2; k++) {
                    const float* qq = accQ + 12 * h + 8 * k;
                    uint32_t a0 = pack_bf16(qq[0], qq[1]), a1 = pack_bf16(qq[2], qq[3]);
                    if (h == 1 && k == 0) { a0 |= zero; a1 |= zero; }
                    const uint32_t a2 = pack_bf16(qq[4], qq[5]), a3 = pack_bf16(qq[6], qq[7]);
                    mma16816(sB, a0, a1, a2, a3, Kb[4 * h + 2 * k], Kb[4 * h + 2 * k + 1]);
                    mma16816(sA, a0, a1, a2, a3, Ka[4 * h + 2 * k], Ka[4 * h + 2 * k + 1]);
                    mma16816(sC, a0, a1, a2, a3, Kc[4 * h + 2 * k], Kc[4 * h + 2 * k + 1]);
                }
                const bool n0 = pm & 1, n1 = (int)pm < 0;
                const float l00 = n0 ? sB[0] : (first ? -INFINITY : sA[0]), l01 = n1 ? sB[1] : (first ? -INFINITY : sA[1]);
                const float l10 = n0 ? sC[2] : sB[2], l11 = n1 ? sC[3] : sB[3];
                const float x0 = -ls0 * quad_max(fmaxf(l00, l01)), x1 = -ls1 * quad_max(fmaxf(l10, l11));
                const float e00 = ex2(fmaf(l00, ls0, x0)), e01 = ex2(fmaf(l01, ls0, x0)), e10 = ex2(fmaf(l10, ls1, x1)), e11 = ex2(fmaf(l11, ls1, x1));
                const float i0 = rcp_approx(quad_sum(e00 + e01)), i1 = rcp_approx(quad_sum(e10 + e11));
                const uint32_t P0 = pack_bf16(e00 * i0, e01 * i0), P1 = pack_bf16(e10 * i1, e11 * i1);
                pB0[h] = P0 & pm; pA[h] = P0 & ~pm; pC[h] = P1 & pm; pB1[h] = P1 & ~pm; z0[h] = P0 & zero; z1[h] = P1 & zero;
            }
            float o[8][4];
            #pragma unroll
            for (int j = 0; j < 8; j++) {
                o[j][0] = o[j][1] = o[j][2] = o[j][3] = 0.f;
                mma16816(o[j], pB0[j >> 2], pB1[j >> 2], z0[j >> 2], pC[j >> 2], Vb[j - (j >> 2)], Vc[j - (j >> 2)]);
            }
            if (tid == 0) STAMP(12);
            FST(16);
            take_over(Va, 1);
            if (lane == 0) mbar_arrive(bars + 8 * B_DONEQ);
            if (tid == 0) STAMP(16);
            #pragma unroll
            for (int j = 0; j < 8; j++) mma1688(o[j], pA[j >> 2], z1[j >> 2], Va[j - (j >> 2)]);
            #pragma unroll
            for (int j = 0; j < 7; j++) {
                float v[4];
                #pragma unroll
                for (int c = 0; c < 4; c++) v[c] = j < 3 ? o[j][c] : j > 3 ? o[j + 1][c] : (t < 2 ? o[3][c] : o[4][c]);
                od[j * 256] = pack_bf16(v[0], v[1]);
                od[j * 256 + 32] = pack_bf16(v[2], v[3]);
            }
            if (tid == 0) STAMP(5);
            FST(17);
        }
        const int z = get_tag() - ep, slot1 = slot + z, tid1 = tid + z, warp1 = warp + z;
        ep += z;
        {
        ASSIGN_WORK(slot1)
        const int tid = tid1, lane = tid & 31, wg = warp1 >> 2, w = warp1 & 3, g = lane >> 2, t = lane & 3;
        tl = &sc->tiles[ep & 1];
        const uint32_t live = wg ^ 1;
        uint32_t rb0, rb1, late[14];
        const unsigned short* pb = (const unsigned short*)(live ? b2 + tt2 * 64 : b1 + ft * 64) + 16 * w + g;
        auto stage_late = [&]() {
            #pragma unroll
            for (int c = 0; c < 14; c++) asm volatile("st.shared.u32 [%0], %1;" :: "r"(sb + SM_H + wg * 8192 + (tid & 127) * 4 + c * 512), "r"(late[c]) : "memory");
            fence_async_smem();
            named_sync(1 + wg, 128);
        };
        auto store_late = [&](bool on, uint32_t* p) {
            #pragma unroll
            for (int c = 0; c < 4; c++)
                if (elect() && on && (c < 3 || w < 2)) bulk_st(p + (4 * c + w) * 256, sb + SM_H + wg * 8192 + (4 * c + w) * 512, 512);
            asm volatile("cp.async.bulk.commit_group;" ::: "memory");
        };
        auto undef = [](float (&v)[56]) {
            #pragma unroll
            for (int i = 0; i < 56; i++) asm volatile("" : "=f"(v[i]));
        };
        {
            float acc[56];
            const int hrow = 32 * (w >> 1) + 2 * ((lane & 7) + (lane & 8)) + (w & 1);
            const uint32_t ha = sb + SM_H + hrow * 128 + (((lane >> 4) ^ (hrow & 7)) << 4);
            uint4* sp = sc->stats + tt2 * 256 + 16 * w + g + 8 * (t & 1);
            uint4* sp_out = sp + q * 64;
            const uint4* sp_in = sp + (t & 2) * 64;
            uint32_t* hd = tl->hn + ((q >> 1) * 32 + (tt2 >> 1)) * 7168 + (q & 1) * 3584 + (tt2 & 1) * 128 + w * 32 + lane;
            pin_ptr(never, sp_out); pin_ptr(never, sp_in); pin_ptr(never, hd);
            float s0 = 0.f, s1 = 0.f, q0 = 0.f, q1 = 0.f, s2 = 0.f, s3 = 0.f, q2 = 0.f, q3 = 0.f;
            auto sums = [&](int j0, int j1) {
                #pragma unroll
                for (int j = j0; j < j1; j++) {
                    s0 += acc[4 * j]; s2 += acc[4 * j + 1]; q0 = fmaf(acc[4 * j], acc[4 * j], q0); q2 = fmaf(acc[4 * j + 1], acc[4 * j + 1], q2);
                    s1 += acc[4 * j + 2]; s3 += acc[4 * j + 3]; q1 = fmaf(acc[4 * j + 2], acc[4 * j + 2], q1); q3 = fmaf(acc[4 * j + 3], acc[4 * j + 3], q3);
                }
            };
            if (live) {
                mbar_wait(bars + 8 * B_FULLWO, 0);
                #pragma unroll
                for (int jp = 0; jp < 7; jp++) {
                    uint32_t xx[4];
                    ldsm4(xx, hcol(ha, jp));
                    #pragma unroll
                    for (int r = 0; r < 4; r++) { acc[8 * jp + 2 * r] = bf_lo(xx[r]); acc[8 * jp + 2 * r + 1] = bf_hi(xx[r]); }
                }
                reg_fence(acc);
                if (SPIN2) { named_sync(12, 256); spin_mma(bars + 8 * B_FULLX, never); }
                auto od_ = [&](int s) { return mkdesc(sb + SM_QO + s * 2048, 1024, 128, 0); };
                auto wd_ = [&](int s) { return mkdesc(sb + slot_wo(s >> 2) + (s & 3) * 2048, 8192, 1024, 1); };
                float accl[32], accr[24];
                #pragma unroll
                for (int i = 0; i < 5; i++) {
                    if (i < 4) mbar_wait(bars + 8 * (B_FULLO + i), 0);
                    if (i == 0 && tid == 0) STAMP(7);
                    if (i == 1) { rb0 = ld_u16(pb); rb1 = ld_u16(pb + 8); }
                    wg_fence();
                    #pragma unroll
                    for (int ss = 0; ss < 7; ss++) {
                        if (i < 3) wgmma_ss112<0, 1>(acc, od_(7 * i + ss), wd_(7 * i + ss));
                        else if (i == 4) wgmma_ss64<0, 1>(accl, od_(21 + ss), wd_(21 + ss));
                        else if (ss == 0) wgmma_ss48<0, 1, 0>(accr, od_(21), wd_(21) + 512);
                        else wgmma_ss48<0, 1>(accr, od_(21 + ss), wd_(21 + ss) + 512);
                    }
                    wg_commit();
                    if (i > 0) {
                        wg_wait<1>();
                        if (i == 3) {
                            reg_fence(acc);
                            #pragma unroll
                            for (int c = 0; c < 32; c++) accl[c] = __uint_as_float(__float_as_uint(acc[c]) | never);
                            reg_fence(accl);
                        }
                        if (i < 4 && leader) mbar_arrive(bars + 8 * (B_DONEO + i - 1));
                    }
                }
                reg_fence(accr);
                #pragma unroll
                for (int c = 0; c < 24; c++) acc[32 + c] += accr[c];
                sums(8, 14);
                pin4(never, s0, s1, s2, s3); pin4(never, q0, q1, q2, q3);
                wg_wait<0>();
                reg_fence(accl);
                #pragma unroll
                for (int c = 0; c < 32; c++) acc[c] = accl[c];
                if (leader) mbar_arrive(bars + 8 * (B_DONEO + 3));
                if (tid == 0) STAMP(8);
            } else { undef(acc); if (SPIN2) named_arrive(12, 256); }
            if (live || (DRY2 && w == 3)) {
            sums(0, 8);
            s0 += s2; s1 += s3; q0 += q2; q1 += q3;
            float sr = ((t & 1) ? s1 : s0) + __shfl_xor_sync(0xffffffffu, (t & 1) ? s0 : s1, 1), qr = ((t & 1) ? q1 : q0) + __shfl_xor_sync(0xffffffffu, (t & 1) ? q0 : q1, 1);
            sr += __shfl_xor_sync(0xffffffffu, sr, 2); qr += __shfl_xor_sync(0xffffffffu, qr, 2);
            st_relaxed4_if(t < 2 * live, sp_out, __float_as_uint(sr), __float_as_uint(qr), ep);
            const uint32_t tp = clock32();
            if (live) named_arrive(5, 256);
            if (tid == 0) STAMP(9);
            #pragma unroll
            for (int jp = 0; jp < 7; jp++)
                stsm4_if(live, hcol(ha, jp), pack_bf16(acc[8 * jp], acc[8 * jp + 1]), pack_bf16(acc[8 * jp + 2], acc[8 * jp + 3]),
                      pack_bf16(acc[8 * jp + 4], acc[8 * jp + 5]), pack_bf16(acc[8 * jp + 6], acc[8 * jp + 7]));
            uint4 v0, v1;
            if (POLL0) { while (clock32() - tp < POLL0) {} __syncwarp(); }
            do { v0 = ld_relaxed4(sp_in); v1 = ld_relaxed4(sp_in + 64); } while (live && __any_sync(0xffffffffu, v0.w != ep || v1.w != ep));
            if (tid == 0) STAMP(10);
            sr = __uint_as_float(v0.x) + __uint_as_float(v1.x); qr = __uint_as_float(v0.y) + __uint_as_float(v1.y);
            sr += __shfl_xor_sync(0xffffffffu, sr, 2); qr += __shfl_xor_sync(0xffffffffu, qr, 2);
            const float m = sr * (1.f / D_), var = fmaxf(qr * (1.f / D_) - m * m, 0.f);
            const float r = rsqrt_approx(fmaf(var, 4.f + 4.f * LN_EPS, 4.f * LN_EPS * LN_EPS)), c = -m * r;
            const float r0 = __shfl_sync(0xffffffffu, r, lane & ~1), c0 = __shfl_sync(0xffffffffu, c, lane & ~1);
            const float r1 = __shfl_sync(0xffffffffu, r, lane | 1), c1 = __shfl_sync(0xffffffffu, c, lane | 1);
            #pragma unroll
            for (int j = 0; j < 14; j++) st_global_if(live, hd + j * 256, pack_bf16(fmaf(acc[4 * j], r0, c0), fmaf(acc[4 * j + 1], r0, c0)));
            if (never) mbar_arrive(bars);
            #pragma unroll
            for (int j = 0; j < 14; j++) late[j] = pack_bf16(fmaf(acc[4 * j + 2], r1, c1), fmaf(acc[4 * j + 3], r1, c1));
            if (tid == 0) STAMP(11);
            }
        }
        if (!live) {
            check_tiles<0>(w, 4, 4, tl->o + tt2 * 14336, false, lane, true);
            rb0 = ld_u16(pb); rb1 = ld_u16(pb + 8);
            named_sync(5, 256);
            auto phase3 = [&](auto nc) {
                constexpr int NC = nc.value;
                float acc[4 * NC];
                uint32_t* ud = tl->u + (pr3 * 28 + (ft >> 1) + (NC == 14 ? 4 : 0)) * 7168 + col3 * 256 + (ft & 1) * 128 + w * 32 + lane;
                #pragma unroll
                for (int j = 0; j < 4 * NC; j++) acc[j] = 0.5f * bf_lo((j & 2) ? rb1 : rb0);
                #pragma unroll 1
                for (uint32_t pass = never; pass < 2; pass++) {
                    if (pass) {
                        if (SPIN3) { named_sync(3, 256); spin_mma(bars + 8 * (B_FULLX + 1), never); }
                        mix_mainloop<32>(TSVAL acc, leader);
                        if (leader) STAMP(14);
                    }
                    uint32_t pk[NC];
                    #pragma unroll
                    for (int j = 0; j < NC; j++) {
                        const float k = j < GDEP ? GELU_K1 : __uint_as_float(__float_as_uint(GELU_K1) | (pk[j - GDEP] & never));
                        pk[j] = pack_bf16(gelu_half(acc[4 * j], k), gelu_half(acc[4 * j + 1], k));
                        st_global_if(pass, ud + j * 256, pk[j]);
                    }
                }
                if (leader) STAMP(15);
                #pragma unroll
                for (int j = 0; j < NC; j++) late[j] = pack_bf16(gelu_half(acc[4 * j + 2], GELU_K1), gelu_half(acc[4 * j + 3], GELU_K1));
                if (NC == 14) {
                    stage_late();
                    mbar_wait(bars + 8 * (B_FULLB + LATE_AT4), 1);
                    store_late(true, tl->u + (pr3 * 28 + (ft >> 1) + 14) * 7168 + col3 * 256 + (ft & 1) * 128);
                } else {
                    #pragma unroll
                    for (int c = 0; c < NC; c++) st_global_if(1, ud + 4 * 7168 + c * 256, late[c]);
                    if (SPIN4) named_arrive(13, 256);
                }
            };
            if (early) phase3(Int<10>()); else phase3(Int<14>());
            if (w) {
                if (early && w == 1) fetch_times(TSVAL sc->go, 1, ep, lane);
                check_tiles<2>(CH_U - 1 + w, 3, 28, tl->u + (q >> 1) * 28 * 7168 + (q & 1) * 3584, false, lane, false);
                mbar_wait(bars + 8 * (B_DONE + CL_AT), 1);
                const int l = slot * 48 + (tid - 160) / 2;
                #pragma unroll
                for (int i = 0; i < 7; i++)
                    st_relaxed4_if(i < 6 || l < sizeof(Tiles) / 128 - 6 * 6144, (uint4*)&sc->tiles[~ep & 1] + (i * 6144 + l) * 8 + (lane & 7), EMPTY, EMPTY, EMPTY);
            }
            if (leader) mbar_wait_wd(bars + 8 * B_END, 0);
            return;
        }
        {
            float acc[56];
            const uint32_t ad = sb + SM_H + (16 * w + (lane & 15)) * 128 + (((lane >> 4) ^ (lane & 7)) << 4);
            const float bb0 = bf_lo(rb0), bb1 = bf_lo(rb1);
            named_sync(1, 128);
            #pragma unroll
            for (int jp = 0; jp < 7; jp++) {
                uint32_t hh[4];
                ldsm4(hh, hcol(ad, jp));
                #pragma unroll
                for (int r = 0; r < 4; r++) { acc[8 * jp + 2 * r] = bf_lo(hh[r]) + ((r & 1) ? bb1 : bb0); acc[8 * jp + 2 * r + 1] = bf_hi(hh[r]) + ((r & 1) ? bb1 : bb0); }
            }
            #pragma unroll 1
            for (uint32_t pass = never; pass < 2; pass++) {
                if (pass) {
                    const int nl = (early ? LATE_E : LATE_N) * 4;
                    named_sync(1, 128);
                    stage_late();
                    if (SPIN3) named_arrive(3, 256);
                    #pragma unroll 1
                    for (int k = 0; k < 2; k++) {
                        check_tiles<1>(w + nl * k, 4, k ? 32 : nl, tl->hn + pr3 * 32 * 7168 + col3 * 256, early, lane, k == 0);
                        store_late(k == 0, tl->hn + ((q >> 1) * 32 + 16 + (tt2 >> 1)) * 7168 + (q & 1) * 3584 + (tt2 & 1) * 128);
                    }
                    mbar_wait(bars + 8 * (B_DONE + START4), 0);
                    if (SPIN4 && early) { named_sync(13, 256); spin_mma(bars + 8 * (B_FULLX + 2), never); }
                    mix_mainloop<28>(TSVAL acc, leader);
                    if (leader) mbar_arrive(bars + 8 * B_END);
                    if (tid == 0) STAMP(18);
                }
                #pragma unroll
                for (int jp = 0; jp < 7; jp++)
                    stsm4_if(1, hcol(ad, jp), pack_bf16(acc[8 * jp], acc[8 * jp + 1]), pack_bf16(acc[8 * jp + 2], acc[8 * jp + 3]),
                             pack_bf16(acc[8 * jp + 4], acc[8 * jp + 5]), pack_bf16(acc[8 * jp + 6], acc[8 * jp + 7]));
                fence_async_smem();
                __syncwarp();
            }
            if (elect()) {
                tma2d_store(&tm_out64, c64, tt2 * 64 + 16 * w, sb + SM_H + w * 2048);
                tma2d_store(&tm_out48, c48, tt2 * 64 + 16 * w, sb + SM_H + 8192 + w * 2048);
            }
            asm volatile("cp.async.bulk.commit_group;" ::: "memory");
            asm volatile("cp.async.bulk.wait_group.read 0;" ::: "memory");
            if (tid == 0) { sc->epoch[slot] = ep; STAMP(19); }
        }
        }
    } else {
        asm volatile("setmaxnreg.dec.sync.aligned.u32 56;");
        int warp2; asm("mov.u32 %0, %1;" : "=r"(warp2) : "r"(warp));
        if (warp2 > 8) {
            ASSIGN_WORK(get_slot())
            if (slot >= 128) return;
            uint32_t ep, cl;
            uint4* const oh = sc->hint_o + (2 * tb * 32 + hp * 4) * 2 + (lane & 3);
            uint4* const hu = sc->hint_u + (early ? ech * 8 + ft : 40 + q * 20 + ft) * 2;
            if (warp == 10) {
                post_hint(sc->hint_h + (q * 32 + tt2) * 2, 0, lane);
                post_hint(hu, 0, lane);
            }
            if (warp == 11) {
                ep = ld_volatile(&sc->epoch[slot]) + 1; cl = ld_acquire(&sc->clean);
                post_hint(sc->hint_k + (tb * 8 + hp) * 2, 0, lane);
                if (lane < (tb < 15 ? 4 : 0)) st_relaxed4(oh + 128, 0, 0, 0, 0);
                if (lane < (tb ? 0 : 4)) st_relaxed4(oh, 0, 0, 0, 0);
            }
            if (elect()) {
                if (warp == 9) {
                    #pragma unroll
                    for (int i = B_DONE1; i < B_DONEO; i++) mbar_init(bars + 8 * i, i < B_DONEX ? 2 : i == B_DONEX ? 8 : 9);
                }
                #pragma unroll
                for (int i = 0; i < 54; i++) mbar_init(bars + 8 * (B_DONEO + i) + (warp - 9) * 432, 1);
                asm volatile("fence.mbarrier_init.release.cluster;" ::: "memory");
            }
            named_sync(8, 128);
            if (warp < 11) mbar_expect(sb + SM_RAW + 8 * (tid - 288), early && tid >= 292 && tid < 324 ? 10240 : 14336);
            if (warp == 9) { named_arrive(4, 64); named_arrive(9, 160); named_arrive(10, 160); }
            if (warp < 11) {
                ep = get_tag();
                mbar_wait(bars + 8 * (B_DONE1 + HALO_AT), 0);
                #pragma unroll 1
                for (int kv = 0; kv < 2; kv++) {
                    uint4 v0 = {}, v1 = {}, v2 = {};
                    if (tb > 0) {
                        const uint4* hg = sc->halo + ((((tb - 1) * 8 + hp) * 2 + warp - 9) * 2 + kv) * 96 + lane;
                        if (kv == 0) while (ld_relaxed(sc->hint_k + ((tb - 1) * 8 + hp) * 2) != ep) {}
                        do { v0 = ld_relaxed4(hg); v1 = ld_relaxed4(hg + 32); v2 = ld_relaxed4(hg + 64); } while (!__all_sync(0xffffffffu, v0.w == ep && v1.w == ep && v2.w == ep));
                    }
                    if (kv) mbar_wait(bars + 8 * (B_DONE1 + 5), 0);
                    const uint32_t hs = kv ? sb + lane * 16 + (warp - 9) * 1024 + SM_HALOV + 8192 : halo_kin(warp - 9, lane);
                    sts4(hs, v0.x, v0.y, v0.z, v1.x); sts4(hs + (kv ? 512 : 16), v1.y, v1.z, v2.x, v2.y);
                    __syncwarp();
                    if (lane == 0) mbar_arrive(bars + 8 * (B_HALO + 2 * kv + warp - 9));
                }
                if (tid == 288) STAMP(21);
            } else {
                const long long t0 = clock64();
                while (__any_sync(0xffffffffu, (int)(cl - ep) < 0)) { cl = ld_acquire(&sc->clean); if (clock64() - t0 > WD_CLKS) __trap(); }
                if (lane == 0) { *(volatile uint32_t*)(smem_raw + SM_TAG) = ep; mbar_arrive(bars + 8 * B_CLR); }
                uint4* hg = sc->halo + (tb * 8 + hp) * 384 + lane;
                #pragma unroll 1
                for (int kv = 0; kv < 2; kv++) {
                    const uint32_t hs = sb + lane * 16 + 3072 + (kv ? SM_HALOV : SM_HALOK);
                    named_sync(6 + kv, 96);
                    #pragma unroll
                    for (int p = 0; p < 2; p++) {
                        const uint4 u0 = lds4(hs + p * 4096), u1 = lds4(hs + p * 4096 + 512);
                        st_relaxed4(hg + p * 192, u0.x, u0.y, u0.z, ep); st_relaxed4(hg + p * 192 + 32, u0.w, u1.x, u1.y, ep); st_relaxed4(hg + p * 192 + 64, u1.z, u1.w, ep, ep);
                    }
                    hg += 96;
                    if (kv == 0) {
                        post_hint(sc->hint_k + (tb * 8 + hp) * 2, ep, lane);
                        #pragma unroll
                        for (int j = 0; j < 6; j++) st_relaxed4(hg + j * 32 + (j / 3) * 96, 0, 0, 0, 0);
                    }
                }
                const uint32_t now = gtime32() - LATE_O;
                if (lane < (tb < 15 ? 4 : 0)) st_relaxed4(oh + 128, ep, now, ep, now);
                if (lane < (tb ? 0 : 4)) st_relaxed4(oh, ep, now, ep, now);
                if (lane == 0) STAMP(23);
                if (lane == 0) mbar_arrive(bars + 8 * B_DONEQ);
            }
            if (warp > 9) {
                const Tiles* const tl = &sc->tiles[ep & 1];
                if (warp == 10) {
                    mbar_wait(bars + 8 * (B_FULLO + 3), 0);
                    mbar_wait(bars + 8 * (B_DONEO + HINT_H), 0);
                    post_time(sc->hint_h + (q * 32 + tt2) * 2, ep, lane);
                    mbar_wait(bars + 8 * (B_DONE + (early ? HINT_E : HINT_U)), 0);
                    post_time(hu, ep, lane);
                }
                if (warp == 11) {
                    mbar_wait(bars + 8 * (B_DONE + (early ? POLL_E : POLL_N)), 0);
                    fetch_times(TSVAL sc->go, 0, ep, lane);
                }
                check_tiles<2>(11 - warp, 2, CH_U, tl->u + (q >> 1) * 28 * 7168 + (q & 1) * 3584, false, lane, true);
            } else {
                int aslot = 0;
                if (lane == 0) { prefetch_map(&tm_out64); prefetch_map(&tm_out48); }
                #pragma unroll 1
                for (int i = 0; i < 30; i++) {
                    if (i == POLL_I && !early) fetch_times(TSVAL sc->go, 1, ep, lane);
                    int d = 2 * i - 11 + (i >= A4_FROM ? A4_DLY : 0);
                    if (early) d = i < 16 ? 1 + (i - NA_SLOTS) * AE_END / 9 : max(d, AE_W2);
                    mbar_wait(bars + 8 * (i < NA_SLOTS ? B_DONEQ + ((A_SCHED >> (4 * i)) & 15) : B_DONE + (d & 31)), d >= 32);
                    if (elect()) {
                        const uint32_t bar = bars + 8 * (B_FULLA + (i & 15)), dst = sb + SM_ARING + aslot * 16384;
                        mbar_expect(bar, 16384);
                        if (i < 16) tma5d(dst, &tm_w1, ft * 64, (i & 7) * 8, i >> 3, bar);
                        else tma5d(dst, &tm_w2, tt2 * 64, 8 * (i < 20 ? i & 1 : i < 25 ? i - 18 : i - 23), i < 20 ? (i >> 1) & 1 : i >= 25, bar);
                    }
                    aslot = aslot == NA_SLOTS - 1 ? 0 : aslot + 1;
                }
            }
        } else {
            const int slot0 = get_slot(), row0 = (slot0 >> 5) * 256 + (slot0 & 12) * 16;
            if (elect()) {
                prefetch_map(&tm_x);
                #pragma unroll
                for (int i = 0; i < 7; i++) mbar_init(bars + 8 * i, 1);
                asm volatile("fence.mbarrier_init.release.cluster;" ::: "memory");
            }
            named_arrive(0, 288);
            if (elect()) {
                #pragma unroll 1
                for (int kb = 0; kb < 7; kb++) {
                    load_x(kb, row0);
                    if (kb == 0) STAMP(22);
                }
                #pragma unroll
                for (int i = 7; i < B_DONE1; i++) mbar_init(bars + 8 * i, 1);
                asm volatile("fence.mbarrier_init.release.cluster;" ::: "memory");
            }
            named_arrive(8, 128);
            ASSIGN_WORK(get_slot())
            if (slot >= 128) return;
            #pragma unroll 1
            for (int kb = 0; kb < 7; kb++) {
                if (kb == 6) { named_sync(4, 64); mbar_wait(bars + 8 * B_DONEX, 0); }
                if (elect()) {
                    const uint32_t st = sb + slot_kv(kb), bar = bars + 8 * (B_FULLKV + kb);
                    mbar_expect(bar, 16384);
                    #pragma unroll
                    for (int i = 0; i < 2; i++) {
                        const int n = 2 * kb + (i ^ (G & 1));
                        tma2d(st + (n & 1) * 8192, &tm_wqkv, (n < 7 ? 448 : 896) + wcol, (n < 7 ? n : n - 7) * 64, bar);
                    }
                }
            }
            if (elect()) {
                mbar_expect(bars + 8 * B_FQ, 32768);
                mbar_expect(bars + 8 * (B_FQ + 1), 24576);
                #pragma unroll 1
                for (int i = 0; i < 7; i++) { const int j = i == 6 ? i : i ^ (G & 1); tma2d(sb + SM_QO + j * 8192, &tm_wqkv, wcol, j * 64, bars + 8 * (B_FQ + (i >> 2))); }
                mbar_expect(bars + 8 * B_FULLWO, 512 * 112 * 2);
            }
            #pragma unroll 1
            for (int i = 0; i < 7; i++) {
                const int kb = ((q & 1 ? WO_ORD1 : WO_ORD0) >> (4 * i)) & 7;
                if (kb < 5) mbar_wait(bars + 8 * (B_DONE1 + kb), 0);
                if (elect()) {
                    tma2d(sb + slot_wo(kb), &tm_wo64, c64, kb * 64, bars + 8 * B_FULLWO);
                    tma2d(sb + slot_wo(kb) + 8192, &tm_wo48, c48, kb * 64, bars + 8 * B_FULLWO);
                }
            }
            if (elect()) {
                tma2d(sb + SM_H, &tm_xr64, c64, tt2 * 64, bars + 8 * B_FULLWO);
                tma2d(sb + SM_H + 8192, &tm_xr48, c48, tt2 * 64, bars + 8 * B_FULLWO);
            }
            if (smem_u32(smem_raw) != SB) __trap();
            const uint32_t ep = get_tag();
            const Tiles* const tl = &sc->tiles[ep & 1];
            mbar_wait(bars + 8 * (B_DONE1 + 6), 0);
            const uint32_t t_o = last_hint(TSVAL sc->hint_o + (tt2 * 32 + lane) * 2, ep, 38);
            mbar_wait(bars + 8 * B_DONEQ, 0);
            wait_until(t_o + GO_O);
            if (elect()) {
                #pragma unroll
                for (int i = 0; i < 4; i++) {
                    bulk_ld(sb + SM_QO + i * 14336, tl->o + tt2 * 14336 + i * 3584, 14336, sb + SM_RAW + 8 * i);
                }
            }
            if (lane == 0) STAMP(20);
            if (SPIN2) { wait_until(t_o + GO_O + STOP2); if (lane == 0) mbar_arrive(bars + 8 * B_FULLX); }
            mbar_wait(bars + 8 * (B_DONEO + 2), 0);
            const uint32_t* src = tl->hn + pr3 * 32 * 7168 + col3 * 256;
            uint32_t bytes = early ? 10240 : 14336, dst = sb + SM_BRING, top = dst + (early ? NE_SLOTS * 10240 : NB_SLOTS * 14336), raw = sb + SM_RAW + 32;
            auto issue = [&]() {
                if (elect()) bulk_ld(dst, src, bytes, raw);
                src += 7168; raw += 8; dst += bytes;
                if (dst == top) dst = sb + SM_BRING;
            };
            uint2 th;
            do { th = ld_relaxed2((const uint2*)sc->go + (lane & 15)); } while (!__all_sync(0xffffffffu, th.x == ep));
            STAMP(42);
            mbar_wait(bars + 8 * (B_DONEO + 3), 0);
            {
                uint32_t bit = 1, wait = ~0u;
                #pragma unroll 1
                do {
                    while (wait & bit) wait = __ballot_sync(0xffffffffu, (int)(gtime32() - th.y - GO_H) < 0);
                    if (bit == 1) STAMP(29);
                    issue();
                    if (SPIN3 && bit == 1 << STOP3 && lane == 0) mbar_arrive(bars + 8 * (B_FULLX + 1));
                    bit *= 2;
                } while (dst != sb + SM_BRING);
            }
            uint32_t done = bars + 8 * B_DONE;
            #pragma unroll 1
            do { mbar_wait(done, 0); done += 8; issue(); } while (raw != sb + SM_RAW + 288);
            if (early) mbar_wait(bars + 8 * (B_DONE + 31), 0);
            src = tl->u + (q >> 1) * 28 * 7168 + (q & 1) * 3584; bytes = 14336; dst = sb + SM_BRING; top = dst + NB_SLOTS * 14336;
            done = bars + 8 * (B_DONE + 24);
            #pragma unroll 1
            for (uint32_t par = 0; par < 2; par++) {
                mbar_wait(bars + 8 * (B_GO + par), 0);
                const uint32_t ts = *(volatile uint32_t*)(smem_raw + SM_TIME + 128 * par + 4 * lane);
                if (par) done = bars + 8 * B_DONE;
                uint32_t bit = 1, wait = ~0u;
                #pragma unroll 1
                do {
                    while (wait & bit) wait = __ballot_sync(0xffffffffu, (int)(gtime32() - ts) < 0);
                    if (bit == 1) STAMP(par ? 36 : 30);
                    mbar_wait(done, par); done += 8;
                    issue();
                    if (SPIN4 && bit == 1 << STOP3 && lane + par == 0) mbar_arrive(bars + 8 * (B_FULLX + 2));
                    bit *= 2;
                } while (bit != (par ? 1 << 20 : 1 << 8));
            }
        }
    }
}

typedef CUresult (*EncodeFn)(CUtensorMap*, CUtensorMapDataType, cuuint32_t, void*, const cuuint64_t*, const cuuint64_t*, const cuuint32_t*,
                             const cuuint32_t*, CUtensorMapInterleave, CUtensorMapSwizzle, CUtensorMapL2promotion, CUtensorMapFloatOOBfill);

void make_map(EncodeFn fn, CUtensorMap* tm, const void* ptr, int rank, const cuuint64_t* dims, const cuuint64_t* strides, const cuuint32_t* box, CUtensorMapSwizzle sw) {
    cuuint32_t es[5] = {1, 1, 1, 1, 1};
    fn(tm, CU_TENSOR_MAP_DATA_TYPE_BFLOAT16, rank, const_cast<void*>(ptr), dims, strides, box, es, CU_TENSOR_MAP_INTERLEAVE_NONE, sw,
       CU_TENSOR_MAP_L2_PROMOTION_NONE, CU_TENSOR_MAP_FLOAT_OOB_FILL_NONE);
}

}

extern "C" void kernel_launch(void* const* d_in, const int* in_sizes, int n_in, void* d_out, int out_size) {
    const __nv_bfloat16* x = (const __nv_bfloat16*)d_in[0];
    const __nv_bfloat16* wqkv = (const __nv_bfloat16*)d_in[1];
    const __nv_bfloat16* wo = (const __nv_bfloat16*)d_in[2];
    const __nv_bfloat16* w1 = (const __nv_bfloat16*)d_in[4];
    const __nv_bfloat16* b1 = (const __nv_bfloat16*)d_in[5];
    const __nv_bfloat16* w2 = (const __nv_bfloat16*)d_in[6];
    const __nv_bfloat16* b2 = (const __nv_bfloat16*)d_in[7];

    void* fnp = nullptr; cudaDriverEntryPointQueryResult qr;
    cudaGetDriverEntryPoint("cuTensorMapEncodeTiled", &fnp, cudaEnableDefault, &qr);
    EncodeFn fn = (EncodeFn)fnp;
    CUtensorMap tx, twqkv, two64, two48, tw1, tw2, txr64, txr48, tout64, tout48;
    { cuuint64_t d[3] = {448, 2, 1024}, s[2] = {896, 1792}; cuuint32_t b[3] = {64, 1, 64}; make_map(fn, &tx, x, 3, d, s, b, CU_TENSOR_MAP_SWIZZLE_128B); }
    { cuuint64_t d[2] = {1344, 448}, s[1] = {2688}; cuuint32_t b[2] = {64, 64}; make_map(fn, &twqkv, wqkv, 2, d, s, b, CU_TENSOR_MAP_SWIZZLE_128B); }
    { cuuint64_t d[2] = {448, 448}, s[1] = {896}; cuuint32_t b[2] = {64, 64}; make_map(fn, &two64, wo, 2, d, s, b, CU_TENSOR_MAP_SWIZZLE_128B); }
    { cuuint64_t d[2] = {448, 448}, s[1] = {896}; cuuint32_t b[2] = {48, 64}; make_map(fn, &two48, wo, 2, d, s, b, CU_TENSOR_MAP_SWIZZLE_128B); }
    { cuuint64_t d[5] = {1792, 8, 2, 64, 2}, s[4] = {2 * 3584, 3584, 32 * 3584, 16 * 3584}; cuuint32_t b[5] = {64, 8, 2, 8, 1}; make_map(fn, &tw1, w1, 5, d, s, b, CU_TENSOR_MAP_SWIZZLE_128B); }
    { cuuint64_t d[5] = {2048, 8, 2, 56, 2}, s[4] = {4096, 16 * 4096, 32 * 4096, 8 * 4096}; cuuint32_t b[5] = {64, 8, 2, 8, 1}; make_map(fn, &tw2, w2, 5, d, s, b, CU_TENSOR_MAP_SWIZZLE_128B); }
    { cuuint64_t d[2] = {448, 2048}, s[1] = {896}; cuuint32_t b[2] = {64, 64}; make_map(fn, &txr64, x, 2, d, s, b, CU_TENSOR_MAP_SWIZZLE_128B); }
    { cuuint64_t d[2] = {448, 2048}, s[1] = {896}; cuuint32_t b[2] = {48, 64}; make_map(fn, &txr48, x, 2, d, s, b, CU_TENSOR_MAP_SWIZZLE_128B); }
    { cuuint64_t d[2] = {448, 2048}, s[1] = {896}; cuuint32_t b[2] = {64, 16}; make_map(fn, &tout64, d_out, 2, d, s, b, CU_TENSOR_MAP_SWIZZLE_128B); }
    { cuuint64_t d[2] = {448, 2048}, s[1] = {896}; cuuint32_t b[2] = {48, 16}; make_map(fn, &tout48, d_out, 2, d, s, b, CU_TENSOR_MAP_SWIZZLE_128B); }

    void* scv = nullptr;
    cudaGetSymbolAddress(&scv, g_scratch);
    Scratch* scp = (Scratch*)scv;
    int dev = 0, sms = 0;
    cudaGetDevice(&dev);
    cudaDeviceGetAttribute(&sms, cudaDevAttrMultiProcessorCount, dev);
    if (sms == 132) {
        cudaFuncSetAttribute(fused_kernel<true>, cudaFuncAttributeMaxDynamicSharedMemorySize, SM_TOTAL);
        fused_kernel<true><<<132, 384, SM_TOTAL>>>(scp, wo, w1, b1, w2, b2, tx, twqkv, two64, two48, tw1, tw2, txr64, txr48, tout64, tout48);
    } else {
        cudaFuncSetAttribute(fused_kernel<false>, cudaFuncAttributeMaxDynamicSharedMemorySize, SM_TOTAL);
        fused_kernel<false><<<132, 384, SM_TOTAL>>>(scp, wo, w1, b1, w2, b2, tx, twqkv, two64, two48, tw1, tw2, txr64, txr48, tout64, tout48);
    }
}
```

```cpp
#include <cuda_runtime.h>
#include <cuda_bf16.h>
#include <cuda.h>
#include <stdint.h>

namespace {

constexpr int D_ = 448;
constexpr float LN_EPS = 1e-5f;
constexpr float LOG2E_SCALE = 0.1889822365046136f * 1.4426950408889634f;

struct Tiles {
    uint32_t o[32 * 57344 / 4];
    uint32_t hn[4 * 32 * 14336 / 4];
    uint32_t u[4 * 28 * 14336 / 4];
};
struct Scratch {
    uint4 halo[128 * 2 * 2 * 3 * 32];
    uint4 stats[32 * 4 * 64];
    uint4 hint_k[128 * 2];
    uint4 hint_o[32 * 32 * 2];
    uint4 hint_h[4 * 32 * 2];
    uint4 hint_u[128 * 2];
    uint4 go[24];
    uint32_t epoch[160];
    uint32_t clean;
    alignas(1024) Tiles tiles[2];
};
__device__ Scratch g_scratch;
#define STAMP(i) do {} while (0)
#define FST(i) do {} while (0)
#define TSARG
#define TSVAL

constexpr uint32_t SB = 1024;
constexpr int SM_SLOT = 16384;
__device__ __forceinline__ constexpr uint32_t slot_x(int kb) { return (kb ? 6 + kb : 0) * SM_SLOT; }
__device__ __forceinline__ constexpr uint32_t slot_kv(int kb) { return (kb < 5 ? 2 + kb : 6 - kb) * SM_SLOT; }
__device__ __forceinline__ constexpr uint32_t slot_wo(int kb) { return (kb < 6 ? 2 + kb : 12) * SM_SLOT; }
constexpr int SM_QO = 8 * SM_SLOT;
constexpr int SM_HALOK = SM_QO + 57344, SM_HALOV = 1 * SM_SLOT;
constexpr int NA_SLOTS = 6, NB_SLOTS = 8;
constexpr int SM_ARING = 0;
constexpr int SM_BRING = NA_SLOTS * 16384;
constexpr int SM_H = 212992;
__device__ __forceinline__ uint32_t halo_kin(int par, int lane) { return SB + SM_H + 8192 + par * 4096 + lane * 128 + ((~lane & 6) << 4); }
constexpr int SM_BAR = 229376;
constexpr int SM_TAG = SM_BAR + 1536;
constexpr int SM_TIME = SM_TAG + 256;
constexpr int SM_TOTAL = SM_TIME + 256;
constexpr int B_FULLX = 0;
constexpr int B_FULLKV = 7;
constexpr int B_FQ = 14;
constexpr int B_DONE1 = 16;
constexpr int B_DONEX = 23;
constexpr int B_DONEQ = 24;
constexpr int B_DONEO = 25;
constexpr int B_FULLO = 29;
constexpr int B_FULLWO = 33;
constexpr int B_END = 34;
constexpr int B_HALO = 35;
constexpr int B_FULLA = 39;
constexpr int B_FULLB = 55;
constexpr int B_DONE = 87;
constexpr int B_GO = 119;
constexpr int B_CLR = 121;
constexpr int SM_RAW = SM_BAR + 8 * 122;

constexpr long long WD_CLKS = 2000000000ll;

template<int N> struct Int { static constexpr int value = N; };
template<int A, int B, class F> __device__ __forceinline__ void static_for(F&& f) { if constexpr (A < B) { f(Int<A>()); static_for<A + 1, B>(f); } }

__device__ __forceinline__ uint32_t smem_u32(const void* p) { return (uint32_t)__cvta_generic_to_shared(p); }
__device__ __forceinline__ void mbar_init(uint32_t bar, uint32_t cnt) { asm volatile("mbarrier.init.shared::cta.b64 [%0], %1;" :: "r"(bar), "r"(cnt) : "memory"); }
__device__ __forceinline__ void mbar_expect(uint32_t bar, uint32_t bytes) { asm volatile("mbarrier.arrive.expect_tx.shared::cta.b64 _, [%0], %1;" :: "r"(bar), "r"(bytes) : "memory"); }
__device__ __forceinline__ void mbar_arrive(uint32_t bar) { asm volatile("mbarrier.arrive.shared::cta.b64 _, [%0];" :: "r"(bar) : "memory"); }
__device__ __forceinline__ bool mbar_try(uint32_t bar, uint32_t parity) {
    uint32_t ok;
    asm volatile("{\n.reg .pred p;\nmbarrier.try_wait.parity.shared::cta.b64 p, [%1], %2;\nselp.u32 %0, 1, 0, p;\n}" : "=r"(ok) : "r"(bar), "r"(parity) : "memory");
    return ok;
}
__device__ __forceinline__ bool mbar_test(uint32_t bar, uint32_t parity) {
    uint32_t ok;
    asm volatile("{\n.reg .pred p;\nmbarrier.test_wait.parity.shared::cta.b64 p, [%1], %2;\nselp.u32 %0, 1, 0, p;\n}" : "=r"(ok) : "r"(bar), "r"(parity) : "memory");
    return ok;
}
__device__ __forceinline__ void mbar_wait(uint32_t bar, uint32_t parity) {
    asm volatile("{\n.reg .pred p;\n"
                 "WAIT_LOOP:\n"
                 "mbarrier.try_wait.parity.shared::cta.b64 p, [%0], %1;\n"
                 "@!p bra WAIT_LOOP;\n}" :: "r"(bar), "r"(parity) : "memory");
}
__device__ __forceinline__ void mbar_wait_wd(uint32_t bar, uint32_t parity) {
    asm volatile("{\n.reg .pred p, q;\n.reg .u32 s, t;\nmov.u32 s, %%clock;\n"
                 "WAIT_LOOP:\n"
                 "mbarrier.try_wait.parity.shared::cta.b64 p, [%0], %1;\nmov.u32 t, %%clock;\nsub.u32 t, t, s;\nsetp.lt.and.s32 q, t, 0, !p;\n@q trap;\n"
                 "@!p bra WAIT_LOOP;\n}" :: "r"(bar), "r"(parity) : "memory");
}
__device__ __forceinline__ bool elect() { uint32_t p; asm volatile("{\n.reg .pred P;\nelect.sync _|P, 0xffffffff;\nselp.u32 %0, 1, 0, P;\n}" : "=r"(p)); return p; }
__device__ __forceinline__ void tma2d(uint32_t dst, const CUtensorMap* tm, int c0, int c1, uint32_t bar) {
    asm volatile("cp.async.bulk.tensor.2d.shared::cluster.global.mbarrier::complete_tx::bytes [%0], [%1, {%3, %4}], [%2];" :: "r"(dst), "l"(tm), "r"(bar), "r"(c0), "r"(c1) : "memory");
}
__device__ __forceinline__ void tma3d(uint32_t dst, const CUtensorMap* tm, int c0, int c1, int c2, uint32_t bar) {
    asm volatile("cp.async.bulk.tensor.3d.shared::cluster.global.mbarrier::complete_tx::bytes [%0], [%1, {%3, %4, %5}], [%2];" :: "r"(dst), "l"(tm), "r"(bar), "r"(c0), "r"(c1), "r"(c2) : "memory");
}
__device__ __forceinline__ void tma5d(uint32_t dst, const CUtensorMap* tm, int c0, int c3, int c4, uint32_t bar) {
    asm volatile("cp.async.bulk.tensor.5d.shared::cluster.global.mbarrier::complete_tx::bytes [%0], [%1, {%3, 0, 0, %4, %5}], [%2];" :: "r"(dst), "l"(tm), "r"(bar), "r"(c0), "r"(c3), "r"(c4) : "memory");
}
__device__ __forceinline__ void tma5d_prefetch(const CUtensorMap* tm, int c0, int c3, int c4) {
    asm volatile("cp.async.bulk.prefetch.tensor.5d.L2.global [%0, {%1, 0, 0, %2, %3}];" :: "l"(tm), "r"(c0), "r"(c3), "r"(c4) : "memory");
}
__device__ __forceinline__ void tma2d_store(const CUtensorMap* tm, int c0, int c1, uint32_t src) {
    asm volatile("cp.async.bulk.tensor.2d.global.shared::cta.bulk_group [%0, {%2, %3}], [%1];" :: "l"(tm), "r"(src), "r"(c0), "r"(c1) : "memory");
}
__device__ __forceinline__ void bulk_st(void* dst, uint32_t src, uint32_t bytes) {
    asm volatile("cp.async.bulk.global.shared::cta.bulk_group [%0], [%1], %2;" :: "l"(dst), "r"(src), "r"(bytes) : "memory");
}
__device__ __forceinline__ void bulk_ld(uint32_t dst, const void* src, uint32_t bytes, uint32_t bar) {
    asm volatile("cp.async.bulk.shared::cluster.global.mbarrier::complete_tx::bytes [%0], [%1], %2, [%3];" :: "r"(dst), "l"(src), "r"(bytes), "r"(bar) : "memory");
}
__device__ __forceinline__ void bulk_prefetch(const void* src, uint32_t bytes) { asm volatile("cp.async.bulk.prefetch.L2.global [%0], %1;" :: "l"(src), "r"(bytes) : "memory"); }
__device__ __forceinline__ void prefetch_map(const CUtensorMap* tm) { asm volatile("prefetch.tensormap [%0];" :: "l"(tm) : "memory"); }
__device__ __forceinline__ void st_global_if(uint32_t c, uint32_t* p, uint32_t v) {
    asm volatile("{\n.reg .pred p;\nsetp.ne.u32 p, %2, 0;\n@p st.global.u32 [%0], %1;\n}" :: "l"(p), "r"(v), "r"(c) : "memory");
}
__device__ __forceinline__ void st_relaxed4_if(bool c, uint4* p, uint32_t a, uint32_t b, uint32_t d) {
    asm volatile("{\n.reg .b128 t;\n.reg .b64 a, b;\n.reg .pred p;\nsetp.ne.u32 p, %4, 0;\nmov.b64 a, {%1, %2};\nmov.b64 b, {%3, %3};\nmov.b128 t, {a, b};\n@p st.relaxed.gpu.global.b128 [%0], t;\n}" :: "l"(p), "r"(a), "r"(b), "r"(d), "r"((uint32_t)c) : "memory");
}
__device__ __forceinline__ void pin_ptr(uint32_t never, const void* a) {
    asm volatile("{\n.reg .pred p;\nsetp.ne.u32 p, %1, 0;\n@p st.shared.u64 [%1], %0;\n}" :: "l"(a), "r"(never) : "memory");
}
__device__ __forceinline__ void pin4(uint32_t never, float a, float b, float c, float d) {
    asm volatile("{\n.reg .pred p;\nsetp.ne.u32 p, %4, 0;\n@p st.shared.v4.f32 [%4], {%0,%1,%2,%3};\n}" :: "f"(a), "f"(b), "f"(c), "f"(d), "r"(never) : "memory");
}
__device__ __forceinline__ void fence_async_smem() { asm volatile("fence.proxy.async.shared::cta;" ::: "memory"); }
__device__ __forceinline__ uint32_t ld_acquire(const void* p) { uint32_t v; asm volatile("ld.acquire.gpu.global.u32 %0, [%1];" : "=r"(v) : "l"(p) : "memory"); return v; }
__device__ __forceinline__ void st_release(void* p, uint32_t v) { asm volatile("st.release.gpu.global.u32 [%0], %1;" :: "l"(p), "r"(v) : "memory"); }
__device__ __forceinline__ uint32_t ld_relaxed(const void* p) { uint32_t v; asm volatile("ld.relaxed.gpu.global.u32 %0, [%1];" : "=r"(v) : "l"(p) : "memory"); return v; }
__device__ __forceinline__ uint2 ld_relaxed2(const void* p) {
    uint2 v; asm volatile("{\n.reg .b64 a;\nld.relaxed.gpu.global.b64 a, [%2];\nmov.b64 {%0, %1}, a;\n}" : "=r"(v.x), "=r"(v.y) : "l"(p) : "memory"); return v;
}
__device__ __forceinline__ void st_relaxed2(void* p, uint32_t a, uint32_t b) {
    asm volatile("{\n.reg .b64 a;\nmov.b64 a, {%1, %2};\nst.relaxed.gpu.global.b64 [%0], a;\n}" :: "l"(p), "r"(a), "r"(b) : "memory");
}
__device__ __forceinline__ uint4 ld_relaxed4(const uint4* p) {
    uint4 v;
    asm volatile("{\n.reg .b128 t;\n.reg .b64 a, b;\nld.relaxed.gpu.global.b128 t, [%4];\nmov.b128 {a, b}, t;\nmov.b64 {%0, %1}, a;\nmov.b64 {%2, %3}, b;\n}" : "=r"(v.x), "=r"(v.y), "=r"(v.z), "=r"(v.w) : "l"(p) : "memory");
    return v;
}
__device__ __forceinline__ void st_relaxed4(uint4* p, uint32_t a, uint32_t b, uint32_t c, uint32_t d) {
    asm volatile("{\n.reg .b128 t;\n.reg .b64 a, b;\nmov.b64 a, {%1, %2};\nmov.b64 b, {%3, %4};\nmov.b128 t, {a, b};\nst.relaxed.gpu.global.b128 [%0], t;\n}" :: "l"(p), "r"(a), "r"(b), "r"(c), "r"(d) : "memory");
}
__device__ __forceinline__ uint32_t ld_u16(const unsigned short* p) { uint32_t v; asm volatile("ld.volatile.global.u16 %0, [%1];" : "=r"(v) : "l"(p) : "memory"); return v; }
__device__ __forceinline__ uint32_t ld_volatile(const uint32_t* p) { uint32_t v; asm volatile("ld.volatile.global.u32 %0, [%1];" : "=r"(v) : "l"(p) : "memory"); return v; }
__device__ __forceinline__ void named_arrive(int id, int n) { asm volatile("bar.arrive %0, %1;" :: "r"(id), "r"(n) : "memory"); }
__device__ __forceinline__ void named_sync(int id, int n) { asm volatile("bar.sync %0, %1;" :: "r"(id), "r"(n) : "memory"); }
__device__ __forceinline__ void named_arrive_if(uint32_t c, int id, int n) { asm volatile("{\n.reg .pred p;\nsetp.ne.u32 p, %2, 0;\n@p bar.arrive %0, %1;\n}" :: "r"(id), "r"(n), "r"(c) : "memory"); }
__device__ __forceinline__ bool named_any(int id, int n, bool v) {
    uint32_t r; asm volatile("{\n.reg .pred p, q;\nsetp.ne.u32 p, %3, 0;\nbar.red.or.pred q, %1, %2, p;\nselp.u32 %0, 1, 0, q;\n}" : "=r"(r) : "r"(id), "r"(n), "r"((uint32_t)v) : "memory"); return r;
}
__device__ __forceinline__ void wg_fence() { asm volatile("wgmma.fence.sync.aligned;" ::: "memory"); }
__device__ __forceinline__ void wg_commit() { asm volatile("wgmma.commit_group.sync.aligned;" ::: "memory"); }
template<int N> __device__ __forceinline__ void wg_wait() { asm volatile("wgmma.wait_group.sync.aligned %0;" :: "n"(N) : "memory"); }
template<int N> __device__ __forceinline__ void reg_fence(float (&d)[N]) {
    #pragma unroll
    for (int i = 0; i < N; i++) asm volatile("" : "+f"(d[i]) :: "memory");
}
__device__ __forceinline__ constexpr uint64_t mkdesc(uint32_t addr, uint32_t lbo, uint32_t sbo, uint32_t sw) {
    return (uint64_t)((addr & 0x3FFFF) >> 4) | ((uint64_t)(lbo >> 4) << 16) | ((uint64_t)(sbo >> 4) << 32) | ((uint64_t)sw << 62);
}
__device__ __forceinline__ void ldsm4(uint32_t (&r)[4], uint32_t addr) {
    asm volatile("ldmatrix.sync.aligned.m8n8.x4.shared.b16 {%0,%1,%2,%3}, [%4];" : "=r"(r[0]), "=r"(r[1]), "=r"(r[2]), "=r"(r[3]) : "r"(addr) : "memory");
}
__device__ __forceinline__ void stsm4_if(uint32_t c, uint32_t addr, uint32_t r0, uint32_t r1, uint32_t r2, uint32_t r3) {
    asm volatile("{\n.reg .pred p;\nsetp.ne.u32 p, %5, 0;\n@p stmatrix.sync.aligned.m8n8.x4.shared.b16 [%0], {%1,%2,%3,%4};\n}" :: "r"(addr), "r"(r0), "r"(r1), "r"(r2), "r"(r3), "r"(c) : "memory");
}
__device__ __forceinline__ void sts4(uint32_t a, uint32_t x, uint32_t y, uint32_t z, uint32_t w) { asm volatile("st.shared.v4.u32 [%0], {%1,%2,%3,%4};" :: "r"(a), "r"(x), "r"(y), "r"(z), "r"(w) : "memory"); }
__device__ __forceinline__ uint4 lds4(uint32_t a) { uint4 v; asm volatile("ld.shared.v4.u32 {%0,%1,%2,%3}, [%4];" : "=r"(v.x), "=r"(v.y), "=r"(v.z), "=r"(v.w) : "r"(a) : "memory"); return v; }
__device__ __forceinline__ uint32_t movtrans(uint32_t a) { uint32_t d; asm volatile("movmatrix.sync.aligned.m8n8.trans.b16 %0, %1;" : "=r"(d) : "r"(a)); return d; }
__device__ __forceinline__ uint32_t pack_bf16(float lo, float hi) { uint32_t r; asm("cvt.rn.bf16x2.f32 %0, %1, %2;" : "=r"(r) : "f"(hi), "f"(lo)); return r; }
__device__ __forceinline__ void sub_bf16x2(uint32_t& a, uint32_t b) { asm volatile("sub.rn.bf16x2 %0, %0, %1;" : "+r"(a) : "r"(b)); }
__device__ __forceinline__ float bf_lo(uint32_t v) { return __uint_as_float(v << 16); }
__device__ __forceinline__ float bf_hi(uint32_t v) { return __uint_as_float(v & 0xffff0000u); }
__device__ __forceinline__ void mma16816(float (&c)[4], uint32_t a0, uint32_t a1, uint32_t a2, uint32_t a3, uint32_t b0, uint32_t b1) {
    asm volatile("mma.sync.aligned.m16n8k16.row.col.f32.bf16.bf16.f32 {%0,%1,%2,%3}, {%4,%5,%6,%7}, {%8,%9}, {%0,%1,%2,%3};"
        : "+f"(c[0]), "+f"(c[1]), "+f"(c[2]), "+f"(c[3]) : "r"(a0), "r"(a1), "r"(a2), "r"(a3), "r"(b0), "r"(b1));
}
__device__ __forceinline__ void mma1688(float (&c)[4], uint32_t a0, uint32_t a1, uint32_t b0) {
    asm volatile("mma.sync.aligned.m16n8k8.row.col.f32.bf16.bf16.f32 {%0,%1,%2,%3}, {%4,%5}, {%6}, {%0,%1,%2,%3};"
        : "+f"(c[0]), "+f"(c[1]), "+f"(c[2]), "+f"(c[3]) : "r"(a0), "r"(a1), "r"(b0));
}
__device__ __forceinline__ float quad_sum(float v) { v += __shfl_xor_sync(0xffffffffu, v, 1); v += __shfl_xor_sync(0xffffffffu, v, 2); return v; }
__device__ __forceinline__ float quad_max(float v) { v = fmaxf(v, __shfl_xor_sync(0xffffffffu, v, 1)); v = fmaxf(v, __shfl_xor_sync(0xffffffffu, v, 2)); return v; }
__device__ __forceinline__ float ex2(float x) { float y; asm("ex2.approx.ftz.f32 %0, %1;" : "=f"(y) : "f"(x)); return y; }
__device__ __forceinline__ float rsqrt_approx(float x) { float y; asm("rsqrt.approx.ftz.f32 %0, %1;" : "=f"(y) : "f"(x)); return y; }
__device__ __forceinline__ float rcp_approx(float x) { float y; asm("rcp.approx.ftz.f32 %0, %1;" : "=f"(y) : "f"(x)); return y; }
constexpr float GELU_K1 = 2.f * 0.7978845608028654f;
__device__ __forceinline__ float gelu_half(float hx, float k1) {
    const float z = hx * fmaf(hx * hx, 8.f * 0.044715f * 0.7978845608028654f, k1);
    float t; asm("tanh.approx.f32 %0, %1;" : "=f"(t) : "f"(z));
    return fmaf(hx, t, hx);
}
__device__ __forceinline__ uint32_t gtime32() { uint32_t t; asm volatile("mov.u32 %0, %%globaltimer_lo;" : "=r"(t)); return t; }
__device__ __forceinline__ uint32_t clock32() { uint32_t t; asm volatile("mov.u32 %0, %%clock;" : "=r"(t)); return t; }
#define PF_PACE 160
#define PF_AT 16500
#define PF_N 256
#define NSQ 6
#define NPIPE 1
#define HALO_AT 3
#define HINT_U 18
#define HINT_E 16
#define SP_AT 2000
#define A_SCHED 0x322188
#define WO_ORD0 0x4321065
#define WO_ORD1 0x3465210
#define CL_AT 23
#define WARM_AT 300
#define A_HOLD 31
#define GO_H 1700
#define GO_E 1830
#define GO_U 2200
#define GO_O 1280
#define LATE_O 256
#define DRY2 1
#define LATE_AT 0
#define LATE_AT4 0
#define HINT_H 0
#define SLACK 0
#define SLACK_U 128
#define GDEP 4
#define START4 30
#define EMAP 1
#define DEPTH_N 1
#define DEPTH_E 2
#define PFE_AT 99
#define PFN_END 0
#define NE_SLOTS 11
#define POLL_E 26
#define POLL_U 22
#define CH_U 28
#define AE_END 18
#define AE_W2 27
#define PF1_AT 12000
#define PF1_N 80
#define PF1_PACE 160
#define HOLD 0
#define X0 1
#define GO_E2 300
#define GO_U2 400
#define POLL_I 20
#define POLL_N 19
#define LATES 0x11111111u
#define GATE_J 22
#define GATE_D 16
#define ROLES 0x65432107u
#define LATE_E 1
#define LATE_N 1
#define CL_I0 0
#define CL_SP 1000
#define POLL0 250
#define A4_FROM 23
#define A4_DLY 2
#define SPIN2 1
#define SPIN3 1
#define SPIN4 0
#define SPIN_N 2
#define STOP2 200
#define STOP3 3
#define PF0_AT 5000
#define PF0_N 48
#define PF0_PACE 140
#define POLL_H 3
#define CH_H 8
#define HINT_F 2
template<int TB> __device__ __forceinline__ void wgmma_rs56(float (&d)[28], const uint32_t (&a)[4], uint64_t db, int sc) {
    asm volatile("{\n.reg .pred p;\nsetp.ne.b32 p, %33, 0;\n"
        "wgmma.mma_async.sync.aligned.m64n56k16.f32.bf16.bf16 {%0, %1, %2, %3, %4, %5, %6, %7, %8, %9, %10, %11, %12, %13, %14, %15, %16, %17, %18, %19, %20, %21, %22, %23, %24, %25, %26, %27}, {%28, %29, %30, %31}, %32, p, 1, 1, %34;\n}\n"
        : "+f"(d[0]), "+f"(d[1]), "+f"(d[2]), "+f"(d[3]), "+f"(d[4]), "+f"(d[5]), "+f"(d[6]), "+f"(d[7]), "+f"(d[8]), "+f"(d[9]), "+f"(d[10]), "+f"(d[11]), "+f"(d[12]), "+f"(d[13]), "+f"(d[14]), "+f"(d[15]), "+f"(d[16]), "+f"(d[17]), "+f"(d[18]), "+f"(d[19]), "+f"(d[20]), "+f"(d[21]), "+f"(d[22]), "+f"(d[23]), "+f"(d[24]), "+f"(d[25]), "+f"(d[26]), "+f"(d[27])
        : "r"(a[0]), "r"(a[1]), "r"(a[2]), "r"(a[3]), "l"(db), "r"(sc), "n"(TB));
}

template<int TA, int TB, int SC = 1> __device__ __forceinline__ void wgmma_ss112(float (&d)[56], uint64_t da, uint64_t db) {
    asm volatile("wgmma.mma_async.sync.aligned.m64n112k16.f32.bf16.bf16 {%0, %1, %2, %3, %4, %5, %6, %7, %8, %9, %10, %11, %12, %13, %14, %15, %16, %17, %18, %19, %20, %21, %22, %23, %24, %25, %26, %27, %28, %29, %30, %31, %32, %33, %34, %35, %36, %37, %38, %39, %40, %41, %42, %43, %44, %45, %46, %47, %48, %49, %50, %51, %52, %53, %54, %55}, %56, %57, %60, 1, 1, %58, %59;\n"
        : "+f"(d[0]), "+f"(d[1]), "+f"(d[2]), "+f"(d[3]), "+f"(d[4]), "+f"(d[5]), "+f"(d[6]), "+f"(d[7]), "+f"(d[8]), "+f"(d[9]), "+f"(d[10]), "+f"(d[11]), "+f"(d[12]), "+f"(d[13]), "+f"(d[14]), "+f"(d[15]), "+f"(d[16]), "+f"(d[17]), "+f"(d[18]), "+f"(d[19]), "+f"(d[20]), "+f"(d[21]), "+f"(d[22]), "+f"(d[23]), "+f"(d[24]), "+f"(d[25]), "+f"(d[26]), "+f"(d[27]), "+f"(d[28]), "+f"(d[29]), "+f"(d[30]), "+f"(d[31]), "+f"(d[32]), "+f"(d[33]), "+f"(d[34]), "+f"(d[35]), "+f"(d[36]), "+f"(d[37]), "+f"(d[38]), "+f"(d[39]), "+f"(d[40]), "+f"(d[41]), "+f"(d[42]), "+f"(d[43]), "+f"(d[44]), "+f"(d[45]), "+f"(d[46]), "+f"(d[47]), "+f"(d[48]), "+f"(d[49]), "+f"(d[50]), "+f"(d[51]), "+f"(d[52]), "+f"(d[53]), "+f"(d[54]), "+f"(d[55])
        : "l"(da), "l"(db), "n"(TA), "n"(TB), "n"(SC));
}

template<int TA, int TB, int SC = 1> __device__ __forceinline__ void wgmma_ss80(float (&d)[40], uint64_t da, uint64_t db) {
    asm volatile("wgmma.mma_async.sync.aligned.m64n80k16.f32.bf16.bf16 {%0, %1, %2, %3, %4, %5, %6, %7, %8, %9, %10, %11, %12, %13, %14, %15, %16, %17, %18, %19, %20, %21, %22, %23, %24, %25, %26, %27, %28, %29, %30, %31, %32, %33, %34, %35, %36, %37, %38, %39}, %40, %41, %44, 1, 1, %42, %43;\n"
        : "+f"(d[0]), "+f"(d[1]), "+f"(d[2]), "+f"(d[3]), "+f"(d[4]), "+f"(d[5]), "+f"(d[6]), "+f"(d[7]), "+f"(d[8]), "+f"(d[9]), "+f"(d[10]), "+f"(d[11]), "+f"(d[12]), "+f"(d[13]), "+f"(d[14]), "+f"(d[15]), "+f"(d[16]), "+f"(d[17]), "+f"(d[18]), "+f"(d[19]), "+f"(d[20]), "+f"(d[21]), "+f"(d[22]), "+f"(d[23]), "+f"(d[24]), "+f"(d[25]), "+f"(d[26]), "+f"(d[27]), "+f"(d[28]), "+f"(d[29]), "+f"(d[30]), "+f"(d[31]), "+f"(d[32]), "+f"(d[33]), "+f"(d[34]), "+f"(d[35]), "+f"(d[36]), "+f"(d[37]), "+f"(d[38]), "+f"(d[39])
        : "l"(da), "l"(db), "n"(TA), "n"(TB), "n"(SC));
}

template<int TA, int TB, int SC = 1> __device__ __forceinline__ void wgmma_ss64(float (&d)[32], uint64_t da, uint64_t db) {
    asm volatile("wgmma.mma_async.sync.aligned.m64n64k16.f32.bf16.bf16 {%0, %1, %2, %3, %4, %5, %6, %7, %8, %9, %10, %11, %12, %13, %14, %15, %16, %17, %18, %19, %20, %21, %22, %23, %24, %25, %26, %27, %28, %29, %30, %31}, %32, %33, %36, 1, 1, %34, %35;\n"
        : "+f"(d[0]), "+f"(d[1]), "+f"(d[2]), "+f"(d[3]), "+f"(d[4]), "+f"(d[5]), "+f"(d[6]), "+f"(d[7]), "+f"(d[8]), "+f"(d[9]), "+f"(d[10]), "+f"(d[11]), "+f"(d[12]), "+f"(d[13]), "+f"(d[14]), "+f"(d[15]), "+f"(d[16]), "+f"(d[17]), "+f"(d[18]), "+f"(d[19]), "+f"(d[20]), "+f"(d[21]), "+f"(d[22]), "+f"(d[23]), "+f"(d[24]), "+f"(d[25]), "+f"(d[26]), "+f"(d[27]), "+f"(d[28]), "+f"(d[29]), "+f"(d[30]), "+f"(d[31])
        : "l"(da), "l"(db), "n"(TA), "n"(TB), "n"(SC));
}

template<int TA, int TB, int SC = 1> __device__ __forceinline__ void wgmma_ss48(float (&d)[24], uint64_t da, uint64_t db) {
    asm volatile("wgmma.mma_async.sync.aligned.m64n48k16.f32.bf16.bf16 {%0, %1, %2, %3, %4, %5, %6, %7, %8, %9, %10, %11, %12, %13, %14, %15, %16, %17, %18, %19, %20, %21, %22, %23}, %24, %25, %28, 1, 1, %26, %27;\n"
        : "+f"(d[0]), "+f"(d[1]), "+f"(d[2]), "+f"(d[3]), "+f"(d[4]), "+f"(d[5]), "+f"(d[6]), "+f"(d[7]), "+f"(d[8]), "+f"(d[9]), "+f"(d[10]), "+f"(d[11]), "+f"(d[12]), "+f"(d[13]), "+f"(d[14]), "+f"(d[15]), "+f"(d[16]), "+f"(d[17]), "+f"(d[18]), "+f"(d[19]), "+f"(d[20]), "+f"(d[21]), "+f"(d[22]), "+f"(d[23])
        : "l"(da), "l"(db), "n"(TA), "n"(TB), "n"(SC));
}

template<int NKB, int NR>
__device__ __forceinline__ void mix_mainloop(TSARG float (&acc)[NR], bool leader) {
    constexpr uint32_t sb = SB, bars = sb + SM_BAR, par = NKB == 28;
    constexpr int A0 = NKB == 32 ? 0 : 16 % NA_SLOTS;
    constexpr int DEPTH = NR == 56 ? DEPTH_N : DEPTH_E;
    int bslot = 0, aslot = A0;
    reg_fence(acc);
    #pragma unroll 1
    for (int i = 0; i < NKB / 2; i++) {
        mbar_wait(bars + 8 * (B_FULLA + i), par);
        const uint64_t adesc = mkdesc(sb + SM_ARING, 8192, 1024, 1) + (uint32_t)(aslot * 1024);
        aslot = aslot == NA_SLOTS - 1 ? 0 : aslot + 1;
        #pragma unroll
        for (int jj = 0; jj < 2; jj++) {
            const int j = 2 * i + jj;
            mbar_wait(bars + 8 * (B_FULLB + j), par);
            const uint64_t bdesc = mkdesc(sb + SM_BRING, 128, 1024, 0) + (uint32_t)(bslot * NR * 16);
            bslot = bslot == (NR == 56 ? NB_SLOTS : NE_SLOTS) - 1 ? 0 : bslot + 1;
            wg_fence();
            #pragma unroll
            for (int s = 0; s < 4; s++) {
                if constexpr (NR == 56) wgmma_ss112<1, 1>(acc, adesc + jj * 512 + s * 128, bdesc + s * 16);
                else wgmma_ss80<1, 1>(acc, adesc + jj * 512 + s * 128, bdesc + s * 16);
            }
            wg_commit();
            wg_wait<DEPTH>();
            if (j >= DEPTH && leader) mbar_arrive(bars + 8 * (B_DONE + j - DEPTH));
        }
    }
    if (DEPTH == 2) { wg_wait<1>(); if (leader) mbar_arrive(bars + 8 * (B_DONE + NKB - 2)); }
    wg_wait<0>();
    reg_fence(acc);
    if (leader) mbar_arrive(bars + 8 * (B_DONE + NKB - 1));
}

__device__ __forceinline__ void spin_mma(uint32_t bar, uint32_t never) {
    float d[56];
    #pragma unroll
    for (int i = 0; i < 56; i++) d[i] = 0.f;
    reg_fence(d);
    #pragma unroll 1
    do {
        wg_fence();
        #pragma unroll
        for (int s = 0; s < SPIN_N; s++) wgmma_ss112<1, 1>(d, mkdesc(SB + 2 * SM_SLOT + s * 2048, 8192, 1024, 1), mkdesc(SB + 3 * SM_SLOT + s * 256, 128, 1024, 0));
        wg_commit();
        wg_wait<1>();
    } while (!named_any(11, 128, mbar_test(bar, 1)));
    wg_wait<0>();
    reg_fence(d);
    pin4(never, d[0], d[1], d[2], d[3]);
}

constexpr uint32_t EMPTY = 0xFFFFFFFFu;
__device__ __forceinline__ void post_hint(uint4* p, uint32_t ep, int lane) { if (lane < 2) st_relaxed4(p + lane, ep, ep, ep, ep); }
__device__ __forceinline__ void post_time(uint4* p, uint32_t ep, int lane) { const uint32_t now = gtime32(); if (lane < 2) st_relaxed4(p + lane, ep, now, ep, now); }

__device__ __forceinline__ uint32_t last_hint(TSARG const uint4* hint, uint32_t ep, int st) {
    uint2 v;
    do { v = ld_relaxed2(hint); } while (!__all_sync(0xffffffffu, v.x == ep));
    const uint32_t t1 = gtime32() + 256;
    if (elect()) STAMP(st);
    return t1 - __reduce_min_sync(0xffffffffu, t1 - v.y);
}
__device__ __forceinline__ uint32_t later(uint32_t a, uint32_t b) { return a + max((int)(b - a), 0); }
__device__ __forceinline__ void fetch_times(TSARG const uint4* go, int k, uint32_t ep, int lane) {
    const uint2* p = (const uint2*)(go + 8 + 8 * k) + (k ? lane % 10 : lane & 3);
    uint2 v;
    do { v = ld_relaxed2(p); } while (!__all_sync(0xffffffffu, v.x == ep));
    v.y += k ? (lane < 10 ? GO_U : GO_U + GO_U2) : (lane < 4 ? GO_E : GO_E + GO_E2);
    asm volatile("st.shared.u32 [%0], %1;" :: "r"(SB + SM_TIME + 128 * k + 4 * lane), "r"(v.y) : "memory");
    __syncwarp();
    if (lane == 0) { mbar_arrive(SB + SM_BAR + 8 * (B_GO + k)); STAMP(k ? 43 : 24); }
    __syncwarp();
}
__device__ __forceinline__ void wait_until(uint32_t t) { while ((int)(gtime32() - t) < 0) {} __syncwarp(); }

__device__ __forceinline__ uint32_t check_tile(uint32_t raw, uint32_t full, uint32_t dst, uint32_t lofs, const uint32_t* src, uint32_t bytes, int lane) {
    uint32_t cnt;
    asm volatile("{\n.reg .pred p, e;\n.reg .u32 a, b, c, d;\nmov.u32 %0, 0;\n"
                 "AGAIN:\nand.b32 a, %0, 1;\n"
                 "WAIT:\nmbarrier.try_wait.parity.shared::cta.b64 p, [%1], a;\n@!p bra.uni WAIT;\n"
                 "ld.shared.u32 a, [%4];\nld.shared.u32 b, [%4+4096];\nld.shared.u32 c, [%5+-8192];\nld.shared.u32 d, [%5+-4096];\n"
                 "add.u32 %0, %0, 1;\nmax.u32 a, a, b;\nmax.u32 c, c, d;\nmax.u32 a, a, c;\nsetp.lt.u32 e, %8, 32;\nsetp.eq.and.u32 p, a, 0xFFFFFFFF, e;\n"
                 "vote.sync.any.pred p, p, 0xffffffff;\nsetp.eq.and.u32 e, %8, 0, !p;\n@e mbarrier.arrive.shared::cta.b64 _, [%2];\n"
                 "elect.sync _|e, 0xffffffff;\nand.pred e, e, p;\n"
                 "@e mbarrier.arrive.expect_tx.shared::cta.b64 _, [%1], %7;\n"
                 "@e cp.async.bulk.shared::cluster.global.mbarrier::complete_tx::bytes [%3], [%6], %7, [%1];\n"
                 "@p bra.uni AGAIN;\n}"
                 : "=&r"(cnt) : "r"(raw), "r"(full), "r"(dst), "r"(dst + lofs), "r"(dst + lofs + bytes), "l"(src), "r"(bytes), "r"(lane) : "memory");
    return cnt;
}

template<int ST>
__device__ __forceinline__ void check_tiles(int j, int step, int n, const uint32_t* src, bool small, int lane, bool dry) {
    const uint32_t bytes = small ? 10240 : 14336, nb = small ? NE_SLOTS : NB_SLOTS, lofs = lane * 128 + (lane & 3) * 32 + (lane >> 2) * 4;
    uint32_t sl = j % nb;
    #pragma unroll 1
    for (int inc = dry ? 0 : step; j < n; j += inc, inc = step) {
        const uint32_t c = check_tile(inc ? SB + SM_RAW + 8 * (j + (ST ? 32 * ST - 28 : 0)) : SB + SM_BAR + 8 * B_CLR, SB + SM_BAR + 8 * (j + (ST ? B_FULLB : B_FULLO)),
                                      SB + (ST ? SM_BRING : SM_QO) + sl * bytes, lofs, src + j * (ST ? 7168 : 3584), bytes, inc ? lane : 32);
        sl += inc;
        if (sl >= nb) sl -= nb;
    }
}

__device__ __forceinline__ uint32_t hcol(uint32_t a, int jp) { return (a ^ ((jp & 3) << 5)) + (jp >> 2) * 8192; }

__device__ __forceinline__ uint32_t get_tag() {
    mbar_wait(SB + SM_BAR + 8 * B_CLR, 0);
    uint32_t v; asm volatile("ld.shared.u32 %0, [%1];" : "=r"(v) : "r"(SB + SM_TAG) : "memory"); return v;
}

template<bool USE_SMID>
__global__ void __launch_bounds__(384, 1)
fused_kernel(Scratch* __restrict__ sc, const __nv_bfloat16* __restrict__ wo,
             const __nv_bfloat16* __restrict__ w1, const __nv_bfloat16* __restrict__ b1,
             const __nv_bfloat16* __restrict__ w2, const __nv_bfloat16* __restrict__ b2,
             const __grid_constant__ CUtensorMap tm_x, const __grid_constant__ CUtensorMap tm_wqkv,
             const __grid_constant__ CUtensorMap tm_wo64, const __grid_constant__ CUtensorMap tm_wo48,
             const __grid_constant__ CUtensorMap tm_w1, const __grid_constant__ CUtensorMap tm_w2,
             const __grid_constant__ CUtensorMap tm_xr64, const __grid_constant__ CUtensorMap tm_xr48,
             const __grid_constant__ CUtensorMap tm_out64, const __grid_constant__ CUtensorMap tm_out48) {
    extern __shared__ __align__(1024) uint8_t smem_raw[];
    constexpr uint32_t sb = SB;
    constexpr uint32_t bars = sb + SM_BAR;
    const int tid = threadIdx.x, lane = tid & 31;
    auto get_slot = [&]() {
        int slot;
    if (USE_SMID) {
        asm volatile("{\n.reg .u32 s, t, u, d, a, b, c;\n.reg .pred p, r;\n"
            "mov.u32 s, %%smid;\nshr.u32 t, s, 1;\nsub.u32 u, t, 32;\nmul.lo.u32 d, u, 37;\nshr.u32 d, d, 8;\n"
            "and.b32 a, t, 7;\nshl.b32 a, a, 3;\nshr.u32 c, t, 3;\nadd.u32 a, a, c;\n"
            "mad.lo.u32 b, d, -55, 12;\nshl.b32 c, u, 3;\nadd.u32 b, b, c;\n"
            "setp.lt.u32 p, t, 32;\nselp.u32 a, a, b, p;\n"
            "setp.lt.u32 r, t, 62;\nselp.s32 c, 4, -58, r;\nadd.u32 c, t, c;\nsetp.lt.u32 p, t, 60;\nselp.u32 a, a, c, p;\n"
            "and.b32 s, s, 1;\nshl.b32 a, a, 1;\nadd.u32 %0, a, s;\n}" : "=r"(slot));
    } else slot = blockIdx.x;
        return slot;
    };
    auto load_x = [&](int kb, int row) {
        const uint32_t st = sb + slot_x(kb), bar = bars + 8 * (B_FULLX + kb);
        mbar_expect(bar, 16384);
        tma3d(st, &tm_x, kb * 64, 0, row, bar); tma3d(st + 8192, &tm_x, kb * 64, 1, row, bar);
    };
    const int warp = __shfl_sync(0xffffffffu, tid >> 5, 0);
#define ASSIGN_WORK(s) \
    const int slot = (s), G = slot >> 4, mi = slot & 15; \
    const int tb = 4 * (G >> 1) + (mi >> 2), hp = 2 * (mi & 3) + (G & 1), wcol = (hp * 56) & ~15; \
    const int q = mi & 3, tt2 = 4 * G + (mi >> 2), c64 = 64 * q, c48 = 256 + 48 * q; \
    const int R = (ROLES >> (4 * G)) & 7; \
    const bool early = R < 3; \
    const int ech = R < 2 ? q : 4 + (mi & 1), ft = R == 2 ? mi >> 1 : 4 * (R - !early) + (mi >> 2); \
    const int pr3 = early ? ech >= 3 : q >> 1, col3 = early ? (ech - 3 * pr3) * 9 : (q & 1) * 14;

    if (warp < 8) {
        ASSIGN_WORK(get_slot())
        if (slot >= 128) {
            const uint32_t ep = ld_volatile(&sc->epoch[slot]) + 1;
            if (mi == 0 && warp > 0) {
                const int k = warp % 3;
                uint2* go = (uint2*)(sc->go + 8 * k) + lane;
                if (warp < 4 && lane < 16) st_relaxed2(go, 0, 0);
                while (ld_relaxed(k ? sc->go : sc->hint_k) != ep) __nanosleep(200);
                __nanosleep(warp * 60);
                const uint4* hint = (k ? sc->hint_u : sc->hint_h) + (k == 2 ? 48 + min(lane, 19) : lane) * 2;
                uint2 v[4];
                do {
                    #pragma unroll
                    for (int i = 0; i < 4; i++) v[i] = ld_relaxed2(hint + (k == 0 ? 64 * i : k == 2 ? 40 * i : 32 * (i & 1)));
                } while (!__all_sync(0xffffffffu, v[0].x == ep && v[1].x == ep && v[2].x == ep && v[3].x == ep));
                uint32_t t = later(later(v[0].y, v[1].y), later(v[2].y, v[3].y));
                t = later(t, __shfl_xor_sync(0xffffffffu, t, 1));
                if (k == 1) { t = later(t, __shfl_xor_sync(0xffffffffu, t, 8)); t = later(t, __shfl_xor_sync(0xffffffffu, t, 16)); }
                if (k == 0) {
                    const uint32_t now = gtime32() + 256;
                    t = later(t, now - __reduce_min_sync(0xffffffffu, now - t) - SLACK);
                }
                t = __shfl_sync(0xffffffffu, t, 2 * lane);
                if (lane < 16) st_relaxed2(go, ep, t);
            }
            if (mi == 1 && warp >= 4 && ld_volatile(&sc->clean) != ep) {
                for (int l = (tid - 128) / 2; l < sizeof(Tiles) / 128; l += 64) st_relaxed4((uint4*)&sc->tiles[ep & 1] + l * 8 + (lane & 7), EMPTY, EMPTY, EMPTY, EMPTY);
                named_sync(1, 128);
                if (tid == 128) st_release(&sc->clean, ep);
            }
            if (tid == 0) {
                const long long t0 = clock64();
                while (clock64() - t0 < SP_AT) {}
                #pragma unroll 1
                for (int i = 0; i < 7; i++) bulk_prefetch((const char*)wo + (i * 4 + mi) * 14336, 14336);
                uint32_t t = (uint32_t)t0 + PF0_AT;
                #pragma unroll 1
                for (int i = 0; i < PF0_N; i++) {
                    while ((int)(clock32() - t) < 0) {}
                    bulk_prefetch((const char*)w1 + i * 114688 + mi * 14336, 14336);
                    t += PF0_PACE;
                }
                if (mi) {
                    t = (uint32_t)t0 + PF1_AT;
                    #pragma unroll 1
                    for (int i = mi - 1; i < PF1_N; i += 3) {
                        while ((int)(clock32() - t) < 0) {}
                        tma5d_prefetch(&tm_w1, (i & 7) * 64, (i + 48) & 56, (i + 48) >> 6);
                        t += PF1_PACE;
                    }
                    t = (uint32_t)t0 + PF_AT;
                    #pragma unroll 1
                    for (int i = mi - 1; i < PF_N; i += 3) {
                        while ((int)(clock32() - t) < 0) {}
                        bulk_prefetch((const char*)w2 + (i < 128 ? i * 16384 : (i - 64 >> 1) * 65536 + (i & 1) * 16384), 16384);
                        t += PF_PACE;
                    }
                }
                while (ld_relaxed(sc->hint_u + 254) != ep) { __nanosleep(500); if (clock64() - t0 > WD_CLKS) __trap(); }
                sc->epoch[slot] = ep;
                if (mi == 1) sc->clean = ep + 1;
            }
            return;
        }
        {
            const int w = warp & 3, wg = warp >> 2, g = lane >> 2, t = lane & 3;
            if (WARM_AT) { const uint32_t t0 = clock32(); while (clock32() - t0 < WARM_AT) {} __syncwarp(); }
            if (w > 0) post_hint(sc->hint_o + ((2 * tb + (w >> 1)) * 32 + hp * 4 + (w & 1) * 2 + wg) * 2, 0, lane);
            if (wg == 0) {
                if (t < 2) st_relaxed4(sc->stats + tt2 * 256 + q * 64 + 16 * w + g + 8 * t, 0, 0, 0, 0);
            }
        }
        named_sync(0, 288);
        asm volatile("setmaxnreg.inc.sync.aligned.u32 224;");
        int tid; asm volatile("mov.u32 %0, %%tid.x;" : "=r"(tid));
        const int lane = tid & 31, warp = __shfl_sync(0xffffffffu, tid >> 5, 0), wg = warp >> 2;
        uint32_t ep;
        Tiles* tl;
        const int w = warp & 3, g = lane >> 2, t = lane & 3;
        const bool leader = (tid & 127) == 0;
        const uint32_t never = gridDim.y - 1;
        {
            uint32_t a[28][4];
            float accK[28], accV[28], accQ[28];
            const int lrow = 16 * w + (lane & 7) + (lane & 8);
            const uint32_t lbase = sb + wg * 8192 + lrow * 128;
            const uint32_t lx = (lane >> 4) ^ (lane & 7);
            const uint32_t wofs = hp & 1;
            auto pin2 = [&](uint32_t x0, uint32_t x1) {
                asm volatile("{\n.reg .pred p;\nsetp.ne.u32 p, %2, 0;\n@p st.shared.v2.b32 [%0], {%0,%1};\n}" :: "r"(x0), "r"(x1), "r"(never) : "memory");
            };
            float cS[2][4] = {}, cA[2][4] = {}, cB[2][4] = {}, q0, q1, p0, p1;
            auto sq = [&](float& acc, uint32_t v) { const float lo = bf_lo(v), hi = bf_hi(v); acc = fmaf(hi, hi, fmaf(lo, lo, acc)); };
            #pragma unroll
            for (int kb = 0; kb < 8; kb++) {
                if (kb < 7) {
                    mbar_wait(bars + 8 * (B_FULLX + kb), 0);
                    if (kb == 0 && tid == 0) STAMP(0);
                    if (kb == 6 && tid == 0) STAMP(25);
                    if (kb == 0) FST(0); if (kb == 2) FST(1); if (kb == 4) FST(2); if (kb == 6) FST(3);
                    #pragma unroll
                    for (int s = 4 * kb; s < 4 * kb + 4; s++) ldsm4(a[s], lbase + slot_x(kb) + ((lx ^ (2 * (s & 3))) << 4));
                }
                if (kb == 5) named_sync(9 + wg, 160);
                if (kb == NPIPE) continue;
                const int kc = kb < NPIPE ? kb : kb - 1;
                if (kc == NSQ) { p0 = cS[0][0] + cS[1][0]; p1 = cS[0][2] + cS[1][2]; }
                #pragma unroll
                for (int s = 4 * kc; s < 4 * kc + 4; s++) {
                    mma16816(cS[s & 1], a[s][0], a[s][1], a[s][2], a[s][3], 0x3F803F80u, 0x3F803F80u);
                    if (kc < NSQ) {
                        mma1688(cA[0], a[s][0], a[s][1], a[s][0]); mma1688(cA[1], a[s][2], a[s][3], a[s][2]);
                        mma1688(cB[0], a[s][0], a[s][1], a[s][1]); mma1688(cB[1], a[s][2], a[s][3], a[s][3]);
                    }
                }
            }
            const float m0 = (cS[0][0] + cS[1][0]) * (1.f / D_), m1 = (cS[0][2] + cS[1][2]) * (1.f / D_);
            const uint32_t mm0 = pack_bf16(m0, m0), mm1 = pack_bf16(m1, m1);
            if (lane == 0) mbar_arrive(bars + 8 * B_DONEX);
            auto center = [&](int s) { sub_bf16x2(a[s][0], mm0); sub_bf16x2(a[s][1], mm1); sub_bf16x2(a[s][2], mm0); sub_bf16x2(a[s][3], mm1); };
            uint32_t Ka[8], Kb[8], Kc[8], Va[8], Vb[7], Vc[8];
            float r0, r1, ls0, ls1;
            uint32_t pm, zero;
            uint32_t* od;
            uint4* oh;
            auto kpack = [&](uint32_t (&k)[8], int j, int c, float r) {
                const uint32_t v = pack_bf16(accK[4 * j + c] * r, accK[4 * j + c + 1] * r);
                if (j == 3) { k[3] = t < 2 ? v : 0u; k[4] = t < 2 ? 0u : v; } else k[j + (j > 3)] = v;
            };
            auto batch = [&](auto c0, auto c1) {
                constexpr int n0 = c0.value, n1 = c1.value;
                wg_fence();
                static_for<n0, n1>([&](auto nc) {
                    constexpr int n = nc.value;
                    if (n == 4) { center(4); center(5); center(6); center(7); wg_fence(); }
                    const uint64_t desc = mkdesc(sb + (n < 56 ? slot_kv(n >> 3) + (n & 7) * 2048 : SM_QO + (n - 56) * 2048), 8192, 1024, 1) + wofs;
                    wgmma_rs56<1>(n < 28 ? accK : n < 56 ? accV : accQ, a[n % 28], desc, n % 28 != 0);
                });
                wg_commit();
                if (n0 > 0) wg_wait<1>();
            };
            const uint32_t hs = sb + tid * 16 + warp * 512;
            auto hand_over = [&](const uint32_t (&v)[8], int kv) {
                mbar_wait(bars + 8 * (kv ? B_DONE1 + 5 : B_DONEX), 0);
                sts4(hs + (kv ? SM_HALOV : SM_HALOK), v[0], v[1], v[2], v[3]); sts4(hs + (kv ? SM_HALOV : SM_HALOK) + 512, v[4], v[5], v[6], v[7]);
                if (w == 3) named_arrive(6 + kv, 96);
            };
            auto take_over = [&](uint32_t (&v)[8], int kv) {
                if (w == 0) mbar_wait(bars + 8 * (B_HALO + 2 * kv + wg), 0);
                const uint32_t ad = w ? hs + (kv ? SM_HALOV : SM_HALOK) - 1024 : kv ? sb + lane * 16 + wg * 1024 + SM_HALOV + 8192 : halo_kin(wg, lane);
                const uint4 u0 = lds4(ad), u1 = lds4(ad + (w || kv ? 512 : 16));
                v[0] = u0.x; v[1] = u0.y; v[2] = u0.z; v[3] = u0.w; v[4] = u1.x; v[5] = u1.y; v[6] = u1.z; v[7] = u1.w;
            };
            center(0); center(1); center(2); center(3);
            static_for<0, 7>([&](auto pc) {
                constexpr int p = pc.value;
                mbar_wait(bars + 8 * (B_FULLKV + p), 0);
                if (p == 0 && tid == 0) STAMP(26);
                if (p == 3 && tid == 0) STAMP(27);
                FST(4 + p);
                batch(Int<8 * p>(), Int<8 * p + 8>());
                if (p > 0 && leader) mbar_arrive(bars + 8 * (B_DONE1 + p - 1));
                #pragma unroll
                for (int s = 8 * p + 8; s < 8 * p + 16 && s < 28; s++) center(s);
                if (p == 1) {
                    const float c0 = bf_hi(mm0), c1 = bf_hi(mm1);
                    q0 = fmaf(c0, fmaf(c0, 64.f * NSQ, -2.f * p0), (g & 1) ? cA[0][1] + cA[1][1] : cA[0][0] + cA[1][0]) - D_ * (m0 - c0) * (m0 - c0);
                    q1 = fmaf(c1, fmaf(c1, 64.f * NSQ, -2.f * p1), (g & 1) ? cB[0][3] + cB[1][3] : cB[0][2] + cB[1][2]) - D_ * (m1 - c1) * (m1 - c1);
                    asm("" : "+f"(q0), "+f"(q1));
                    q0 = t == (g >> 1) ? q0 : 0.f; q1 = t == (g >> 1) ? q1 : 0.f;
                    pin2(__float_as_uint(q0), __float_as_uint(q1));
                }
                constexpr int PK = NSQ < 5 ? 5 : 4, NR = 28 - 4 * NSQ;
                if (p >= 2 && p < PK) {
                    #pragma unroll
                    for (int s = 4 * NSQ + NR * (p - 2) / (PK - 2); s < 4 * NSQ + NR * (p - 1) / (PK - 2); s++) { sq(q0, a[s][0]); sq(q1, a[s][1]); sq(q0, a[s][2]); sq(q1, a[s][3]); }
                    pin2(__float_as_uint(q0), __float_as_uint(q1));
                }
                if (p == PK - 1) { q0 = quad_sum(q0); q1 = quad_sum(q1); }
                if (p == PK) {
                    r0 = rsqrt_approx(fmaxf(q0 * (1.f / D_), 0.f) + LN_EPS); r1 = rsqrt_approx(fmaxf(q1 * (1.f / D_), 0.f) + LN_EPS);
                    reg_fence(accK);
                    #pragma unroll
                    for (int j = 0; j < 7; j++) kpack(Kc, j, 2, r1);
                    hand_over(Kc, 0);
                }
                if (p == PK + 1) {
                    #pragma unroll
                    for (int j = 0; j < 7; j++) kpack(Kb, j, 0, r0);
                    #pragma unroll
                    for (int j = 0; j < 8; j += 2) pin2(Kb[j], Kb[j + 1]);
                    ls0 = LOG2E_SCALE * r0; ls1 = LOG2E_SCALE * r1;
                    pm = (2 * t <= g ? 0xFFFFu : 0u) | (2 * t + 1 <= g ? 0xFFFF0000u : 0u);
                    zero = never; asm volatile("" : "+r"(zero));
                    pin2(__float_as_uint(ls0), __float_as_uint(ls1)); pin2(pm, zero);
                }
                if (p == 2) ep = get_tag();
                if (p == 6) {
                    tl = &sc->tiles[ep & 1];
                    const int tt = 2 * tb + (w >> 1);
                    od = tl->o + tt * 14336 + (7 * hp) * 256 + (2 * (2 * (w & 1) + wg)) * 32 + lane;
                    oh = sc->hint_o + (tt * 32 + hp * 4 + (w & 1) * 2 + wg) * 2 + (lane & 1);
                    pin2((uint32_t)(uint64_t)od, (uint32_t)((uint64_t)od >> 32));
                    pin2((uint32_t)(uint64_t)oh, (uint32_t)((uint64_t)oh >> 32));
                }
            });
            if (tid == 0) STAMP(1);
            FST(11);
            mbar_wait(bars + 8 * B_FQ, 0);
            batch(Int<56>(), Int<60>());
            reg_fence(accV);
            if (leader) mbar_arrive(bars + 8 * (B_DONE1 + 6));
            if (tid == 0) STAMP(2);
            FST(12);
            #pragma unroll
            for (int j = 0; j < 7; j++) Vc[j] = movtrans(pack_bf16(accV[4 * j + 2] * r1, accV[4 * j + 3] * r1));
            Vc[7] = Vc[6];
            hand_over(Vc, 1);
            batch(Int<60>(), Int<66>());
            #pragma unroll
            for (int j = 0; j < 7; j++) {
                Vb[j] = movtrans(pack_bf16(accV[4 * j] * r0, accV[4 * j + 1] * r0));
                Vc[j] |= zero;
            }
            batch(Int<66>(), Int<72>());
            #pragma unroll
            for (int j = 0; j < 7; j++) pin2(Vb[j], Vc[j]);
            mbar_wait(bars + 8 * (B_FQ + 1), 0);
            FST(13);
            if (w > 0 && lane < 2) { const uint32_t now = gtime32(); st_relaxed4(oh, ep, now, ep, now); }
            batch(Int<72>(), Int<84>());
            FST(14);
            named_sync(1 + wg, 128);
            take_over(Ka, 0);
            if (tid == 0) STAMP(3);
            wg_wait<0>();
            reg_fence(accQ);
            if (tid == 0) STAMP(4);
            FST(15);
            const bool first = (tb == 0 && w == 0);
            uint32_t pA[2], pB0[2], pB1[2], pC[2], z0[2], z1[2];
            #pragma unroll
            for (int h = 0; h < 2; h++) {
                float sA[4] = {0.f, 0.f, 0.f, 0.f}, sB[4] = {0.f, 0.f, 0.f, 0.f}, sC[4] = {0.f, 0.f, 0.f, 0.f};
                #pragma unroll
                for (int k = 0; k < 2; k++) {
                    const float* qq = accQ + 12 * h + 8 * k;
                    uint32_t a0 = pack_bf16(qq[0], qq[1]), a1 = pack_bf16(qq[2], qq[3]);
                    if (h == 1 && k == 0) { a0 |= zero; a1 |= zero; }
                    const uint32_t a2 = pack_bf16(qq[4], qq[5]), a3 = pack_bf16(qq[6], qq[7]);
                    mma16816(sB, a0, a1, a2, a3, Kb[4 * h + 2 * k], Kb[4 * h + 2 * k + 1]);
                    mma16816(sA, a0, a1, a2, a3, Ka[4 * h + 2 * k], Ka[4 * h + 2 * k + 1]);
                    mma16816(sC, a0, a1, a2, a3, Kc[4 * h + 2 * k], Kc[4 * h + 2 * k + 1]);
                }
                const bool n0 = pm & 1, n1 = (int)pm < 0;
                const float l00 = n0 ? sB[0] : (first ? -INFINITY : sA[0]), l01 = n1 ? sB[1] : (first ? -INFINITY : sA[1]);
                const float l10 = n0 ? sC[2] : sB[2], l11 = n1 ? sC[3] : sB[3];
                const float x0 = -ls0 * quad_max(fmaxf(l00, l01)), x1 = -ls1 * quad_max(fmaxf(l10, l11));
                const float e00 = ex2(fmaf(l00, ls0, x0)), e01 = ex2(fmaf(l01, ls0, x0)), e10 = ex2(fmaf(l10, ls1, x1)), e11 = ex2(fmaf(l11, ls1, x1));
                const float i0 = rcp_approx(quad_sum(e00 + e01)), i1 = rcp_approx(quad_sum(e10 + e11));
                const uint32_t P0 = pack_bf16(e00 * i0, e01 * i0), P1 = pack_bf16(e10 * i1, e11 * i1);
                pB0[h] = P0 & pm; pA[h] = P0 & ~pm; pC[h] = P1 & pm; pB1[h] = P1 & ~pm; z0[h] = P0 & zero; z1[h] = P1 & zero;
            }
            float o[8][4];
            #pragma unroll
            for (int j = 0; j < 8; j++) {
                o[j][0] = o[j][1] = o[j][2] = o[j][3] = 0.f;
                mma16816(o[j], pB0[j >> 2], pB1[j >> 2], z0[j >> 2], pC[j >> 2], Vb[j - (j >> 2)], Vc[j - (j >> 2)]);
            }
            if (tid == 0) STAMP(12);
            FST(16);
            take_over(Va, 1);
            if (lane == 0) mbar_arrive(bars + 8 * B_DONEQ);
            if (tid == 0) STAMP(16);
            #pragma unroll
            for (int j = 0; j < 8; j++) mma1688(o[j], pA[j >> 2], z1[j >> 2], Va[j - (j >> 2)]);
            #pragma unroll
            for (int j = 0; j < 7; j++) {
                float v[4];
                #pragma unroll
                for (int c = 0; c < 4; c++) v[c] = j < 3 ? o[j][c] : j > 3 ? o[j + 1][c] : (t < 2 ? o[3][c] : o[4][c]);
                od[j * 256] = pack_bf16(v[0], v[1]);
                od[j * 256 + 32] = pack_bf16(v[2], v[3]);
            }
            if (tid == 0) STAMP(5);
            FST(17);
        }
        const int z = get_tag() - ep, slot1 = slot + z, tid1 = tid + z, warp1 = warp + z;
        ep += z;
        {
        ASSIGN_WORK(slot1)
        const int tid = tid1, lane = tid & 31, wg = warp1 >> 2, w = warp1 & 3, g = lane >> 2, t = lane & 3;
        tl = &sc->tiles[ep & 1];
        const uint32_t live = wg ^ 1;
        uint32_t rb0, rb1, late[14];
        const unsigned short* pb = (const unsigned short*)(live ? b2 + tt2 * 64 : b1 + ft * 64) + 16 * w + g;
        auto stage_late = [&]() {
            #pragma unroll
            for (int c = 0; c < 14; c++) asm volatile("st.shared.u32 [%0], %1;" :: "r"(sb + SM_H + wg * 8192 + (tid & 127) * 4 + c * 512), "r"(late[c]) : "memory");
            fence_async_smem();
            named_sync(1 + wg, 128);
        };
        auto store_late = [&](bool on, uint32_t* p) {
            #pragma unroll
            for (int c = 0; c < 4; c++)
                if (elect() && on && (c < 3 || w < 2)) bulk_st(p + (4 * c + w) * 256, sb + SM_H + wg * 8192 + (4 * c + w) * 512, 512);
            asm volatile("cp.async.bulk.commit_group;" ::: "memory");
        };
        auto undef = [](float (&v)[56]) {
            #pragma unroll
            for (int i = 0; i < 56; i++) asm volatile("" : "=f"(v[i]));
        };
        {
            float acc[56];
            const int hrow = 32 * (w >> 1) + 2 * ((lane & 7) + (lane & 8)) + (w & 1);
            const uint32_t ha = sb + SM_H + hrow * 128 + (((lane >> 4) ^ (hrow & 7)) << 4);
            uint4* sp = sc->stats + tt2 * 256 + 16 * w + g + 8 * (t & 1);
            uint4* sp_out = sp + q * 64;
            const uint4* sp_in = sp + (t & 2) * 64;
            uint32_t* hd = tl->hn + ((q >> 1) * 32 + (tt2 >> 1)) * 7168 + (q & 1) * 3584 + (tt2 & 1) * 128 + w * 32 + lane;
            pin_ptr(never, sp_out); pin_ptr(never, sp_in); pin_ptr(never, hd);
            float s0 = 0.f, s1 = 0.f, q0 = 0.f, q1 = 0.f, s2 = 0.f, s3 = 0.f, q2 = 0.f, q3 = 0.f;
            auto sums = [&](int j0, int j1) {
                #pragma unroll
                for (int j = j0; j < j1; j++) {
                    s0 += acc[4 * j]; s2 += acc[4 * j + 1]; q0 = fmaf(acc[4 * j], acc[4 * j], q0); q2 = fmaf(acc[4 * j + 1], acc[4 * j + 1], q2);
                    s1 += acc[4 * j + 2]; s3 += acc[4 * j + 3]; q1 = fmaf(acc[4 * j + 2], acc[4 * j + 2], q1); q3 = fmaf(acc[4 * j + 3], acc[4 * j + 3], q3);
                }
            };
            if (live) {
                mbar_wait(bars + 8 * B_FULLWO, 0);
                #pragma unroll
                for (int jp = 0; jp < 7; jp++) {
                    uint32_t xx[4];
                    ldsm4(xx, hcol(ha, jp));
                    #pragma unroll
                    for (int r = 0; r < 4; r++) { acc[8 * jp + 2 * r] = bf_lo(xx[r]); acc[8 * jp + 2 * r + 1] = bf_hi(xx[r]); }
                }
                reg_fence(acc);
                if (SPIN2) { named_sync(12, 256); spin_mma(bars + 8 * B_FULLX, never); }
                auto od_ = [&](int s) { return mkdesc(sb + SM_QO + s * 2048, 1024, 128, 0); };
                auto wd_ = [&](int s) { return mkdesc(sb + slot_wo(s >> 2) + (s & 3) * 2048, 8192, 1024, 1); };
                float accl[32], accr[24];
                #pragma unroll
                for (int i = 0; i < 5; i++) {
                    if (i < 4) mbar_wait(bars + 8 * (B_FULLO + i), 0);
                    if (i == 0 && tid == 0) STAMP(7);
                    if (i == 1) { rb0 = ld_u16(pb); rb1 = ld_u16(pb + 8); }
                    wg_fence();
                    #pragma unroll
                    for (int ss = 0; ss < 7; ss++) {
                        if (i < 3) wgmma_ss112<0, 1>(acc, od_(7 * i + ss), wd_(7 * i + ss));
                        else if (i == 4) wgmma_ss64<0, 1>(accl, od_(21 + ss), wd_(21 + ss));
                        else if (ss == 0) wgmma_ss48<0, 1, 0>(accr, od_(21), wd_(21) + 512);
                        else wgmma_ss48<0, 1>(accr, od_(21 + ss), wd_(21 + ss) + 512);
                    }
                    wg_commit();
                    if (i > 0) {
                        wg_wait<1>();
                        if (i == 3) {
                            reg_fence(acc);
                            #pragma unroll
                            for (int c = 0; c < 32; c++) accl[c] = __uint_as_float(__float_as_uint(acc[c]) | never);
                            reg_fence(accl);
                        }
                        if (i < 4 && leader) mbar_arrive(bars + 8 * (B_DONEO + i - 1));
                    }
                }
                reg_fence(accr);
                #pragma unroll
                for (int c = 0; c < 24; c++) acc[32 + c] += accr[c];
                sums(8, 14);
                pin4(never, s0, s1, s2, s3); pin4(never, q0, q1, q2, q3);
                wg_wait<0>();
                reg_fence(accl);
                #pragma unroll
                for (int c = 0; c < 32; c++) acc[c] = accl[c];
                if (leader) mbar_arrive(bars + 8 * (B_DONEO + 3));
                if (tid == 0) STAMP(8);
            } else { undef(acc); if (SPIN2) named_arrive(12, 256); }
            if (live || (DRY2 && w == 3)) {
            sums(0, 8);
            s0 += s2; s1 += s3; q0 += q2; q1 += q3;
            float sr = ((t & 1) ? s1 : s0) + __shfl_xor_sync(0xffffffffu, (t & 1) ? s0 : s1, 1), qr = ((t & 1) ? q1 : q0) + __shfl_xor_sync(0xffffffffu, (t & 1) ? q0 : q1, 1);
            sr += __shfl_xor_sync(0xffffffffu, sr, 2); qr += __shfl_xor_sync(0xffffffffu, qr, 2);
            st_relaxed4_if(t < 2 * live, sp_out, __float_as_uint(sr), __float_as_uint(qr), ep);
            const uint32_t tp = clock32();
            if (live) named_arrive(5, 256);
            if (tid == 0) STAMP(9);
            #pragma unroll
            for (int jp = 0; jp < 7; jp++)
                stsm4_if(live, hcol(ha, jp), pack_bf16(acc[8 * jp], acc[8 * jp + 1]), pack_bf16(acc[8 * jp + 2], acc[8 * jp + 3]),
                      pack_bf16(acc[8 * jp + 4], acc[8 * jp + 5]), pack_bf16(acc[8 * jp + 6], acc[8 * jp + 7]));
            uint4 v0, v1;
            if (POLL0) { while (clock32() - tp < POLL0) {} __syncwarp(); }
            do { v0 = ld_relaxed4(sp_in); v1 = ld_relaxed4(sp_in + 64); } while (live && __any_sync(0xffffffffu, v0.w != ep || v1.w != ep));
            if (tid == 0) STAMP(10);
            sr = __uint_as_float(v0.x) + __uint_as_float(v1.x); qr = __uint_as_float(v0.y) + __uint_as_float(v1.y);
            sr += __shfl_xor_sync(0xffffffffu, sr, 2); qr += __shfl_xor_sync(0xffffffffu, qr, 2);
            const float m = sr * (1.f / D_), var = fmaxf(qr * (1.f / D_) - m * m, 0.f);
            const float r = rsqrt_approx(fmaf(var, 4.f + 4.f * LN_EPS, 4.f * LN_EPS * LN_EPS)), c = -m * r;
            const float r0 = __shfl_sync(0xffffffffu, r, lane & ~1), c0 = __shfl_sync(0xffffffffu, c, lane & ~1);
            const float r1 = __shfl_sync(0xffffffffu, r, lane | 1), c1 = __shfl_sync(0xffffffffu, c, lane | 1);
            #pragma unroll
            for (int j = 0; j < 14; j++) st_global_if(live, hd + j * 256, pack_bf16(fmaf(acc[4 * j], r0, c0), fmaf(acc[4 * j + 1], r0, c0)));
            if (never) mbar_arrive(bars);
            #pragma unroll
            for (int j = 0; j < 14; j++) late[j] = pack_bf16(fmaf(acc[4 * j + 2], r1, c1), fmaf(acc[4 * j + 3], r1, c1));
            if (tid == 0) STAMP(11);
            }
        }
        if (!live) {
            if (w < 2) check_tiles<0>(w, 2, 4, tl->o + tt2 * 14336, false, lane, true);
            rb0 = ld_u16(pb); rb1 = ld_u16(pb + 8);
            named_sync(5, 256);
            auto phase3 = [&](auto nc) {
                constexpr int NC = nc.value;
                float acc[4 * NC];
                uint32_t* ud = tl->u + (pr3 * 28 + (ft >> 1) + (NC == 14 ? 4 : 0)) * 7168 + col3 * 256 + (ft & 1) * 128 + w * 32 + lane;
                #pragma unroll
                for (int j = 0; j < 4 * NC; j++) acc[j] = 0.5f * bf_lo((j & 2) ? rb1 : rb0);
                #pragma unroll 1
                for (uint32_t pass = never; pass < 2; pass++) {
                    if (pass) {
                        mix_mainloop<32>(TSVAL acc, leader);
                        if (leader) STAMP(14);
                    }
                    uint32_t pk[NC];
                    #pragma unroll
                    for (int j = 0; j < NC; j++) {
                        const float k = j < GDEP ? GELU_K1 : __uint_as_float(__float_as_uint(GELU_K1) | (pk[j - GDEP] & never));
                        pk[j] = pack_bf16(gelu_half(acc[4 * j], k), gelu_half(acc[4 * j + 1], k));
                        st_global_if(pass, ud + j * 256, pk[j]);
                    }
                }
                if (leader) STAMP(15);
                #pragma unroll
                for (int j = 0; j < NC; j++) late[j] = pack_bf16(gelu_half(acc[4 * j + 2], GELU_K1), gelu_half(acc[4 * j + 3], GELU_K1));
                if (NC == 14) {
                    stage_late();
                    mbar_wait(bars + 8 * (B_FULLB + LATE_AT4), 1);
                    store_late(true, tl->u + (pr3 * 28 + (ft >> 1) + 14) * 7168 + col3 * 256 + (ft & 1) * 128);
                } else {
                    #pragma unroll
                    for (int c = 0; c < NC; c++) st_global_if(1, ud + 4 * 7168 + c * 256, late[c]);
                    if (SPIN4) named_arrive(13, 256);
                }
            };
            if (early) phase3(Int<10>()); else phase3(Int<14>());
            if (w) {
                if (early && w == 1) fetch_times(TSVAL sc->go, 1, ep, lane);
                check_tiles<2>(CH_U - 1 + w, 3, 28, tl->u + (q >> 1) * 28 * 7168 + (q & 1) * 3584, false, lane, false);
                mbar_wait(bars + 8 * (B_DONE + CL_AT), 1);
                const int l = slot * 48 + (tid - 160) / 2;
                #pragma unroll
                for (int i = 0; i < 7; i++)
                    st_relaxed4_if(i < 6 || l < sizeof(Tiles) / 128 - 6 * 6144, (uint4*)&sc->tiles[~ep & 1] + (i * 6144 + l) * 8 + (lane & 7), EMPTY, EMPTY, EMPTY);
            }
            if (leader) mbar_wait_wd(bars + 8 * B_END, 0);
            return;
        }
        {
            float acc[56];
            const uint32_t ad = sb + SM_H + (16 * w + (lane & 15)) * 128 + (((lane >> 4) ^ (lane & 7)) << 4);
            const float bb0 = bf_lo(rb0), bb1 = bf_lo(rb1);
            named_sync(1, 128);
            #pragma unroll
            for (int jp = 0; jp < 7; jp++) {
                uint32_t hh[4];
                ldsm4(hh, hcol(ad, jp));
                #pragma unroll
                for (int r = 0; r < 4; r++) { acc[8 * jp + 2 * r] = bf_lo(hh[r]) + ((r & 1) ? bb1 : bb0); acc[8 * jp + 2 * r + 1] = bf_hi(hh[r]) + ((r & 1) ? bb1 : bb0); }
            }
            #pragma unroll 1
            for (uint32_t pass = never; pass < 2; pass++) {
                if (pass) {
                    named_sync(1, 128);
                    stage_late();
                    if (tid == 0) STAMP(39);
                    if (SPIN3) spin_mma(bars + 8 * (B_FULLX + 1), never);
                    mbar_wait(bars + 8 * (B_FULLB + LATE_AT), 0);
                    store_late(true, tl->hn + ((q >> 1) * 32 + 16 + (tt2 >> 1)) * 7168 + (q & 1) * 3584 + (tt2 & 1) * 128);
                    check_tiles<1>(CH_H + w, 4, 32, tl->hn + pr3 * 32 * 7168 + col3 * 256, early, lane, false);
                    mbar_wait(bars + 8 * (B_DONE + START4), 0);
                    if (SPIN4 && early) { named_sync(13, 256); spin_mma(bars + 8 * (B_FULLX + 2), never); }
                    mix_mainloop<28>(TSVAL acc, leader);
                    if (leader) mbar_arrive(bars + 8 * B_END);
                    if (tid == 0) STAMP(18);
                }
                #pragma unroll
                for (int jp = 0; jp < 7; jp++)
                    stsm4_if(1, hcol(ad, jp), pack_bf16(acc[8 * jp], acc[8 * jp + 1]), pack_bf16(acc[8 * jp + 2], acc[8 * jp + 3]),
                             pack_bf16(acc[8 * jp + 4], acc[8 * jp + 5]), pack_bf16(acc[8 * jp + 6], acc[8 * jp + 7]));
                fence_async_smem();
                __syncwarp();
            }
            if (elect()) {
                tma2d_store(&tm_out64, c64, tt2 * 64 + 16 * w, sb + SM_H + w * 2048);
                tma2d_store(&tm_out48, c48, tt2 * 64 + 16 * w, sb + SM_H + 8192 + w * 2048);
            }
            asm volatile("cp.async.bulk.commit_group;" ::: "memory");
            asm volatile("cp.async.bulk.wait_group.read 0;" ::: "memory");
            if (tid == 0) { sc->epoch[slot] = ep; STAMP(19); }
        }
        }
    } else {
        asm volatile("setmaxnreg.dec.sync.aligned.u32 56;");
        int warp2; asm("mov.u32 %0, %1;" : "=r"(warp2) : "r"(warp));
        if (warp2 > 8) {
            ASSIGN_WORK(get_slot())
            if (slot >= 128) return;
            uint32_t ep, cl;
            uint4* const oh = sc->hint_o + (2 * tb * 32 + hp * 4) * 2 + (lane & 3);
            uint4* const hu = sc->hint_u + (early ? ech * 8 + ft : 40 + q * 20 + ft) * 2;
            if (warp == 10) {
                post_hint(sc->hint_h + (q * 32 + tt2) * 2, 0, lane);
                post_hint(hu, 0, lane);
            }
            if (warp == 11) {
                ep = ld_volatile(&sc->epoch[slot]) + 1; cl = ld_acquire(&sc->clean);
                post_hint(sc->hint_k + (tb * 8 + hp) * 2, 0, lane);
                if (lane < (tb < 15 ? 4 : 0)) st_relaxed4(oh + 128, 0, 0, 0, 0);
                if (lane < (tb ? 0 : 4)) st_relaxed4(oh, 0, 0, 0, 0);
            }
            if (elect()) {
                if (warp == 9) {
                    #pragma unroll
                    for (int i = B_DONE1; i < B_DONEO; i++) mbar_init(bars + 8 * i, i < B_DONEX ? 2 : i == B_DONEX ? 8 : 9);
                }
                #pragma unroll
                for (int i = 0; i < 54; i++) mbar_init(bars + 8 * (B_DONEO + i) + (warp - 9) * 432, 1);
                asm volatile("fence.mbarrier_init.release.cluster;" ::: "memory");
            }
            named_sync(8, 128);
            if (warp < 11) mbar_expect(sb + SM_RAW + 8 * (tid - 288), early && tid >= 292 && tid < 324 ? 10240 : 14336);
            if (warp == 9) { named_arrive(4, 64); named_arrive(9, 160); named_arrive(10, 160); }
            if (warp < 11) {
                ep = get_tag();
                mbar_wait(bars + 8 * (B_DONE1 + HALO_AT), 0);
                #pragma unroll 1
                for (int kv = 0; kv < 2; kv++) {
                    uint4 v0 = {}, v1 = {}, v2 = {};
                    if (tb > 0) {
                        const uint4* hg = sc->halo + ((((tb - 1) * 8 + hp) * 2 + warp - 9) * 2 + kv) * 96 + lane;
                        if (kv == 0) while (ld_relaxed(sc->hint_k + ((tb - 1) * 8 + hp) * 2) != ep) {}
                        do { v0 = ld_relaxed4(hg); v1 = ld_relaxed4(hg + 32); v2 = ld_relaxed4(hg + 64); } while (!__all_sync(0xffffffffu, v0.w == ep && v1.w == ep && v2.w == ep));
                    }
                    if (kv) mbar_wait(bars + 8 * (B_DONE1 + 5), 0);
                    const uint32_t hs = kv ? sb + lane * 16 + (warp - 9) * 1024 + SM_HALOV + 8192 : halo_kin(warp - 9, lane);
                    sts4(hs, v0.x, v0.y, v0.z, v1.x); sts4(hs + (kv ? 512 : 16), v1.y, v1.z, v2.x, v2.y);
                    __syncwarp();
                    if (lane == 0) mbar_arrive(bars + 8 * (B_HALO + 2 * kv + warp - 9));
                }
                if (tid == 288) STAMP(21);
            } else {
                const long long t0 = clock64();
                while (__any_sync(0xffffffffu, (int)(cl - ep) < 0)) { cl = ld_acquire(&sc->clean); if (clock64() - t0 > WD_CLKS) __trap(); }
                if (lane == 0) { *(volatile uint32_t*)(smem_raw + SM_TAG) = ep; mbar_arrive(bars + 8 * B_CLR); }
                uint4* hg = sc->halo + (tb * 8 + hp) * 384 + lane;
                #pragma unroll 1
                for (int kv = 0; kv < 2; kv++) {
                    const uint32_t hs = sb + lane * 16 + 3072 + (kv ? SM_HALOV : SM_HALOK);
                    named_sync(6 + kv, 96);
                    #pragma unroll
                    for (int p = 0; p < 2; p++) {
                        const uint4 u0 = lds4(hs + p * 4096), u1 = lds4(hs + p * 4096 + 512);
                        st_relaxed4(hg + p * 192, u0.x, u0.y, u0.z, ep); st_relaxed4(hg + p * 192 + 32, u0.w, u1.x, u1.y, ep); st_relaxed4(hg + p * 192 + 64, u1.z, u1.w, ep, ep);
                    }
                    hg += 96;
                    if (kv == 0) {
                        post_hint(sc->hint_k + (tb * 8 + hp) * 2, ep, lane);
                        #pragma unroll
                        for (int j = 0; j < 6; j++) st_relaxed4(hg + j * 32 + (j / 3) * 96, 0, 0, 0, 0);
                    }
                }
                const uint32_t now = gtime32() - LATE_O;
                if (lane < (tb < 15 ? 4 : 0)) st_relaxed4(oh + 128, ep, now, ep, now);
                if (lane < (tb ? 0 : 4)) st_relaxed4(oh, ep, now, ep, now);
                if (lane == 0) STAMP(23);
                if (lane == 0) mbar_arrive(bars + 8 * B_DONEQ);
            }
            if (warp > 9) {
                const Tiles* const tl = &sc->tiles[ep & 1];
                check_tiles<1>(11 - warp, 2, CH_H, tl->hn + pr3 * 32 * 7168 + col3 * 256, early, lane, true);
                if (warp == 10) {
                    mbar_wait(bars + 8 * (B_DONE + (early ? HINT_E : HINT_U)), 0);
                    post_time(hu, ep, lane);
                }
                if (warp == 11) {
                    mbar_wait(bars + 8 * (B_DONE + (early ? POLL_E : POLL_N)), 0);
                    fetch_times(TSVAL sc->go, 0, ep, lane);
                }
                check_tiles<2>(11 - warp, 2, CH_U, tl->u + (q >> 1) * 28 * 7168 + (q & 1) * 3584, false, lane, true);
            } else {
                int aslot = 0;
                if (lane == 0) { prefetch_map(&tm_out64); prefetch_map(&tm_out48); }
                #pragma unroll
                for (int i = 0; i < HINT_F; i++) mbar_wait(bars + 8 * (B_FULLO + i), 0);
                post_time(sc->hint_h + (q * 32 + tt2) * 2, ep, lane);
                #pragma unroll 1
                for (int i = 0; i < 30; i++) {
                    if (i == POLL_I && !early) fetch_times(TSVAL sc->go, 1, ep, lane);
                    int d = 2 * i - 11 + (i >= A4_FROM ? A4_DLY : 0);
                    if (early) d = i < 16 ? 1 + (i - NA_SLOTS) * AE_END / 9 : max(d, AE_W2);
                    mbar_wait(bars + 8 * (i < NA_SLOTS ? B_DONEQ + ((A_SCHED >> (4 * i)) & 15) : B_DONE + (d & 31)), d >= 32);
                    if (elect()) {
                        const uint32_t bar = bars + 8 * (B_FULLA + (i & 15)), dst = sb + SM_ARING + aslot * 16384;
                        mbar_expect(bar, 16384);
                        if (i < 16) tma5d(dst, &tm_w1, ft * 64, (i & 7) * 8, i >> 3, bar);
                        else tma5d(dst, &tm_w2, tt2 * 64, 8 * (i < 20 ? i & 1 : i < 25 ? i - 18 : i - 23), i < 20 ? (i >> 1) & 1 : i >= 25, bar);
                    }
                    aslot = aslot == NA_SLOTS - 1 ? 0 : aslot + 1;
                }
            }
        } else {
            const int slot0 = get_slot(), row0 = (slot0 >> 5) * 256 + (slot0 & 12) * 16;
            if (elect()) {
                prefetch_map(&tm_x);
                #pragma unroll
                for (int i = 0; i < 7; i++) mbar_init(bars + 8 * i, 1);
                asm volatile("fence.mbarrier_init.release.cluster;" ::: "memory");
            }
            named_arrive(0, 288);
            if (elect()) {
                #pragma unroll 1
                for (int kb = 0; kb < 7; kb++) {
                    load_x(kb, row0);
                    if (kb == 0) STAMP(22);
                }
                #pragma unroll
                for (int i = 7; i < B_DONE1; i++) mbar_init(bars + 8 * i, 1);
                asm volatile("fence.mbarrier_init.release.cluster;" ::: "memory");
            }
            named_arrive(8, 128);
            ASSIGN_WORK(get_slot())
            if (slot >= 128) return;
            #pragma unroll 1
            for (int kb = 0; kb < 7; kb++) {
                if (kb == 6) { named_sync(4, 64); mbar_wait(bars + 8 * B_DONEX, 0); }
                if (elect()) {
                    const uint32_t st = sb + slot_kv(kb), bar = bars + 8 * (B_FULLKV + kb);
                    mbar_expect(bar, 16384);
                    #pragma unroll
                    for (int i = 0; i < 2; i++) {
                        const int n = 2 * kb + (i ^ (G & 1));
                        tma2d(st + (n & 1) * 8192, &tm_wqkv, (n < 7 ? 448 : 896) + wcol, (n < 7 ? n : n - 7) * 64, bar);
                    }
                }
            }
            if (elect()) {
                mbar_expect(bars + 8 * B_FQ, 32768);
                mbar_expect(bars + 8 * (B_FQ + 1), 24576);
                #pragma unroll 1
                for (int i = 0; i < 7; i++) { const int j = i == 6 ? i : i ^ (G & 1); tma2d(sb + SM_QO + j * 8192, &tm_wqkv, wcol, j * 64, bars + 8 * (B_FQ + (i >> 2))); }
                mbar_expect(bars + 8 * B_FULLWO, 512 * 112 * 2);
            }
            #pragma unroll 1
            for (int i = 0; i < 7; i++) {
                const int kb = ((q & 1 ? WO_ORD1 : WO_ORD0) >> (4 * i)) & 7;
                if (kb < 5) mbar_wait(bars + 8 * (B_DONE1 + kb), 0);
                if (elect()) {
                    tma2d(sb + slot_wo(kb), &tm_wo64, c64, kb * 64, bars + 8 * B_FULLWO);
                    tma2d(sb + slot_wo(kb) + 8192, &tm_wo48, c48, kb * 64, bars + 8 * B_FULLWO);
                }
            }
            if (elect()) {
                tma2d(sb + SM_H, &tm_xr64, c64, tt2 * 64, bars + 8 * B_FULLWO);
                tma2d(sb + SM_H + 8192, &tm_xr48, c48, tt2 * 64, bars + 8 * B_FULLWO);
            }
            if (smem_u32(smem_raw) != SB) __trap();
            const uint32_t ep = get_tag();
            const Tiles* const tl = &sc->tiles[ep & 1];
            mbar_wait(bars + 8 * (B_DONE1 + 6), 0);
            const uint32_t t_o = last_hint(TSVAL sc->hint_o + (tt2 * 32 + lane) * 2, ep, 38);
            mbar_wait(bars + 8 * B_DONEQ, 0);
            wait_until(t_o + GO_O);
            if (elect()) {
                #pragma unroll
                for (int i = 0; i < 4; i++) {
                    bulk_ld(sb + SM_QO + i * 14336, tl->o + tt2 * 14336 + i * 3584, 14336, sb + SM_RAW + 8 * i);
                }
            }
            if (lane == 0) STAMP(20);
            if (SPIN2) { wait_until(t_o + GO_O + STOP2); if (lane == 0) mbar_arrive(bars + 8 * B_FULLX); }
            mbar_wait(bars + 8 * (B_DONEO + POLL_H), 0);
            const uint32_t* src = tl->hn + pr3 * 32 * 7168 + col3 * 256;
            uint32_t bytes = early ? 10240 : 14336, dst = sb + SM_BRING, top = dst + (early ? NE_SLOTS * 10240 : NB_SLOTS * 14336), raw = sb + SM_RAW + 32;
            auto issue = [&]() {
                if (elect()) bulk_ld(dst, src, bytes, raw);
                src += 7168; raw += 8; dst += bytes;
                if (dst == top) dst = sb + SM_BRING;
            };
            uint2 th;
            do { th = ld_relaxed2((const uint2*)sc->go + (lane & 15)); } while (!__all_sync(0xffffffffu, th.x == ep));
            STAMP(42);
            mbar_wait(bars + 8 * (B_DONEO + 3), 0);
            {
                uint32_t bit = 1, wait = ~0u;
                #pragma unroll 1
                do {
                    while (wait & bit) wait = __ballot_sync(0xffffffffu, (int)(gtime32() - th.y - GO_H) < 0);
                    if (bit == 1) STAMP(29);
                    issue();
                    if (SPIN3 && bit == 1 << STOP3 && lane == 0) mbar_arrive(bars + 8 * (B_FULLX + 1));
                    bit *= 2;
                } while (dst != sb + SM_BRING);
            }
            uint32_t done = bars + 8 * B_DONE;
            #pragma unroll 1
            do { mbar_wait(done, 0); done += 8; issue(); } while (raw != sb + SM_RAW + 288);
            if (early) mbar_wait(bars + 8 * (B_DONE + 31), 0);
            src = tl->u + (q >> 1) * 28 * 7168 + (q & 1) * 3584; bytes = 14336; dst = sb + SM_BRING; top = dst + NB_SLOTS * 14336;
            done = bars + 8 * (B_DONE + 24);
            #pragma unroll 1
            for (uint32_t par = 0; par < 2; par++) {
                mbar_wait(bars + 8 * (B_GO + par), 0);
                const uint32_t ts = *(volatile uint32_t*)(smem_raw + SM_TIME + 128 * par + 4 * lane);
                if (par) done = bars + 8 * B_DONE;
                uint32_t bit = 1, wait = ~0u;
                #pragma unroll 1
                do {
                    while (wait & bit) wait = __ballot_sync(0xffffffffu, (int)(gtime32() - ts) < 0);
                    if (bit == 1) STAMP(par ? 36 : 30);
                    mbar_wait(done, par); done += 8;
                    issue();
                    if (SPIN4 && bit == 1 << STOP3 && lane + par == 0) mbar_arrive(bars + 8 * (B_FULLX + 2));
                    bit *= 2;
                } while (bit != (par ? 1 << 20 : 1 << 8));
            }
        }
    }
}

typedef CUresult (*EncodeFn)(CUtensorMap*, CUtensorMapDataType, cuuint32_t, void*, const cuuint64_t*, const cuuint64_t*, const cuuint32_t*,
                             const cuuint32_t*, CUtensorMapInterleave, CUtensorMapSwizzle, CUtensorMapL2promotion, CUtensorMapFloatOOBfill);

void make_map(EncodeFn fn, CUtensorMap* tm, const void* ptr, int rank, const cuuint64_t* dims, const cuuint64_t* strides, const cuuint32_t* box, CUtensorMapSwizzle sw) {
    cuuint32_t es[5] = {1, 1, 1, 1, 1};
    fn(tm, CU_TENSOR_MAP_DATA_TYPE_BFLOAT16, rank, const_cast<void*>(ptr), dims, strides, box, es, CU_TENSOR_MAP_INTERLEAVE_NONE, sw,
       CU_TENSOR_MAP_L2_PROMOTION_NONE, CU_TENSOR_MAP_FLOAT_OOB_FILL_NONE);
}

}

extern "C" void kernel_launch(void* const* d_in, const int* in_sizes, int n_in, void* d_out, int out_size) {
    const __nv_bfloat16* x = (const __nv_bfloat16*)d_in[0];
    const __nv_bfloat16* wqkv = (const __nv_bfloat16*)d_in[1];
    const __nv_bfloat16* wo = (const __nv_bfloat16*)d_in[2];
    const __nv_bfloat16* w1 = (const __nv_bfloat16*)d_in[4];
    const __nv_bfloat16* b1 = (const __nv_bfloat16*)d_in[5];
    const __nv_bfloat16* w2 = (const __nv_bfloat16*)d_in[6];
    const __nv_bfloat16* b2 = (const __nv_bfloat16*)d_in[7];

    void* fnp = nullptr; cudaDriverEntryPointQueryResult qr;
    cudaGetDriverEntryPoint("cuTensorMapEncodeTiled", &fnp, cudaEnableDefault, &qr);
    EncodeFn fn = (EncodeFn)fnp;
    CUtensorMap tx, twqkv, two64, two48, tw1, tw2, txr64, txr48, tout64, tout48;
    { cuuint64_t d[3] = {448, 2, 1024}, s[2] = {896, 1792}; cuuint32_t b[3] = {64, 1, 64}; make_map(fn, &tx, x, 3, d, s, b, CU_TENSOR_MAP_SWIZZLE_128B); }
    { cuuint64_t d[2] = {1344, 448}, s[1] = {2688}; cuuint32_t b[2] = {64, 64}; make_map(fn, &twqkv, wqkv, 2, d, s, b, CU_TENSOR_MAP_SWIZZLE_128B); }
    { cuuint64_t d[2] = {448, 448}, s[1] = {896}; cuuint32_t b[2] = {64, 64}; make_map(fn, &two64, wo, 2, d, s, b, CU_TENSOR_MAP_SWIZZLE_128B); }
    { cuuint64_t d[2] = {448, 448}, s[1] = {896}; cuuint32_t b[2] = {48, 64}; make_map(fn, &two48, wo, 2, d, s, b, CU_TENSOR_MAP_SWIZZLE_128B); }
    { cuuint64_t d[5] = {1792, 8, 2, 64, 2}, s[4] = {2 * 3584, 3584, 32 * 3584, 16 * 3584}; cuuint32_t b[5] = {64, 8, 2, 8, 1}; make_map(fn, &tw1, w1, 5, d, s, b, CU_TENSOR_MAP_SWIZZLE_128B); }
    { cuuint64_t d[5] = {2048, 8, 2, 56, 2}, s[4] = {4096, 16 * 4096, 32 * 4096, 8 * 4096}; cuuint32_t b[5] = {64, 8, 2, 8, 1}; make_map(fn, &tw2, w2, 5, d, s, b, CU_TENSOR_MAP_SWIZZLE_128B); }
    { cuuint64_t d[2] = {448, 2048}, s[1] = {896}; cuuint32_t b[2] = {64, 64}; make_map(fn, &txr64, x, 2, d, s, b, CU_TENSOR_MAP_SWIZZLE_128B); }
    { cuuint64_t d[2] = {448, 2048}, s[1] = {896}; cuuint32_t b[2] = {48, 64}; make_map(fn, &txr48, x, 2, d, s, b, CU_TENSOR_MAP_SWIZZLE_128B); }
    { cuuint64_t d[2] = {448, 2048}, s[1] = {896}; cuuint32_t b[2] = {64, 16}; make_map(fn, &tout64, d_out, 2, d, s, b, CU_TENSOR_MAP_SWIZZLE_128B); }
    { cuuint64_t d[2] = {448, 2048}, s[1] = {896}; cuuint32_t b[2] = {48, 16}; make_map(fn, &tout48, d_out, 2, d, s, b, CU_TENSOR_MAP_SWIZZLE_128B); }

    void* scv = nullptr;
    cudaGetSymbolAddress(&scv, g_scratch);
    Scratch* scp = (Scratch*)scv;
    int dev = 0, sms = 0;
    cudaGetDevice(&dev);
    cudaDeviceGetAttribute(&sms, cudaDevAttrMultiProcessorCount, dev);
    if (sms == 132) {
        cudaFuncSetAttribute(fused_kernel<true>, cudaFuncAttributeMaxDynamicSharedMemorySize, SM_TOTAL);
        fused_kernel<true><<<132, 384, SM_TOTAL>>>(scp, wo, w1, b1, w2, b2, tx, twqkv, two64, two48, tw1, tw2, txr64, txr48, tout64, tout48);
    } else {
        cudaFuncSetAttribute(fused_kernel<false>, cudaFuncAttributeMaxDynamicSharedMemorySize, SM_TOTAL);
        fused_kernel<false><<<132, 384, SM_TOTAL>>>(scp, wo, w1, b1, w2, b2, tx, twqkv, two64, two48, tw1, tw2, txr64, txr48, tout64, tout48);
    }
}
```

```cpp
#include <cuda_runtime.h>
#include <cuda_bf16.h>
#include <cuda.h>
#include <stdint.h>

namespace {

constexpr int D_ = 448;
constexpr float LN_EPS = 1e-5f;
constexpr float LOG2E_SCALE = 0.1889822365046136f * 1.4426950408889634f;

struct Tiles {
    uint32_t o[32 * 57344 / 4];
    uint32_t hn[4 * 32 * 14336 / 4];
    uint32_t u[4 * 28 * 14336 / 4];
};
struct Scratch {
    uint4 halo[128 * 2 * 2 * 3 * 32];
    uint4 stats[32 * 4 * 64];
    uint4 hint_k[128 * 2];
    uint4 hint_o[32 * 32 * 2];
    uint4 hint_h[4 * 32 * 2];
    uint4 hint_u[128 * 2];
    uint4 go[24];
    uint32_t epoch[160];
    uint32_t clean;
    alignas(1024) Tiles tiles[2];
};
__device__ Scratch g_scratch;
#define STAMP(i) do {} while (0)
#define FST(i) do {} while (0)
#define TSARG
#define TSVAL

constexpr uint32_t SB = 1024;
constexpr int SM_SLOT = 16384;
__device__ __forceinline__ constexpr uint32_t slot_x(int kb) { return (kb ? 6 + kb : 0) * SM_SLOT; }
__device__ __forceinline__ constexpr uint32_t slot_kv(int kb) { return (kb < 5 ? 2 + kb : 6 - kb) * SM_SLOT; }
__device__ __forceinline__ constexpr uint32_t slot_wo(int kb) { return (kb < 6 ? 2 + kb : 12) * SM_SLOT; }
constexpr int SM_QO = 8 * SM_SLOT;
constexpr int SM_HALOK = SM_QO + 57344, SM_HALOV = 1 * SM_SLOT;
constexpr int NA_SLOTS = 6, NB_SLOTS = 8;
constexpr int SM_ARING = 0;
constexpr int SM_BRING = NA_SLOTS * 16384;
constexpr int SM_H = 212992;
__device__ __forceinline__ uint32_t halo_kin(int par, int lane) { return SB + SM_H + 8192 + par * 4096 + lane * 128 + ((~lane & 6) << 4); }
constexpr int SM_BAR = 229376;
constexpr int SM_TAG = SM_BAR + 1536;
constexpr int SM_TIME = SM_TAG + 256;
constexpr int SM_TOTAL = SM_TIME + 256;
constexpr int B_FULLX = 0;
constexpr int B_FULLKV = 7;
constexpr int B_FQ = 14;
constexpr int B_DONE1 = 16;
constexpr int B_DONEX = 23;
constexpr int B_DONEQ = 24;
constexpr int B_DONEO = 25;
constexpr int B_FULLO = 29;
constexpr int B_FULLWO = 33;
constexpr int B_END = 34;
constexpr int B_HALO = 35;
constexpr int B_FULLA = 39;
constexpr int B_FULLB = 55;
constexpr int B_DONE = 87;
constexpr int B_GO = 119;
constexpr int B_CLR = 121;
constexpr int SM_RAW = SM_BAR + 8 * 122;

constexpr long long WD_CLKS = 2000000000ll;

template<int N> struct Int { static constexpr int value = N; };
template<int A, int B, class F> __device__ __forceinline__ void static_for(F&& f) { if constexpr (A < B) { f(Int<A>()); static_for<A + 1, B>(f); } }

__device__ __forceinline__ uint32_t smem_u32(const void* p) { return (uint32_t)__cvta_generic_to_shared(p); }
__device__ __forceinline__ void mbar_init(uint32_t bar, uint32_t cnt) { asm volatile("mbarrier.init.shared::cta.b64 [%0], %1;" :: "r"(bar), "r"(cnt) : "memory"); }
__device__ __forceinline__ void mbar_expect(uint32_t bar, uint32_t bytes) { asm volatile("mbarrier.arrive.expect_tx.shared::cta.b64 _, [%0], %1;" :: "r"(bar), "r"(bytes) : "memory"); }
__device__ __forceinline__ void mbar_arrive(uint32_t bar) { asm volatile("mbarrier.arrive.shared::cta.b64 _, [%0];" :: "r"(bar) : "memory"); }
__device__ __forceinline__ bool mbar_try(uint32_t bar, uint32_t parity) {
    uint32_t ok;
    asm volatile("{\n.reg .pred p;\nmbarrier.try_wait.parity.shared::cta.b64 p, [%1], %2;\nselp.u32 %0, 1, 0, p;\n}" : "=r"(ok) : "r"(bar), "r"(parity) : "memory");
    return ok;
}
__device__ __forceinline__ bool mbar_test(uint32_t bar, uint32_t parity) {
    uint32_t ok;
    asm volatile("{\n.reg .pred p;\nmbarrier.test_wait.parity.shared::cta.b64 p, [%1], %2;\nselp.u32 %0, 1, 0, p;\n}" : "=r"(ok) : "r"(bar), "r"(parity) : "memory");
    return ok;
}
__device__ __forceinline__ void mbar_wait(uint32_t bar, uint32_t parity) {
    asm volatile("{\n.reg .pred p;\n"
                 "WAIT_LOOP:\n"
                 "mbarrier.try_wait.parity.shared::cta.b64 p, [%0], %1;\n"
                 "@!p bra WAIT_LOOP;\n}" :: "r"(bar), "r"(parity) : "memory");
}
__device__ __forceinline__ void mbar_wait_wd(uint32_t bar, uint32_t parity) {
    asm volatile("{\n.reg .pred p, q;\n.reg .u32 s, t;\nmov.u32 s, %%clock;\n"
                 "WAIT_LOOP:\n"
                 "mbarrier.try_wait.parity.shared::cta.b64 p, [%0], %1;\nmov.u32 t, %%clock;\nsub.u32 t, t, s;\nsetp.lt.and.s32 q, t, 0, !p;\n@q trap;\n"
                 "@!p bra WAIT_LOOP;\n}" :: "r"(bar), "r"(parity) : "memory");
}
__device__ __forceinline__ bool elect() { uint32_t p; asm volatile("{\n.reg .pred P;\nelect.sync _|P, 0xffffffff;\nselp.u32 %0, 1, 0, P;\n}" : "=r"(p)); return p; }
__device__ __forceinline__ void tma2d(uint32_t dst, const CUtensorMap* tm, int c0, int c1, uint32_t bar) {
    asm volatile("cp.async.bulk.tensor.2d.shared::cluster.global.mbarrier::complete_tx::bytes [%0], [%1, {%3, %4}], [%2];" :: "r"(dst), "l"(tm), "r"(bar), "r"(c0), "r"(c1) : "memory");
}
__device__ __forceinline__ void tma3d(uint32_t dst, const CUtensorMap* tm, int c0, int c1, int c2, uint32_t bar) {
    asm volatile("cp.async.bulk.tensor.3d.shared::cluster.global.mbarrier::complete_tx::bytes [%0], [%1, {%3, %4, %5}], [%2];" :: "r"(dst), "l"(tm), "r"(bar), "r"(c0), "r"(c1), "r"(c2) : "memory");
}
__device__ __forceinline__ void tma5d(uint32_t dst, const CUtensorMap* tm, int c0, int c3, int c4, uint32_t bar) {
    asm volatile("cp.async.bulk.tensor.5d.shared::cluster.global.mbarrier::complete_tx::bytes [%0], [%1, {%3, 0, 0, %4, %5}], [%2];" :: "r"(dst), "l"(tm), "r"(bar), "r"(c0), "r"(c3), "r"(c4) : "memory");
}
__device__ __forceinline__ void tma5d_prefetch(const CUtensorMap* tm, int c0, int c3, int c4) {
    asm volatile("cp.async.bulk.prefetch.tensor.5d.L2.global [%0, {%1, 0, 0, %2, %3}];" :: "l"(tm), "r"(c0), "r"(c3), "r"(c4) : "memory");
}
__device__ __forceinline__ void tma2d_store(const CUtensorMap* tm, int c0, int c1, uint32_t src) {
    asm volatile("cp.async.bulk.tensor.2d.global.shared::cta.bulk_group [%0, {%2, %3}], [%1];" :: "l"(tm), "r"(src), "r"(c0), "r"(c1) : "memory");
}
__device__ __forceinline__ void bulk_st(void* dst, uint32_t src, uint32_t bytes) {
    asm volatile("cp.async.bulk.global.shared::cta.bulk_group [%0], [%1], %2;" :: "l"(dst), "r"(src), "r"(bytes) : "memory");
}
__device__ __forceinline__ void bulk_ld(uint32_t dst, const void* src, uint32_t bytes, uint32_t bar) {
    asm volatile("cp.async.bulk.shared::cluster.global.mbarrier::complete_tx::bytes [%0], [%1], %2, [%3];" :: "r"(dst), "l"(src), "r"(bytes), "r"(bar) : "memory");
}
__device__ __forceinline__ void bulk_prefetch(const void* src, uint32_t bytes) { asm volatile("cp.async.bulk.prefetch.L2.global [%0], %1;" :: "l"(src), "r"(bytes) : "memory"); }
__device__ __forceinline__ void prefetch_map(const CUtensorMap* tm) { asm volatile("prefetch.tensormap [%0];" :: "l"(tm) : "memory"); }
__device__ __forceinline__ void st_global_if(uint32_t c, uint32_t* p, uint32_t v) {
    asm volatile("{\n.reg .pred p;\nsetp.ne.u32 p, %2, 0;\n@p st.global.u32 [%0], %1;\n}" :: "l"(p), "r"(v), "r"(c) : "memory");
}
__device__ __forceinline__ void st_relaxed4_if(bool c, uint4* p, uint32_t a, uint32_t b, uint32_t d) {
    asm volatile("{\n.reg .b128 t;\n.reg .b64 a, b;\n.reg .pred p;\nsetp.ne.u32 p, %4, 0;\nmov.b64 a, {%1, %2};\nmov.b64 b, {%3, %3};\nmov.b128 t, {a, b};\n@p st.relaxed.gpu.global.b128 [%0], t;\n}" :: "l"(p), "r"(a), "r"(b), "r"(d), "r"((uint32_t)c) : "memory");
}
__device__ __forceinline__ void pin_ptr(uint32_t never, const void* a) {
    asm volatile("{\n.reg .pred p;\nsetp.ne.u32 p, %1, 0;\n@p st.shared.u64 [%1], %0;\n}" :: "l"(a), "r"(never) : "memory");
}
__device__ __forceinline__ void pin4(uint32_t never, float a, float b, float c, float d) {
    asm volatile("{\n.reg .pred p;\nsetp.ne.u32 p, %4, 0;\n@p st.shared.v4.f32 [%4], {%0,%1,%2,%3};\n}" :: "f"(a), "f"(b), "f"(c), "f"(d), "r"(never) : "memory");
}
__device__ __forceinline__ void fence_async_smem() { asm volatile("fence.proxy.async.shared::cta;" ::: "memory"); }
__device__ __forceinline__ uint32_t ld_acquire(const void* p) { uint32_t v; asm volatile("ld.acquire.gpu.global.u32 %0, [%1];" : "=r"(v) : "l"(p) : "memory"); return v; }
__device__ __forceinline__ void st_release(void* p, uint32_t v) { asm volatile("st.release.gpu.global.u32 [%0], %1;" :: "l"(p), "r"(v) : "memory"); }
__device__ __forceinline__ uint32_t ld_relaxed(const void* p) { uint32_t v; asm volatile("ld.relaxed.gpu.global.u32 %0, [%1];" : "=r"(v) : "l"(p) : "memory"); return v; }
__device__ __forceinline__ uint2 ld_relaxed2(const void* p) {
    uint2 v; asm volatile("{\n.reg .b64 a;\nld.relaxed.gpu.global.b64 a, [%2];\nmov.b64 {%0, %1}, a;\n}" : "=r"(v.x), "=r"(v.y) : "l"(p) : "memory"); return v;
}
__device__ __forceinline__ void st_relaxed2(void* p, uint32_t a, uint32_t b) {
    asm volatile("{\n.reg .b64 a;\nmov.b64 a, {%1, %2};\nst.relaxed.gpu.global.b64 [%0], a;\n}" :: "l"(p), "r"(a), "r"(b) : "memory");
}
__device__ __forceinline__ uint4 ld_relaxed4(const uint4* p) {
    uint4 v;
    asm volatile("{\n.reg .b128 t;\n.reg .b64 a, b;\nld.relaxed.gpu.global.b128 t, [%4];\nmov.b128 {a, b}, t;\nmov.b64 {%0, %1}, a;\nmov.b64 {%2, %3}, b;\n}" : "=r"(v.x), "=r"(v.y), "=r"(v.z), "=r"(v.w) : "l"(p) : "memory");
    return v;
}
__device__ __forceinline__ void st_relaxed4(uint4* p, uint32_t a, uint32_t b, uint32_t c, uint32_t d) {
    asm volatile("{\n.reg .b128 t;\n.reg .b64 a, b;\nmov.b64 a, {%1, %2};\nmov.b64 b, {%3, %4};\nmov.b128 t, {a, b};\nst.relaxed.gpu.global.b128 [%0], t;\n}" :: "l"(p), "r"(a), "r"(b), "r"(c), "r"(d) : "memory");
}
__device__ __forceinline__ uint32_t ld_u16(const unsigned short* p) { uint32_t v; asm volatile("ld.volatile.global.u16 %0, [%1];" : "=r"(v) : "l"(p) : "memory"); return v; }
__device__ __forceinline__ uint32_t ld_volatile(const uint32_t* p) { uint32_t v; asm volatile("ld.volatile.global.u32 %0, [%1];" : "=r"(v) : "l"(p) : "memory"); return v; }
__device__ __forceinline__ void named_arrive(int id, int n) { asm volatile("bar.arrive %0, %1;" :: "r"(id), "r"(n) : "memory"); }
__device__ __forceinline__ void named_sync(int id, int n) { asm volatile("bar.sync %0, %1;" :: "r"(id), "r"(n) : "memory"); }
__device__ __forceinline__ void named_arrive_if(uint32_t c, int id, int n) { asm volatile("{\n.reg .pred p;\nsetp.ne.u32 p, %2, 0;\n@p bar.arrive %0, %1;\n}" :: "r"(id), "r"(n), "r"(c) : "memory"); }
__device__ __forceinline__ bool named_any(int id, int n, bool v) {
    uint32_t r; asm volatile("{\n.reg .pred p, q;\nsetp.ne.u32 p, %3, 0;\nbar.red.or.pred q, %1, %2, p;\nselp.u32 %0, 1, 0, q;\n}" : "=r"(r) : "r"(id), "r"(n), "r"((uint32_t)v) : "memory"); return r;
}
__device__ __forceinline__ void wg_fence() { asm volatile("wgmma.fence.sync.aligned;" ::: "memory"); }
__device__ __forceinline__ void wg_commit() { asm volatile("wgmma.commit_group.sync.aligned;" ::: "memory"); }
template<int N> __device__ __forceinline__ void wg_wait() { asm volatile("wgmma.wait_group.sync.aligned %0;" :: "n"(N) : "memory"); }
template<int N> __device__ __forceinline__ void reg_fence(float (&d)[N]) {
    #pragma unroll
    for (int i = 0; i < N; i++) asm volatile("" : "+f"(d[i]) :: "memory");
}
__device__ __forceinline__ constexpr uint64_t mkdesc(uint32_t addr, uint32_t lbo, uint32_t sbo, uint32_t sw) {
    return (uint64_t)((addr & 0x3FFFF) >> 4) | ((uint64_t)(lbo >> 4) << 16) | ((uint64_t)(sbo >> 4) << 32) | ((uint64_t)sw << 62);
}
__device__ __forceinline__ void ldsm4(uint32_t (&r)[4], uint32_t addr) {
    asm volatile("ldmatrix.sync.aligned.m8n8.x4.shared.b16 {%0,%1,%2,%3}, [%4];" : "=r"(r[0]), "=r"(r[1]), "=r"(r[2]), "=r"(r[3]) : "r"(addr) : "memory");
}
__device__ __forceinline__ void stsm4_if(uint32_t c, uint32_t addr, uint32_t r0, uint32_t r1, uint32_t r2, uint32_t r3) {
    asm volatile("{\n.reg .pred p;\nsetp.ne.u32 p, %5, 0;\n@p stmatrix.sync.aligned.m8n8.x4.shared.b16 [%0], {%1,%2,%3,%4};\n}" :: "r"(addr), "r"(r0), "r"(r1), "r"(r2), "r"(r3), "r"(c) : "memory");
}
__device__ __forceinline__ void sts4(uint32_t a, uint32_t x, uint32_t y, uint32_t z, uint32_t w) { asm volatile("st.shared.v4.u32 [%0], {%1,%2,%3,%4};" :: "r"(a), "r"(x), "r"(y), "r"(z), "r"(w) : "memory"); }
__device__ __forceinline__ uint4 lds4(uint32_t a) { uint4 v; asm volatile("ld.shared.v4.u32 {%0,%1,%2,%3}, [%4];" : "=r"(v.x), "=r"(v.y), "=r"(v.z), "=r"(v.w) : "r"(a) : "memory"); return v; }
__device__ __forceinline__ uint32_t movtrans(uint32_t a) { uint32_t d; asm volatile("movmatrix.sync.aligned.m8n8.trans.b16 %0, %1;" : "=r"(d) : "r"(a)); return d; }
__device__ __forceinline__ uint32_t pack_bf16(float lo, float hi) { uint32_t r; asm("cvt.rn.bf16x2.f32 %0, %1, %2;" : "=r"(r) : "f"(hi), "f"(lo)); return r; }
__device__ __forceinline__ void sub_bf16x2(uint32_t& a, uint32_t b) { asm volatile("sub.rn.bf16x2 %0, %0, %1;" : "+r"(a) : "r"(b)); }
__device__ __forceinline__ float bf_lo(uint32_t v) { return __uint_as_float(v << 16); }
__device__ __forceinline__ float bf_hi(uint32_t v) { return __uint_as_float(v & 0xffff0000u); }
__device__ __forceinline__ void mma16816(float (&c)[4], uint32_t a0, uint32_t a1, uint32_t a2, uint32_t a3, uint32_t b0, uint32_t b1) {
    asm volatile("mma.sync.aligned.m16n8k16.row.col.f32.bf16.bf16.f32 {%0,%1,%2,%3}, {%4,%5,%6,%7}, {%8,%9}, {%0,%1,%2,%3};"
        : "+f"(c[0]), "+f"(c[1]), "+f"(c[2]), "+f"(c[3]) : "r"(a0), "r"(a1), "r"(a2), "r"(a3), "r"(b0), "r"(b1));
}
__device__ __forceinline__ void mma1688(float (&c)[4], uint32_t a0, uint32_t a1, uint32_t b0) {
    asm volatile("mma.sync.aligned.m16n8k8.row.col.f32.bf16.bf16.f32 {%0,%1,%2,%3}, {%4,%5}, {%6}, {%0,%1,%2,%3};"
        : "+f"(c[0]), "+f"(c[1]), "+f"(c[2]), "+f"(c[3]) : "r"(a0), "r"(a1), "r"(b0));
}
__device__ __forceinline__ float quad_sum(float v) { v += __shfl_xor_sync(0xffffffffu, v, 1); v += __shfl_xor_sync(0xffffffffu, v, 2); return v; }
__device__ __forceinline__ float quad_max(float v) { v = fmaxf(v, __shfl_xor_sync(0xffffffffu, v, 1)); v = fmaxf(v, __shfl_xor_sync(0xffffffffu, v, 2)); return v; }
__device__ __forceinline__ float ex2(float x) { float y; asm("ex2.approx.ftz.f32 %0, %1;" : "=f"(y) : "f"(x)); return y; }
__device__ __forceinline__ float rsqrt_approx(float x) { float y; asm("rsqrt.approx.ftz.f32 %0, %1;" : "=f"(y) : "f"(x)); return y; }
__device__ __forceinline__ float rcp_approx(float x) { float y; asm("rcp.approx.ftz.f32 %0, %1;" : "=f"(y) : "f"(x)); return y; }
constexpr float GELU_K1 = 2.f * 0.7978845608028654f;
__device__ __forceinline__ float gelu_half(float hx, float k1) {
    const float z = hx * fmaf(hx * hx, 8.f * 0.044715f * 0.7978845608028654f, k1);
    float t; asm("tanh.approx.f32 %0, %1;" : "=f"(t) : "f"(z));
    return fmaf(hx, t, hx);
}
__device__ __forceinline__ uint32_t gtime32() { uint64_t t; asm volatile("mov.u64 %0, %%globaltimer;" : "=l"(t)); return (uint32_t)t; }
__device__ __forceinline__ uint32_t clock32() { uint32_t t; asm volatile("mov.u32 %0, %%clock;" : "=r"(t)); return t; }
#define PF_PACE 160
#define PF_AT 16500
#define PF_N 256
#define NSQ 6
#define NPIPE 1
#define HALO_AT 3
#define HINT_U 18
#define HINT_E 16
#define SP_AT 2000
#define A_SCHED 0x322188
#define WO_ORD0 0x4321065
#define WO_ORD1 0x3465210
#define CL_AT 23
#define WARM_AT 300
#define A_HOLD 31
#define GO_H 1730
#define GO_E 1890
#define GO_U 2200
#define GO_O 1312
#define LATE_O 256
#define DRY2 1
#define LATE_AT 0
#define LATE_AT4 0
#define HINT_H 0
#define SLACK 0
#define SLACK_U 128
#define GDEP 4
#define START4 30
#define EMAP 1
#define DEPTH_N 1
#define DEPTH_E 2
#define PFE_AT 99
#define PFN_END 0
#define NE_SLOTS 11
#define POLL_E 26
#define POLL_U 22
#define CH_U 28
#define AE_END 18
#define AE_W2 27
#define PF1_AT 12000
#define PF1_N 80
#define PF1_PACE 160
#define HOLD 0
#define X0 1
#define GO_E2 300
#define GO_U2 400
#define POLL_I 20
#define POLL_N 19
#define LATES 0x11111111u
#define GATE_J 22
#define GATE_D 16
#define ROLES 0x65432107u
#define LATE_E 1
#define LATE_N 1
#define CL_I0 0
#define CL_SP 1000
#define POLL0 250
#define A4_FROM 23
#define A4_DLY 2
#define SPIN2 1
#define SPIN3 0
#define SPIN4 0
#define SPIN_N 2
#define STOP2 200
#define STOP3 3
#define PF0_AT 5000
#define PF0_N 48
#define PF0_PACE 140
#define POLL_H 3
#define CH_H 8
#define HINT_F 2
template<int TB> __device__ __forceinline__ void wgmma_rs56(float (&d)[28], const uint32_t (&a)[4], uint64_t db, int sc) {
    asm volatile("{\n.reg .pred p;\nsetp.ne.b32 p, %33, 0;\n"
        "wgmma.mma_async.sync.aligned.m64n56k16.f32.bf16.bf16 {%0, %1, %2, %3, %4, %5, %6, %7, %8, %9, %10, %11, %12, %13, %14, %15, %16, %17, %18, %19, %20, %21, %22, %23, %24, %25, %26, %27}, {%28, %29, %30, %31}, %32, p, 1, 1, %34;\n}\n"
        : "+f"(d[0]), "+f"(d[1]), "+f"(d[2]), "+f"(d[3]), "+f"(d[4]), "+f"(d[5]), "+f"(d[6]), "+f"(d[7]), "+f"(d[8]), "+f"(d[9]), "+f"(d[10]), "+f"(d[11]), "+f"(d[12]), "+f"(d[13]), "+f"(d[14]), "+f"(d[15]), "+f"(d[16]), "+f"(d[17]), "+f"(d[18]), "+f"(d[19]), "+f"(d[20]), "+f"(d[21]), "+f"(d[22]), "+f"(d[23]), "+f"(d[24]), "+f"(d[25]), "+f"(d[26]), "+f"(d[27])
        : "r"(a[0]), "r"(a[1]), "r"(a[2]), "r"(a[3]), "l"(db), "r"(sc), "n"(TB));
}

template<int TA, int TB, int SC = 1> __device__ __forceinline__ void wgmma_ss112(float (&d)[56], uint64_t da, uint64_t db) {
    asm volatile("wgmma.mma_async.sync.aligned.m64n112k16.f32.bf16.bf16 {%0, %1, %2, %3, %4, %5, %6, %7, %8, %9, %10, %11, %12, %13, %14, %15, %16, %17, %18, %19, %20, %21, %22, %23, %24, %25, %26, %27, %28, %29, %30, %31, %32, %33, %34, %35, %36, %37, %38, %39, %40, %41, %42, %43, %44, %45, %46, %47, %48, %49, %50, %51, %52, %53, %54, %55}, %56, %57, %60, 1, 1, %58, %59;\n"
        : "+f"(d[0]), "+f"(d[1]), "+f"(d[2]), "+f"(d[3]), "+f"(d[4]), "+f"(d[5]), "+f"(d[6]), "+f"(d[7]), "+f"(d[8]), "+f"(d[9]), "+f"(d[10]), "+f"(d[11]), "+f"(d[12]), "+f"(d[13]), "+f"(d[14]), "+f"(d[15]), "+f"(d[16]), "+f"(d[17]), "+f"(d[18]), "+f"(d[19]), "+f"(d[20]), "+f"(d[21]), "+f"(d[22]), "+f"(d[23]), "+f"(d[24]), "+f"(d[25]), "+f"(d[26]), "+f"(d[27]), "+f"(d[28]), "+f"(d[29]), "+f"(d[30]), "+f"(d[31]), "+f"(d[32]), "+f"(d[33]), "+f"(d[34]), "+f"(d[35]), "+f"(d[36]), "+f"(d[37]), "+f"(d[38]), "+f"(d[39]), "+f"(d[40]), "+f"(d[41]), "+f"(d[42]), "+f"(d[43]), "+f"(d[44]), "+f"(d[45]), "+f"(d[46]), "+f"(d[47]), "+f"(d[48]), "+f"(d[49]), "+f"(d[50]), "+f"(d[51]), "+f"(d[52]), "+f"(d[53]), "+f"(d[54]), "+f"(d[55])
        : "l"(da), "l"(db), "n"(TA), "n"(TB), "n"(SC));
}

template<int TA, int TB, int SC = 1> __device__ __forceinline__ void wgmma_ss80(float (&d)[40], uint64_t da, uint64_t db) {
    asm volatile("wgmma.mma_async.sync.aligned.m64n80k16.f32.bf16.bf16 {%0, %1, %2, %3, %4, %5, %6, %7, %8, %9, %10, %11, %12, %13, %14, %15, %16, %17, %18, %19, %20, %21, %22, %23, %24, %25, %26, %27, %28, %29, %30, %31, %32, %33, %34, %35, %36, %37, %38, %39}, %40, %41, %44, 1, 1, %42, %43;\n"
        : "+f"(d[0]), "+f"(d[1]), "+f"(d[2]), "+f"(d[3]), "+f"(d[4]), "+f"(d[5]), "+f"(d[6]), "+f"(d[7]), "+f"(d[8]), "+f"(d[9]), "+f"(d[10]), "+f"(d[11]), "+f"(d[12]), "+f"(d[13]), "+f"(d[14]), "+f"(d[15]), "+f"(d[16]), "+f"(d[17]), "+f"(d[18]), "+f"(d[19]), "+f"(d[20]), "+f"(d[21]), "+f"(d[22]), "+f"(d[23]), "+f"(d[24]), "+f"(d[25]), "+f"(d[26]), "+f"(d[27]), "+f"(d[28]), "+f"(d[29]), "+f"(d[30]), "+f"(d[31]), "+f"(d[32]), "+f"(d[33]), "+f"(d[34]), "+f"(d[35]), "+f"(d[36]), "+f"(d[37]), "+f"(d[38]), "+f"(d[39])
        : "l"(da), "l"(db), "n"(TA), "n"(TB), "n"(SC));
}

template<int TA, int TB, int SC = 1> __device__ __forceinline__ void wgmma_ss64(float (&d)[32], uint64_t da, uint64_t db) {
    asm volatile("wgmma.mma_async.sync.aligned.m64n64k16.f32.bf16.bf16 {%0, %1, %2, %3, %4, %5, %6, %7, %8, %9, %10, %11, %12, %13, %14, %15, %16, %17, %18, %19, %20, %21, %22, %23, %24, %25, %26, %27, %28, %29, %30, %31}, %32, %33, %36, 1, 1, %34, %35;\n"
        : "+f"(d[0]), "+f"(d[1]), "+f"(d[2]), "+f"(d[3]), "+f"(d[4]), "+f"(d[5]), "+f"(d[6]), "+f"(d[7]), "+f"(d[8]), "+f"(d[9]), "+f"(d[10]), "+f"(d[11]), "+f"(d[12]), "+f"(d[13]), "+f"(d[14]), "+f"(d[15]), "+f"(d[16]), "+f"(d[17]), "+f"(d[18]), "+f"(d[19]), "+f"(d[20]), "+f"(d[21]), "+f"(d[22]), "+f"(d[23]), "+f"(d[24]), "+f"(d[25]), "+f"(d[26]), "+f"(d[27]), "+f"(d[28]), "+f"(d[29]), "+f"(d[30]), "+f"(d[31])
        : "l"(da), "l"(db), "n"(TA), "n"(TB), "n"(SC));
}

template<int TA, int TB, int SC = 1> __device__ __forceinline__ void wgmma_ss48(float (&d)[24], uint64_t da, uint64_t db) {
    asm volatile("wgmma.mma_async.sync.aligned.m64n48k16.f32.bf16.bf16 {%0, %1, %2, %3, %4, %5, %6, %7, %8, %9, %10, %11, %12, %13, %14, %15, %16, %17, %18, %19, %20, %21, %22, %23}, %24, %25, %28, 1, 1, %26, %27;\n"
        : "+f"(d[0]), "+f"(d[1]), "+f"(d[2]), "+f"(d[3]), "+f"(d[4]), "+f"(d[5]), "+f"(d[6]), "+f"(d[7]), "+f"(d[8]), "+f"(d[9]), "+f"(d[10]), "+f"(d[11]), "+f"(d[12]), "+f"(d[13]), "+f"(d[14]), "+f"(d[15]), "+f"(d[16]), "+f"(d[17]), "+f"(d[18]), "+f"(d[19]), "+f"(d[20]), "+f"(d[21]), "+f"(d[22]), "+f"(d[23])
        : "l"(da), "l"(db), "n"(TA), "n"(TB), "n"(SC));
}

template<int NKB, int NR>
__device__ __forceinline__ void mix_mainloop(TSARG float (&acc)[NR], bool leader) {
    constexpr uint32_t sb = SB, bars = sb + SM_BAR, par = NKB == 28;
    constexpr int A0 = NKB == 32 ? 0 : 16 % NA_SLOTS;
    constexpr int DEPTH = NR == 56 ? DEPTH_N : DEPTH_E;
    int bslot = 0, aslot = A0;
    reg_fence(acc);
    #pragma unroll 1
    for (int i = 0; i < NKB / 2; i++) {
        mbar_wait(bars + 8 * (B_FULLA + i), par);
        const uint64_t adesc = mkdesc(sb + SM_ARING, 8192, 1024, 1) + (uint32_t)(aslot * 1024);
        aslot = aslot == NA_SLOTS - 1 ? 0 : aslot + 1;
        #pragma unroll
        for (int jj = 0; jj < 2; jj++) {
            const int j = 2 * i + jj;
            mbar_wait(bars + 8 * (B_FULLB + j), par);
            const uint64_t bdesc = mkdesc(sb + SM_BRING, 128, 1024, 0) + (uint32_t)(bslot * NR * 16);
            bslot = bslot == (NR == 56 ? NB_SLOTS : NE_SLOTS) - 1 ? 0 : bslot + 1;
            wg_fence();
            #pragma unroll
            for (int s = 0; s < 4; s++) {
                if constexpr (NR == 56) wgmma_ss112<1, 1>(acc, adesc + jj * 512 + s * 128, bdesc + s * 16);
                else wgmma_ss80<1, 1>(acc, adesc + jj * 512 + s * 128, bdesc + s * 16);
            }
            wg_commit();
            wg_wait<DEPTH>();
            if (j >= DEPTH && leader) mbar_arrive(bars + 8 * (B_DONE + j - DEPTH));
        }
    }
    if (DEPTH == 2) { wg_wait<1>(); if (leader) mbar_arrive(bars + 8 * (B_DONE + NKB - 2)); }
    wg_wait<0>();
    reg_fence(acc);
    if (leader) mbar_arrive(bars + 8 * (B_DONE + NKB - 1));
}

__device__ __forceinline__ void spin_mma(uint32_t bar, uint32_t never) {
    float d[56];
    #pragma unroll
    for (int i = 0; i < 56; i++) d[i] = 0.f;
    reg_fence(d);
    #pragma unroll 1
    do {
        wg_fence();
        #pragma unroll
        for (int s = 0; s < SPIN_N; s++) wgmma_ss112<1, 1>(d, mkdesc(SB + 2 * SM_SLOT + s * 2048, 8192, 1024, 1), mkdesc(SB + 3 * SM_SLOT + s * 256, 128, 1024, 0));
        wg_commit();
        wg_wait<1>();
    } while (!named_any(11, 128, mbar_test(bar, 1)));
    wg_wait<0>();
    reg_fence(d);
    pin4(never, d[0], d[1], d[2], d[3]);
}

constexpr uint32_t EMPTY = 0xFFFFFFFFu;
__device__ __forceinline__ void post_hint(uint4* p, uint32_t ep, int lane) { if (lane < 2) st_relaxed4(p + lane, ep, ep, ep, ep); }
__device__ __forceinline__ void post_time(uint4* p, uint32_t ep, int lane) { const uint32_t now = gtime32(); if (lane < 2) st_relaxed4(p + lane, ep, now, ep, now); }

__device__ __forceinline__ uint32_t last_hint(TSARG const uint4* hint, uint32_t ep, int st) {
    uint2 v;
    do { v = ld_relaxed2(hint); } while (!__all_sync(0xffffffffu, v.x == ep));
    const uint32_t t1 = gtime32() + 256;
    if (elect()) STAMP(st);
    return t1 - __reduce_min_sync(0xffffffffu, t1 - v.y);
}
__device__ __forceinline__ uint32_t later(uint32_t a, uint32_t b) { return a + max((int)(b - a), 0); }
__device__ __forceinline__ void fetch_times(TSARG const uint4* go, int k, uint32_t ep, int lane) {
    const uint2* p = (const uint2*)(go + 8 + 8 * k) + (k ? lane % 10 : lane & 3);
    uint2 v;
    do { v = ld_relaxed2(p); } while (!__all_sync(0xffffffffu, v.x == ep));
    v.y += k ? (lane < 10 ? GO_U : GO_U + GO_U2) : (lane < 4 ? GO_E : GO_E + GO_E2);
    asm volatile("st.shared.u32 [%0], %1;" :: "r"(SB + SM_TIME + 128 * k + 4 * lane), "r"(v.y) : "memory");
    __syncwarp();
    if (lane == 0) { mbar_arrive(SB + SM_BAR + 8 * (B_GO + k)); STAMP(k ? 43 : 24); }
    __syncwarp();
}
__device__ __forceinline__ void wait_until(uint32_t t) {
    asm volatile("{\n.reg .pred p;\n.reg .u64 a;\n.reg .u32 l, h;\nWAIT_LOOP:\nmov.u64 a, %%globaltimer;\nmov.b64 {l, h}, a;\nsub.u32 l, l, %0;\nsetp.lt.s32 p, l, 0;\n@p bra.uni WAIT_LOOP;\n}" :: "r"(t) : "memory");
}

__device__ __forceinline__ uint32_t check_tile(uint32_t raw, uint32_t full, uint32_t dst, uint32_t lofs, const uint32_t* src, uint32_t bytes, int lane) {
    uint32_t cnt;
    asm volatile("{\n.reg .pred p, e;\n.reg .u32 a, b, c, d;\nmov.u32 %0, 0;\n"
                 "AGAIN:\nand.b32 a, %0, 1;\n"
                 "WAIT:\nmbarrier.try_wait.parity.shared::cta.b64 p, [%1], a;\n@!p bra.uni WAIT;\n"
                 "ld.shared.u32 a, [%4];\nld.shared.u32 b, [%4+4096];\nld.shared.u32 c, [%5+-8192];\nld.shared.u32 d, [%5+-4096];\n"
                 "add.u32 %0, %0, 1;\nmax.u32 a, a, b;\nmax.u32 c, c, d;\nmax.u32 a, a, c;\nsetp.lt.u32 e, %8, 32;\nsetp.eq.and.u32 p, a, 0xFFFFFFFF, e;\n"
                 "vote.sync.any.pred p, p, 0xffffffff;\nsetp.eq.and.u32 e, %8, 0, !p;\n@e mbarrier.arrive.shared::cta.b64 _, [%2];\n"
                 "elect.sync _|e, 0xffffffff;\nand.pred e, e, p;\n"
                 "@e mbarrier.arrive.expect_tx.shared::cta.b64 _, [%1], %7;\n"
                 "@e cp.async.bulk.shared::cluster.global.mbarrier::complete_tx::bytes [%3], [%6], %7, [%1];\n"
                 "@p bra.uni AGAIN;\n}"
                 : "=&r"(cnt) : "r"(raw), "r"(full), "r"(dst), "r"(dst + lofs), "r"(dst + lofs + bytes), "l"(src), "r"(bytes), "r"(lane) : "memory");
    return cnt;
}

template<int ST>
__device__ __forceinline__ void check_tiles(int j, int step, int n, const uint32_t* src, bool small, int lane, bool dry) {
    const uint32_t bytes = small ? 10240 : 14336, nb = small ? NE_SLOTS : NB_SLOTS, lofs = lane * 128 + (lane & 3) * 32 + (lane >> 2) * 4;
    uint32_t sl = j % nb;
    #pragma unroll 1
    for (int inc = dry ? 0 : step; j < n; j += inc, inc = step) {
        const uint32_t c = check_tile(inc ? SB + SM_RAW + 8 * (j + (ST ? 32 * ST - 28 : 0)) : SB + SM_BAR + 8 * B_CLR, SB + SM_BAR + 8 * (j + (ST ? B_FULLB : B_FULLO)),
                                      SB + (ST ? SM_BRING : SM_QO) + sl * bytes, lofs, src + j * (ST ? 7168 : 3584), bytes, inc ? lane : 32);
        sl += inc;
        if (sl >= nb) sl -= nb;
    }
}

__device__ __forceinline__ uint32_t hcol(uint32_t a, int jp) { return (a ^ ((jp & 3) << 5)) + (jp >> 2) * 8192; }

__device__ __forceinline__ uint32_t get_tag() {
    mbar_wait(SB + SM_BAR + 8 * B_CLR, 0);
    uint32_t v; asm volatile("ld.shared.u32 %0, [%1];" : "=r"(v) : "r"(SB + SM_TAG) : "memory"); return v;
}

template<bool USE_SMID>
__global__ void __launch_bounds__(384, 1)
fused_kernel(Scratch* __restrict__ sc, const __nv_bfloat16* __restrict__ wo,
             const __nv_bfloat16* __restrict__ w1, const __nv_bfloat16* __restrict__ b1,
             const __nv_bfloat16* __restrict__ w2, const __nv_bfloat16* __restrict__ b2,
             const __grid_constant__ CUtensorMap tm_x, const __grid_constant__ CUtensorMap tm_wqkv,
             const __grid_constant__ CUtensorMap tm_wo64, const __grid_constant__ CUtensorMap tm_wo48,
             const __grid_constant__ CUtensorMap tm_w1, const __grid_constant__ CUtensorMap tm_w2,
             const __grid_constant__ CUtensorMap tm_xr64, const __grid_constant__ CUtensorMap tm_xr48,
             const __grid_constant__ CUtensorMap tm_out64, const __grid_constant__ CUtensorMap tm_out48) {
    extern __shared__ __align__(1024) uint8_t smem_raw[];
    constexpr uint32_t sb = SB;
    constexpr uint32_t bars = sb + SM_BAR;
    const int tid = threadIdx.x, lane = tid & 31;
    auto get_slot = [&]() {
        int slot;
    if (USE_SMID) {
        asm volatile("{\n.reg .u32 s, t, u, d, a, b, c;\n.reg .pred p, r;\n"
            "mov.u32 s, %%smid;\nshr.u32 t, s, 1;\nsub.u32 u, t, 32;\nmul.lo.u32 d, u, 37;\nshr.u32 d, d, 8;\n"
            "and.b32 a, t, 7;\nshl.b32 a, a, 3;\nshr.u32 c, t, 3;\nadd.u32 a, a, c;\n"
            "mad.lo.u32 b, d, -55, 12;\nshl.b32 c, u, 3;\nadd.u32 b, b, c;\n"
            "setp.lt.u32 p, t, 32;\nselp.u32 a, a, b, p;\n"
            "setp.lt.u32 r, t, 62;\nselp.s32 c, 4, -58, r;\nadd.u32 c, t, c;\nsetp.lt.u32 p, t, 60;\nselp.u32 a, a, c, p;\n"
            "and.b32 s, s, 1;\nshl.b32 a, a, 1;\nadd.u32 %0, a, s;\n}" : "=r"(slot));
    } else slot = blockIdx.x;
        return slot;
    };
    auto load_x = [&](int kb, int row) {
        const uint32_t st = sb + slot_x(kb), bar = bars + 8 * (B_FULLX + kb);
        mbar_expect(bar, 16384);
        tma3d(st, &tm_x, kb * 64, 0, row, bar); tma3d(st + 8192, &tm_x, kb * 64, 1, row, bar);
    };
    const int warp = __shfl_sync(0xffffffffu, tid >> 5, 0);
#define ASSIGN_WORK(s) \
    const int slot = (s), G = slot >> 4, mi = slot & 15; \
    const int tb = 4 * (G >> 1) + (mi >> 2), hp = 2 * (mi & 3) + (G & 1), wcol = (hp * 56) & ~15; \
    const int q = mi & 3, tt2 = 4 * G + (mi >> 2), c64 = 64 * q, c48 = 256 + 48 * q; \
    const int R = (ROLES >> (4 * G)) & 7; \
    const bool early = R < 3; \
    const int ech = R < 2 ? q : 4 + (mi & 1), ft = R == 2 ? mi >> 1 : 4 * (R - !early) + (mi >> 2); \
    const int pr3 = early ? ech >= 3 : q >> 1, col3 = early ? (ech - 3 * pr3) * 9 : (q & 1) * 14;

    if (warp < 8) {
        ASSIGN_WORK(get_slot())
        if (slot >= 128) {
            const uint32_t ep = ld_volatile(&sc->epoch[slot]) + 1;
            if (mi == 0 && warp > 0) {
                const int k = warp % 3;
                uint2* go = (uint2*)(sc->go + 8 * k) + lane;
                if (warp < 4 && lane < 16) st_relaxed2(go, 0, 0);
                while (ld_relaxed(k ? sc->go : sc->hint_k) != ep) __nanosleep(200);
                __nanosleep(warp * 60);
                const uint4* hint = (k ? sc->hint_u : sc->hint_h) + (k == 2 ? 48 + min(lane, 19) : lane) * 2;
                uint2 v[4];
                do {
                    #pragma unroll
                    for (int i = 0; i < 4; i++) v[i] = ld_relaxed2(hint + (k == 0 ? 64 * i : k == 2 ? 40 * i : 32 * (i & 1)));
                } while (!__all_sync(0xffffffffu, v[0].x == ep && v[1].x == ep && v[2].x == ep && v[3].x == ep));
                uint32_t t = later(later(v[0].y, v[1].y), later(v[2].y, v[3].y));
                t = later(t, __shfl_xor_sync(0xffffffffu, t, 1));
                if (k == 1) { t = later(t, __shfl_xor_sync(0xffffffffu, t, 8)); t = later(t, __shfl_xor_sync(0xffffffffu, t, 16)); }
                if (k == 0) {
                    const uint32_t now = gtime32() + 256;
                    t = later(t, now - __reduce_min_sync(0xffffffffu, now - t) - SLACK);
                }
                t = __shfl_sync(0xffffffffu, t, 2 * lane);
                if (lane < 16) st_relaxed2(go, ep, t);
            }
            if (mi == 1 && warp >= 4 && ld_volatile(&sc->clean) != ep) {
                for (int l = (tid - 128) / 2; l < sizeof(Tiles) / 128; l += 64) st_relaxed4((uint4*)&sc->tiles[ep & 1] + l * 8 + (lane & 7), EMPTY, EMPTY, EMPTY, EMPTY);
                named_sync(1, 128);
                if (tid == 128) st_release(&sc->clean, ep);
            }
            if (tid == 0) {
                const long long t0 = clock64();
                while (clock64() - t0 < SP_AT) {}
                #pragma unroll 1
                for (int i = 0; i < 7; i++) bulk_prefetch((const char*)wo + (i * 4 + mi) * 14336, 14336);
                uint32_t t = (uint32_t)t0 + PF0_AT;
                #pragma unroll 1
                for (int i = 0; i < PF0_N; i++) {
                    while ((int)(clock32() - t) < 0) {}
                    bulk_prefetch((const char*)w1 + i * 114688 + mi * 14336, 14336);
                    t += PF0_PACE;
                }
                if (mi) {
                    t = (uint32_t)t0 + PF1_AT;
                    #pragma unroll 1
                    for (int i = mi - 1; i < PF1_N; i += 3) {
                        while ((int)(clock32() - t) < 0) {}
                        tma5d_prefetch(&tm_w1, (i & 7) * 64, (i + 48) & 56, (i + 48) >> 6);
                        t += PF1_PACE;
                    }
                    t = (uint32_t)t0 + PF_AT;
                    #pragma unroll 1
                    for (int i = mi - 1; i < PF_N; i += 3) {
                        while ((int)(clock32() - t) < 0) {}
                        bulk_prefetch((const char*)w2 + (i < 128 ? i * 16384 : (i - 64 >> 1) * 65536 + (i & 1) * 16384), 16384);
                        t += PF_PACE;
                    }
                }
                while (ld_relaxed(sc->hint_u + 254) != ep) { __nanosleep(500); if (clock64() - t0 > WD_CLKS) __trap(); }
                sc->epoch[slot] = ep;
                if (mi == 1) sc->clean = ep + 1;
            }
            return;
        }
        {
            const int w = warp & 3, wg = warp >> 2, g = lane >> 2, t = lane & 3;
            if (WARM_AT) { const uint32_t t0 = clock32(); while (clock32() - t0 < WARM_AT) {} __syncwarp(); }
            if (w > 0) post_hint(sc->hint_o + ((2 * tb + (w >> 1)) * 32 + hp * 4 + (w & 1) * 2 + wg) * 2, 0, lane);
            if (wg == 0) {
                if (t < 2) st_relaxed4(sc->stats + tt2 * 256 + q * 64 + 16 * w + g + 8 * t, 0, 0, 0, 0);
            }
        }
        named_sync(0, 288);
        asm volatile("setmaxnreg.inc.sync.aligned.u32 224;");
        int tid; asm volatile("mov.u32 %0, %%tid.x;" : "=r"(tid));
        const int lane = tid & 31, warp = __shfl_sync(0xffffffffu, tid >> 5, 0), wg = warp >> 2;
        uint32_t ep;
        Tiles* tl;
        const int w = warp & 3, g = lane >> 2, t = lane & 3;
        const bool leader = (tid & 127) == 0;
        const uint32_t never = gridDim.y - 1;
        {
            uint32_t a[28][4];
            float accK[28], accV[28], accQ[28];
            const int lrow = 16 * w + (lane & 7) + (lane & 8);
            const uint32_t lbase = sb + wg * 8192 + lrow * 128;
            const uint32_t lx = (lane >> 4) ^ (lane & 7);
            const uint32_t wofs = hp & 1;
            auto pin2 = [&](uint32_t x0, uint32_t x1) {
                asm volatile("{\n.reg .pred p;\nsetp.ne.u32 p, %2, 0;\n@p st.shared.v2.b32 [%0], {%0,%1};\n}" :: "r"(x0), "r"(x1), "r"(never) : "memory");
            };
            float cS[2][4] = {}, cA[2][4] = {}, cB[2][4] = {}, q0, q1, p0, p1;
            auto sq = [&](float& acc, uint32_t v) { const float lo = bf_lo(v), hi = bf_hi(v); acc = fmaf(hi, hi, fmaf(lo, lo, acc)); };
            #pragma unroll
            for (int kb = 0; kb < 8; kb++) {
                if (kb < 7) {
                    mbar_wait(bars + 8 * (B_FULLX + kb), 0);
                    if (kb == 0 && tid == 0) STAMP(0);
                    if (kb == 6 && tid == 0) STAMP(25);
                    if (kb == 0) FST(0); if (kb == 2) FST(1); if (kb == 4) FST(2); if (kb == 6) FST(3);
                    #pragma unroll
                    for (int s = 4 * kb; s < 4 * kb + 4; s++) ldsm4(a[s], lbase + slot_x(kb) + ((lx ^ (2 * (s & 3))) << 4));
                }
                if (kb == 5) named_sync(9 + wg, 160);
                if (kb == NPIPE) continue;
                const int kc = kb < NPIPE ? kb : kb - 1;
                if (kc == NSQ) { p0 = cS[0][0] + cS[1][0]; p1 = cS[0][2] + cS[1][2]; }
                #pragma unroll
                for (int s = 4 * kc; s < 4 * kc + 4; s++) {
                    mma16816(cS[s & 1], a[s][0], a[s][1], a[s][2], a[s][3], 0x3F803F80u, 0x3F803F80u);
                    if (kc < NSQ) {
                        mma1688(cA[0], a[s][0], a[s][1], a[s][0]); mma1688(cA[1], a[s][2], a[s][3], a[s][2]);
                        mma1688(cB[0], a[s][0], a[s][1], a[s][1]); mma1688(cB[1], a[s][2], a[s][3], a[s][3]);
                    }
                }
            }
            const float m0 = (cS[0][0] + cS[1][0]) * (1.f / D_), m1 = (cS[0][2] + cS[1][2]) * (1.f / D_);
            const uint32_t mm0 = pack_bf16(m0, m0), mm1 = pack_bf16(m1, m1);
            if (lane == 0) mbar_arrive(bars + 8 * B_DONEX);
            auto center = [&](int s) { sub_bf16x2(a[s][0], mm0); sub_bf16x2(a[s][1], mm1); sub_bf16x2(a[s][2], mm0); sub_bf16x2(a[s][3], mm1); };
            uint32_t Ka[8], Kb[8], Kc[8], Va[8], Vb[7], Vc[8];
            float r0, r1, ls0, ls1;
            uint32_t pm, zero;
            uint32_t* od;
            uint4* oh;
            auto kpack = [&](uint32_t (&k)[8], int j, int c, float r) {
                const uint32_t v = pack_bf16(accK[4 * j + c] * r, accK[4 * j + c + 1] * r);
                if (j == 3) { k[3] = t < 2 ? v : 0u; k[4] = t < 2 ? 0u : v; } else k[j + (j > 3)] = v;
            };
            auto batch = [&](auto c0, auto c1) {
                constexpr int n0 = c0.value, n1 = c1.value;
                wg_fence();
                static_for<n0, n1>([&](auto nc) {
                    constexpr int n = nc.value;
                    if (n == 4) { center(4); center(5); center(6); center(7); wg_fence(); }
                    const uint64_t desc = mkdesc(sb + (n < 56 ? slot_kv(n >> 3) + (n & 7) * 2048 : SM_QO + (n - 56) * 2048), 8192, 1024, 1) + wofs;
                    wgmma_rs56<1>(n < 28 ? accK : n < 56 ? accV : accQ, a[n % 28], desc, n % 28 != 0);
                });
                wg_commit();
                if (n0 > 0) wg_wait<1>();
            };
            const uint32_t hs = sb + tid * 16 + warp * 512;
            auto hand_over = [&](const uint32_t (&v)[8], int kv) {
                mbar_wait(bars + 8 * (kv ? B_DONE1 + 5 : B_DONEX), 0);
                sts4(hs + (kv ? SM_HALOV : SM_HALOK), v[0], v[1], v[2], v[3]); sts4(hs + (kv ? SM_HALOV : SM_HALOK) + 512, v[4], v[5], v[6], v[7]);
                if (w == 3) named_arrive(6 + kv, 96);
            };
            auto take_over = [&](uint32_t (&v)[8], int kv) {
                if (w == 0) mbar_wait(bars + 8 * (B_HALO + 2 * kv + wg), 0);
                const uint32_t ad = w ? hs + (kv ? SM_HALOV : SM_HALOK) - 1024 : kv ? sb + lane * 16 + wg * 1024 + SM_HALOV + 8192 : halo_kin(wg, lane);
                const uint4 u0 = lds4(ad), u1 = lds4(ad + (w || kv ? 512 : 16));
                v[0] = u0.x; v[1] = u0.y; v[2] = u0.z; v[3] = u0.w; v[4] = u1.x; v[5] = u1.y; v[6] = u1.z; v[7] = u1.w;
            };
            center(0); center(1); center(2); center(3);
            static_for<0, 7>([&](auto pc) {
                constexpr int p = pc.value;
                mbar_wait(bars + 8 * (B_FULLKV + p), 0);
                if (p == 0 && tid == 0) STAMP(26);
                if (p == 3 && tid == 0) STAMP(27);
                FST(4 + p);
                batch(Int<8 * p>(), Int<8 * p + 8>());
                if (p > 0 && leader) mbar_arrive(bars + 8 * (B_DONE1 + p - 1));
                #pragma unroll
                for (int s = 8 * p + 8; s < 8 * p + 16 && s < 28; s++) center(s);
                if (p == 1) {
                    const float c0 = bf_hi(mm0), c1 = bf_hi(mm1);
                    q0 = fmaf(c0, fmaf(c0, 64.f * NSQ, -2.f * p0), (g & 1) ? cA[0][1] + cA[1][1] : cA[0][0] + cA[1][0]) - D_ * (m0 - c0) * (m0 - c0);
                    q1 = fmaf(c1, fmaf(c1, 64.f * NSQ, -2.f * p1), (g & 1) ? cB[0][3] + cB[1][3] : cB[0][2] + cB[1][2]) - D_ * (m1 - c1) * (m1 - c1);
                    asm("" : "+f"(q0), "+f"(q1));
                    q0 = t == (g >> 1) ? q0 : 0.f; q1 = t == (g >> 1) ? q1 : 0.f;
                    pin2(__float_as_uint(q0), __float_as_uint(q1));
                }
                constexpr int PK = NSQ < 5 ? 5 : 4, NR = 28 - 4 * NSQ;
                if (p >= 2 && p < PK) {
                    #pragma unroll
                    for (int s = 4 * NSQ + NR * (p - 2) / (PK - 2); s < 4 * NSQ + NR * (p - 1) / (PK - 2); s++) { sq(q0, a[s][0]); sq(q1, a[s][1]); sq(q0, a[s][2]); sq(q1, a[s][3]); }
                    pin2(__float_as_uint(q0), __float_as_uint(q1));
                }
                if (p == PK - 1) { q0 = quad_sum(q0); q1 = quad_sum(q1); }
                if (p == PK) {
                    r0 = rsqrt_approx(fmaxf(q0 * (1.f / D_), 0.f) + LN_EPS); r1 = rsqrt_approx(fmaxf(q1 * (1.f / D_), 0.f) + LN_EPS);
                    reg_fence(accK);
                    #pragma unroll
                    for (int j = 0; j < 7; j++) kpack(Kc, j, 2, r1);
                    hand_over(Kc, 0);
                }
                if (p == PK + 1) {
                    #pragma unroll
                    for (int j = 0; j < 7; j++) kpack(Kb, j, 0, r0);
                    #pragma unroll
                    for (int j = 0; j < 8; j += 2) pin2(Kb[j], Kb[j + 1]);
                    ls0 = LOG2E_SCALE * r0; ls1 = LOG2E_SCALE * r1;
                    pm = (2 * t <= g ? 0xFFFFu : 0u) | (2 * t + 1 <= g ? 0xFFFF0000u : 0u);
                    zero = never; asm volatile("" : "+r"(zero));
                    pin2(__float_as_uint(ls0), __float_as_uint(ls1)); pin2(pm, zero);
                }
                if (p == 2) ep = get_tag();
                if (p == 6) {
                    tl = &sc->tiles[ep & 1];
                    const int tt = 2 * tb + (w >> 1);
                    od = tl->o + tt * 14336 + (7 * hp) * 256 + (2 * (2 * (w & 1) + wg)) * 32 + lane;
                    oh = sc->hint_o + (tt * 32 + hp * 4 + (w & 1) * 2 + wg) * 2 + (lane & 1);
                    pin2((uint32_t)(uint64_t)od, (uint32_t)((uint64_t)od >> 32));
                    pin2((uint32_t)(uint64_t)oh, (uint32_t)((uint64_t)oh >> 32));
                }
            });
            if (tid == 0) STAMP(1);
            FST(11);
            mbar_wait(bars + 8 * B_FQ, 0);
            batch(Int<56>(), Int<60>());
            reg_fence(accV);
            if (leader) mbar_arrive(bars + 8 * (B_DONE1 + 6));
            if (tid == 0) STAMP(2);
            FST(12);
            #pragma unroll
            for (int j = 0; j < 7; j++) Vc[j] = movtrans(pack_bf16(accV[4 * j + 2] * r1, accV[4 * j + 3] * r1));
            Vc[7] = Vc[6];
            hand_over(Vc, 1);
            batch(Int<60>(), Int<66>());
            #pragma unroll
            for (int j = 0; j < 7; j++) {
                Vb[j] = movtrans(pack_bf16(accV[4 * j] * r0, accV[4 * j + 1] * r0));
                Vc[j] |= zero;
            }
            batch(Int<66>(), Int<72>());
            #pragma unroll
            for (int j = 0; j < 7; j++) pin2(Vb[j], Vc[j]);
            mbar_wait(bars + 8 * (B_FQ + 1), 0);
            FST(13);
            if (w > 0 && lane < 2) { const uint32_t now = gtime32(); st_relaxed4(oh, ep, now, ep, now); }
            batch(Int<72>(), Int<84>());
            FST(14);
            named_sync(1 + wg, 128);
            take_over(Ka, 0);
            if (tid == 0) STAMP(3);
            wg_wait<0>();
            reg_fence(accQ);
            if (tid == 0) STAMP(4);
            FST(15);
            const bool first = (tb == 0 && w == 0);
            uint32_t pA[2], pB0[2], pB1[2], pC[2], z0[2], z1[2];
            #pragma unroll
            for (int h = 0; h < 2; h++) {
                float sA[4] = {0.f, 0.f, 0.f, 0.f}, sB[4] = {0.f, 0.f, 0.f, 0.f}, sC[4] = {0.f, 0.f, 0.f, 0.f};
                #pragma unroll
                for (int k = 0; k < 2; k++) {
                    const float* qq = accQ + 12 * h + 8 * k;
                    uint32_t a0 = pack_bf16(qq[0], qq[1]), a1 = pack_bf16(qq[2], qq[3]);
                    if (h == 1 && k == 0) { a0 |= zero; a1 |= zero; }
                    const uint32_t a2 = pack_bf16(qq[4], qq[5]), a3 = pack_bf16(qq[6], qq[7]);
                    mma16816(sB, a0, a1, a2, a3, Kb[4 * h + 2 * k], Kb[4 * h + 2 * k + 1]);
                    mma16816(sA, a0, a1, a2, a3, Ka[4 * h + 2 * k], Ka[4 * h + 2 * k + 1]);
                    mma16816(sC, a0, a1, a2, a3, Kc[4 * h + 2 * k], Kc[4 * h + 2 * k + 1]);
                }
                const bool n0 = pm & 1, n1 = (int)pm < 0;
                const float l00 = n0 ? sB[0] : (first ? -INFINITY : sA[0]), l01 = n1 ? sB[1] : (first ? -INFINITY : sA[1]);
                const float l10 = n0 ? sC[2] : sB[2], l11 = n1 ? sC[3] : sB[3];
                const float x0 = -ls0 * quad_max(fmaxf(l00, l01)), x1 = -ls1 * quad_max(fmaxf(l10, l11));
                const float e00 = ex2(fmaf(l00, ls0, x0)), e01 = ex2(fmaf(l01, ls0, x0)), e10 = ex2(fmaf(l10, ls1, x1)), e11 = ex2(fmaf(l11, ls1, x1));
                const float i0 = rcp_approx(quad_sum(e00 + e01)), i1 = rcp_approx(quad_sum(e10 + e11));
                const uint32_t P0 = pack_bf16(e00 * i0, e01 * i0), P1 = pack_bf16(e10 * i1, e11 * i1);
                pB0[h] = P0 & pm; pA[h] = P0 & ~pm; pC[h] = P1 & pm; pB1[h] = P1 & ~pm; z0[h] = P0 & zero; z1[h] = P1 & zero;
            }
            float o[8][4];
            #pragma unroll
            for (int j = 0; j < 8; j++) {
                o[j][0] = o[j][1] = o[j][2] = o[j][3] = 0.f;
                mma16816(o[j], pB0[j >> 2], pB1[j >> 2], z0[j >> 2], pC[j >> 2], Vb[j - (j >> 2)], Vc[j - (j >> 2)]);
            }
            if (tid == 0) STAMP(12);
            FST(16);
            take_over(Va, 1);
            if (lane == 0) mbar_arrive(bars + 8 * B_DONEQ);
            if (tid == 0) STAMP(16);
            #pragma unroll
            for (int j = 0; j < 8; j++) mma1688(o[j], pA[j >> 2], z1[j >> 2], Va[j - (j >> 2)]);
            #pragma unroll
            for (int j = 0; j < 7; j++) {
                float v[4];
                #pragma unroll
                for (int c = 0; c < 4; c++) v[c] = j < 3 ? o[j][c] : j > 3 ? o[j + 1][c] : (t < 2 ? o[3][c] : o[4][c]);
                od[j * 256] = pack_bf16(v[0], v[1]);
                od[j * 256 + 32] = pack_bf16(v[2], v[3]);
            }
            if (tid == 0) STAMP(5);
            FST(17);
        }
        const int z = get_tag() - ep, slot1 = slot + z, tid1 = tid + z, warp1 = warp + z;
        ep += z;
        {
        ASSIGN_WORK(slot1)
        const int tid = tid1, lane = tid & 31, wg = warp1 >> 2, w = warp1 & 3, g = lane >> 2, t = lane & 3;
        tl = &sc->tiles[ep & 1];
        const uint32_t live = wg ^ 1;
        uint32_t rb0, rb1, late[14];
        const unsigned short* pb = (const unsigned short*)(live ? b2 + tt2 * 64 : b1 + ft * 64) + 16 * w + g;
        auto stage_late = [&]() {
            #pragma unroll
            for (int c = 0; c < 14; c++) asm volatile("st.shared.u32 [%0], %1;" :: "r"(sb + SM_H + wg * 8192 + (tid & 127) * 4 + c * 512), "r"(late[c]) : "memory");
            fence_async_smem();
            named_sync(1 + wg, 128);
        };
        auto store_late = [&](bool on, uint32_t* p) {
            #pragma unroll
            for (int c = 0; c < 4; c++)
                if (elect() && on && (c < 3 || w < 2)) bulk_st(p + (4 * c + w) * 256, sb + SM_H + wg * 8192 + (4 * c + w) * 512, 512);
            asm volatile("cp.async.bulk.commit_group;" ::: "memory");
        };
        auto undef = [](float (&v)[56]) {
            #pragma unroll
            for (int i = 0; i < 56; i++) asm volatile("" : "=f"(v[i]));
        };
        {
            float acc[56];
            const int hrow = 32 * (w >> 1) + 2 * ((lane & 7) + (lane & 8)) + (w & 1);
            const uint32_t ha = sb + SM_H + hrow * 128 + (((lane >> 4) ^ (hrow & 7)) << 4);
            uint4* sp = sc->stats + tt2 * 256 + 16 * w + g + 8 * (t & 1);
            uint4* sp_out = sp + q * 64;
            const uint4* sp_in = sp + (t & 2) * 64;
            uint32_t* hd = tl->hn + ((q >> 1) * 32 + (tt2 >> 1)) * 7168 + (q & 1) * 3584 + (tt2 & 1) * 128 + w * 32 + lane;
            pin_ptr(never, sp_out); pin_ptr(never, sp_in); pin_ptr(never, hd);
            float s0 = 0.f, s1 = 0.f, q0 = 0.f, q1 = 0.f, s2 = 0.f, s3 = 0.f, q2 = 0.f, q3 = 0.f;
            auto sums = [&](int j0, int j1) {
                #pragma unroll
                for (int j = j0; j < j1; j++) {
                    s0 += acc[4 * j]; s2 += acc[4 * j + 1]; q0 = fmaf(acc[4 * j], acc[4 * j], q0); q2 = fmaf(acc[4 * j + 1], acc[4 * j + 1], q2);
                    s1 += acc[4 * j + 2]; s3 += acc[4 * j + 3]; q1 = fmaf(acc[4 * j + 2], acc[4 * j + 2], q1); q3 = fmaf(acc[4 * j + 3], acc[4 * j + 3], q3);
                }
            };
            if (live) {
                mbar_wait(bars + 8 * B_FULLWO, 0);
                #pragma unroll
                for (int jp = 0; jp < 7; jp++) {
                    uint32_t xx[4];
                    ldsm4(xx, hcol(ha, jp));
                    #pragma unroll
                    for (int r = 0; r < 4; r++) { acc[8 * jp + 2 * r] = bf_lo(xx[r]); acc[8 * jp + 2 * r + 1] = bf_hi(xx[r]); }
                }
                reg_fence(acc);
                if (SPIN2) { named_sync(12, 256); spin_mma(bars + 8 * B_FULLX, never); }
                auto od_ = [&](int s) { return mkdesc(sb + SM_QO + s * 2048, 1024, 128, 0); };
                auto wd_ = [&](int s) { return mkdesc(sb + slot_wo(s >> 2) + (s & 3) * 2048, 8192, 1024, 1); };
                float accl[32], accr[24];
                #pragma unroll
                for (int i = 0; i < 5; i++) {
                    if (i < 4) mbar_wait(bars + 8 * (B_FULLO + i), 0);
                    if (i == 0 && tid == 0) STAMP(7);
                    if (i == 1) { rb0 = ld_u16(pb); rb1 = ld_u16(pb + 8); }
                    wg_fence();
                    #pragma unroll
                    for (int ss = 0; ss < 7; ss++) {
                        if (i < 3) wgmma_ss112<0, 1>(acc, od_(7 * i + ss), wd_(7 * i + ss));
                        else if (i == 4) wgmma_ss64<0, 1>(accl, od_(21 + ss), wd_(21 + ss));
                        else if (ss == 0) wgmma_ss48<0, 1, 0>(accr, od_(21), wd_(21) + 512);
                        else wgmma_ss48<0, 1>(accr, od_(21 + ss), wd_(21 + ss) + 512);
                    }
                    wg_commit();
                    if (i > 0) {
                        wg_wait<1>();
                        if (i == 3) {
                            reg_fence(acc);
                            #pragma unroll
                            for (int c = 0; c < 32; c++) accl[c] = __uint_as_float(__float_as_uint(acc[c]) | never);
                            reg_fence(accl);
                        }
                        if (i < 4 && leader) mbar_arrive(bars + 8 * (B_DONEO + i - 1));
                    }
                }
                reg_fence(accr);
                #pragma unroll
                for (int c = 0; c < 24; c++) acc[32 + c] += accr[c];
                sums(8, 14);
                pin4(never, s0, s1, s2, s3); pin4(never, q0, q1, q2, q3);
                wg_wait<0>();
                reg_fence(accl);
                #pragma unroll
                for (int c = 0; c < 32; c++) acc[c] = accl[c];
                if (leader) mbar_arrive(bars + 8 * (B_DONEO + 3));
                if (tid == 0) STAMP(8);
            } else { undef(acc); if (SPIN2) named_arrive(12, 256); }
            if (live || (DRY2 && w == 3)) {
            sums(0, 8);
            s0 += s2; s1 += s3; q0 += q2; q1 += q3;
            float sr = ((t & 1) ? s1 : s0) + __shfl_xor_sync(0xffffffffu, (t & 1) ? s0 : s1, 1), qr = ((t & 1) ? q1 : q0) + __shfl_xor_sync(0xffffffffu, (t & 1) ? q0 : q1, 1);
            sr += __shfl_xor_sync(0xffffffffu, sr, 2); qr += __shfl_xor_sync(0xffffffffu, qr, 2);
            st_relaxed4_if(t < 2 * live, sp_out, __float_as_uint(sr), __float_as_uint(qr), ep);
            const uint32_t tp = clock32();
            if (live) named_arrive(5, 256);
            if (tid == 0) STAMP(9);
            #pragma unroll
            for (int jp = 0; jp < 7; jp++)
                stsm4_if(live, hcol(ha, jp), pack_bf16(acc[8 * jp], acc[8 * jp + 1]), pack_bf16(acc[8 * jp + 2], acc[8 * jp + 3]),
                      pack_bf16(acc[8 * jp + 4], acc[8 * jp + 5]), pack_bf16(acc[8 * jp + 6], acc[8 * jp + 7]));
            uint4 v0, v1;
            if (POLL0) { while (clock32() - tp < POLL0) {} __syncwarp(); }
            do { v0 = ld_relaxed4(sp_in); v1 = ld_relaxed4(sp_in + 64); } while (live && __any_sync(0xffffffffu, v0.w != ep || v1.w != ep));
            if (tid == 0) STAMP(10);
            sr = __uint_as_float(v0.x) + __uint_as_float(v1.x); qr = __uint_as_float(v0.y) + __uint_as_float(v1.y);
            sr += __shfl_xor_sync(0xffffffffu, sr, 2); qr += __shfl_xor_sync(0xffffffffu, qr, 2);
            const float m = sr * (1.f / D_), var = fmaxf(qr * (1.f / D_) - m * m, 0.f);
            const float r = rsqrt_approx(fmaf(var, 4.f + 4.f * LN_EPS, 4.f * LN_EPS * LN_EPS)), c = -m * r;
            const float r0 = __shfl_sync(0xffffffffu, r, lane & ~1), c0 = __shfl_sync(0xffffffffu, c, lane & ~1);
            const float r1 = __shfl_sync(0xffffffffu, r, lane | 1), c1 = __shfl_sync(0xffffffffu, c, lane | 1);
            #pragma unroll
            for (int j = 0; j < 14; j++) st_global_if(live, hd + j * 256, pack_bf16(fmaf(acc[4 * j], r0, c0), fmaf(acc[4 * j + 1], r0, c0)));
            if (never) mbar_arrive(bars);
            if (SPIN3) named_arrive_if(live, 3, 256);
            #pragma unroll
            for (int j = 0; j < 14; j++) late[j] = pack_bf16(fmaf(acc[4 * j + 2], r1, c1), fmaf(acc[4 * j + 3], r1, c1));
            if (tid == 0) STAMP(11);
            }
        }
        if (!live) {
            if (w < 2) check_tiles<0>(w, 2, 4, tl->o + tt2 * 14336, false, lane, true);
            rb0 = ld_u16(pb); rb1 = ld_u16(pb + 8);
            named_sync(5, 256);
            auto phase3 = [&](auto nc) {
                constexpr int NC = nc.value;
                float acc[4 * NC];
                uint32_t* ud = tl->u + (pr3 * 28 + (ft >> 1) + (NC == 14 ? 4 : 0)) * 7168 + col3 * 256 + (ft & 1) * 128 + w * 32 + lane;
                #pragma unroll
                for (int j = 0; j < 4 * NC; j++) acc[j] = 0.5f * bf_lo((j & 2) ? rb1 : rb0);
                #pragma unroll 1
                for (uint32_t pass = never; pass < 2; pass++) {
                    if (pass) {
                        if (SPIN3) { named_sync(3, 256); spin_mma(bars + 8 * (B_FULLX + 1), never); }
                        mix_mainloop<32>(TSVAL acc, leader);
                        if (leader) STAMP(14);
                    }
                    uint32_t pk[NC];
                    #pragma unroll
                    for (int j = 0; j < NC; j++) {
                        const float k = j < GDEP ? GELU_K1 : __uint_as_float(__float_as_uint(GELU_K1) | (pk[j - GDEP] & never));
                        pk[j] = pack_bf16(gelu_half(acc[4 * j], k), gelu_half(acc[4 * j + 1], k));
                        st_global_if(pass, ud + j * 256, pk[j]);
                    }
                }
                if (leader) STAMP(15);
                #pragma unroll
                for (int j = 0; j < NC; j++) late[j] = pack_bf16(gelu_half(acc[4 * j + 2], GELU_K1), gelu_half(acc[4 * j + 3], GELU_K1));
                if (NC == 14) {
                    stage_late();
                    mbar_wait(bars + 8 * (B_FULLB + LATE_AT4), 1);
                    store_late(true, tl->u + (pr3 * 28 + (ft >> 1) + 14) * 7168 + col3 * 256 + (ft & 1) * 128);
                } else {
                    #pragma unroll
                    for (int c = 0; c < NC; c++) st_global_if(1, ud + 4 * 7168 + c * 256, late[c]);
                    if (SPIN4) named_arrive(13, 256);
                }
            };
            if (early) phase3(Int<10>()); else phase3(Int<14>());
            if (w) {
                if (early && w == 1) fetch_times(TSVAL sc->go, 1, ep, lane);
                check_tiles<2>(CH_U - 1 + w, 3, 28, tl->u + (q >> 1) * 28 * 7168 + (q & 1) * 3584, false, lane, false);
                mbar_wait(bars + 8 * (B_DONE + CL_AT), 1);
                const int l = slot * 48 + (tid - 160) / 2;
                #pragma unroll
                for (int i = 0; i < 7; i++)
                    st_relaxed4_if(i < 6 || l < sizeof(Tiles) / 128 - 6 * 6144, (uint4*)&sc->tiles[~ep & 1] + (i * 6144 + l) * 8 + (lane & 7), EMPTY, EMPTY, EMPTY);
            }
            if (leader) mbar_wait_wd(bars + 8 * B_END, 0);
            return;
        }
        {
            float acc[56];
            const uint32_t ad = sb + SM_H + (16 * w + (lane & 15)) * 128 + (((lane >> 4) ^ (lane & 7)) << 4);
            const float bb0 = bf_lo(rb0), bb1 = bf_lo(rb1);
            named_sync(1, 128);
            #pragma unroll
            for (int jp = 0; jp < 7; jp++) {
                uint32_t hh[4];
                ldsm4(hh, hcol(ad, jp));
                #pragma unroll
                for (int r = 0; r < 4; r++) { acc[8 * jp + 2 * r] = bf_lo(hh[r]) + ((r & 1) ? bb1 : bb0); acc[8 * jp + 2 * r + 1] = bf_hi(hh[r]) + ((r & 1) ? bb1 : bb0); }
            }
            #pragma unroll 1
            for (uint32_t pass = never; pass < 2; pass++) {
                if (pass) {
                    named_sync(1, 128);
                    stage_late();
                    if (tid == 0) STAMP(39);
                    mbar_wait(bars + 8 * (B_FULLB + LATE_AT), 0);
                    store_late(true, tl->hn + ((q >> 1) * 32 + 16 + (tt2 >> 1)) * 7168 + (q & 1) * 3584 + (tt2 & 1) * 128);
                    check_tiles<1>(CH_H + w, 4, 32, tl->hn + pr3 * 32 * 7168 + col3 * 256, early, lane, false);
                    mbar_wait(bars + 8 * (B_DONE + START4), 0);
                    if (SPIN4 && early) { named_sync(13, 256); spin_mma(bars + 8 * (B_FULLX + 2), never); }
                    mix_mainloop<28>(TSVAL acc, leader);
                    if (leader) mbar_arrive(bars + 8 * B_END);
                    if (tid == 0) STAMP(18);
                }
                #pragma unroll
                for (int jp = 0; jp < 7; jp++)
                    stsm4_if(1, hcol(ad, jp), pack_bf16(acc[8 * jp], acc[8 * jp + 1]), pack_bf16(acc[8 * jp + 2], acc[8 * jp + 3]),
                             pack_bf16(acc[8 * jp + 4], acc[8 * jp + 5]), pack_bf16(acc[8 * jp + 6], acc[8 * jp + 7]));
                fence_async_smem();
                __syncwarp();
            }
            if (elect()) {
                tma2d_store(&tm_out64, c64, tt2 * 64 + 16 * w, sb + SM_H + w * 2048);
                tma2d_store(&tm_out48, c48, tt2 * 64 + 16 * w, sb + SM_H + 8192 + w * 2048);
            }
            asm volatile("cp.async.bulk.commit_group;" ::: "memory");
            asm volatile("cp.async.bulk.wait_group.read 0;" ::: "memory");
            if (tid == 0) { sc->epoch[slot] = ep; STAMP(19); }
        }
        }
    } else {
        asm volatile("setmaxnreg.dec.sync.aligned.u32 56;");
        int warp2; asm("mov.u32 %0, %1;" : "=r"(warp2) : "r"(warp));
        if (warp2 > 8) {
            ASSIGN_WORK(get_slot())
            if (slot >= 128) return;
            uint32_t ep, cl;
            uint4* const oh = sc->hint_o + (2 * tb * 32 + hp * 4) * 2 + (lane & 3);
            uint4* const hu = sc->hint_u + (early ? ech * 8 + ft : 40 + q * 20 + ft) * 2;
            if (warp == 10) {
                post_hint(sc->hint_h + (q * 32 + tt2) * 2, 0, lane);
                post_hint(hu, 0, lane);
            }
            if (warp == 11) {
                ep = ld_volatile(&sc->epoch[slot]) + 1; cl = ld_acquire(&sc->clean);
                post_hint(sc->hint_k + (tb * 8 + hp) * 2, 0, lane);
                if (lane < (tb < 15 ? 4 : 0)) st_relaxed4(oh + 128, 0, 0, 0, 0);
                if (lane < (tb ? 0 : 4)) st_relaxed4(oh, 0, 0, 0, 0);
            }
            if (elect()) {
                if (warp == 9) {
                    #pragma unroll
                    for (int i = B_DONE1; i < B_DONEO; i++) mbar_init(bars + 8 * i, i < B_DONEX ? 2 : i == B_DONEX ? 8 : 9);
                }
                #pragma unroll
                for (int i = 0; i < 54; i++) mbar_init(bars + 8 * (B_DONEO + i) + (warp - 9) * 432, 1);
                asm volatile("fence.mbarrier_init.release.cluster;" ::: "memory");
            }
            named_sync(8, 128);
            if (warp < 11) mbar_expect(sb + SM_RAW + 8 * (tid - 288), early && tid >= 292 && tid < 324 ? 10240 : 14336);
            if (warp == 9) { named_arrive(4, 64); named_arrive(9, 160); named_arrive(10, 160); }
            if (warp < 11) {
                ep = get_tag();
                mbar_wait(bars + 8 * (B_DONE1 + HALO_AT), 0);
                #pragma unroll 1
                for (int kv = 0; kv < 2; kv++) {
                    uint4 v0 = {}, v1 = {}, v2 = {};
                    if (tb > 0) {
                        const uint4* hg = sc->halo + ((((tb - 1) * 8 + hp) * 2 + warp - 9) * 2 + kv) * 96 + lane;
                        if (kv == 0) while (ld_relaxed(sc->hint_k + ((tb - 1) * 8 + hp) * 2) != ep) {}
                        do { v0 = ld_relaxed4(hg); v1 = ld_relaxed4(hg + 32); v2 = ld_relaxed4(hg + 64); } while (!__all_sync(0xffffffffu, v0.w == ep && v1.w == ep && v2.w == ep));
                    }
                    if (kv) mbar_wait(bars + 8 * (B_DONE1 + 5), 0);
                    const uint32_t hs = kv ? sb + lane * 16 + (warp - 9) * 1024 + SM_HALOV + 8192 : halo_kin(warp - 9, lane);
                    sts4(hs, v0.x, v0.y, v0.z, v1.x); sts4(hs + (kv ? 512 : 16), v1.y, v1.z, v2.x, v2.y);
                    __syncwarp();
                    if (lane == 0) mbar_arrive(bars + 8 * (B_HALO + 2 * kv + warp - 9));
                }
                if (tid == 288) STAMP(21);
            } else {
                const long long t0 = clock64();
                while (__any_sync(0xffffffffu, (int)(cl - ep) < 0)) { cl = ld_acquire(&sc->clean); if (clock64() - t0 > WD_CLKS) __trap(); }
                if (lane == 0) { *(volatile uint32_t*)(smem_raw + SM_TAG) = ep; mbar_arrive(bars + 8 * B_CLR); }
                uint4* hg = sc->halo + (tb * 8 + hp) * 384 + lane;
                #pragma unroll 1
                for (int kv = 0; kv < 2; kv++) {
                    const uint32_t hs = sb + lane * 16 + 3072 + (kv ? SM_HALOV : SM_HALOK);
                    named_sync(6 + kv, 96);
                    #pragma unroll
                    for (int p = 0; p < 2; p++) {
                        const uint4 u0 = lds4(hs + p * 4096), u1 = lds4(hs + p * 4096 + 512);
                        st_relaxed4(hg + p * 192, u0.x, u0.y, u0.z, ep); st_relaxed4(hg + p * 192 + 32, u0.w, u1.x, u1.y, ep); st_relaxed4(hg + p * 192 + 64, u1.z, u1.w, ep, ep);
                    }
                    hg += 96;
                    if (kv == 0) {
                        post_hint(sc->hint_k + (tb * 8 + hp) * 2, ep, lane);
                        #pragma unroll
                        for (int j = 0; j < 6; j++) st_relaxed4(hg + j * 32 + (j / 3) * 96, 0, 0, 0, 0);
                    }
                }
                const uint32_t now = gtime32() - LATE_O;
                if (lane < (tb < 15 ? 4 : 0)) st_relaxed4(oh + 128, ep, now, ep, now);
                if (lane < (tb ? 0 : 4)) st_relaxed4(oh, ep, now, ep, now);
                if (lane == 0) STAMP(23);
                if (lane == 0) mbar_arrive(bars + 8 * B_DONEQ);
            }
            if (warp > 9) {
                const Tiles* const tl = &sc->tiles[ep & 1];
                check_tiles<1>(11 - warp, 2, CH_H, tl->hn + pr3 * 32 * 7168 + col3 * 256, early, lane, true);
                if (warp == 10) {
                    mbar_wait(bars + 8 * (B_DONE + (early ? HINT_E : HINT_U)), 0);
                    post_time(hu, ep, lane);
                }
                if (warp == 11) {
                    mbar_wait(bars + 8 * (B_DONE + (early ? POLL_E : POLL_N)), 0);
                    fetch_times(TSVAL sc->go, 0, ep, lane);
                }
                check_tiles<2>(11 - warp, 2, CH_U, tl->u + (q >> 1) * 28 * 7168 + (q & 1) * 3584, false, lane, true);
            } else {
                int aslot = 0;
                if (lane == 0) { prefetch_map(&tm_out64); prefetch_map(&tm_out48); }
                #pragma unroll
                for (int i = 0; i < HINT_F; i++) mbar_wait(bars + 8 * (B_FULLO + i), 0);
                post_time(sc->hint_h + (q * 32 + tt2) * 2, ep, lane);
                #pragma unroll 1
                for (int i = 0; i < 30; i++) {
                    if (i == POLL_I && !early) fetch_times(TSVAL sc->go, 1, ep, lane);
                    int d = 2 * i - 11 + (i >= A4_FROM ? A4_DLY : 0);
                    if (early) d = i < 16 ? 1 + (i - NA_SLOTS) * AE_END / 9 : max(d, AE_W2);
                    mbar_wait(bars + 8 * (i < NA_SLOTS ? B_DONEQ + ((A_SCHED >> (4 * i)) & 15) : B_DONE + (d & 31)), d >= 32);
                    if (elect()) {
                        const uint32_t bar = bars + 8 * (B_FULLA + (i & 15)), dst = sb + SM_ARING + aslot * 16384;
                        mbar_expect(bar, 16384);
                        if (i < 16) tma5d(dst, &tm_w1, ft * 64, (i & 7) * 8, i >> 3, bar);
                        else tma5d(dst, &tm_w2, tt2 * 64, 8 * (i < 20 ? i & 1 : i < 25 ? i - 18 : i - 23), i < 20 ? (i >> 1) & 1 : i >= 25, bar);
                    }
                    aslot = aslot == NA_SLOTS - 1 ? 0 : aslot + 1;
                }
            }
        } else {
            const int slot0 = get_slot(), row0 = (slot0 >> 5) * 256 + (slot0 & 12) * 16;
            if (elect()) {
                prefetch_map(&tm_x);
                #pragma unroll
                for (int i = 0; i < 7; i++) mbar_init(bars + 8 * i, 1);
                asm volatile("fence.mbarrier_init.release.cluster;" ::: "memory");
            }
            named_arrive(0, 288);
            if (elect()) {
                #pragma unroll 1
                for (int kb = 0; kb < 7; kb++) {
                    load_x(kb, row0);
                    if (kb == 0) STAMP(22);
                }
                #pragma unroll
                for (int i = 7; i < B_DONE1; i++) mbar_init(bars + 8 * i, 1);
                asm volatile("fence.mbarrier_init.release.cluster;" ::: "memory");
            }
            named_arrive(8, 128);
            ASSIGN_WORK(get_slot())
            if (slot >= 128) return;
            #pragma unroll 1
            for (int kb = 0; kb < 7; kb++) {
                if (kb == 6) { named_sync(4, 64); mbar_wait(bars + 8 * B_DONEX, 0); }
                if (elect()) {
                    const uint32_t st = sb + slot_kv(kb), bar = bars + 8 * (B_FULLKV + kb);
                    mbar_expect(bar, 16384);
                    #pragma unroll
                    for (int i = 0; i < 2; i++) {
                        const int n = 2 * kb + (i ^ (G & 1));
                        tma2d(st + (n & 1) * 8192, &tm_wqkv, (n < 7 ? 448 : 896) + wcol, (n < 7 ? n : n - 7) * 64, bar);
                    }
                }
            }
            if (elect()) {
                mbar_expect(bars + 8 * B_FQ, 32768);
                mbar_expect(bars + 8 * (B_FQ + 1), 24576);
                #pragma unroll 1
                for (int i = 0; i < 7; i++) { const int j = i == 6 ? i : i ^ (G & 1); tma2d(sb + SM_QO + j * 8192, &tm_wqkv, wcol, j * 64, bars + 8 * (B_FQ + (i >> 2))); }
                mbar_expect(bars + 8 * B_FULLWO, 512 * 112 * 2);
            }
            #pragma unroll 1
            for (int i = 0; i < 7; i++) {
                const int kb = ((q & 1 ? WO_ORD1 : WO_ORD0) >> (4 * i)) & 7;
                if (kb < 5) mbar_wait(bars + 8 * (B_DONE1 + kb), 0);
                if (elect()) {
                    tma2d(sb + slot_wo(kb), &tm_wo64, c64, kb * 64, bars + 8 * B_FULLWO);
                    tma2d(sb + slot_wo(kb) + 8192, &tm_wo48, c48, kb * 64, bars + 8 * B_FULLWO);
                }
            }
            if (elect()) {
                tma2d(sb + SM_H, &tm_xr64, c64, tt2 * 64, bars + 8 * B_FULLWO);
                tma2d(sb + SM_H + 8192, &tm_xr48, c48, tt2 * 64, bars + 8 * B_FULLWO);
            }
            if (smem_u32(smem_raw) != SB) __trap();
            const uint32_t ep = get_tag();
            const Tiles* const tl = &sc->tiles[ep & 1];
            mbar_wait(bars + 8 * (B_DONE1 + 6), 0);
            const uint32_t t_o = last_hint(TSVAL sc->hint_o + (tt2 * 32 + lane) * 2, ep, 38);
            mbar_wait(bars + 8 * B_DONEQ, 0);
            wait_until(t_o + GO_O);
            if (elect()) {
                #pragma unroll
                for (int i = 0; i < 4; i++) {
                    bulk_ld(sb + SM_QO + i * 14336, tl->o + tt2 * 14336 + i * 3584, 14336, sb + SM_RAW + 8 * i);
                }
            }
            if (lane == 0) STAMP(20);
            if (SPIN2) { wait_until(t_o + GO_O + STOP2); if (lane == 0) mbar_arrive(bars + 8 * B_FULLX); }
            mbar_wait(bars + 8 * (B_DONEO + POLL_H), 0);
            const uint32_t* src = tl->hn + pr3 * 32 * 7168 + col3 * 256;
            uint32_t bytes = early ? 10240 : 14336, dst = sb + SM_BRING, top = dst + (early ? NE_SLOTS * 10240 : NB_SLOTS * 14336), raw = sb + SM_RAW + 32;
            auto issue = [&]() {
                if (elect()) bulk_ld(dst, src, bytes, raw);
                src += 7168; raw += 8; dst += bytes;
                if (dst == top) dst = sb + SM_BRING;
            };
            uint2 th;
            do { th = ld_relaxed2((const uint2*)sc->go + (lane & 15)); } while (!__all_sync(0xffffffffu, th.x == ep));
            STAMP(42);
            mbar_wait(bars + 8 * (B_DONEO + 3), 0);
            {
                uint32_t bit = 1, wait = ~1u;
                wait_until(__shfl_sync(0xffffffffu, th.y, 0) + GO_H);
                #pragma unroll 1
                do {
                    while (wait & bit) wait = __ballot_sync(0xffffffffu, (int)(gtime32() - th.y - GO_H) < 0);
                    if (bit == 1) STAMP(29);
                    issue();
                    if (SPIN3 && bit == 1 << STOP3 && lane == 0) mbar_arrive(bars + 8 * (B_FULLX + 1));
                    bit *= 2;
                } while (dst != sb + SM_BRING);
            }
            uint32_t done = bars + 8 * B_DONE;
            #pragma unroll 1
            do { mbar_wait(done, 0); done += 8; issue(); } while (raw != sb + SM_RAW + 288);
            if (early) mbar_wait(bars + 8 * (B_DONE + 31), 0);
            src = tl->u + (q >> 1) * 28 * 7168 + (q & 1) * 3584; bytes = 14336; dst = sb + SM_BRING; top = dst + NB_SLOTS * 14336;
            done = bars + 8 * (B_DONE + 24);
            #pragma unroll 1
            for (uint32_t par = 0; par < 2; par++) {
                mbar_wait(bars + 8 * (B_GO + par), 0);
                const uint32_t ts = *(volatile uint32_t*)(smem_raw + SM_TIME + 128 * par + 4 * lane);
                if (par) done = bars + 8 * B_DONE;
                uint32_t bit = 1, wait = ~1u;
                wait_until(__shfl_sync(0xffffffffu, ts, 0));
                #pragma unroll 1
                do {
                    while (wait & bit) wait = __ballot_sync(0xffffffffu, (int)(gtime32() - ts) < 0);
                    if (bit == 1) STAMP(par ? 36 : 30);
                    mbar_wait(done, par); done += 8;
                    issue();
                    if (SPIN4 && bit == 1 << STOP3 && lane + par == 0) mbar_arrive(bars + 8 * (B_FULLX + 2));
                    bit *= 2;
                } while (bit != (par ? 1 << 20 : 1 << 8));
            }
        }
    }
}

typedef CUresult (*EncodeFn)(CUtensorMap*, CUtensorMapDataType, cuuint32_t, void*, const cuuint64_t*, const cuuint64_t*, const cuuint32_t*,
                             const cuuint32_t*, CUtensorMapInterleave, CUtensorMapSwizzle, CUtensorMapL2promotion, CUtensorMapFloatOOBfill);

void make_map(EncodeFn fn, CUtensorMap* tm, const void* ptr, int rank, const cuuint64_t* dims, const cuuint64_t* strides, const cuuint32_t* box, CUtensorMapSwizzle sw) {
    cuuint32_t es[5] = {1, 1, 1, 1, 1};
    fn(tm, CU_TENSOR_MAP_DATA_TYPE_BFLOAT16, rank, const_cast<void*>(ptr), dims, strides, box, es, CU_TENSOR_MAP_INTERLEAVE_NONE, sw,
       CU_TENSOR_MAP_L2_PROMOTION_NONE, CU_TENSOR_MAP_FLOAT_OOB_FILL_NONE);
}

}

extern "C" void kernel_launch(void* const* d_in, const int* in_sizes, int n_in, void* d_out, int out_size) {
    const __nv_bfloat16* x = (const __nv_bfloat16*)d_in[0];
    const __nv_bfloat16* wqkv = (const __nv_bfloat16*)d_in[1];
    const __nv_bfloat16* wo = (const __nv_bfloat16*)d_in[2];
    const __nv_bfloat16* w1 = (const __nv_bfloat16*)d_in[4];
    const __nv_bfloat16* b1 = (const __nv_bfloat16*)d_in[5];
    const __nv_bfloat16* w2 = (const __nv_bfloat16*)d_in[6];
    const __nv_bfloat16* b2 = (const __nv_bfloat16*)d_in[7];

    void* fnp = nullptr; cudaDriverEntryPointQueryResult qr;
    cudaGetDriverEntryPoint("cuTensorMapEncodeTiled", &fnp, cudaEnableDefault, &qr);
    EncodeFn fn = (EncodeFn)fnp;
    CUtensorMap tx, twqkv, two64, two48, tw1, tw2, txr64, txr48, tout64, tout48;
    { cuuint64_t d[3] = {448, 2, 1024}, s[2] = {896, 1792}; cuuint32_t b[3] = {64, 1, 64}; make_map(fn, &tx, x, 3, d, s, b, CU_TENSOR_MAP_SWIZZLE_128B); }
    { cuuint64_t d[2] = {1344, 448}, s[1] = {2688}; cuuint32_t b[2] = {64, 64}; make_map(fn, &twqkv, wqkv, 2, d, s, b, CU_TENSOR_MAP_SWIZZLE_128B); }
    { cuuint64_t d[2] = {448, 448}, s[1] = {896}; cuuint32_t b[2] = {64, 64}; make_map(fn, &two64, wo, 2, d, s, b, CU_TENSOR_MAP_SWIZZLE_128B); }
    { cuuint64_t d[2] = {448, 448}, s[1] = {896}; cuuint32_t b[2] = {48, 64}; make_map(fn, &two48, wo, 2, d, s, b, CU_TENSOR_MAP_SWIZZLE_128B); }
    { cuuint64_t d[5] = {1792, 8, 2, 64, 2}, s[4] = {2 * 3584, 3584, 32 * 3584, 16 * 3584}; cuuint32_t b[5] = {64, 8, 2, 8, 1}; make_map(fn, &tw1, w1, 5, d, s, b, CU_TENSOR_MAP_SWIZZLE_128B); }
    { cuuint64_t d[5] = {2048, 8, 2, 56, 2}, s[4] = {4096, 16 * 4096, 32 * 4096, 8 * 4096}; cuuint32_t b[5] = {64, 8, 2, 8, 1}; make_map(fn, &tw2, w2, 5, d, s, b, CU_TENSOR_MAP_SWIZZLE_128B); }
    { cuuint64_t d[2] = {448, 2048}, s[1] = {896}; cuuint32_t b[2] = {64, 64}; make_map(fn, &txr64, x, 2, d, s, b, CU_TENSOR_MAP_SWIZZLE_128B); }
    { cuuint64_t d[2] = {448, 2048}, s[1] = {896}; cuuint32_t b[2] = {48, 64}; make_map(fn, &txr48, x, 2, d, s, b, CU_TENSOR_MAP_SWIZZLE_128B); }
    { cuuint64_t d[2] = {448, 2048}, s[1] = {896}; cuuint32_t b[2] = {64, 16}; make_map(fn, &tout64, d_out, 2, d, s, b, CU_TENSOR_MAP_SWIZZLE_128B); }
    { cuuint64_t d[2] = {448, 2048}, s[1] = {896}; cuuint32_t b[2] = {48, 16}; make_map(fn, &tout48, d_out, 2, d, s, b, CU_TENSOR_MAP_SWIZZLE_128B); }

    void* scv = nullptr;
    cudaGetSymbolAddress(&scv, g_scratch);
    Scratch* scp = (Scratch*)scv;
    int dev = 0, sms = 0;
    cudaGetDevice(&dev);
    cudaDeviceGetAttribute(&sms, cudaDevAttrMultiProcessorCount, dev);
    if (sms == 132) {
        cudaFuncSetAttribute(fused_kernel<true>, cudaFuncAttributeMaxDynamicSharedMemorySize, SM_TOTAL);
        fused_kernel<true><<<132, 384, SM_TOTAL>>>(scp, wo, w1, b1, w2, b2, tx, twqkv, two64, two48, tw1, tw2, txr64, txr48, tout64, tout48);
    } else {
        cudaFuncSetAttribute(fused_kernel<false>, cudaFuncAttributeMaxDynamicSharedMemorySize, SM_TOTAL);
        fused_kernel<false><<<132, 384, SM_TOTAL>>>(scp, wo, w1, b1, w2, b2, tx, twqkv, two64, two48, tw1, tw2, txr64, txr48, tout64, tout48);
    }
}
```

```cpp
#include <cuda_runtime.h>
#include <cuda_bf16.h>
#include <cuda.h>
#include <stdint.h>

namespace {

constexpr int D_ = 448;
constexpr float LN_EPS = 1e-5f;
constexpr float LOG2E_SCALE = 0.1889822365046136f * 1.4426950408889634f;

struct Tiles {
    uint32_t o[32 * 57344 / 4];
    uint32_t hn[4 * 32 * 14336 / 4];
    uint32_t u[4 * 28 * 14336 / 4];
};
struct Scratch {
    uint4 halo[128 * 2 * 2 * 3 * 32];
    uint4 stats[32 * 4 * 64];
    uint4 hint_k[128 * 2];
    uint4 hint_o[32 * 32 * 2];
    uint4 hint_h[4 * 32 * 2];
    uint4 hint_u[128 * 2];
    uint4 go[24];
    uint32_t epoch[160];
    uint32_t clean;
    alignas(1024) Tiles tiles[2];
};
__device__ Scratch g_scratch;
#define STAMP(i) do {} while (0)
#define FST(i) do {} while (0)
#define TSARG
#define TSVAL

constexpr uint32_t SB = 1024;
constexpr int SM_SLOT = 16384;
__device__ __forceinline__ constexpr uint32_t slot_x(int kb) { return (kb ? 6 + kb : 0) * SM_SLOT; }
__device__ __forceinline__ constexpr uint32_t slot_kv(int kb) { return (kb < 5 ? 2 + kb : 6 - kb) * SM_SLOT; }
__device__ __forceinline__ constexpr uint32_t slot_wo(int kb) { return (kb < 6 ? 2 + kb : 12) * SM_SLOT; }
constexpr int SM_QO = 8 * SM_SLOT;
constexpr int SM_HALOK = SM_QO + 57344, SM_HALOV = 1 * SM_SLOT;
constexpr int NA_SLOTS = 6, NB_SLOTS = 8;
constexpr int SM_ARING = 0;
constexpr int SM_BRING = NA_SLOTS * 16384;
constexpr int SM_H = 212992;
__device__ __forceinline__ uint32_t halo_kin(int par, int lane) { return SB + SM_H + 8192 + par * 4096 + lane * 128 + ((~lane & 6) << 4); }
constexpr int SM_BAR = 229376;
constexpr int SM_TAG = SM_BAR + 1536;
constexpr int SM_TIME = SM_TAG + 256;
constexpr int SM_TOTAL = SM_TIME + 256;
constexpr int B_FULLX = 0;
constexpr int B_FULLKV = 7;
constexpr int B_FQ = 14;
constexpr int B_DONE1 = 16;
constexpr int B_DONEX = 23;
constexpr int B_DONEQ = 24;
constexpr int B_DONEO = 25;
constexpr int B_FULLO = 29;
constexpr int B_FULLWO = 33;
constexpr int B_END = 34;
constexpr int B_HALO = 35;
constexpr int B_FULLA = 39;
constexpr int B_FULLB = 55;
constexpr int B_DONE = 87;
constexpr int B_GO = 119;
constexpr int B_CLR = 121;
constexpr int SM_RAW = SM_BAR + 8 * 122;

constexpr long long WD_CLKS = 2000000000ll;

template<int N> struct Int { static constexpr int value = N; };
template<int A, int B, class F> __device__ __forceinline__ void static_for(F&& f) { if constexpr (A < B) { f(Int<A>()); static_for<A + 1, B>(f); } }

__device__ __forceinline__ uint32_t smem_u32(const void* p) { return (uint32_t)__cvta_generic_to_shared(p); }
__device__ __forceinline__ void mbar_init(uint32_t bar, uint32_t cnt) { asm volatile("mbarrier.init.shared::cta.b64 [%0], %1;" :: "r"(bar), "r"(cnt) : "memory"); }
__device__ __forceinline__ void mbar_expect(uint32_t bar, uint32_t bytes) { asm volatile("mbarrier.arrive.expect_tx.shared::cta.b64 _, [%0], %1;" :: "r"(bar), "r"(bytes) : "memory"); }
__device__ __forceinline__ void mbar_arrive(uint32_t bar) { asm volatile("mbarrier.arrive.shared::cta.b64 _, [%0];" :: "r"(bar) : "memory"); }
__device__ __forceinline__ bool mbar_try(uint32_t bar, uint32_t parity) {
    uint32_t ok;
    asm volatile("{\n.reg .pred p;\nmbarrier.try_wait.parity.shared::cta.b64 p, [%1], %2;\nselp.u32 %0, 1, 0, p;\n}" : "=r"(ok) : "r"(bar), "r"(parity) : "memory");
    return ok;
}
__device__ __forceinline__ bool mbar_test(uint32_t bar, uint32_t parity) {
    uint32_t ok;
    asm volatile("{\n.reg .pred p;\nmbarrier.test_wait.parity.shared::cta.b64 p, [%1], %2;\nselp.u32 %0, 1, 0, p;\n}" : "=r"(ok) : "r"(bar), "r"(parity) : "memory");
    return ok;
}
__device__ __forceinline__ void mbar_wait(uint32_t bar, uint32_t parity) {
    asm volatile("{\n.reg .pred p;\n"
                 "WAIT_LOOP:\n"
                 "mbarrier.try_wait.parity.shared::cta.b64 p, [%0], %1;\n"
                 "@!p bra WAIT_LOOP;\n}" :: "r"(bar), "r"(parity) : "memory");
}
__device__ __forceinline__ void mbar_wait_wd(uint32_t bar, uint32_t parity) {
    asm volatile("{\n.reg .pred p, q;\n.reg .u32 s, t;\nmov.u32 s, %%clock;\n"
                 "WAIT_LOOP:\n"
                 "mbarrier.try_wait.parity.shared::cta.b64 p, [%0], %1;\nmov.u32 t, %%clock;\nsub.u32 t, t, s;\nsetp.lt.and.s32 q, t, 0, !p;\n@q trap;\n"
                 "@!p bra WAIT_LOOP;\n}" :: "r"(bar), "r"(parity) : "memory");
}
__device__ __forceinline__ bool elect() { uint32_t p; asm volatile("{\n.reg .pred P;\nelect.sync _|P, 0xffffffff;\nselp.u32 %0, 1, 0, P;\n}" : "=r"(p)); return p; }
__device__ __forceinline__ void tma2d(uint32_t dst, const CUtensorMap* tm, int c0, int c1, uint32_t bar) {
    asm volatile("cp.async.bulk.tensor.2d.shared::cluster.global.mbarrier::complete_tx::bytes [%0], [%1, {%3, %4}], [%2];" :: "r"(dst), "l"(tm), "r"(bar), "r"(c0), "r"(c1) : "memory");
}
__device__ __forceinline__ void tma3d(uint32_t dst, const CUtensorMap* tm, int c0, int c1, int c2, uint32_t bar) {
    asm volatile("cp.async.bulk.tensor.3d.shared::cluster.global.mbarrier::complete_tx::bytes [%0], [%1, {%3, %4, %5}], [%2];" :: "r"(dst), "l"(tm), "r"(bar), "r"(c0), "r"(c1), "r"(c2) : "memory");
}
__device__ __forceinline__ void tma5d(uint32_t dst, const CUtensorMap* tm, int c0, int c3, int c4, uint32_t bar) {
    asm volatile("cp.async.bulk.tensor.5d.shared::cluster.global.mbarrier::complete_tx::bytes [%0], [%1, {%3, 0, 0, %4, %5}], [%2];" :: "r"(dst), "l"(tm), "r"(bar), "r"(c0), "r"(c3), "r"(c4) : "memory");
}
__device__ __forceinline__ void tma5d_prefetch(const CUtensorMap* tm, int c0, int c3, int c4) {
    asm volatile("cp.async.bulk.prefetch.tensor.5d.L2.global [%0, {%1, 0, 0, %2, %3}];" :: "l"(tm), "r"(c0), "r"(c3), "r"(c4) : "memory");
}
__device__ __forceinline__ void tma2d_store(const CUtensorMap* tm, int c0, int c1, uint32_t src) {
    asm volatile("cp.async.bulk.tensor.2d.global.shared::cta.bulk_group [%0, {%2, %3}], [%1];" :: "l"(tm), "r"(src), "r"(c0), "r"(c1) : "memory");
}
__device__ __forceinline__ void bulk_st(void* dst, uint32_t src, uint32_t bytes) {
    asm volatile("cp.async.bulk.global.shared::cta.bulk_group [%0], [%1], %2;" :: "l"(dst), "r"(src), "r"(bytes) : "memory");
}
__device__ __forceinline__ void bulk_ld(uint32_t dst, const void* src, uint32_t bytes, uint32_t bar) {
    asm volatile("cp.async.bulk.shared::cluster.global.mbarrier::complete_tx::bytes [%0], [%1], %2, [%3];" :: "r"(dst), "l"(src), "r"(bytes), "r"(bar) : "memory");
}
__device__ __forceinline__ void bulk_prefetch(const void* src, uint32_t bytes) { asm volatile("cp.async.bulk.prefetch.L2.global [%0], %1;" :: "l"(src), "r"(bytes) : "memory"); }
__device__ __forceinline__ void prefetch_map(const CUtensorMap* tm) { asm volatile("prefetch.tensormap [%0];" :: "l"(tm) : "memory"); }
__device__ __forceinline__ void st_global_if(uint32_t c, uint32_t* p, uint32_t v) {
    asm volatile("{\n.reg .pred p;\nsetp.ne.u32 p, %2, 0;\n@p st.global.u32 [%0], %1;\n}" :: "l"(p), "r"(v), "r"(c) : "memory");
}
__device__ __forceinline__ void st_relaxed4_if(bool c, uint4* p, uint32_t a, uint32_t b, uint32_t d) {
    asm volatile("{\n.reg .b128 t;\n.reg .b64 a, b;\n.reg .pred p;\nsetp.ne.u32 p, %4, 0;\nmov.b64 a, {%1, %2};\nmov.b64 b, {%3, %3};\nmov.b128 t, {a, b};\n@p st.relaxed.gpu.global.b128 [%0], t;\n}" :: "l"(p), "r"(a), "r"(b), "r"(d), "r"((uint32_t)c) : "memory");
}
__device__ __forceinline__ void pin_ptr(uint32_t never, const void* a) {
    asm volatile("{\n.reg .pred p;\nsetp.ne.u32 p, %1, 0;\n@p st.shared.u64 [%1], %0;\n}" :: "l"(a), "r"(never) : "memory");
}
__device__ __forceinline__ void pin4(uint32_t never, float a, float b, float c, float d) {
    asm volatile("{\n.reg .pred p;\nsetp.ne.u32 p, %4, 0;\n@p st.shared.v4.f32 [%4], {%0,%1,%2,%3};\n}" :: "f"(a), "f"(b), "f"(c), "f"(d), "r"(never) : "memory");
}
__device__ __forceinline__ void fence_async_smem() { asm volatile("fence.proxy.async.shared::cta;" ::: "memory"); }
__device__ __forceinline__ uint32_t ld_acquire(const void* p) { uint32_t v; asm volatile("ld.acquire.gpu.global.u32 %0, [%1];" : "=r"(v) : "l"(p) : "memory"); return v; }
__device__ __forceinline__ void st_release(void* p, uint32_t v) { asm volatile("st.release.gpu.global.u32 [%0], %1;" :: "l"(p), "r"(v) : "memory"); }
__device__ __forceinline__ uint32_t ld_relaxed(const void* p) { uint32_t v; asm volatile("ld.relaxed.gpu.global.u32 %0, [%1];" : "=r"(v) : "l"(p) : "memory"); return v; }
__device__ __forceinline__ uint2 ld_relaxed2(const void* p) {
    uint2 v; asm volatile("{\n.reg .b64 a;\nld.relaxed.gpu.global.b64 a, [%2];\nmov.b64 {%0, %1}, a;\n}" : "=r"(v.x), "=r"(v.y) : "l"(p) : "memory"); return v;
}
__device__ __forceinline__ void st_relaxed2(void* p, uint32_t a, uint32_t b) {
    asm volatile("{\n.reg .b64 a;\nmov.b64 a, {%1, %2};\nst.relaxed.gpu.global.b64 [%0], a;\n}" :: "l"(p), "r"(a), "r"(b) : "memory");
}
__device__ __forceinline__ uint4 ld_relaxed4(const uint4* p) {
    uint4 v;
    asm volatile("{\n.reg .b128 t;\n.reg .b64 a, b;\nld.relaxed.gpu.global.b128 t, [%4];\nmov.b128 {a, b}, t;\nmov.b64 {%0, %1}, a;\nmov.b64 {%2, %3}, b;\n}" : "=r"(v.x), "=r"(v.y), "=r"(v.z), "=r"(v.w) : "l"(p) : "memory");
    return v;
}
__device__ __forceinline__ void st_relaxed4(uint4* p, uint32_t a, uint32_t b, uint32_t c, uint32_t d) {
    asm volatile("{\n.reg .b128 t;\n.reg .b64 a, b;\nmov.b64 a, {%1, %2};\nmov.b64 b, {%3, %4};\nmov.b128 t, {a, b};\nst.relaxed.gpu.global.b128 [%0], t;\n}" :: "l"(p), "r"(a), "r"(b), "r"(c), "r"(d) : "memory");
}
__device__ __forceinline__ uint32_t ld_u16(const unsigned short* p) { uint32_t v; asm volatile("ld.volatile.global.u16 %0, [%1];" : "=r"(v) : "l"(p) : "memory"); return v; }
__device__ __forceinline__ uint32_t ld_volatile(const uint32_t* p) { uint32_t v; asm volatile("ld.volatile.global.u32 %0, [%1];" : "=r"(v) : "l"(p) : "memory"); return v; }
__device__ __forceinline__ void named_arrive(int id, int n) { asm volatile("bar.arrive %0, %1;" :: "r"(id), "r"(n) : "memory"); }
__device__ __forceinline__ void named_sync(int id, int n) { asm volatile("bar.sync %0, %1;" :: "r"(id), "r"(n) : "memory"); }
__device__ __forceinline__ void named_arrive_if(uint32_t c, int id, int n) { asm volatile("{\n.reg .pred p;\nsetp.ne.u32 p, %2, 0;\n@p bar.arrive %0, %1;\n}" :: "r"(id), "r"(n), "r"(c) : "memory"); }
__device__ __forceinline__ bool named_any(int id, int n, bool v) {
    uint32_t r; asm volatile("{\n.reg .pred p, q;\nsetp.ne.u32 p, %3, 0;\nbar.red.or.pred q, %1, %2, p;\nselp.u32 %0, 1, 0, q;\n}" : "=r"(r) : "r"(id), "r"(n), "r"((uint32_t)v) : "memory"); return r;
}
__device__ __forceinline__ void wg_fence() { asm volatile("wgmma.fence.sync.aligned;" ::: "memory"); }
__device__ __forceinline__ void wg_commit() { asm volatile("wgmma.commit_group.sync.aligned;" ::: "memory"); }
template<int N> __device__ __forceinline__ void wg_wait() { asm volatile("wgmma.wait_group.sync.aligned %0;" :: "n"(N) : "memory"); }
template<int N> __device__ __forceinline__ void reg_fence(float (&d)[N]) {
    #pragma unroll
    for (int i = 0; i < N; i++) asm volatile("" : "+f"(d[i]) :: "memory");
}
__device__ __forceinline__ constexpr uint64_t mkdesc(uint32_t addr, uint32_t lbo, uint32_t sbo, uint32_t sw) {
    return (uint64_t)((addr & 0x3FFFF) >> 4) | ((uint64_t)(lbo >> 4) << 16) | ((uint64_t)(sbo >> 4) << 32) | ((uint64_t)sw << 62);
}
__device__ __forceinline__ void ldsm4(uint32_t (&r)[4], uint32_t addr) {
    asm volatile("ldmatrix.sync.aligned.m8n8.x4.shared.b16 {%0,%1,%2,%3}, [%4];" : "=r"(r[0]), "=r"(r[1]), "=r"(r[2]), "=r"(r[3]) : "r"(addr) : "memory");
}
__device__ __forceinline__ void stsm4_if(uint32_t c, uint32_t addr, uint32_t r0, uint32_t r1, uint32_t r2, uint32_t r3) {
    asm volatile("{\n.reg .pred p;\nsetp.ne.u32 p, %5, 0;\n@p stmatrix.sync.aligned.m8n8.x4.shared.b16 [%0], {%1,%2,%3,%4};\n}" :: "r"(addr), "r"(r0), "r"(r1), "r"(r2), "r"(r3), "r"(c) : "memory");
}
__device__ __forceinline__ void sts4(uint32_t a, uint32_t x, uint32_t y, uint32_t z, uint32_t w) { asm volatile("st.shared.v4.u32 [%0], {%1,%2,%3,%4};" :: "r"(a), "r"(x), "r"(y), "r"(z), "r"(w) : "memory"); }
__device__ __forceinline__ uint4 lds4(uint32_t a) { uint4 v; asm volatile("ld.shared.v4.u32 {%0,%1,%2,%3}, [%4];" : "=r"(v.x), "=r"(v.y), "=r"(v.z), "=r"(v.w) : "r"(a) : "memory"); return v; }
__device__ __forceinline__ uint32_t movtrans(uint32_t a) { uint32_t d; asm volatile("movmatrix.sync.aligned.m8n8.trans.b16 %0, %1;" : "=r"(d) : "r"(a)); return d; }
__device__ __forceinline__ uint32_t pack_bf16(float lo, float hi) { uint32_t r; asm("cvt.rn.bf16x2.f32 %0, %1, %2;" : "=r"(r) : "f"(hi), "f"(lo)); return r; }
__device__ __forceinline__ void sub_bf16x2(uint32_t& a, uint32_t b) { asm volatile("sub.rn.bf16x2 %0, %0, %1;" : "+r"(a) : "r"(b)); }
__device__ __forceinline__ float bf_lo(uint32_t v) { return __uint_as_float(v << 16); }
__device__ __forceinline__ float bf_hi(uint32_t v) { return __uint_as_float(v & 0xffff0000u); }
__device__ __forceinline__ void mma16816(float (&c)[4], uint32_t a0, uint32_t a1, uint32_t a2, uint32_t a3, uint32_t b0, uint32_t b1) {
    asm volatile("mma.sync.aligned.m16n8k16.row.col.f32.bf16.bf16.f32 {%0,%1,%2,%3}, {%4,%5,%6,%7}, {%8,%9}, {%0,%1,%2,%3};"
        : "+f"(c[0]), "+f"(c[1]), "+f"(c[2]), "+f"(c[3]) : "r"(a0), "r"(a1), "r"(a2), "r"(a3), "r"(b0), "r"(b1));
}
__device__ __forceinline__ void mma1688(float (&c)[4], uint32_t a0, uint32_t a1, uint32_t b0) {
    asm volatile("mma.sync.aligned.m16n8k8.row.col.f32.bf16.bf16.f32 {%0,%1,%2,%3}, {%4,%5}, {%6}, {%0,%1,%2,%3};"
        : "+f"(c[0]), "+f"(c[1]), "+f"(c[2]), "+f"(c[3]) : "r"(a0), "r"(a1), "r"(b0));
}
__device__ __forceinline__ float quad_sum(float v) { v += __shfl_xor_sync(0xffffffffu, v, 1); v += __shfl_xor_sync(0xffffffffu, v, 2); return v; }
__device__ __forceinline__ float quad_max(float v) { v = fmaxf(v, __shfl_xor_sync(0xffffffffu, v, 1)); v = fmaxf(v, __shfl_xor_sync(0xffffffffu, v, 2)); return v; }
__device__ __forceinline__ float ex2(float x) { float y; asm("ex2.approx.ftz.f32 %0, %1;" : "=f"(y) : "f"(x)); return y; }
__device__ __forceinline__ float rsqrt_approx(float x) { float y; asm("rsqrt.approx.ftz.f32 %0, %1;" : "=f"(y) : "f"(x)); return y; }
__device__ __forceinline__ float rcp_approx(float x) { float y; asm("rcp.approx.ftz.f32 %0, %1;" : "=f"(y) : "f"(x)); return y; }
constexpr float GELU_K1 = 2.f * 0.7978845608028654f;
__device__ __forceinline__ float gelu_half(float hx, float k1) {
    const float z = hx * fmaf(hx * hx, 8.f * 0.044715f * 0.7978845608028654f, k1);
    float t; asm("tanh.approx.f32 %0, %1;" : "=f"(t) : "f"(z));
    return fmaf(hx, t, hx);
}
__device__ __forceinline__ uint32_t gtime32() { uint64_t t; asm volatile("mov.u64 %0, %%globaltimer;" : "=l"(t)); return (uint32_t)t; }
__device__ __forceinline__ uint32_t clock32() { uint32_t t; asm volatile("mov.u32 %0, %%clock;" : "=r"(t)); return t; }
#define PF_PACE 160
#define PF_AT 16500
#define PF_N 192
#define NSQ 6
#define NPIPE 1
#define HALO_AT 3
#define HINT_U 18
#define HINT_E 16
#define SP_AT 2000
#define A_SCHED 0x322188
#define WO_ORD0 0x4321065
#define WO_ORD1 0x3465210
#define CL_AT 23
#define WARM_AT 300
#define A_HOLD 31
#define GO_H 1730
#define GO_E 1900
#define GO_U 2120
#define GO_O 1312
#define LATE_O 256
#define DRY2 1
#define LATE_AT 0
#define LATE_AT4 0
#define HINT_H 0
#define SLACK 0
#define SLACK_U 128
#define GDEP 4
#define START4 30
#define EMAP 1
#define DEPTH_N 1
#define DEPTH_E 2
#define PFE_AT 99
#define PFN_END 0
#define NE_SLOTS 11
#define POLL_E 26
#define POLL_U 22
#define CH_U 28
#define AE_END 18
#define AE_W2 27
#define PF1_AT 12000
#define PF1_N 80
#define PF1_PACE 160
#define HOLD 0
#define X0 1
#define GO_E2 300
#define GO_U2 400
#define POLL_I 20
#define POLL_N 19
#define LATES 0x11111111u
#define GATE_J 22
#define GATE_D 16
#define ROLES 0x65431027u
#define LATE_E 1
#define LATE_N 1
#define CL_I0 0
#define CL_SP 1000
#define POLL0 250
#define A4_FROM 23
#define A4_DLY 2
#define SPIN2 1
#define SPIN3 0
#define SPIN4 0
#define SPIN_N 2
#define STOP2 200
#define STOP3 3
#define PF0_AT 5000
#define PF0_N 48
#define PF0_PACE 140
#define POLL_H 3
#define CH_H 8
#define HINT_F 2
#define CL_N 4
#define CL_P2 7
template<int TB> __device__ __forceinline__ void wgmma_rs56(float (&d)[28], const uint32_t (&a)[4], uint64_t db, int sc) {
    asm volatile("{\n.reg .pred p;\nsetp.ne.b32 p, %33, 0;\n"
        "wgmma.mma_async.sync.aligned.m64n56k16.f32.bf16.bf16 {%0, %1, %2, %3, %4, %5, %6, %7, %8, %9, %10, %11, %12, %13, %14, %15, %16, %17, %18, %19, %20, %21, %22, %23, %24, %25, %26, %27}, {%28, %29, %30, %31}, %32, p, 1, 1, %34;\n}\n"
        : "+f"(d[0]), "+f"(d[1]), "+f"(d[2]), "+f"(d[3]), "+f"(d[4]), "+f"(d[5]), "+f"(d[6]), "+f"(d[7]), "+f"(d[8]), "+f"(d[9]), "+f"(d[10]), "+f"(d[11]), "+f"(d[12]), "+f"(d[13]), "+f"(d[14]), "+f"(d[15]), "+f"(d[16]), "+f"(d[17]), "+f"(d[18]), "+f"(d[19]), "+f"(d[20]), "+f"(d[21]), "+f"(d[22]), "+f"(d[23]), "+f"(d[24]), "+f"(d[25]), "+f"(d[26]), "+f"(d[27])
        : "r"(a[0]), "r"(a[1]), "r"(a[2]), "r"(a[3]), "l"(db), "r"(sc), "n"(TB));
}

template<int TA, int TB, int SC = 1> __device__ __forceinline__ void wgmma_ss112(float (&d)[56], uint64_t da, uint64_t db) {
    asm volatile("wgmma.mma_async.sync.aligned.m64n112k16.f32.bf16.bf16 {%0, %1, %2, %3, %4, %5, %6, %7, %8, %9, %10, %11, %12, %13, %14, %15, %16, %17, %18, %19, %20, %21, %22, %23, %24, %25, %26, %27, %28, %29, %30, %31, %32, %33, %34, %35, %36, %37, %38, %39, %40, %41, %42, %43, %44, %45, %46, %47, %48, %49, %50, %51, %52, %53, %54, %55}, %56, %57, %60, 1, 1, %58, %59;\n"
        : "+f"(d[0]), "+f"(d[1]), "+f"(d[2]), "+f"(d[3]), "+f"(d[4]), "+f"(d[5]), "+f"(d[6]), "+f"(d[7]), "+f"(d[8]), "+f"(d[9]), "+f"(d[10]), "+f"(d[11]), "+f"(d[12]), "+f"(d[13]), "+f"(d[14]), "+f"(d[15]), "+f"(d[16]), "+f"(d[17]), "+f"(d[18]), "+f"(d[19]), "+f"(d[20]), "+f"(d[21]), "+f"(d[22]), "+f"(d[23]), "+f"(d[24]), "+f"(d[25]), "+f"(d[26]), "+f"(d[27]), "+f"(d[28]), "+f"(d[29]), "+f"(d[30]), "+f"(d[31]), "+f"(d[32]), "+f"(d[33]), "+f"(d[34]), "+f"(d[35]), "+f"(d[36]), "+f"(d[37]), "+f"(d[38]), "+f"(d[39]), "+f"(d[40]), "+f"(d[41]), "+f"(d[42]), "+f"(d[43]), "+f"(d[44]), "+f"(d[45]), "+f"(d[46]), "+f"(d[47]), "+f"(d[48]), "+f"(d[49]), "+f"(d[50]), "+f"(d[51]), "+f"(d[52]), "+f"(d[53]), "+f"(d[54]), "+f"(d[55])
        : "l"(da), "l"(db), "n"(TA), "n"(TB), "n"(SC));
}

template<int TA, int TB, int SC = 1> __device__ __forceinline__ void wgmma_ss80(float (&d)[40], uint64_t da, uint64_t db) {
    asm volatile("wgmma.mma_async.sync.aligned.m64n80k16.f32.bf16.bf16 {%0, %1, %2, %3, %4, %5, %6, %7, %8, %9, %10, %11, %12, %13, %14, %15, %16, %17, %18, %19, %20, %21, %22, %23, %24, %25, %26, %27, %28, %29, %30, %31, %32, %33, %34, %35, %36, %37, %38, %39}, %40, %41, %44, 1, 1, %42, %43;\n"
        : "+f"(d[0]), "+f"(d[1]), "+f"(d[2]), "+f"(d[3]), "+f"(d[4]), "+f"(d[5]), "+f"(d[6]), "+f"(d[7]), "+f"(d[8]), "+f"(d[9]), "+f"(d[10]), "+f"(d[11]), "+f"(d[12]), "+f"(d[13]), "+f"(d[14]), "+f"(d[15]), "+f"(d[16]), "+f"(d[17]), "+f"(d[18]), "+f"(d[19]), "+f"(d[20]), "+f"(d[21]), "+f"(d[22]), "+f"(d[23]), "+f"(d[24]), "+f"(d[25]), "+f"(d[26]), "+f"(d[27]), "+f"(d[28]), "+f"(d[29]), "+f"(d[30]), "+f"(d[31]), "+f"(d[32]), "+f"(d[33]), "+f"(d[34]), "+f"(d[35]), "+f"(d[36]), "+f"(d[37]), "+f"(d[38]), "+f"(d[39])
        : "l"(da), "l"(db), "n"(TA), "n"(TB), "n"(SC));
}

template<int TA, int TB, int SC = 1> __device__ __forceinline__ void wgmma_ss64(float (&d)[32], uint64_t da, uint64_t db) {
    asm volatile("wgmma.mma_async.sync.aligned.m64n64k16.f32.bf16.bf16 {%0, %1, %2, %3, %4, %5, %6, %7, %8, %9, %10, %11, %12, %13, %14, %15, %16, %17, %18, %19, %20, %21, %22, %23, %24, %25, %26, %27, %28, %29, %30, %31}, %32, %33, %36, 1, 1, %34, %35;\n"
        : "+f"(d[0]), "+f"(d[1]), "+f"(d[2]), "+f"(d[3]), "+f"(d[4]), "+f"(d[5]), "+f"(d[6]), "+f"(d[7]), "+f"(d[8]), "+f"(d[9]), "+f"(d[10]), "+f"(d[11]), "+f"(d[12]), "+f"(d[13]), "+f"(d[14]), "+f"(d[15]), "+f"(d[16]), "+f"(d[17]), "+f"(d[18]), "+f"(d[19]), "+f"(d[20]), "+f"(d[21]), "+f"(d[22]), "+f"(d[23]), "+f"(d[24]), "+f"(d[25]), "+f"(d[26]), "+f"(d[27]), "+f"(d[28]), "+f"(d[29]), "+f"(d[30]), "+f"(d[31])
        : "l"(da), "l"(db), "n"(TA), "n"(TB), "n"(SC));
}

template<int TA, int TB, int SC = 1> __device__ __forceinline__ void wgmma_ss48(float (&d)[24], uint64_t da, uint64_t db) {
    asm volatile("wgmma.mma_async.sync.aligned.m64n48k16.f32.bf16.bf16 {%0, %1, %2, %3, %4, %5, %6, %7, %8, %9, %10, %11, %12, %13, %14, %15, %16, %17, %18, %19, %20, %21, %22, %23}, %24, %25, %28, 1, 1, %26, %27;\n"
        : "+f"(d[0]), "+f"(d[1]), "+f"(d[2]), "+f"(d[3]), "+f"(d[4]), "+f"(d[5]), "+f"(d[6]), "+f"(d[7]), "+f"(d[8]), "+f"(d[9]), "+f"(d[10]), "+f"(d[11]), "+f"(d[12]), "+f"(d[13]), "+f"(d[14]), "+f"(d[15]), "+f"(d[16]), "+f"(d[17]), "+f"(d[18]), "+f"(d[19]), "+f"(d[20]), "+f"(d[21]), "+f"(d[22]), "+f"(d[23])
        : "l"(da), "l"(db), "n"(TA), "n"(TB), "n"(SC));
}

template<int NKB, int NR>
__device__ __forceinline__ void mix_mainloop(TSARG float (&acc)[NR], bool leader) {
    constexpr uint32_t sb = SB, bars = sb + SM_BAR, par = NKB == 28;
    constexpr int A0 = NKB == 32 ? 0 : 16 % NA_SLOTS;
    constexpr int DEPTH = NR == 56 ? DEPTH_N : DEPTH_E;
    int bslot = 0, aslot = A0;
    reg_fence(acc);
    #pragma unroll 1
    for (int i = 0; i < NKB / 2; i++) {
        mbar_wait(bars + 8 * (B_FULLA + i), par);
        const uint64_t adesc = mkdesc(sb + SM_ARING, 8192, 1024, 1) + (uint32_t)(aslot * 1024);
        aslot = aslot == NA_SLOTS - 1 ? 0 : aslot + 1;
        #pragma unroll
        for (int jj = 0; jj < 2; jj++) {
            const int j = 2 * i + jj;
            mbar_wait(bars + 8 * (B_FULLB + j), par);
            const uint64_t bdesc = mkdesc(sb + SM_BRING, 128, 1024, 0) + (uint32_t)(bslot * NR * 16);
            bslot = bslot == (NR == 56 ? NB_SLOTS : NE_SLOTS) - 1 ? 0 : bslot + 1;
            wg_fence();
            #pragma unroll
            for (int s = 0; s < 4; s++) {
                if constexpr (NR == 56) wgmma_ss112<1, 1>(acc, adesc + jj * 512 + s * 128, bdesc + s * 16);
                else wgmma_ss80<1, 1>(acc, adesc + jj * 512 + s * 128, bdesc + s * 16);
            }
            wg_commit();
            wg_wait<DEPTH>();
            if (j >= DEPTH && leader) mbar_arrive(bars + 8 * (B_DONE + j - DEPTH));
        }
    }
    if (DEPTH == 2) { wg_wait<1>(); if (leader) mbar_arrive(bars + 8 * (B_DONE + NKB - 2)); }
    wg_wait<0>();
    reg_fence(acc);
    if (leader) mbar_arrive(bars + 8 * (B_DONE + NKB - 1));
}

__device__ __forceinline__ void spin_mma(uint32_t bar, uint32_t never) {
    float d[56];
    #pragma unroll
    for (int i = 0; i < 56; i++) d[i] = 0.f;
    reg_fence(d);
    #pragma unroll 1
    do {
        wg_fence();
        #pragma unroll
        for (int s = 0; s < SPIN_N; s++) wgmma_ss112<1, 1>(d, mkdesc(SB + 2 * SM_SLOT + s * 2048, 8192, 1024, 1), mkdesc(SB + 3 * SM_SLOT + s * 256, 128, 1024, 0));
        wg_commit();
        wg_wait<1>();
    } while (!named_any(11, 128, mbar_test(bar, 1)));
    wg_wait<0>();
    reg_fence(d);
    pin4(never, d[0], d[1], d[2], d[3]);
}

constexpr uint32_t EMPTY = 0xFFFFFFFFu;
__device__ __forceinline__ void post_hint(uint4* p, uint32_t ep, int lane) { if (lane < 2) st_relaxed4(p + lane, ep, ep, ep, ep); }
__device__ __forceinline__ void post_time(uint4* p, uint32_t ep, int lane) { const uint32_t now = gtime32(); if (lane < 2) st_relaxed4(p + lane, ep, now, ep, now); }

__device__ __forceinline__ uint32_t last_hint(TSARG const uint4* hint, uint32_t ep, int st) {
    uint2 v;
    do { v = ld_relaxed2(hint); } while (!__all_sync(0xffffffffu, v.x == ep));
    const uint32_t t1 = gtime32() + 256;
    if (elect()) STAMP(st);
    return t1 - __reduce_min_sync(0xffffffffu, t1 - v.y);
}
__device__ __forceinline__ uint32_t later(uint32_t a, uint32_t b) { return a + max((int)(b - a), 0); }
__device__ __forceinline__ void fetch_times(TSARG const uint4* go, int k, uint32_t ep, int lane) {
    const uint2* p = (const uint2*)(go + 8 + 8 * k) + (k ? lane % 10 : lane & 3);
    uint2 v;
    do { v = ld_relaxed2(p); } while (!__all_sync(0xffffffffu, v.x == ep));
    v.y += k ? (lane < 10 ? GO_U : GO_U + GO_U2) : (lane < 4 ? GO_E : GO_E + GO_E2);
    asm volatile("st.shared.u32 [%0], %1;" :: "r"(SB + SM_TIME + 128 * k + 4 * lane), "r"(v.y) : "memory");
    __syncwarp();
    if (lane == 0) { mbar_arrive(SB + SM_BAR + 8 * (B_GO + k)); STAMP(k ? 43 : 24); }
    __syncwarp();
}
__device__ __forceinline__ void wait_until(uint32_t t) {
    asm volatile("{\n.reg .pred p;\n.reg .u64 a;\n.reg .u32 l, h;\nWAIT_LOOP:\nmov.u64 a, %%globaltimer;\nmov.b64 {l, h}, a;\nsub.u32 l, l, %0;\nsetp.lt.s32 p, l, 0;\n@p bra.uni WAIT_LOOP;\n}" :: "r"(t) : "memory");
}

__device__ __forceinline__ uint32_t check_tile(uint32_t raw, uint32_t full, uint32_t dst, uint32_t lofs, const uint32_t* src, uint32_t bytes, int lane) {
    uint32_t cnt;
    asm volatile("{\n.reg .pred p, e;\n.reg .u32 a, b, c, d;\nmov.u32 %0, 0;\n"
                 "AGAIN:\nand.b32 a, %0, 1;\n"
                 "WAIT:\nmbarrier.try_wait.parity.shared::cta.b64 p, [%1], a;\n@!p bra.uni WAIT;\n"
                 "ld.shared.u32 a, [%4];\nld.shared.u32 b, [%4+4096];\nld.shared.u32 c, [%5+-8192];\nld.shared.u32 d, [%5+-4096];\n"
                 "add.u32 %0, %0, 1;\nmax.u32 a, a, b;\nmax.u32 c, c, d;\nmax.u32 a, a, c;\nsetp.lt.u32 e, %8, 32;\nsetp.eq.and.u32 p, a, 0xFFFFFFFF, e;\n"
                 "vote.sync.any.pred p, p, 0xffffffff;\nsetp.eq.and.u32 e, %8, 0, !p;\n@e mbarrier.arrive.shared::cta.b64 _, [%2];\n"
                 "elect.sync _|e, 0xffffffff;\nand.pred e, e, p;\n"
                 "@e mbarrier.arrive.expect_tx.shared::cta.b64 _, [%1], %7;\n"
                 "@e cp.async.bulk.shared::cluster.global.mbarrier::complete_tx::bytes [%3], [%6], %7, [%1];\n"
                 "@p bra.uni AGAIN;\n}"
                 : "=&r"(cnt) : "r"(raw), "r"(full), "r"(dst), "r"(dst + lofs), "r"(dst + lofs + bytes), "l"(src), "r"(bytes), "r"(lane) : "memory");
    return cnt;
}

template<int ST>
__device__ __forceinline__ void check_tiles(int j, int step, int n, const uint32_t* src, bool small, int lane, bool dry) {
    const uint32_t bytes = small ? 10240 : 14336, nb = small ? NE_SLOTS : NB_SLOTS, lofs = lane * 128 + (lane & 3) * 32 + (lane >> 2) * 4;
    uint32_t sl = j % nb;
    #pragma unroll 1
    for (int inc = dry ? 0 : step; j < n; j += inc, inc = step) {
        const uint32_t c = check_tile(inc ? SB + SM_RAW + 8 * (j + (ST ? 32 * ST - 28 : 0)) : SB + SM_BAR + 8 * B_CLR, SB + SM_BAR + 8 * (j + (ST ? B_FULLB : B_FULLO)),
                                      SB + (ST ? SM_BRING : SM_QO) + sl * bytes, lofs, src + j * (ST ? 7168 : 3584), bytes, inc ? lane : 32);
        sl += inc;
        if (sl >= nb) sl -= nb;
    }
}

__device__ __forceinline__ uint32_t hcol(uint32_t a, int jp) { return (a ^ ((jp & 3) << 5)) + (jp >> 2) * 8192; }

__device__ __forceinline__ uint32_t get_tag() {
    mbar_wait(SB + SM_BAR + 8 * B_CLR, 0);
    uint32_t v; asm volatile("ld.shared.u32 %0, [%1];" : "=r"(v) : "r"(SB + SM_TAG) : "memory"); return v;
}

template<bool USE_SMID>
__global__ void __launch_bounds__(384, 1)
fused_kernel(Scratch* __restrict__ sc, const __nv_bfloat16* __restrict__ wo,
             const __nv_bfloat16* __restrict__ w1, const __nv_bfloat16* __restrict__ b1,
             const __nv_bfloat16* __restrict__ w2, const __nv_bfloat16* __restrict__ b2,
             const __grid_constant__ CUtensorMap tm_x, const __grid_constant__ CUtensorMap tm_wqkv,
             const __grid_constant__ CUtensorMap tm_wo64, const __grid_constant__ CUtensorMap tm_wo48,
             const __grid_constant__ CUtensorMap tm_w1, const __grid_constant__ CUtensorMap tm_w2,
             const __grid_constant__ CUtensorMap tm_xr64, const __grid_constant__ CUtensorMap tm_xr48,
             const __grid_constant__ CUtensorMap tm_out64, const __grid_constant__ CUtensorMap tm_out48) {
    extern __shared__ __align__(1024) uint8_t smem_raw[];
    constexpr uint32_t sb = SB;
    constexpr uint32_t bars = sb + SM_BAR;
    const int tid = threadIdx.x, lane = tid & 31;
    auto get_slot = [&]() {
        int slot;
    if (USE_SMID) {
        asm volatile("{\n.reg .u32 s, t, u, d, a, b, c;\n.reg .pred p, r;\n"
            "mov.u32 s, %%smid;\nshr.u32 t, s, 1;\nsub.u32 u, t, 32;\nmul.lo.u32 d, u, 37;\nshr.u32 d, d, 8;\n"
            "and.b32 a, t, 7;\nshl.b32 a, a, 3;\nshr.u32 c, t, 3;\nadd.u32 a, a, c;\n"
            "mad.lo.u32 b, d, -55, 12;\nshl.b32 c, u, 3;\nadd.u32 b, b, c;\n"
            "setp.lt.u32 p, t, 32;\nselp.u32 a, a, b, p;\n"
            "setp.lt.u32 r, t, 62;\nselp.s32 c, 4, -58, r;\nadd.u32 c, t, c;\nsetp.lt.u32 p, t, 60;\nselp.u32 a, a, c, p;\n"
            "and.b32 s, s, 1;\nshl.b32 a, a, 1;\nadd.u32 %0, a, s;\n}" : "=r"(slot));
    } else slot = blockIdx.x;
        return slot;
    };
    auto load_x = [&](int kb, int row) {
        const uint32_t st = sb + slot_x(kb), bar = bars + 8 * (B_FULLX + kb);
        mbar_expect(bar, 16384);
        tma3d(st, &tm_x, kb * 64, 0, row, bar); tma3d(st + 8192, &tm_x, kb * 64, 1, row, bar);
    };
    const int warp = __shfl_sync(0xffffffffu, tid >> 5, 0);
#define ASSIGN_WORK(s) \
    const int slot = (s), G = slot >> 4, mi = slot & 15; \
    const int tb = 4 * (G >> 1) + (mi >> 2), hp = 2 * (mi & 3) + (G & 1), wcol = (hp * 56) & ~15; \
    const int q = mi & 3, tt2 = 4 * G + (mi >> 2), c64 = 64 * q, c48 = 256 + 48 * q; \
    const int R = (ROLES >> (4 * G)) & 7; \
    const bool early = R < 3; \
    const int ech = R < 2 ? q : 4 + (mi & 1), ft = R == 2 ? mi >> 1 : 4 * (R - !early) + (mi >> 2); \
    const int pr3 = early ? ech >= 3 : q >> 1, col3 = early ? (ech - 3 * pr3) * 9 : (q & 1) * 14;

    if (warp < 8) {
        ASSIGN_WORK(get_slot())
        if (slot >= 128) {
            const uint32_t ep = ld_volatile(&sc->epoch[slot]) + 1;
            if (mi == 0 && warp > 0) {
                const int k = warp % 3;
                uint2* go = (uint2*)(sc->go + 8 * k) + lane;
                if (warp < 4 && lane < 16) st_relaxed2(go, 0, 0);
                while (ld_relaxed(k ? sc->go : sc->hint_k) != ep) __nanosleep(200);
                __nanosleep(warp * 60);
                const uint4* hint = (k ? sc->hint_u : sc->hint_h) + (k == 2 ? 48 + min(lane, 19) : lane) * 2;
                uint2 v[4];
                do {
                    #pragma unroll
                    for (int i = 0; i < 4; i++) v[i] = ld_relaxed2(hint + (k == 0 ? 64 * i : k == 2 ? 40 * i : 32 * (i & 1)));
                } while (!__all_sync(0xffffffffu, v[0].x == ep && v[1].x == ep && v[2].x == ep && v[3].x == ep));
                uint32_t t = later(later(v[0].y, v[1].y), later(v[2].y, v[3].y));
                t = later(t, __shfl_xor_sync(0xffffffffu, t, 1));
                if (k == 1) { t = later(t, __shfl_xor_sync(0xffffffffu, t, 8)); t = later(t, __shfl_xor_sync(0xffffffffu, t, 16)); }
                if (k == 0) {
                    const uint32_t now = gtime32() + 256;
                    t = later(t, now - __reduce_min_sync(0xffffffffu, now - t) - SLACK);
                }
                t = __shfl_sync(0xffffffffu, t, 2 * lane);
                if (lane < 16) st_relaxed2(go, ep, t);
            }
            if (mi == 1 && warp >= 4 && ld_volatile(&sc->clean) != ep) {
                for (int l = (tid - 128) / 2; l < sizeof(Tiles) / 128; l += 64) st_relaxed4((uint4*)&sc->tiles[ep & 1] + l * 8 + (lane & 7), EMPTY, EMPTY, EMPTY, EMPTY);
                named_sync(1, 128);
                if (tid == 128) st_release(&sc->clean, ep);
            }
            if (tid == 0) {
                const long long t0 = clock64();
                while (clock64() - t0 < SP_AT) {}
                #pragma unroll 1
                for (int i = 0; i < 7; i++) bulk_prefetch((const char*)wo + (i * 4 + mi) * 14336, 14336);
                uint32_t t = (uint32_t)t0 + PF0_AT;
                #pragma unroll 1
                for (int i = 0; i < PF0_N; i++) {
                    while ((int)(clock32() - t) < 0) {}
                    bulk_prefetch((const char*)w1 + i * 114688 + mi * 14336, 14336);
                    t += PF0_PACE;
                }
                if (mi) {
                    t = (uint32_t)t0 + PF1_AT;
                    #pragma unroll 1
                    for (int i = mi - 1; i < PF1_N; i += 3) {
                        while ((int)(clock32() - t) < 0) {}
                        tma5d_prefetch(&tm_w1, (i & 7) * 64, (i + 48) & 56, (i + 48) >> 6);
                        t += PF1_PACE;
                    }
                    t = (uint32_t)t0 + PF_AT;
                    #pragma unroll 1
                    for (int i = mi - 1; i < PF_N; i += 3) {
                        while ((int)(clock32() - t) < 0) {}
                        bulk_prefetch((const char*)w2 + (i < 128 ? i * 16384 : (i - 64 >> 1) * 65536 + (i & 1) * 16384), 16384);
                        t += PF_PACE;
                    }
                }
                while (ld_relaxed(sc->hint_u + 254) != ep) { __nanosleep(500); if (clock64() - t0 > WD_CLKS) __trap(); }
                sc->epoch[slot] = ep;
                if (mi == 1) sc->clean = ep + 1;
            }
            return;
        }
        {
            const int w = warp & 3, wg = warp >> 2, g = lane >> 2, t = lane & 3;
            if (WARM_AT) { const uint32_t t0 = clock32(); while (clock32() - t0 < WARM_AT) {} __syncwarp(); }
            if (w > 0) post_hint(sc->hint_o + ((2 * tb + (w >> 1)) * 32 + hp * 4 + (w & 1) * 2 + wg) * 2, 0, lane);
            if (wg == 0) {
                if (t < 2) st_relaxed4(sc->stats + tt2 * 256 + q * 64 + 16 * w + g + 8 * t, 0, 0, 0, 0);
            }
        }
        named_sync(0, 288);
        asm volatile("setmaxnreg.inc.sync.aligned.u32 224;");
        int tid; asm volatile("mov.u32 %0, %%tid.x;" : "=r"(tid));
        const int lane = tid & 31, warp = __shfl_sync(0xffffffffu, tid >> 5, 0), wg = warp >> 2;
        uint32_t ep;
        Tiles* tl;
        const int w = warp & 3, g = lane >> 2, t = lane & 3;
        const bool leader = (tid & 127) == 0;
        const uint32_t never = gridDim.y - 1;
        {
            uint32_t a[28][4];
            float accK[28], accV[28], accQ[28];
            const int lrow = 16 * w + (lane & 7) + (lane & 8);
            const uint32_t lbase = sb + wg * 8192 + lrow * 128;
            const uint32_t lx = (lane >> 4) ^ (lane & 7);
            const uint32_t wofs = hp & 1;
            auto pin2 = [&](uint32_t x0, uint32_t x1) {
                asm volatile("{\n.reg .pred p;\nsetp.ne.u32 p, %2, 0;\n@p st.shared.v2.b32 [%0], {%0,%1};\n}" :: "r"(x0), "r"(x1), "r"(never) : "memory");
            };
            float cS[2][4] = {}, cA[2][4] = {}, cB[2][4] = {}, q0, q1, p0, p1;
            auto sq = [&](float& acc, uint32_t v) { const float lo = bf_lo(v), hi = bf_hi(v); acc = fmaf(hi, hi, fmaf(lo, lo, acc)); };
            #pragma unroll
            for (int kb = 0; kb < 8; kb++) {
                if (kb < 7) {
                    mbar_wait(bars + 8 * (B_FULLX + kb), 0);
                    if (kb == 0 && tid == 0) STAMP(0);
                    if (kb == 6 && tid == 0) STAMP(25);
                    if (kb == 0) FST(0); if (kb == 2) FST(1); if (kb == 4) FST(2); if (kb == 6) FST(3);
                    #pragma unroll
                    for (int s = 4 * kb; s < 4 * kb + 4; s++) ldsm4(a[s], lbase + slot_x(kb) + ((lx ^ (2 * (s & 3))) << 4));
                }
                if (kb == 5) named_sync(9 + wg, 160);
                if (kb == NPIPE) continue;
                const int kc = kb < NPIPE ? kb : kb - 1;
                if (kc == NSQ) { p0 = cS[0][0] + cS[1][0]; p1 = cS[0][2] + cS[1][2]; }
                #pragma unroll
                for (int s = 4 * kc; s < 4 * kc + 4; s++) {
                    mma16816(cS[s & 1], a[s][0], a[s][1], a[s][2], a[s][3], 0x3F803F80u, 0x3F803F80u);
                    if (kc < NSQ) {
                        mma1688(cA[0], a[s][0], a[s][1], a[s][0]); mma1688(cA[1], a[s][2], a[s][3], a[s][2]);
                        mma1688(cB[0], a[s][0], a[s][1], a[s][1]); mma1688(cB[1], a[s][2], a[s][3], a[s][3]);
                    }
                }
            }
            const float m0 = (cS[0][0] + cS[1][0]) * (1.f / D_), m1 = (cS[0][2] + cS[1][2]) * (1.f / D_);
            const uint32_t mm0 = pack_bf16(m0, m0), mm1 = pack_bf16(m1, m1);
            if (lane == 0) mbar_arrive(bars + 8 * B_DONEX);
            auto center = [&](int s) { sub_bf16x2(a[s][0], mm0); sub_bf16x2(a[s][1], mm1); sub_bf16x2(a[s][2], mm0); sub_bf16x2(a[s][3], mm1); };
            uint32_t Ka[8], Kb[8], Kc[8], Va[8], Vb[7], Vc[8];
            float r0, r1, ls0, ls1;
            uint32_t pm, zero;
            uint32_t* od;
            uint4* oh;
            auto kpack = [&](uint32_t (&k)[8], int j, int c, float r) {
                const uint32_t v = pack_bf16(accK[4 * j + c] * r, accK[4 * j + c + 1] * r);
                if (j == 3) { k[3] = t < 2 ? v : 0u; k[4] = t < 2 ? 0u : v; } else k[j + (j > 3)] = v;
            };
            auto batch = [&](auto c0, auto c1) {
                constexpr int n0 = c0.value, n1 = c1.value;
                wg_fence();
                static_for<n0, n1>([&](auto nc) {
                    constexpr int n = nc.value;
                    if (n == 4) { center(4); center(5); center(6); center(7); wg_fence(); }
                    const uint64_t desc = mkdesc(sb + (n < 56 ? slot_kv(n >> 3) + (n & 7) * 2048 : SM_QO + (n - 56) * 2048), 8192, 1024, 1) + wofs;
                    wgmma_rs56<1>(n < 28 ? accK : n < 56 ? accV : accQ, a[n % 28], desc, n % 28 != 0);
                });
                wg_commit();
                if (n0 > 0) wg_wait<1>();
            };
            const uint32_t hs = sb + tid * 16 + warp * 512;
            auto hand_over = [&](const uint32_t (&v)[8], int kv) {
                mbar_wait(bars + 8 * (kv ? B_DONE1 + 5 : B_DONEX), 0);
                sts4(hs + (kv ? SM_HALOV : SM_HALOK), v[0], v[1], v[2], v[3]); sts4(hs + (kv ? SM_HALOV : SM_HALOK) + 512, v[4], v[5], v[6], v[7]);
                if (w == 3) named_arrive(6 + kv, 96);
            };
            auto take_over = [&](uint32_t (&v)[8], int kv) {
                if (w == 0) mbar_wait(bars + 8 * (B_HALO + 2 * kv + wg), 0);
                const uint32_t ad = w ? hs + (kv ? SM_HALOV : SM_HALOK) - 1024 : kv ? sb + lane * 16 + wg * 1024 + SM_HALOV + 8192 : halo_kin(wg, lane);
                const uint4 u0 = lds4(ad), u1 = lds4(ad + (w || kv ? 512 : 16));
                v[0] = u0.x; v[1] = u0.y; v[2] = u0.z; v[3] = u0.w; v[4] = u1.x; v[5] = u1.y; v[6] = u1.z; v[7] = u1.w;
            };
            center(0); center(1); center(2); center(3);
            static_for<0, 7>([&](auto pc) {
                constexpr int p = pc.value;
                mbar_wait(bars + 8 * (B_FULLKV + p), 0);
                if (p == 0 && tid == 0) STAMP(26);
                if (p == 3 && tid == 0) STAMP(27);
                FST(4 + p);
                batch(Int<8 * p>(), Int<8 * p + 8>());
                if (p > 0 && leader) mbar_arrive(bars + 8 * (B_DONE1 + p - 1));
                #pragma unroll
                for (int s = 8 * p + 8; s < 8 * p + 16 && s < 28; s++) center(s);
                if (p == 1) {
                    const float c0 = bf_hi(mm0), c1 = bf_hi(mm1);
                    q0 = fmaf(c0, fmaf(c0, 64.f * NSQ, -2.f * p0), (g & 1) ? cA[0][1] + cA[1][1] : cA[0][0] + cA[1][0]) - D_ * (m0 - c0) * (m0 - c0);
                    q1 = fmaf(c1, fmaf(c1, 64.f * NSQ, -2.f * p1), (g & 1) ? cB[0][3] + cB[1][3] : cB[0][2] + cB[1][2]) - D_ * (m1 - c1) * (m1 - c1);
                    asm("" : "+f"(q0), "+f"(q1));
                    q0 = t == (g >> 1) ? q0 : 0.f; q1 = t == (g >> 1) ? q1 : 0.f;
                    pin2(__float_as_uint(q0), __float_as_uint(q1));
                }
                constexpr int PK = NSQ < 5 ? 5 : 4, NR = 28 - 4 * NSQ;
                if (p >= 2 && p < PK) {
                    #pragma unroll
                    for (int s = 4 * NSQ + NR * (p - 2) / (PK - 2); s < 4 * NSQ + NR * (p - 1) / (PK - 2); s++) { sq(q0, a[s][0]); sq(q1, a[s][1]); sq(q0, a[s][2]); sq(q1, a[s][3]); }
                    pin2(__float_as_uint(q0), __float_as_uint(q1));
                }
                if (p == PK - 1) { q0 = quad_sum(q0); q1 = quad_sum(q1); }
                if (p == PK) {
                    r0 = rsqrt_approx(fmaxf(q0 * (1.f / D_), 0.f) + LN_EPS); r1 = rsqrt_approx(fmaxf(q1 * (1.f / D_), 0.f) + LN_EPS);
                    reg_fence(accK);
                    #pragma unroll
                    for (int j = 0; j < 7; j++) kpack(Kc, j, 2, r1);
                    hand_over(Kc, 0);
                }
                if (p == PK + 1) {
                    #pragma unroll
                    for (int j = 0; j < 7; j++) kpack(Kb, j, 0, r0);
                    #pragma unroll
                    for (int j = 0; j < 8; j += 2) pin2(Kb[j], Kb[j + 1]);
                    ls0 = LOG2E_SCALE * r0; ls1 = LOG2E_SCALE * r1;
                    pm = (2 * t <= g ? 0xFFFFu : 0u) | (2 * t + 1 <= g ? 0xFFFF0000u : 0u);
                    zero = never; asm volatile("" : "+r"(zero));
                    pin2(__float_as_uint(ls0), __float_as_uint(ls1)); pin2(pm, zero);
                }
                if (p == 2) ep = get_tag();
                if (p == 6) {
                    tl = &sc->tiles[ep & 1];
                    const int tt = 2 * tb + (w >> 1);
                    od = tl->o + tt * 14336 + (7 * hp) * 256 + (2 * (2 * (w & 1) + wg)) * 32 + lane;
                    oh = sc->hint_o + (tt * 32 + hp * 4 + (w & 1) * 2 + wg) * 2 + (lane & 1);
                    pin2((uint32_t)(uint64_t)od, (uint32_t)((uint64_t)od >> 32));
                    pin2((uint32_t)(uint64_t)oh, (uint32_t)((uint64_t)oh >> 32));
                }
            });
            if (tid == 0) STAMP(1);
            FST(11);
            mbar_wait(bars + 8 * B_FQ, 0);
            batch(Int<56>(), Int<60>());
            reg_fence(accV);
            if (leader) mbar_arrive(bars + 8 * (B_DONE1 + 6));
            if (tid == 0) STAMP(2);
            FST(12);
            #pragma unroll
            for (int j = 0; j < 7; j++) Vc[j] = movtrans(pack_bf16(accV[4 * j + 2] * r1, accV[4 * j + 3] * r1));
            Vc[7] = Vc[6];
            hand_over(Vc, 1);
            batch(Int<60>(), Int<66>());
            #pragma unroll
            for (int j = 0; j < 7; j++) {
                Vb[j] = movtrans(pack_bf16(accV[4 * j] * r0, accV[4 * j + 1] * r0));
                Vc[j] |= zero;
            }
            batch(Int<66>(), Int<72>());
            #pragma unroll
            for (int j = 0; j < 7; j++) pin2(Vb[j], Vc[j]);
            mbar_wait(bars + 8 * (B_FQ + 1), 0);
            FST(13);
            if (w > 0 && lane < 2) { const uint32_t now = gtime32(); st_relaxed4(oh, ep, now, ep, now); }
            batch(Int<72>(), Int<84>());
            FST(14);
            named_sync(1 + wg, 128);
            take_over(Ka, 0);
            if (tid == 0) STAMP(3);
            wg_wait<0>();
            reg_fence(accQ);
            if (tid == 0) STAMP(4);
            FST(15);
            const bool first = (tb == 0 && w == 0);
            uint32_t pA[2], pB0[2], pB1[2], pC[2], z0[2], z1[2];
            #pragma unroll
            for (int h = 0; h < 2; h++) {
                float sA[4] = {0.f, 0.f, 0.f, 0.f}, sB[4] = {0.f, 0.f, 0.f, 0.f}, sC[4] = {0.f, 0.f, 0.f, 0.f};
                #pragma unroll
                for (int k = 0; k < 2; k++) {
                    const float* qq = accQ + 12 * h + 8 * k;
                    uint32_t a0 = pack_bf16(qq[0], qq[1]), a1 = pack_bf16(qq[2], qq[3]);
                    if (h == 1 && k == 0) { a0 |= zero; a1 |= zero; }
                    const uint32_t a2 = pack_bf16(qq[4], qq[5]), a3 = pack_bf16(qq[6], qq[7]);
                    mma16816(sB, a0, a1, a2, a3, Kb[4 * h + 2 * k], Kb[4 * h + 2 * k + 1]);
                    mma16816(sA, a0, a1, a2, a3, Ka[4 * h + 2 * k], Ka[4 * h + 2 * k + 1]);
                    mma16816(sC, a0, a1, a2, a3, Kc[4 * h + 2 * k], Kc[4 * h + 2 * k + 1]);
                }
                const bool n0 = pm & 1, n1 = (int)pm < 0;
                const float l00 = n0 ? sB[0] : (first ? -INFINITY : sA[0]), l01 = n1 ? sB[1] : (first ? -INFINITY : sA[1]);
                const float l10 = n0 ? sC[2] : sB[2], l11 = n1 ? sC[3] : sB[3];
                const float x0 = -ls0 * quad_max(fmaxf(l00, l01)), x1 = -ls1 * quad_max(fmaxf(l10, l11));
                const float e00 = ex2(fmaf(l00, ls0, x0)), e01 = ex2(fmaf(l01, ls0, x0)), e10 = ex2(fmaf(l10, ls1, x1)), e11 = ex2(fmaf(l11, ls1, x1));
                const float i0 = rcp_approx(quad_sum(e00 + e01)), i1 = rcp_approx(quad_sum(e10 + e11));
                const uint32_t P0 = pack_bf16(e00 * i0, e01 * i0), P1 = pack_bf16(e10 * i1, e11 * i1);
                pB0[h] = P0 & pm; pA[h] = P0 & ~pm; pC[h] = P1 & pm; pB1[h] = P1 & ~pm; z0[h] = P0 & zero; z1[h] = P1 & zero;
            }
            float o[8][4];
            #pragma unroll
            for (int j = 0; j < 8; j++) {
                o[j][0] = o[j][1] = o[j][2] = o[j][3] = 0.f;
                mma16816(o[j], pB0[j >> 2], pB1[j >> 2], z0[j >> 2], pC[j >> 2], Vb[j - (j >> 2)], Vc[j - (j >> 2)]);
            }
            if (tid == 0) STAMP(12);
            FST(16);
            take_over(Va, 1);
            if (lane == 0) mbar_arrive(bars + 8 * B_DONEQ);
            if (tid == 0) STAMP(16);
            #pragma unroll
            for (int j = 0; j < 8; j++) mma1688(o[j], pA[j >> 2], z1[j >> 2], Va[j - (j >> 2)]);
            #pragma unroll
            for (int j = 0; j < 7; j++) {
                float v[4];
                #pragma unroll
                for (int c = 0; c < 4; c++) v[c] = j < 3 ? o[j][c] : j > 3 ? o[j + 1][c] : (t < 2 ? o[3][c] : o[4][c]);
                od[j * 256] = pack_bf16(v[0], v[1]);
                od[j * 256 + 32] = pack_bf16(v[2], v[3]);
            }
            if (tid == 0) STAMP(5);
            FST(17);
        }
        const int z = get_tag() - ep, slot1 = slot + z, tid1 = tid + z, warp1 = warp + z;
        ep += z;
        {
        ASSIGN_WORK(slot1)
        const int tid = tid1, lane = tid & 31, wg = warp1 >> 2, w = warp1 & 3, g = lane >> 2, t = lane & 3;
        tl = &sc->tiles[ep & 1];
        const uint32_t live = wg ^ 1;
        uint32_t rb0, rb1, late[14];
        const unsigned short* pb = (const unsigned short*)(live ? b2 + tt2 * 64 : b1 + ft * 64) + 16 * w + g;
        auto stage_late = [&]() {
            #pragma unroll
            for (int c = 0; c < 14; c++) asm volatile("st.shared.u32 [%0], %1;" :: "r"(sb + SM_H + wg * 8192 + (tid & 127) * 4 + c * 512), "r"(late[c]) : "memory");
            fence_async_smem();
            named_sync(1 + wg, 128);
        };
        auto store_late = [&](bool on, uint32_t* p) {
            #pragma unroll
            for (int c = 0; c < 4; c++)
                if (elect() && on && (c < 3 || w < 2)) bulk_st(p + (4 * c + w) * 256, sb + SM_H + wg * 8192 + (4 * c + w) * 512, 512);
            asm volatile("cp.async.bulk.commit_group;" ::: "memory");
        };
        auto undef = [](float (&v)[56]) {
            #pragma unroll
            for (int i = 0; i < 56; i++) asm volatile("" : "=f"(v[i]));
        };
        {
            float acc[56];
            const int hrow = 32 * (w >> 1) + 2 * ((lane & 7) + (lane & 8)) + (w & 1);
            const uint32_t ha = sb + SM_H + hrow * 128 + (((lane >> 4) ^ (hrow & 7)) << 4);
            uint4* sp = sc->stats + tt2 * 256 + 16 * w + g + 8 * (t & 1);
            uint4* sp_out = sp + q * 64;
            const uint4* sp_in = sp + (t & 2) * 64;
            uint32_t* hd = tl->hn + ((q >> 1) * 32 + (tt2 >> 1)) * 7168 + (q & 1) * 3584 + (tt2 & 1) * 128 + w * 32 + lane;
            pin_ptr(never, sp_out); pin_ptr(never, sp_in); pin_ptr(never, hd);
            float s0 = 0.f, s1 = 0.f, q0 = 0.f, q1 = 0.f, s2 = 0.f, s3 = 0.f, q2 = 0.f, q3 = 0.f;
            auto sums = [&](int j0, int j1) {
                #pragma unroll
                for (int j = j0; j < j1; j++) {
                    s0 += acc[4 * j]; s2 += acc[4 * j + 1]; q0 = fmaf(acc[4 * j], acc[4 * j], q0); q2 = fmaf(acc[4 * j + 1], acc[4 * j + 1], q2);
                    s1 += acc[4 * j + 2]; s3 += acc[4 * j + 3]; q1 = fmaf(acc[4 * j + 2], acc[4 * j + 2], q1); q3 = fmaf(acc[4 * j + 3], acc[4 * j + 3], q3);
                }
            };
            if (live) {
                mbar_wait(bars + 8 * B_FULLWO, 0);
                #pragma unroll
                for (int jp = 0; jp < 7; jp++) {
                    uint32_t xx[4];
                    ldsm4(xx, hcol(ha, jp));
                    #pragma unroll
                    for (int r = 0; r < 4; r++) { acc[8 * jp + 2 * r] = bf_lo(xx[r]); acc[8 * jp + 2 * r + 1] = bf_hi(xx[r]); }
                }
                reg_fence(acc);
                if (SPIN2) { named_sync(12, 256); spin_mma(bars + 8 * B_FULLX, never); }
                auto od_ = [&](int s) { return mkdesc(sb + SM_QO + s * 2048, 1024, 128, 0); };
                auto wd_ = [&](int s) { return mkdesc(sb + slot_wo(s >> 2) + (s & 3) * 2048, 8192, 1024, 1); };
                float accl[32], accr[24];
                #pragma unroll
                for (int i = 0; i < 5; i++) {
                    if (i < 4) mbar_wait(bars + 8 * (B_FULLO + i), 0);
                    if (i == 0 && tid == 0) STAMP(7);
                    if (i == 1) { rb0 = ld_u16(pb); rb1 = ld_u16(pb + 8); }
                    wg_fence();
                    #pragma unroll
                    for (int ss = 0; ss < 7; ss++) {
                        if (i < 3) wgmma_ss112<0, 1>(acc, od_(7 * i + ss), wd_(7 * i + ss));
                        else if (i == 4) wgmma_ss64<0, 1>(accl, od_(21 + ss), wd_(21 + ss));
                        else if (ss == 0) wgmma_ss48<0, 1, 0>(accr, od_(21), wd_(21) + 512);
                        else wgmma_ss48<0, 1>(accr, od_(21 + ss), wd_(21 + ss) + 512);
                    }
                    wg_commit();
                    if (i > 0) {
                        wg_wait<1>();
                        if (i == 3) {
                            reg_fence(acc);
                            #pragma unroll
                            for (int c = 0; c < 32; c++) accl[c] = __uint_as_float(__float_as_uint(acc[c]) | never);
                            reg_fence(accl);
                        }
                        if (i < 4 && leader) mbar_arrive(bars + 8 * (B_DONEO + i - 1));
                    }
                }
                reg_fence(accr);
                #pragma unroll
                for (int c = 0; c < 24; c++) acc[32 + c] += accr[c];
                sums(8, 14);
                pin4(never, s0, s1, s2, s3); pin4(never, q0, q1, q2, q3);
                wg_wait<0>();
                reg_fence(accl);
                #pragma unroll
                for (int c = 0; c < 32; c++) acc[c] = accl[c];
                if (leader) mbar_arrive(bars + 8 * (B_DONEO + 3));
                if (tid == 0) STAMP(8);
            } else { undef(acc); if (SPIN2) named_arrive(12, 256); }
            if (live || (DRY2 && w == 3)) {
            sums(0, 8);
            s0 += s2; s1 += s3; q0 += q2; q1 += q3;
            float sr = ((t & 1) ? s1 : s0) + __shfl_xor_sync(0xffffffffu, (t & 1) ? s0 : s1, 1), qr = ((t & 1) ? q1 : q0) + __shfl_xor_sync(0xffffffffu, (t & 1) ? q0 : q1, 1);
            sr += __shfl_xor_sync(0xffffffffu, sr, 2); qr += __shfl_xor_sync(0xffffffffu, qr, 2);
            st_relaxed4_if(t < 2 * live, sp_out, __float_as_uint(sr), __float_as_uint(qr), ep);
            const uint32_t tp = clock32();
            if (live) named_arrive(5, 256);
            if (tid == 0) STAMP(9);
            #pragma unroll
            for (int jp = 0; jp < 7; jp++)
                stsm4_if(live, hcol(ha, jp), pack_bf16(acc[8 * jp], acc[8 * jp + 1]), pack_bf16(acc[8 * jp + 2], acc[8 * jp + 3]),
                      pack_bf16(acc[8 * jp + 4], acc[8 * jp + 5]), pack_bf16(acc[8 * jp + 6], acc[8 * jp + 7]));
            uint4 v0, v1;
            if (POLL0) { while (clock32() - tp < POLL0) {} __syncwarp(); }
            do { v0 = ld_relaxed4(sp_in); v1 = ld_relaxed4(sp_in + 64); } while (live && __any_sync(0xffffffffu, v0.w != ep || v1.w != ep));
            if (tid == 0) STAMP(10);
            sr = __uint_as_float(v0.x) + __uint_as_float(v1.x); qr = __uint_as_float(v0.y) + __uint_as_float(v1.y);
            sr += __shfl_xor_sync(0xffffffffu, sr, 2); qr += __shfl_xor_sync(0xffffffffu, qr, 2);
            const float m = sr * (1.f / D_), var = fmaxf(qr * (1.f / D_) - m * m, 0.f);
            const float r = rsqrt_approx(fmaf(var, 4.f + 4.f * LN_EPS, 4.f * LN_EPS * LN_EPS)), c = -m * r;
            const float r0 = __shfl_sync(0xffffffffu, r, lane & ~1), c0 = __shfl_sync(0xffffffffu, c, lane & ~1);
            const float r1 = __shfl_sync(0xffffffffu, r, lane | 1), c1 = __shfl_sync(0xffffffffu, c, lane | 1);
            #pragma unroll
            for (int j = 0; j < 14; j++) st_global_if(live, hd + j * 256, pack_bf16(fmaf(acc[4 * j], r0, c0), fmaf(acc[4 * j + 1], r0, c0)));
            if (never) mbar_arrive(bars);
            if (SPIN3) named_arrive_if(live, 3, 256);
            #pragma unroll
            for (int j = 0; j < 14; j++) late[j] = pack_bf16(fmaf(acc[4 * j + 2], r1, c1), fmaf(acc[4 * j + 3], r1, c1));
            if (tid == 0) STAMP(11);
            }
        }
        if (!live) {
            if (w < 2) check_tiles<0>(w, 2, 4, tl->o + tt2 * 14336, false, lane, true);
            rb0 = ld_u16(pb); rb1 = ld_u16(pb + 8);
            auto reset_tiles = [&](int v, int i0, int i1) {
                const int l = slot * 48 + v * 16 + lane / 2;
                #pragma unroll
                for (int i = i0; i < i1; i++)
                    st_relaxed4_if(i < 6 || l < sizeof(Tiles) / 128 - 6 * 6144, (uint4*)&sc->tiles[~ep & 1] + (i * 6144 + l) * 8 + (lane & 7), EMPTY, EMPTY, EMPTY);
            };
            if (CL_N && w < 3) { mbar_wait(bars + 8 * (B_DONEO + CL_P2), 0); reset_tiles(w, 0, CL_N); }
            named_sync(5, 256);
            auto phase3 = [&](auto nc) {
                constexpr int NC = nc.value;
                float acc[4 * NC];
                uint32_t* ud = tl->u + (pr3 * 28 + (ft >> 1) + (NC == 14 ? 4 : 0)) * 7168 + col3 * 256 + (ft & 1) * 128 + w * 32 + lane;
                #pragma unroll
                for (int j = 0; j < 4 * NC; j++) acc[j] = 0.5f * bf_lo((j & 2) ? rb1 : rb0);
                #pragma unroll 1
                for (uint32_t pass = never; pass < 2; pass++) {
                    if (pass) {
                        if (SPIN3) { named_sync(3, 256); spin_mma(bars + 8 * (B_FULLX + 1), never); }
                        mix_mainloop<32>(TSVAL acc, leader);
                        if (leader) STAMP(14);
                    }
                    uint32_t pk[NC];
                    #pragma unroll
                    for (int j = 0; j < NC; j++) {
                        const float k = j < GDEP ? GELU_K1 : __uint_as_float(__float_as_uint(GELU_K1) | (pk[j - GDEP] & never));
                        pk[j] = pack_bf16(gelu_half(acc[4 * j], k), gelu_half(acc[4 * j + 1], k));
                        st_global_if(pass, ud + j * 256, pk[j]);
                    }
                }
                if (leader) STAMP(15);
                #pragma unroll
                for (int j = 0; j < NC; j++) late[j] = pack_bf16(gelu_half(acc[4 * j + 2], GELU_K1), gelu_half(acc[4 * j + 3], GELU_K1));
                if (NC == 14) {
                    stage_late();
                    mbar_wait(bars + 8 * (B_FULLB + LATE_AT4), 1);
                    store_late(true, tl->u + (pr3 * 28 + (ft >> 1) + 14) * 7168 + col3 * 256 + (ft & 1) * 128);
                } else {
                    #pragma unroll
                    for (int c = 0; c < NC; c++) st_global_if(1, ud + 4 * 7168 + c * 256, late[c]);
                    if (SPIN4) named_arrive(13, 256);
                }
            };
            if (early) phase3(Int<10>()); else phase3(Int<14>());
            if (w) {
                if (early && w == 1) fetch_times(TSVAL sc->go, 1, ep, lane);
                check_tiles<2>(CH_U - 1 + w, 3, 28, tl->u + (q >> 1) * 28 * 7168 + (q & 1) * 3584, false, lane, false);
                if (CL_N < 7) { mbar_wait(bars + 8 * (B_DONE + CL_AT), 1); reset_tiles(w - 1, CL_N, 7); }
            }
            if (leader) mbar_wait_wd(bars + 8 * B_END, 0);
            return;
        }
        {
            float acc[56];
            const uint32_t ad = sb + SM_H + (16 * w + (lane & 15)) * 128 + (((lane >> 4) ^ (lane & 7)) << 4);
            const float bb0 = bf_lo(rb0), bb1 = bf_lo(rb1);
            named_sync(1, 128);
            #pragma unroll
            for (int jp = 0; jp < 7; jp++) {
                uint32_t hh[4];
                ldsm4(hh, hcol(ad, jp));
                #pragma unroll
                for (int r = 0; r < 4; r++) { acc[8 * jp + 2 * r] = bf_lo(hh[r]) + ((r & 1) ? bb1 : bb0); acc[8 * jp + 2 * r + 1] = bf_hi(hh[r]) + ((r & 1) ? bb1 : bb0); }
            }
            #pragma unroll 1
            for (uint32_t pass = never; pass < 2; pass++) {
                if (pass) {
                    named_sync(1, 128);
                    stage_late();
                    if (tid == 0) STAMP(39);
                    mbar_wait(bars + 8 * (B_FULLB + LATE_AT), 0);
                    store_late(true, tl->hn + ((q >> 1) * 32 + 16 + (tt2 >> 1)) * 7168 + (q & 1) * 3584 + (tt2 & 1) * 128);
                    check_tiles<1>(CH_H + w, 4, 32, tl->hn + pr3 * 32 * 7168 + col3 * 256, early, lane, false);
                    mbar_wait(bars + 8 * (B_DONE + START4), 0);
                    if (SPIN4 && early) { named_sync(13, 256); spin_mma(bars + 8 * (B_FULLX + 2), never); }
                    mix_mainloop<28>(TSVAL acc, leader);
                    if (leader) mbar_arrive(bars + 8 * B_END);
                    if (tid == 0) STAMP(18);
                }
                #pragma unroll
                for (int jp = 0; jp < 7; jp++)
                    stsm4_if(1, hcol(ad, jp), pack_bf16(acc[8 * jp], acc[8 * jp + 1]), pack_bf16(acc[8 * jp + 2], acc[8 * jp + 3]),
                             pack_bf16(acc[8 * jp + 4], acc[8 * jp + 5]), pack_bf16(acc[8 * jp + 6], acc[8 * jp + 7]));
                fence_async_smem();
                __syncwarp();
            }
            if (elect()) {
                tma2d_store(&tm_out64, c64, tt2 * 64 + 16 * w, sb + SM_H + w * 2048);
                tma2d_store(&tm_out48, c48, tt2 * 64 + 16 * w, sb + SM_H + 8192 + w * 2048);
            }
            asm volatile("cp.async.bulk.commit_group;" ::: "memory");
            asm volatile("cp.async.bulk.wait_group.read 0;" ::: "memory");
            if (tid == 0) { sc->epoch[slot] = ep; STAMP(19); }
        }
        }
    } else {
        asm volatile("setmaxnreg.dec.sync.aligned.u32 56;");
        int warp2; asm("mov.u32 %0, %1;" : "=r"(warp2) : "r"(warp));
        if (warp2 > 8) {
            ASSIGN_WORK(get_slot())
            if (slot >= 128) return;
            uint32_t ep, cl;
            uint4* const oh = sc->hint_o + (2 * tb * 32 + hp * 4) * 2 + (lane & 3);
            uint4* const hu = sc->hint_u + (early ? ech * 8 + ft : 40 + q * 20 + ft) * 2;
            if (warp == 10) {
                post_hint(sc->hint_h + (q * 32 + tt2) * 2, 0, lane);
                post_hint(hu, 0, lane);
            }
            if (warp == 11) {
                ep = ld_volatile(&sc->epoch[slot]) + 1; cl = ld_acquire(&sc->clean);
                post_hint(sc->hint_k + (tb * 8 + hp) * 2, 0, lane);
                if (lane < (tb < 15 ? 4 : 0)) st_relaxed4(oh + 128, 0, 0, 0, 0);
                if (lane < (tb ? 0 : 4)) st_relaxed4(oh, 0, 0, 0, 0);
            }
            if (elect()) {
                if (warp == 9) {
                    #pragma unroll
                    for (int i = B_DONE1; i < B_DONEO; i++) mbar_init(bars + 8 * i, i < B_DONEX ? 2 : i == B_DONEX ? 8 : 9);
                }
                #pragma unroll
                for (int i = 0; i < 54; i++) mbar_init(bars + 8 * (B_DONEO + i) + (warp - 9) * 432, 1);
                asm volatile("fence.mbarrier_init.release.cluster;" ::: "memory");
            }
            named_sync(8, 128);
            if (warp < 11) mbar_expect(sb + SM_RAW + 8 * (tid - 288), early && tid >= 292 && tid < 324 ? 10240 : 14336);
            if (warp == 9) { named_arrive(4, 64); named_arrive(9, 160); named_arrive(10, 160); }
            if (warp < 11) {
                ep = get_tag();
                mbar_wait(bars + 8 * (B_DONE1 + HALO_AT), 0);
                #pragma unroll 1
                for (int kv = 0; kv < 2; kv++) {
                    uint4 v0 = {}, v1 = {}, v2 = {};
                    if (tb > 0) {
                        const uint4* hg = sc->halo + ((((tb - 1) * 8 + hp) * 2 + warp - 9) * 2 + kv) * 96 + lane;
                        if (kv == 0) while (ld_relaxed(sc->hint_k + ((tb - 1) * 8 + hp) * 2) != ep) {}
                        do { v0 = ld_relaxed4(hg); v1 = ld_relaxed4(hg + 32); v2 = ld_relaxed4(hg + 64); } while (!__all_sync(0xffffffffu, v0.w == ep && v1.w == ep && v2.w == ep));
                    }
                    if (kv) mbar_wait(bars + 8 * (B_DONE1 + 5), 0);
                    const uint32_t hs = kv ? sb + lane * 16 + (warp - 9) * 1024 + SM_HALOV + 8192 : halo_kin(warp - 9, lane);
                    sts4(hs, v0.x, v0.y, v0.z, v1.x); sts4(hs + (kv ? 512 : 16), v1.y, v1.z, v2.x, v2.y);
                    __syncwarp();
                    if (lane == 0) mbar_arrive(bars + 8 * (B_HALO + 2 * kv + warp - 9));
                }
                if (tid == 288) STAMP(21);
            } else {
                const long long t0 = clock64();
                while (__any_sync(0xffffffffu, (int)(cl - ep) < 0)) { cl = ld_acquire(&sc->clean); if (clock64() - t0 > WD_CLKS) __trap(); }
                if (lane == 0) { *(volatile uint32_t*)(smem_raw + SM_TAG) = ep; mbar_arrive(bars + 8 * B_CLR); }
                uint4* hg = sc->halo + (tb * 8 + hp) * 384 + lane;
                #pragma unroll 1
                for (int kv = 0; kv < 2; kv++) {
                    const uint32_t hs = sb + lane * 16 + 3072 + (kv ? SM_HALOV : SM_HALOK);
                    named_sync(6 + kv, 96);
                    #pragma unroll
                    for (int p = 0; p < 2; p++) {
                        const uint4 u0 = lds4(hs + p * 4096), u1 = lds4(hs + p * 4096 + 512);
                        st_relaxed4(hg + p * 192, u0.x, u0.y, u0.z, ep); st_relaxed4(hg + p * 192 + 32, u0.w, u1.x, u1.y, ep); st_relaxed4(hg + p * 192 + 64, u1.z, u1.w, ep, ep);
                    }
                    hg += 96;
                    if (kv == 0) {
                        post_hint(sc->hint_k + (tb * 8 + hp) * 2, ep, lane);
                        #pragma unroll
                        for (int j = 0; j < 6; j++) st_relaxed4(hg + j * 32 + (j / 3) * 96, 0, 0, 0, 0);
                    }
                }
                const uint32_t now = gtime32() - LATE_O;
                if (lane < (tb < 15 ? 4 : 0)) st_relaxed4(oh + 128, ep, now, ep, now);
                if (lane < (tb ? 0 : 4)) st_relaxed4(oh, ep, now, ep, now);
                if (lane == 0) STAMP(23);
                if (lane == 0) mbar_arrive(bars + 8 * B_DONEQ);
            }
            if (warp > 9) {
                const Tiles* const tl = &sc->tiles[ep & 1];
                check_tiles<1>(11 - warp, 2, CH_H, tl->hn + pr3 * 32 * 7168 + col3 * 256, early, lane, true);
                if (warp == 10) {
                    mbar_wait(bars + 8 * (B_DONE + (early ? HINT_E : HINT_U)), 0);
                    post_time(hu, ep, lane);
                }
                if (warp == 11) {
                    mbar_wait(bars + 8 * (B_DONE + (early ? POLL_E : POLL_N)), 0);
                    fetch_times(TSVAL sc->go, 0, ep, lane);
                }
                check_tiles<2>(11 - warp, 2, CH_U, tl->u + (q >> 1) * 28 * 7168 + (q & 1) * 3584, false, lane, true);
            } else {
                int aslot = 0;
                if (lane == 0) { prefetch_map(&tm_out64); prefetch_map(&tm_out48); }
                #pragma unroll
                for (int i = 0; i < HINT_F; i++) mbar_wait(bars + 8 * (B_FULLO + i), 0);
                post_time(sc->hint_h + (q * 32 + tt2) * 2, ep, lane);
                #pragma unroll 1
                for (int i = 0; i < 30; i++) {
                    if (i == POLL_I && !early) fetch_times(TSVAL sc->go, 1, ep, lane);
                    int d = 2 * i - 11 + (i >= A4_FROM ? A4_DLY : 0);
                    if (early) d = i < 16 ? 1 + (i - NA_SLOTS) * AE_END / 9 : max(d, AE_W2);
                    mbar_wait(bars + 8 * (i < NA_SLOTS ? B_DONEQ + ((A_SCHED >> (4 * i)) & 15) : B_DONE + (d & 31)), d >= 32);
                    if (elect()) {
                        const uint32_t bar = bars + 8 * (B_FULLA + (i & 15)), dst = sb + SM_ARING + aslot * 16384;
                        mbar_expect(bar, 16384);
                        if (i < 16) tma5d(dst, &tm_w1, ft * 64, (i & 7) * 8, i >> 3, bar);
                        else tma5d(dst, &tm_w2, tt2 * 64, 8 * (i < 20 ? i & 1 : i < 25 ? i - 18 : i - 23), i < 20 ? (i >> 1) & 1 : i >= 25, bar);
                    }
                    aslot = aslot == NA_SLOTS - 1 ? 0 : aslot + 1;
                }
            }
        } else {
            const int slot0 = get_slot(), row0 = (slot0 >> 5) * 256 + (slot0 & 12) * 16;
            if (elect()) {
                prefetch_map(&tm_x);
                #pragma unroll
                for (int i = 0; i < 7; i++) mbar_init(bars + 8 * i, 1);
                asm volatile("fence.mbarrier_init.release.cluster;" ::: "memory");
            }
            named_arrive(0, 288);
            if (elect()) {
                #pragma unroll 1
                for (int kb = 0; kb < 7; kb++) {
                    load_x(kb, row0);
                    if (kb == 0) STAMP(22);
                }
                #pragma unroll
                for (int i = 7; i < B_DONE1; i++) mbar_init(bars + 8 * i, 1);
                asm volatile("fence.mbarrier_init.release.cluster;" ::: "memory");
            }
            named_arrive(8, 128);
            ASSIGN_WORK(get_slot())
            if (slot >= 128) return;
            #pragma unroll 1
            for (int kb = 0; kb < 7; kb++) {
                if (kb == 6) { named_sync(4, 64); mbar_wait(bars + 8 * B_DONEX, 0); }
                if (elect()) {
                    const uint32_t st = sb + slot_kv(kb), bar = bars + 8 * (B_FULLKV + kb);
                    mbar_expect(bar, 16384);
                    #pragma unroll
                    for (int i = 0; i < 2; i++) {
                        const int n = 2 * kb + (i ^ (G & 1));
                        tma2d(st + (n & 1) * 8192, &tm_wqkv, (n < 7 ? 448 : 896) + wcol, (n < 7 ? n : n - 7) * 64, bar);
                    }
                }
            }
            if (elect()) {
                mbar_expect(bars + 8 * B_FQ, 32768);
                mbar_expect(bars + 8 * (B_FQ + 1), 24576);
                #pragma unroll 1
                for (int i = 0; i < 7; i++) { const int j = i == 6 ? i : i ^ (G & 1); tma2d(sb + SM_QO + j * 8192, &tm_wqkv, wcol, j * 64, bars + 8 * (B_FQ + (i >> 2))); }
                mbar_expect(bars + 8 * B_FULLWO, 512 * 112 * 2);
            }
            #pragma unroll 1
            for (int i = 0; i < 7; i++) {
                const int kb = ((q & 1 ? WO_ORD1 : WO_ORD0) >> (4 * i)) & 7;
                if (kb < 5) mbar_wait(bars + 8 * (B_DONE1 + kb), 0);
                if (elect()) {
                    tma2d(sb + slot_wo(kb), &tm_wo64, c64, kb * 64, bars + 8 * B_FULLWO);
                    tma2d(sb + slot_wo(kb) + 8192, &tm_wo48, c48, kb * 64, bars + 8 * B_FULLWO);
                }
            }
            if (elect()) {
                tma2d(sb + SM_H, &tm_xr64, c64, tt2 * 64, bars + 8 * B_FULLWO);
                tma2d(sb + SM_H + 8192, &tm_xr48, c48, tt2 * 64, bars + 8 * B_FULLWO);
            }
            if (smem_u32(smem_raw) != SB) __trap();
            const uint32_t ep = get_tag();
            const Tiles* const tl = &sc->tiles[ep & 1];
            mbar_wait(bars + 8 * (B_DONE1 + 6), 0);
            const uint32_t t_o = last_hint(TSVAL sc->hint_o + (tt2 * 32 + lane) * 2, ep, 38);
            mbar_wait(bars + 8 * B_DONEQ, 0);
            wait_until(t_o + GO_O);
            if (elect()) {
                #pragma unroll
                for (int i = 0; i < 4; i++) {
                    bulk_ld(sb + SM_QO + i * 14336, tl->o + tt2 * 14336 + i * 3584, 14336, sb + SM_RAW + 8 * i);
                }
            }
            if (lane == 0) STAMP(20);
            if (SPIN2) { wait_until(t_o + GO_O + STOP2); if (lane == 0) mbar_arrive(bars + 8 * B_FULLX); }
            mbar_wait(bars + 8 * (B_DONEO + POLL_H), 0);
            const uint32_t* src = tl->hn + pr3 * 32 * 7168 + col3 * 256;
            uint32_t bytes = early ? 10240 : 14336, dst = sb + SM_BRING, top = dst + (early ? NE_SLOTS * 10240 : NB_SLOTS * 14336), raw = sb + SM_RAW + 32;
            auto issue = [&]() {
                if (elect()) bulk_ld(dst, src, bytes, raw);
                src += 7168; raw += 8; dst += bytes;
                if (dst == top) dst = sb + SM_BRING;
            };
            uint2 th;
            do { th = ld_relaxed2((const uint2*)sc->go + (lane & 15)); } while (!__all_sync(0xffffffffu, th.x == ep));
            STAMP(42);
            mbar_wait(bars + 8 * (B_DONEO + 3), 0);
            {
                uint32_t bit = 1, wait = ~1u;
                wait_until(__shfl_sync(0xffffffffu, th.y, 0) + GO_H);
                #pragma unroll 1
                do {
                    while (wait & bit) wait = __ballot_sync(0xffffffffu, (int)(gtime32() - th.y - GO_H) < 0);
                    if (bit == 1) STAMP(29);
                    issue();
                    if (SPIN3 && bit == 1 << STOP3 && lane == 0) mbar_arrive(bars + 8 * (B_FULLX + 1));
                    bit *= 2;
                } while (dst != sb + SM_BRING);
            }
            uint32_t done = bars + 8 * B_DONE;
            #pragma unroll 1
            do { mbar_wait(done, 0); done += 8; issue(); } while (raw != sb + SM_RAW + 288);
            if (early) mbar_wait(bars + 8 * (B_DONE + 31), 0);
            src = tl->u + (q >> 1) * 28 * 7168 + (q & 1) * 3584; bytes = 14336; dst = sb + SM_BRING; top = dst + NB_SLOTS * 14336;
            done = bars + 8 * (B_DONE + 24);
            #pragma unroll 1
            for (uint32_t par = 0; par < 2; par++) {
                mbar_wait(bars + 8 * (B_GO + par), 0);
                const uint32_t ts = *(volatile uint32_t*)(smem_raw + SM_TIME + 128 * par + 4 * lane);
                if (par) done = bars + 8 * B_DONE;
                uint32_t bit = 1, wait = ~1u;
                wait_until(__shfl_sync(0xffffffffu, ts, 0));
                #pragma unroll 1
                do {
                    while (wait & bit) wait = __ballot_sync(0xffffffffu, (int)(gtime32() - ts) < 0);
                    if (bit == 1) STAMP(par ? 36 : 30);
                    mbar_wait(done, par); done += 8;
                    issue();
                    if (SPIN4 && bit == 1 << STOP3 && lane + par == 0) mbar_arrive(bars + 8 * (B_FULLX + 2));
                    bit *= 2;
                } while (bit != (par ? 1 << 20 : 1 << 8));
            }
        }
    }
}

typedef CUresult (*EncodeFn)(CUtensorMap*, CUtensorMapDataType, cuuint32_t, void*, const cuuint64_t*, const cuuint64_t*, const cuuint32_t*,
                             const cuuint32_t*, CUtensorMapInterleave, CUtensorMapSwizzle, CUtensorMapL2promotion, CUtensorMapFloatOOBfill);

void make_map(EncodeFn fn, CUtensorMap* tm, const void* ptr, int rank, const cuuint64_t* dims, const cuuint64_t* strides, const cuuint32_t* box, CUtensorMapSwizzle sw) {
    cuuint32_t es[5] = {1, 1, 1, 1, 1};
    fn(tm, CU_TENSOR_MAP_DATA_TYPE_BFLOAT16, rank, const_cast<void*>(ptr), dims, strides, box, es, CU_TENSOR_MAP_INTERLEAVE_NONE, sw,
       CU_TENSOR_MAP_L2_PROMOTION_NONE, CU_TENSOR_MAP_FLOAT_OOB_FILL_NONE);
}

}

extern "C" void kernel_launch(void* const* d_in, const int* in_sizes, int n_in, void* d_out, int out_size) {
    const __nv_bfloat16* x = (const __nv_bfloat16*)d_in[0];
    const __nv_bfloat16* wqkv = (const __nv_bfloat16*)d_in[1];
    const __nv_bfloat16* wo = (const __nv_bfloat16*)d_in[2];
    const __nv_bfloat16* w1 = (const __nv_bfloat16*)d_in[4];
    const __nv_bfloat16* b1 = (const __nv_bfloat16*)d_in[5];
    const __nv_bfloat16* w2 = (const __nv_bfloat16*)d_in[6];
    const __nv_bfloat16* b2 = (const __nv_bfloat16*)d_in[7];

    void* fnp = nullptr; cudaDriverEntryPointQueryResult qr;
    cudaGetDriverEntryPoint("cuTensorMapEncodeTiled", &fnp, cudaEnableDefault, &qr);
    EncodeFn fn = (EncodeFn)fnp;
    CUtensorMap tx, twqkv, two64, two48, tw1, tw2, txr64, txr48, tout64, tout48;
    { cuuint64_t d[3] = {448, 2, 1024}, s[2] = {896, 1792}; cuuint32_t b[3] = {64, 1, 64}; make_map(fn, &tx, x, 3, d, s, b, CU_TENSOR_MAP_SWIZZLE_128B); }
    { cuuint64_t d[2] = {1344, 448}, s[1] = {2688}; cuuint32_t b[2] = {64, 64}; make_map(fn, &twqkv, wqkv, 2, d, s, b, CU_TENSOR_MAP_SWIZZLE_128B); }
    { cuuint64_t d[2] = {448, 448}, s[1] = {896}; cuuint32_t b[2] = {64, 64}; make_map(fn, &two64, wo, 2, d, s, b, CU_TENSOR_MAP_SWIZZLE_128B); }
    { cuuint64_t d[2] = {448, 448}, s[1] = {896}; cuuint32_t b[2] = {48, 64}; make_map(fn, &two48, wo, 2, d, s, b, CU_TENSOR_MAP_SWIZZLE_128B); }
    { cuuint64_t d[5] = {1792, 8, 2, 64, 2}, s[4] = {2 * 3584, 3584, 32 * 3584, 16 * 3584}; cuuint32_t b[5] = {64, 8, 2, 8, 1}; make_map(fn, &tw1, w1, 5, d, s, b, CU_TENSOR_MAP_SWIZZLE_128B); }
    { cuuint64_t d[5] = {2048, 8, 2, 56, 2}, s[4] = {4096, 16 * 4096, 32 * 4096, 8 * 4096}; cuuint32_t b[5] = {64, 8, 2, 8, 1}; make_map(fn, &tw2, w2, 5, d, s, b, CU_TENSOR_MAP_SWIZZLE_128B); }
    { cuuint64_t d[2] = {448, 2048}, s[1] = {896}; cuuint32_t b[2] = {64, 64}; make_map(fn, &txr64, x, 2, d, s, b, CU_TENSOR_MAP_SWIZZLE_128B); }
    { cuuint64_t d[2] = {448, 2048}, s[1] = {896}; cuuint32_t b[2] = {48, 64}; make_map(fn, &txr48, x, 2, d, s, b, CU_TENSOR_MAP_SWIZZLE_128B); }
    { cuuint64_t d[2] = {448, 2048}, s[1] = {896}; cuuint32_t b[2] = {64, 16}; make_map(fn, &tout64, d_out, 2, d, s, b, CU_TENSOR_MAP_SWIZZLE_128B); }
    { cuuint64_t d[2] = {448, 2048}, s[1] = {896}; cuuint32_t b[2] = {48, 16}; make_map(fn, &tout48, d_out, 2, d, s, b, CU_TENSOR_MAP_SWIZZLE_128B); }

    void* scv = nullptr;
    cudaGetSymbolAddress(&scv, g_scratch);
    Scratch* scp = (Scratch*)scv;
    int dev = 0, sms = 0;
    cudaGetDevice(&dev);
    cudaDeviceGetAttribute(&sms, cudaDevAttrMultiProcessorCount, dev);
    if (sms == 132) {
        cudaFuncSetAttribute(fused_kernel<true>, cudaFuncAttributeMaxDynamicSharedMemorySize, SM_TOTAL);
        fused_kernel<true><<<132, 384, SM_TOTAL>>>(scp, wo, w1, b1, w2, b2, tx, twqkv, two64, two48, tw1, tw2, txr64, txr48, tout64, tout48);
    } else {
        cudaFuncSetAttribute(fused_kernel<false>, cudaFuncAttributeMaxDynamicSharedMemorySize, SM_TOTAL);
        fused_kernel<false><<<132, 384, SM_TOTAL>>>(scp, wo, w1, b1, w2, b2, tx, twqkv, two64, two48, tw1, tw2, txr64, txr48, tout64, tout48);
    }
}
```

```cpp
#include <cuda_runtime.h>
#include <cuda_bf16.h>
#include <cuda.h>
#include <stdint.h>

namespace {

constexpr int D_ = 448;
constexpr float LN_EPS = 1e-5f;
constexpr float LOG2E_SCALE = 0.1889822365046136f * 1.4426950408889634f;

struct Tiles {
    uint32_t o[32 * 57344 / 4];
    uint32_t hn[4 * 32 * 14336 / 4];
    uint32_t u[4 * 28 * 14336 / 4];
};
struct Scratch {
    uint4 halo[128 * 2 * 2 * 3 * 32];
    uint4 stats[32 * 4 * 64];
    uint4 hint_k[128 * 2];
    uint4 hint_o[32 * 32 * 2];
    uint4 hint_h[4 * 32 * 2];
    uint4 hint_u[128 * 2];
    uint4 go[24];
    uint32_t epoch[160];
    uint32_t clean;
    alignas(1024) Tiles tiles[2];
};
__device__ Scratch g_scratch;
#define STAMP(i) do {} while (0)
#define FST(i) do {} while (0)
#define TSARG
#define TSVAL

constexpr uint32_t SB = 1024;
constexpr int SM_SLOT = 16384;
__device__ __forceinline__ constexpr uint32_t slot_x(int kb) { return (kb ? 6 + kb : 0) * SM_SLOT; }
__device__ __forceinline__ constexpr uint32_t slot_kv(int kb) { return (kb < 5 ? 2 + kb : 6 - kb) * SM_SLOT; }
__device__ __forceinline__ constexpr uint32_t slot_wo(int kb) { return (kb < 6 ? 2 + kb : 12) * SM_SLOT; }
constexpr int SM_QO = 8 * SM_SLOT;
constexpr int SM_HALOK = SM_QO + 57344, SM_HALOV = 1 * SM_SLOT;
constexpr int NA_SLOTS = 6, NB_SLOTS = 8;
constexpr int SM_ARING = 0;
constexpr int SM_BRING = NA_SLOTS * 16384;
constexpr int SM_H = 212992;
__device__ __forceinline__ uint32_t halo_kin(int par, int lane) { return SB + SM_H + 8192 + par * 4096 + lane * 128 + ((~lane & 6) << 4); }
constexpr int SM_BAR = 229376;
constexpr int SM_TAG = SM_BAR + 1536;
constexpr int SM_TIME = SM_TAG + 256;
constexpr int SM_TOTAL = SM_TIME + 256;
constexpr int B_FULLX = 0;
constexpr int B_FULLKV = 7;
constexpr int B_FQ = 14;
constexpr int B_DONE1 = 16;
constexpr int B_DONEX = 23;
constexpr int B_DONEQ = 24;
constexpr int B_DONEO = 25;
constexpr int B_FULLO = 29;
constexpr int B_FULLWO = 33;
constexpr int B_END = 34;
constexpr int B_HALO = 35;
constexpr int B_FULLA = 39;
constexpr int B_FULLB = 55;
constexpr int B_DONE = 87;
constexpr int B_GO = 119;
constexpr int B_CLR = 121;
constexpr int SM_RAW = SM_BAR + 8 * 122;

constexpr long long WD_CLKS = 2000000000ll;

template<int N> struct Int { static constexpr int value = N; };
template<int A, int B, class F> __device__ __forceinline__ void static_for(F&& f) { if constexpr (A < B) { f(Int<A>()); static_for<A + 1, B>(f); } }

__device__ __forceinline__ uint32_t smem_u32(const void* p) { return (uint32_t)__cvta_generic_to_shared(p); }
__device__ __forceinline__ void mbar_init(uint32_t bar, uint32_t cnt) { asm volatile("mbarrier.init.shared::cta.b64 [%0], %1;" :: "r"(bar), "r"(cnt) : "memory"); }
__device__ __forceinline__ void mbar_expect(uint32_t bar, uint32_t bytes) { asm volatile("mbarrier.arrive.expect_tx.shared::cta.b64 _, [%0], %1;" :: "r"(bar), "r"(bytes) : "memory"); }
__device__ __forceinline__ void mbar_arrive(uint32_t bar) { asm volatile("mbarrier.arrive.shared::cta.b64 _, [%0];" :: "r"(bar) : "memory"); }
__device__ __forceinline__ bool mbar_try(uint32_t bar, uint32_t parity) {
    uint32_t ok;
    asm volatile("{\n.reg .pred p;\nmbarrier.try_wait.parity.shared::cta.b64 p, [%1], %2;\nselp.u32 %0, 1, 0, p;\n}" : "=r"(ok) : "r"(bar), "r"(parity) : "memory");
    return ok;
}
__device__ __forceinline__ bool mbar_test(uint32_t bar, uint32_t parity) {
    uint32_t ok;
    asm volatile("{\n.reg .pred p;\nmbarrier.test_wait.parity.shared::cta.b64 p, [%1], %2;\nselp.u32 %0, 1, 0, p;\n}" : "=r"(ok) : "r"(bar), "r"(parity) : "memory");
    return ok;
}
__device__ __forceinline__ void mbar_wait(uint32_t bar, uint32_t parity) {
    asm volatile("{\n.reg .pred p;\n"
                 "WAIT_LOOP:\n"
                 "mbarrier.try_wait.parity.shared::cta.b64 p, [%0], %1;\n"
                 "@!p bra WAIT_LOOP;\n}" :: "r"(bar), "r"(parity) : "memory");
}
__device__ __forceinline__ void mbar_wait_unless(uint32_t ready, uint32_t bar) {
    asm volatile("{\n.reg .pred p;\nsetp.ne.u32 p, %1, 0;\n@p bra.uni DONE;\n"
                 "WAIT_LOOP:\n"
                 "mbarrier.try_wait.parity.shared::cta.b64 p, [%0], 0;\n"
                 "@!p bra.uni WAIT_LOOP;\nDONE:\n}" :: "r"(bar), "r"(ready) : "memory");
}
__device__ __forceinline__ void mbar_wait_wd(uint32_t bar, uint32_t parity) {
    asm volatile("{\n.reg .pred p, q;\n.reg .u32 s, t;\nmov.u32 s, %%clock;\n"
                 "WAIT_LOOP:\n"
                 "mbarrier.try_wait.parity.shared::cta.b64 p, [%0], %1;\nmov.u32 t, %%clock;\nsub.u32 t, t, s;\nsetp.lt.and.s32 q, t, 0, !p;\n@q trap;\n"
                 "@!p bra WAIT_LOOP;\n}" :: "r"(bar), "r"(parity) : "memory");
}
__device__ __forceinline__ bool elect() { uint32_t p; asm volatile("{\n.reg .pred P;\nelect.sync _|P, 0xffffffff;\nselp.u32 %0, 1, 0, P;\n}" : "=r"(p)); return p; }
__device__ __forceinline__ void tma2d(uint32_t dst, const CUtensorMap* tm, int c0, int c1, uint32_t bar) {
    asm volatile("cp.async.bulk.tensor.2d.shared::cluster.global.mbarrier::complete_tx::bytes [%0], [%1, {%3, %4}], [%2];" :: "r"(dst), "l"(tm), "r"(bar), "r"(c0), "r"(c1) : "memory");
}
__device__ __forceinline__ void tma3d(uint32_t dst, const CUtensorMap* tm, int c0, int c1, int c2, uint32_t bar) {
    asm volatile("cp.async.bulk.tensor.3d.shared::cluster.global.mbarrier::complete_tx::bytes [%0], [%1, {%3, %4, %5}], [%2];" :: "r"(dst), "l"(tm), "r"(bar), "r"(c0), "r"(c1), "r"(c2) : "memory");
}
__device__ __forceinline__ void tma5d(uint32_t dst, const CUtensorMap* tm, int c0, int c3, int c4, uint32_t bar) {
    asm volatile("cp.async.bulk.tensor.5d.shared::cluster.global.mbarrier::complete_tx::bytes [%0], [%1, {%3, 0, 0, %4, %5}], [%2];" :: "r"(dst), "l"(tm), "r"(bar), "r"(c0), "r"(c3), "r"(c4) : "memory");
}
__device__ __forceinline__ void tma5d_prefetch(const CUtensorMap* tm, int c0, int c3, int c4) {
    asm volatile("cp.async.bulk.prefetch.tensor.5d.L2.global [%0, {%1, 0, 0, %2, %3}];" :: "l"(tm), "r"(c0), "r"(c3), "r"(c4) : "memory");
}
__device__ __forceinline__ void tma2d_store(const CUtensorMap* tm, int c0, int c1, uint32_t src) {
    asm volatile("cp.async.bulk.tensor.2d.global.shared::cta.bulk_group [%0, {%2, %3}], [%1];" :: "l"(tm), "r"(src), "r"(c0), "r"(c1) : "memory");
}
__device__ __forceinline__ void bulk_st(void* dst, uint32_t src, uint32_t bytes) {
    asm volatile("cp.async.bulk.global.shared::cta.bulk_group [%0], [%1], %2;" :: "l"(dst), "r"(src), "r"(bytes) : "memory");
}
__device__ __forceinline__ void bulk_ld(uint32_t dst, const void* src, uint32_t bytes, uint32_t bar) {
    asm volatile("cp.async.bulk.shared::cluster.global.mbarrier::complete_tx::bytes [%0], [%1], %2, [%3];" :: "r"(dst), "l"(src), "r"(bytes), "r"(bar) : "memory");
}
__device__ __forceinline__ void bulk_prefetch(const void* src, uint32_t bytes) { asm volatile("cp.async.bulk.prefetch.L2.global [%0], %1;" :: "l"(src), "r"(bytes) : "memory"); }
__device__ __forceinline__ void prefetch_map(const CUtensorMap* tm) { asm volatile("prefetch.tensormap [%0];" :: "l"(tm) : "memory"); }
__device__ __forceinline__ void st_global_if(uint32_t c, uint32_t* p, uint32_t v) {
    asm volatile("{\n.reg .pred p;\nsetp.ne.u32 p, %2, 0;\n@p st.global.u32 [%0], %1;\n}" :: "l"(p), "r"(v), "r"(c) : "memory");
}
__device__ __forceinline__ void st_relaxed4_if(bool c, uint4* p, uint32_t a, uint32_t b, uint32_t d) {
    asm volatile("{\n.reg .b128 t;\n.reg .b64 a, b;\n.reg .pred p;\nsetp.ne.u32 p, %4, 0;\nmov.b64 a, {%1, %2};\nmov.b64 b, {%3, %3};\nmov.b128 t, {a, b};\n@p st.relaxed.gpu.global.b128 [%0], t;\n}" :: "l"(p), "r"(a), "r"(b), "r"(d), "r"((uint32_t)c) : "memory");
}
__device__ __forceinline__ void pin_ptr(uint32_t never, const void* a) {
    asm volatile("{\n.reg .pred p;\nsetp.ne.u32 p, %1, 0;\n@p st.shared.u64 [%1], %0;\n}" :: "l"(a), "r"(never) : "memory");
}
__device__ __forceinline__ void pin4(uint32_t never, float a, float b, float c, float d) {
    asm volatile("{\n.reg .pred p;\nsetp.ne.u32 p, %4, 0;\n@p st.shared.v4.f32 [%4], {%0,%1,%2,%3};\n}" :: "f"(a), "f"(b), "f"(c), "f"(d), "r"(never) : "memory");
}
__device__ __forceinline__ void fence_async_smem() { asm volatile("fence.proxy.async.shared::cta;" ::: "memory"); }
__device__ __forceinline__ uint32_t ld_acquire(const void* p) { uint32_t v; asm volatile("ld.acquire.gpu.global.u32 %0, [%1];" : "=r"(v) : "l"(p) : "memory"); return v; }
__device__ __forceinline__ void st_release(void* p, uint32_t v) { asm volatile("st.release.gpu.global.u32 [%0], %1;" :: "l"(p), "r"(v) : "memory"); }
__device__ __forceinline__ uint32_t ld_relaxed(const void* p) { uint32_t v; asm volatile("ld.relaxed.gpu.global.u32 %0, [%1];" : "=r"(v) : "l"(p) : "memory"); return v; }
__device__ __forceinline__ uint2 ld_relaxed2(const void* p) {
    uint2 v; asm volatile("{\n.reg .b64 a;\nld.relaxed.gpu.global.b64 a, [%2];\nmov.b64 {%0, %1}, a;\n}" : "=r"(v.x), "=r"(v.y) : "l"(p) : "memory"); return v;
}
__device__ __forceinline__ void st_relaxed2(void* p, uint32_t a, uint32_t b) {
    asm volatile("{\n.reg .b64 a;\nmov.b64 a, {%1, %2};\nst.relaxed.gpu.global.b64 [%0], a;\n}" :: "l"(p), "r"(a), "r"(b) : "memory");
}
__device__ __forceinline__ uint4 ld_relaxed4(const uint4* p) {
    uint4 v;
    asm volatile("{\n.reg .b128 t;\n.reg .b64 a, b;\nld.relaxed.gpu.global.b128 t, [%4];\nmov.b128 {a, b}, t;\nmov.b64 {%0, %1}, a;\nmov.b64 {%2, %3}, b;\n}" : "=r"(v.x), "=r"(v.y), "=r"(v.z), "=r"(v.w) : "l"(p) : "memory");
    return v;
}
__device__ __forceinline__ void st_relaxed4(uint4* p, uint32_t a, uint32_t b, uint32_t c, uint32_t d) {
    asm volatile("{\n.reg .b128 t;\n.reg .b64 a, b;\nmov.b64 a, {%1, %2};\nmov.b64 b, {%3, %4};\nmov.b128 t, {a, b};\nst.relaxed.gpu.global.b128 [%0], t;\n}" :: "l"(p), "r"(a), "r"(b), "r"(c), "r"(d) : "memory");
}
__device__ __forceinline__ uint32_t ld_u16(const unsigned short* p) { uint32_t v; asm volatile("ld.volatile.global.u16 %0, [%1];" : "=r"(v) : "l"(p) : "memory"); return v; }
__device__ __forceinline__ uint32_t ld_volatile(const uint32_t* p) { uint32_t v; asm volatile("ld.volatile.global.u32 %0, [%1];" : "=r"(v) : "l"(p) : "memory"); return v; }
__device__ __forceinline__ void named_arrive(int id, int n) { asm volatile("bar.arrive %0, %1;" :: "r"(id), "r"(n) : "memory"); }
__device__ __forceinline__ void named_sync(int id, int n) { asm volatile("bar.sync %0, %1;" :: "r"(id), "r"(n) : "memory"); }
__device__ __forceinline__ void named_arrive_if(uint32_t c, int id, int n) { asm volatile("{\n.reg .pred p;\nsetp.ne.u32 p, %2, 0;\n@p bar.arrive %0, %1;\n}" :: "r"(id), "r"(n), "r"(c) : "memory"); }
__device__ __forceinline__ bool named_any(int id, int n, bool v) {
    uint32_t r; asm volatile("{\n.reg .pred p, q;\nsetp.ne.u32 p, %3, 0;\nbar.red.or.pred q, %1, %2, p;\nselp.u32 %0, 1, 0, q;\n}" : "=r"(r) : "r"(id), "r"(n), "r"((uint32_t)v) : "memory"); return r;
}
__device__ __forceinline__ void wg_fence() { asm volatile("wgmma.fence.sync.aligned;" ::: "memory"); }
__device__ __forceinline__ void wg_commit() { asm volatile("wgmma.commit_group.sync.aligned;" ::: "memory"); }
template<int N> __device__ __forceinline__ void wg_wait() { asm volatile("wgmma.wait_group.sync.aligned %0;" :: "n"(N) : "memory"); }
template<int N> __device__ __forceinline__ void reg_fence(float (&d)[N]) {
    #pragma unroll
    for (int i = 0; i < N; i++) asm volatile("" : "+f"(d[i]) :: "memory");
}
__device__ __forceinline__ constexpr uint64_t mkdesc(uint32_t addr, uint32_t lbo, uint32_t sbo, uint32_t sw) {
    return (uint64_t)((addr & 0x3FFFF) >> 4) | ((uint64_t)(lbo >> 4) << 16) | ((uint64_t)(sbo >> 4) << 32) | ((uint64_t)sw << 62);
}
__device__ __forceinline__ void ldsm4(uint32_t (&r)[4], uint32_t addr) {
    asm volatile("ldmatrix.sync.aligned.m8n8.x4.shared.b16 {%0,%1,%2,%3}, [%4];" : "=r"(r[0]), "=r"(r[1]), "=r"(r[2]), "=r"(r[3]) : "r"(addr) : "memory");
}
__device__ __forceinline__ void stsm4_if(uint32_t c, uint32_t addr, uint32_t r0, uint32_t r1, uint32_t r2, uint32_t r3) {
    asm volatile("{\n.reg .pred p;\nsetp.ne.u32 p, %5, 0;\n@p stmatrix.sync.aligned.m8n8.x4.shared.b16 [%0], {%1,%2,%3,%4};\n}" :: "r"(addr), "r"(r0), "r"(r1), "r"(r2), "r"(r3), "r"(c) : "memory");
}
__device__ __forceinline__ void sts4(uint32_t a, uint32_t x, uint32_t y, uint32_t z, uint32_t w) { asm volatile("st.shared.v4.u32 [%0], {%1,%2,%3,%4};" :: "r"(a), "r"(x), "r"(y), "r"(z), "r"(w) : "memory"); }
__device__ __forceinline__ uint4 lds4(uint32_t a) { uint4 v; asm volatile("ld.shared.v4.u32 {%0,%1,%2,%3}, [%4];" : "=r"(v.x), "=r"(v.y), "=r"(v.z), "=r"(v.w) : "r"(a) : "memory"); return v; }
__device__ __forceinline__ uint32_t movtrans(uint32_t a) { uint32_t d; asm volatile("movmatrix.sync.aligned.m8n8.trans.b16 %0, %1;" : "=r"(d) : "r"(a)); return d; }
__device__ __forceinline__ uint32_t pack_bf16(float lo, float hi) { uint32_t r; asm("cvt.rn.bf16x2.f32 %0, %1, %2;" : "=r"(r) : "f"(hi), "f"(lo)); return r; }
__device__ __forceinline__ void sub_bf16x2(uint32_t& a, uint32_t b) { asm volatile("sub.rn.bf16x2 %0, %0, %1;" : "+r"(a) : "r"(b)); }
__device__ __forceinline__ float bf_lo(uint32_t v) { return __uint_as_float(v << 16); }
__device__ __forceinline__ float bf_hi(uint32_t v) { return __uint_as_float(v & 0xffff0000u); }
__device__ __forceinline__ void mma16816(float (&c)[4], uint32_t a0, uint32_t a1, uint32_t a2, uint32_t a3, uint32_t b0, uint32_t b1) {
    asm volatile("mma.sync.aligned.m16n8k16.row.col.f32.bf16.bf16.f32 {%0,%1,%2,%3}, {%4,%5,%6,%7}, {%8,%9}, {%0,%1,%2,%3};"
        : "+f"(c[0]), "+f"(c[1]), "+f"(c[2]), "+f"(c[3]) : "r"(a0), "r"(a1), "r"(a2), "r"(a3), "r"(b0), "r"(b1));
}
__device__ __forceinline__ void mma1688(float (&c)[4], uint32_t a0, uint32_t a1, uint32_t b0) {
    asm volatile("mma.sync.aligned.m16n8k8.row.col.f32.bf16.bf16.f32 {%0,%1,%2,%3}, {%4,%5}, {%6}, {%0,%1,%2,%3};"
        : "+f"(c[0]), "+f"(c[1]), "+f"(c[2]), "+f"(c[3]) : "r"(a0), "r"(a1), "r"(b0));
}
__device__ __forceinline__ float quad_sum(float v) { v += __shfl_xor_sync(0xffffffffu, v, 1); v += __shfl_xor_sync(0xffffffffu, v, 2); return v; }
__device__ __forceinline__ float quad_max(float v) { v = fmaxf(v, __shfl_xor_sync(0xffffffffu, v, 1)); v = fmaxf(v, __shfl_xor_sync(0xffffffffu, v, 2)); return v; }
__device__ __forceinline__ float ex2(float x) { float y; asm("ex2.approx.ftz.f32 %0, %1;" : "=f"(y) : "f"(x)); return y; }
__device__ __forceinline__ float rsqrt_approx(float x) { float y; asm("rsqrt.approx.ftz.f32 %0, %1;" : "=f"(y) : "f"(x)); return y; }
__device__ __forceinline__ float rcp_approx(float x) { float y; asm("rcp.approx.ftz.f32 %0, %1;" : "=f"(y) : "f"(x)); return y; }
constexpr float GELU_K1 = 2.f * 0.7978845608028654f;
__device__ __forceinline__ float gelu_half(float hx, float k1) {
    const float z = hx * fmaf(hx * hx, 8.f * 0.044715f * 0.7978845608028654f, k1);
    float t; asm("tanh.approx.f32 %0, %1;" : "=f"(t) : "f"(z));
    return fmaf(hx, t, hx);
}
__device__ __forceinline__ uint32_t gtime32() { uint64_t t; asm volatile("mov.u64 %0, %%globaltimer;" : "=l"(t)); return (uint32_t)t; }
__device__ __forceinline__ uint32_t clock32() { uint32_t t; asm volatile("mov.u32 %0, %%clock;" : "=r"(t)); return t; }
#define PF_PACE 160
#define PF_AT 16500
#define PF_N 192
#define NSQ 6
#define NPIPE 1
#define HALO_AT 3
#define HINT_U 18
#define HINT_E 16
#define SP_AT 2000
#define A_SCHED 0x322188
#define WO_ORD0 0x4321065
#define WO_ORD1 0x3465210
#define CL_AT 23
#define WARM_AT 300
#define GO_H 1730
#define GO_E 1900
#define GO_U 2120
#define GO_O 1280
#define LATE_O 256
#define DRY2 1
#define LATE_AT 0
#define LATE_AT4 0
#define SLACK 0
#define GDEP 4
#define START4 30
#define DEPTH_N 1
#define DEPTH_E 2
#define NE_SLOTS 11
#define POLL_E 26
#define CH_U 28
#define AE_END 18
#define AE_W2 27
#define PF1_AT 12000
#define PF1_N 80
#define PF1_PACE 160
#define GO_E2 300
#define GO_U2 400
#define POLL_I 20
#define POLL_N 19
#define ROLES 0x65431027u
#define POLL0 250
#define A4_FROM 23
#define A4_DLY 2
#define SPIN2 1
#define SPIN3 0
#define SPIN4 0
#define SPIN_N 2
#define STOP2 150
#define STOP3 3
#define PF0_AT 5000
#define PF0_N 48
#define PF0_PACE 140
#define POLL_H 3
#define CH_H 8
#define HINT_F 2
#define CL_N 4
#define CL_P2 7
#define VTAKE 1
#define DEFER 1
template<int TB> __device__ __forceinline__ void wgmma_rs56(float (&d)[28], const uint32_t (&a)[4], uint64_t db, int sc) {
    asm volatile("{\n.reg .pred p;\nsetp.ne.b32 p, %33, 0;\n"
        "wgmma.mma_async.sync.aligned.m64n56k16.f32.bf16.bf16 {%0, %1, %2, %3, %4, %5, %6, %7, %8, %9, %10, %11, %12, %13, %14, %15, %16, %17, %18, %19, %20, %21, %22, %23, %24, %25, %26, %27}, {%28, %29, %30, %31}, %32, p, 1, 1, %34;\n}\n"
        : "+f"(d[0]), "+f"(d[1]), "+f"(d[2]), "+f"(d[3]), "+f"(d[4]), "+f"(d[5]), "+f"(d[6]), "+f"(d[7]), "+f"(d[8]), "+f"(d[9]), "+f"(d[10]), "+f"(d[11]), "+f"(d[12]), "+f"(d[13]), "+f"(d[14]), "+f"(d[15]), "+f"(d[16]), "+f"(d[17]), "+f"(d[18]), "+f"(d[19]), "+f"(d[20]), "+f"(d[21]), "+f"(d[22]), "+f"(d[23]), "+f"(d[24]), "+f"(d[25]), "+f"(d[26]), "+f"(d[27])
        : "r"(a[0]), "r"(a[1]), "r"(a[2]), "r"(a[3]), "l"(db), "r"(sc), "n"(TB));
}

template<int TA, int TB, int SC = 1> __device__ __forceinline__ void wgmma_ss112(float (&d)[56], uint64_t da, uint64_t db) {
    asm volatile("wgmma.mma_async.sync.aligned.m64n112k16.f32.bf16.bf16 {%0, %1, %2, %3, %4, %5, %6, %7, %8, %9, %10, %11, %12, %13, %14, %15, %16, %17, %18, %19, %20, %21, %22, %23, %24, %25, %26, %27, %28, %29, %30, %31, %32, %33, %34, %35, %36, %37, %38, %39, %40, %41, %42, %43, %44, %45, %46, %47, %48, %49, %50, %51, %52, %53, %54, %55}, %56, %57, %60, 1, 1, %58, %59;\n"
        : "+f"(d[0]), "+f"(d[1]), "+f"(d[2]), "+f"(d[3]), "+f"(d[4]), "+f"(d[5]), "+f"(d[6]), "+f"(d[7]), "+f"(d[8]), "+f"(d[9]), "+f"(d[10]), "+f"(d[11]), "+f"(d[12]), "+f"(d[13]), "+f"(d[14]), "+f"(d[15]), "+f"(d[16]), "+f"(d[17]), "+f"(d[18]), "+f"(d[19]), "+f"(d[20]), "+f"(d[21]), "+f"(d[22]), "+f"(d[23]), "+f"(d[24]), "+f"(d[25]), "+f"(d[26]), "+f"(d[27]), "+f"(d[28]), "+f"(d[29]), "+f"(d[30]), "+f"(d[31]), "+f"(d[32]), "+f"(d[33]), "+f"(d[34]), "+f"(d[35]), "+f"(d[36]), "+f"(d[37]), "+f"(d[38]), "+f"(d[39]), "+f"(d[40]), "+f"(d[41]), "+f"(d[42]), "+f"(d[43]), "+f"(d[44]), "+f"(d[45]), "+f"(d[46]), "+f"(d[47]), "+f"(d[48]), "+f"(d[49]), "+f"(d[50]), "+f"(d[51]), "+f"(d[52]), "+f"(d[53]), "+f"(d[54]), "+f"(d[55])
        : "l"(da), "l"(db), "n"(TA), "n"(TB), "n"(SC));
}

template<int TA, int TB, int SC = 1> __device__ __forceinline__ void wgmma_ss80(float (&d)[40], uint64_t da, uint64_t db) {
    asm volatile("wgmma.mma_async.sync.aligned.m64n80k16.f32.bf16.bf16 {%0, %1, %2, %3, %4, %5, %6, %7, %8, %9, %10, %11, %12, %13, %14, %15, %16, %17, %18, %19, %20, %21, %22, %23, %24, %25, %26, %27, %28, %29, %30, %31, %32, %33, %34, %35, %36, %37, %38, %39}, %40, %41, %44, 1, 1, %42, %43;\n"
        : "+f"(d[0]), "+f"(d[1]), "+f"(d[2]), "+f"(d[3]), "+f"(d[4]), "+f"(d[5]), "+f"(d[6]), "+f"(d[7]), "+f"(d[8]), "+f"(d[9]), "+f"(d[10]), "+f"(d[11]), "+f"(d[12]), "+f"(d[13]), "+f"(d[14]), "+f"(d[15]), "+f"(d[16]), "+f"(d[17]), "+f"(d[18]), "+f"(d[19]), "+f"(d[20]), "+f"(d[21]), "+f"(d[22]), "+f"(d[23]), "+f"(d[24]), "+f"(d[25]), "+f"(d[26]), "+f"(d[27]), "+f"(d[28]), "+f"(d[29]), "+f"(d[30]), "+f"(d[31]), "+f"(d[32]), "+f"(d[33]), "+f"(d[34]), "+f"(d[35]), "+f"(d[36]), "+f"(d[37]), "+f"(d[38]), "+f"(d[39])
        : "l"(da), "l"(db), "n"(TA), "n"(TB), "n"(SC));
}

template<int TA, int TB, int SC = 1> __device__ __forceinline__ void wgmma_ss64(float (&d)[32], uint64_t da, uint64_t db) {
    asm volatile("wgmma.mma_async.sync.aligned.m64n64k16.f32.bf16.bf16 {%0, %1, %2, %3, %4, %5, %6, %7, %8, %9, %10, %11, %12, %13, %14, %15, %16, %17, %18, %19, %20, %21, %22, %23, %24, %25, %26, %27, %28, %29, %30, %31}, %32, %33, %36, 1, 1, %34, %35;\n"
        : "+f"(d[0]), "+f"(d[1]), "+f"(d[2]), "+f"(d[3]), "+f"(d[4]), "+f"(d[5]), "+f"(d[6]), "+f"(d[7]), "+f"(d[8]), "+f"(d[9]), "+f"(d[10]), "+f"(d[11]), "+f"(d[12]), "+f"(d[13]), "+f"(d[14]), "+f"(d[15]), "+f"(d[16]), "+f"(d[17]), "+f"(d[18]), "+f"(d[19]), "+f"(d[20]), "+f"(d[21]), "+f"(d[22]), "+f"(d[23]), "+f"(d[24]), "+f"(d[25]), "+f"(d[26]), "+f"(d[27]), "+f"(d[28]), "+f"(d[29]), "+f"(d[30]), "+f"(d[31])
        : "l"(da), "l"(db), "n"(TA), "n"(TB), "n"(SC));
}

template<int TA, int TB, int SC = 1> __device__ __forceinline__ void wgmma_ss48(float (&d)[24], uint64_t da, uint64_t db) {
    asm volatile("wgmma.mma_async.sync.aligned.m64n48k16.f32.bf16.bf16 {%0, %1, %2, %3, %4, %5, %6, %7, %8, %9, %10, %11, %12, %13, %14, %15, %16, %17, %18, %19, %20, %21, %22, %23}, %24, %25, %28, 1, 1, %26, %27;\n"
        : "+f"(d[0]), "+f"(d[1]), "+f"(d[2]), "+f"(d[3]), "+f"(d[4]), "+f"(d[5]), "+f"(d[6]), "+f"(d[7]), "+f"(d[8]), "+f"(d[9]), "+f"(d[10]), "+f"(d[11]), "+f"(d[12]), "+f"(d[13]), "+f"(d[14]), "+f"(d[15]), "+f"(d[16]), "+f"(d[17]), "+f"(d[18]), "+f"(d[19]), "+f"(d[20]), "+f"(d[21]), "+f"(d[22]), "+f"(d[23])
        : "l"(da), "l"(db), "n"(TA), "n"(TB), "n"(SC));
}

template<int NKB, int NR>
__device__ __forceinline__ void mix_mainloop(TSARG float (&acc)[NR], bool leader) {
    constexpr uint32_t sb = SB, bars = sb + SM_BAR, par = NKB == 28;
    constexpr int A0 = NKB == 32 ? 0 : 16 % NA_SLOTS;
    constexpr int DEPTH = NR == 56 ? DEPTH_N : DEPTH_E;
    int bslot = 0, aslot = A0;
    reg_fence(acc);
    #pragma unroll 1
    for (int i = 0; i < NKB / 2; i++) {
        mbar_wait(bars + 8 * (B_FULLA + i), par);
        const uint64_t adesc = mkdesc(sb + SM_ARING, 8192, 1024, 1) + (uint32_t)(aslot * 1024);
        aslot = aslot == NA_SLOTS - 1 ? 0 : aslot + 1;
        #pragma unroll
        for (int jj = 0; jj < 2; jj++) {
            const int j = 2 * i + jj;
            mbar_wait(bars + 8 * (B_FULLB + j), par);
            const uint64_t bdesc = mkdesc(sb + SM_BRING, 128, 1024, 0) + (uint32_t)(bslot * NR * 16);
            bslot = bslot == (NR == 56 ? NB_SLOTS : NE_SLOTS) - 1 ? 0 : bslot + 1;
            wg_fence();
            #pragma unroll
            for (int s = 0; s < 4; s++) {
                if constexpr (NR == 56) wgmma_ss112<1, 1>(acc, adesc + jj * 512 + s * 128, bdesc + s * 16);
                else wgmma_ss80<1, 1>(acc, adesc + jj * 512 + s * 128, bdesc + s * 16);
            }
            wg_commit();
            wg_wait<DEPTH>();
            if (j >= DEPTH && leader) mbar_arrive(bars + 8 * (B_DONE + j - DEPTH));
        }
    }
    if (DEPTH == 2) { wg_wait<1>(); if (leader) mbar_arrive(bars + 8 * (B_DONE + NKB - 2)); }
    wg_wait<0>();
    reg_fence(acc);
    if (leader) mbar_arrive(bars + 8 * (B_DONE + NKB - 1));
}

__device__ __forceinline__ void spin_mma(uint32_t bar, uint32_t never) {
    float d[56];
    #pragma unroll
    for (int i = 0; i < 56; i++) d[i] = 0.f;
    reg_fence(d);
    #pragma unroll 1
    do {
        wg_fence();
        #pragma unroll
        for (int s = 0; s < SPIN_N; s++) wgmma_ss112<1, 1>(d, mkdesc(SB + 2 * SM_SLOT + s * 2048, 8192, 1024, 1), mkdesc(SB + 3 * SM_SLOT + s * 256, 128, 1024, 0));
        wg_commit();
        wg_wait<1>();
    } while (!named_any(11, 128, mbar_test(bar, 1)));
    wg_wait<0>();
    reg_fence(d);
    pin4(never, d[0], d[1], d[2], d[3]);
}

constexpr uint32_t EMPTY = 0xFFFFFFFFu;
__device__ __forceinline__ void post_hint(uint4* p, uint32_t ep, int lane) { if (lane < 2) st_relaxed4(p + lane, ep, ep, ep, ep); }
__device__ __forceinline__ void post_time(uint4* p, uint32_t ep, int lane) { const uint32_t now = gtime32(); if (lane < 2) st_relaxed4(p + lane, ep, now, ep, now); }

__device__ __forceinline__ uint32_t last_hint(TSARG const uint4* hint, uint32_t ep, int st) {
    uint2 v;
    do { v = ld_relaxed2(hint); } while (!__all_sync(0xffffffffu, v.x == ep));
    const uint32_t t1 = gtime32() + 256;
    if (elect()) STAMP(st);
    return t1 - __reduce_min_sync(0xffffffffu, t1 - v.y);
}
__device__ __forceinline__ uint32_t later(uint32_t a, uint32_t b) { return a + max((int)(b - a), 0); }
__device__ __forceinline__ void fetch_times(TSARG const uint4* go, int k, uint32_t ep, int lane) {
    const uint2* p = (const uint2*)(go + 8 + 8 * k) + (k ? lane % 10 : lane & 3);
    uint2 v;
    do { v = ld_relaxed2(p); } while (!__all_sync(0xffffffffu, v.x == ep));
    v.y += k ? (lane < 10 ? GO_U : GO_U + GO_U2) : (lane < 4 ? GO_E : GO_E + GO_E2);
    asm volatile("st.shared.u32 [%0], %1;" :: "r"(SB + SM_TIME + 128 * k + 4 * lane), "r"(v.y) : "memory");
    __syncwarp();
    if (lane == 0) { mbar_arrive(SB + SM_BAR + 8 * (B_GO + k)); STAMP(k ? 43 : 24); }
    __syncwarp();
}
__device__ __forceinline__ void wait_until(uint32_t t) {
    asm volatile("{\n.reg .pred p;\n.reg .u64 a;\n.reg .u32 l, h;\nWAIT_LOOP:\nmov.u64 a, %%globaltimer;\nmov.b64 {l, h}, a;\nsub.u32 l, l, %0;\nsetp.lt.s32 p, l, 0;\n@p bra.uni WAIT_LOOP;\n}" :: "r"(t) : "memory");
}

__device__ __forceinline__ uint32_t check_tile(uint32_t raw, uint32_t full, uint32_t dst, uint32_t lofs, const uint32_t* src, uint32_t bytes, int lane) {
    uint32_t cnt;
    asm volatile("{\n.reg .pred p, e;\n.reg .u32 a, b, c, d;\nmov.u32 %0, 0;\n"
                 "AGAIN:\nand.b32 a, %0, 1;\n"
                 "WAIT:\nmbarrier.try_wait.parity.shared::cta.b64 p, [%1], a;\n@!p bra.uni WAIT;\n"
                 "ld.shared.u32 a, [%4];\nld.shared.u32 b, [%4+4096];\nld.shared.u32 c, [%5+-8192];\nld.shared.u32 d, [%5+-4096];\n"
                 "add.u32 %0, %0, 1;\nmax.u32 a, a, b;\nmax.u32 c, c, d;\nmax.u32 a, a, c;\nsetp.lt.u32 e, %8, 32;\nsetp.eq.and.u32 p, a, 0xFFFFFFFF, e;\n"
                 "vote.sync.any.pred p, p, 0xffffffff;\nsetp.eq.and.u32 e, %8, 0, !p;\n@e mbarrier.arrive.shared::cta.b64 _, [%2];\n"
                 "elect.sync _|e, 0xffffffff;\nand.pred e, e, p;\n"
                 "@e mbarrier.arrive.expect_tx.shared::cta.b64 _, [%1], %7;\n"
                 "@e cp.async.bulk.shared::cluster.global.mbarrier::complete_tx::bytes [%3], [%6], %7, [%1];\n"
                 "@p bra.uni AGAIN;\n}"
                 : "=&r"(cnt) : "r"(raw), "r"(full), "r"(dst), "r"(dst + lofs), "r"(dst + lofs + bytes), "l"(src), "r"(bytes), "r"(lane) : "memory");
    return cnt;
}

template<int ST>
__device__ __forceinline__ void check_tiles(int j, int step, int n, const uint32_t* src, bool small, int lane, bool dry) {
    const uint32_t bytes = small ? 10240 : 14336, nb = small ? NE_SLOTS : NB_SLOTS, lofs = lane * 128 + (lane & 3) * 32 + (lane >> 2) * 4;
    uint32_t sl = j % nb;
    #pragma unroll 1
    for (int inc = dry ? 0 : step; j < n; j += inc, inc = step) {
        const uint32_t c = check_tile(inc ? SB + SM_RAW + 8 * (j + (ST ? 32 * ST - 28 : 0)) : SB + SM_BAR + 8 * B_CLR, SB + SM_BAR + 8 * (j + (ST ? B_FULLB : B_FULLO)),
                                      SB + (ST ? SM_BRING : SM_QO) + sl * bytes, lofs, src + j * (ST ? 7168 : 3584), bytes, inc ? lane : 32);
        sl += inc;
        if (sl >= nb) sl -= nb;
    }
}

__device__ __forceinline__ uint32_t hcol(uint32_t a, int jp) { return (a ^ ((jp & 3) << 5)) + (jp >> 2) * 8192; }

__device__ __forceinline__ uint32_t get_tag() {
    mbar_wait(SB + SM_BAR + 8 * B_CLR, 0);
    uint32_t v; asm volatile("ld.shared.u32 %0, [%1];" : "=r"(v) : "r"(SB + SM_TAG) : "memory"); return v;
}

template<bool USE_SMID>
__global__ void __launch_bounds__(384, 1)
fused_kernel(Scratch* __restrict__ sc, const __nv_bfloat16* __restrict__ wo,
             const __nv_bfloat16* __restrict__ w1, const __nv_bfloat16* __restrict__ b1,
             const __nv_bfloat16* __restrict__ w2, const __nv_bfloat16* __restrict__ b2,
             const __grid_constant__ CUtensorMap tm_x, const __grid_constant__ CUtensorMap tm_wqkv,
             const __grid_constant__ CUtensorMap tm_wo64, const __grid_constant__ CUtensorMap tm_wo48,
             const __grid_constant__ CUtensorMap tm_w1, const __grid_constant__ CUtensorMap tm_w2,
             const __grid_constant__ CUtensorMap tm_xr64, const __grid_constant__ CUtensorMap tm_xr48,
             const __grid_constant__ CUtensorMap tm_out64, const __grid_constant__ CUtensorMap tm_out48) {
    extern __shared__ __align__(1024) uint8_t smem_raw[];
    constexpr uint32_t sb = SB;
    constexpr uint32_t bars = sb + SM_BAR;
    const int tid = threadIdx.x, lane = tid & 31;
    auto get_slot = [&]() {
        int slot;
    if (USE_SMID) {
        asm volatile("{\n.reg .u32 s, t, u, d, a, b, c;\n.reg .pred p, r;\n"
            "mov.u32 s, %%smid;\nshr.u32 t, s, 1;\nsub.u32 u, t, 32;\nmul.lo.u32 d, u, 37;\nshr.u32 d, d, 8;\n"
            "and.b32 a, t, 7;\nshl.b32 a, a, 3;\nshr.u32 c, t, 3;\nadd.u32 a, a, c;\n"
            "mad.lo.u32 b, d, -55, 12;\nshl.b32 c, u, 3;\nadd.u32 b, b, c;\n"
            "setp.lt.u32 p, t, 32;\nselp.u32 a, a, b, p;\n"
            "setp.lt.u32 r, t, 62;\nselp.s32 c, 4, -58, r;\nadd.u32 c, t, c;\nsetp.lt.u32 p, t, 60;\nselp.u32 a, a, c, p;\n"
            "and.b32 s, s, 1;\nshl.b32 a, a, 1;\nadd.u32 %0, a, s;\n}" : "=r"(slot));
    } else slot = blockIdx.x;
        return slot;
    };
    auto load_x = [&](int kb, int row) {
        const uint32_t st = sb + slot_x(kb), bar = bars + 8 * (B_FULLX + kb);
        mbar_expect(bar, 16384);
        tma3d(st, &tm_x, kb * 64, 0, row, bar); tma3d(st + 8192, &tm_x, kb * 64, 1, row, bar);
    };
    const int warp = __shfl_sync(0xffffffffu, tid >> 5, 0);
#define ASSIGN_WORK(s) \
    const int slot = (s), G = slot >> 4, mi = slot & 15; \
    const int tb = 4 * (G >> 1) + (mi >> 2), hp = 2 * (mi & 3) + (G & 1), wcol = (hp * 56) & ~15; \
    const int q = mi & 3, tt2 = 4 * G + (mi >> 2), c64 = 64 * q, c48 = 256 + 48 * q; \
    const int R = (ROLES >> (4 * G)) & 7; \
    const bool early = R < 3; \
    const int ech = R < 2 ? q : 4 + (mi & 1), ft = R == 2 ? mi >> 1 : 4 * (R - !early) + (mi >> 2); \
    const int pr3 = early ? ech >= 3 : q >> 1, col3 = early ? (ech - 3 * pr3) * 9 : (q & 1) * 14;

    if (warp < 8) {
        ASSIGN_WORK(get_slot())
        if (slot >= 128) {
            const uint32_t ep = ld_volatile(&sc->epoch[slot]) + 1;
            if (mi == 0 && warp > 0) {
                const int k = warp % 3;
                uint2* go = (uint2*)(sc->go + 8 * k) + lane;
                if (warp < 4 && lane < 16) st_relaxed2(go, 0, 0);
                while (ld_relaxed(k ? sc->go : sc->hint_k) != ep) __nanosleep(200);
                __nanosleep(warp * 60);
                const uint4* hint = (k ? sc->hint_u : sc->hint_h) + (k == 2 ? 48 + min(lane, 19) : lane) * 2;
                uint2 v[4];
                do {
                    #pragma unroll
                    for (int i = 0; i < 4; i++) v[i] = ld_relaxed2(hint + (k == 0 ? 64 * i : k == 2 ? 40 * i : 32 * (i & 1)));
                } while (!__all_sync(0xffffffffu, v[0].x == ep && v[1].x == ep && v[2].x == ep && v[3].x == ep));
                uint32_t t = later(later(v[0].y, v[1].y), later(v[2].y, v[3].y));
                t = later(t, __shfl_xor_sync(0xffffffffu, t, 1));
                if (k == 1) { t = later(t, __shfl_xor_sync(0xffffffffu, t, 8)); t = later(t, __shfl_xor_sync(0xffffffffu, t, 16)); }
                if (k == 0) {
                    const uint32_t now = gtime32() + 256;
                    t = later(t, now - __reduce_min_sync(0xffffffffu, now - t) - SLACK);
                }
                t = __shfl_sync(0xffffffffu, t, 2 * lane);
                if (lane < 16) st_relaxed2(go, ep, t);
            }
            if (mi == 1 && warp >= 4 && ld_volatile(&sc->clean) != ep) {
                for (int l = (tid - 128) / 2; l < sizeof(Tiles) / 128; l += 64) st_relaxed4((uint4*)&sc->tiles[ep & 1] + l * 8 + (lane & 7), EMPTY, EMPTY, EMPTY, EMPTY);
                named_sync(1, 128);
                if (tid == 128) st_release(&sc->clean, ep);
            }
            if (tid == 0) {
                const long long t0 = clock64();
                while (clock64() - t0 < SP_AT) {}
                #pragma unroll 1
                for (int i = 0; i < 7; i++) bulk_prefetch((const char*)wo + (i * 4 + mi) * 14336, 14336);
                uint32_t t = (uint32_t)t0 + PF0_AT;
                #pragma unroll 1
                for (int i = 0; i < PF0_N; i++) {
                    while ((int)(clock32() - t) < 0) {}
                    bulk_prefetch((const char*)w1 + i * 114688 + mi * 14336, 14336);
                    t += PF0_PACE;
                }
                if (mi) {
                    t = (uint32_t)t0 + PF1_AT;
                    #pragma unroll 1
                    for (int i = mi - 1; i < PF1_N; i += 3) {
                        while ((int)(clock32() - t) < 0) {}
                        tma5d_prefetch(&tm_w1, (i & 7) * 64, (i + 48) & 56, (i + 48) >> 6);
                        t += PF1_PACE;
                    }
                    t = (uint32_t)t0 + PF_AT;
                    #pragma unroll 1
                    for (int i = mi - 1; i < PF_N; i += 3) {
                        while ((int)(clock32() - t) < 0) {}
                        bulk_prefetch((const char*)w2 + (i < 128 ? i * 16384 : (i - 64 >> 1) * 65536 + (i & 1) * 16384), 16384);
                        t += PF_PACE;
                    }
                }
                while (ld_relaxed(sc->hint_u + 254) != ep) { __nanosleep(500); if (clock64() - t0 > WD_CLKS) __trap(); }
                sc->epoch[slot] = ep;
                if (mi == 1) sc->clean = ep + 1;
            }
            return;
        }
        {
            const int w = warp & 3, wg = warp >> 2, g = lane >> 2, t = lane & 3;
            if (WARM_AT) { const uint32_t t0 = clock32(); while (clock32() - t0 < WARM_AT) {} __syncwarp(); }
            if (w > 0) post_hint(sc->hint_o + ((2 * tb + (w >> 1)) * 32 + hp * 4 + (w & 1) * 2 + wg) * 2, 0, lane);
            if (wg == 0) {
                if (t < 2) st_relaxed4(sc->stats + tt2 * 256 + q * 64 + 16 * w + g + 8 * t, 0, 0, 0, 0);
            }
        }
        named_sync(0, 288);
        asm volatile("setmaxnreg.inc.sync.aligned.u32 224;");
        int tid; asm volatile("mov.u32 %0, %%tid.x;" : "=r"(tid));
        const int lane = tid & 31, warp = __shfl_sync(0xffffffffu, tid >> 5, 0), wg = warp >> 2;
        uint32_t ep;
        Tiles* tl;
        const int w = warp & 3, g = lane >> 2, t = lane & 3;
        const bool leader = (tid & 127) == 0;
        const uint32_t never = gridDim.y - 1;
        {
            uint32_t a[28][4];
            float accK[28], accV[28], accQ[28];
            const int lrow = 16 * w + (lane & 7) + (lane & 8);
            const uint32_t lbase = sb + wg * 8192 + lrow * 128;
            const uint32_t lx = (lane >> 4) ^ (lane & 7);
            const uint32_t wofs = hp & 1;
            auto pin2 = [&](uint32_t x0, uint32_t x1) {
                asm volatile("{\n.reg .pred p;\nsetp.ne.u32 p, %2, 0;\n@p st.shared.v2.b32 [%0], {%0,%1};\n}" :: "r"(x0), "r"(x1), "r"(never) : "memory");
            };
            float cS[2][4] = {}, cA[2][4] = {}, cB[2][4] = {}, q0, q1, p0, p1;
            auto sq = [&](float& acc, uint32_t v) { const float lo = bf_lo(v), hi = bf_hi(v); acc = fmaf(hi, hi, fmaf(lo, lo, acc)); };
            uint32_t ready = 0;
            #pragma unroll
            for (int kb = 0; kb < 8; kb++) {
                if (kb < 7) {
                    mbar_wait_unless(ready, bars + 8 * (B_FULLX + kb));
                    if (kb == 0 && tid == 0) STAMP(0);
                    if (kb == 6 && tid == 0) STAMP(25);
                    if (kb == 0) FST(0); if (kb == 2) FST(1); if (kb == 4) FST(2); if (kb == 6) FST(3);
                    #pragma unroll
                    for (int s = 4 * kb; s < 4 * kb + 4; s++) ldsm4(a[s], lbase + slot_x(kb) + ((lx ^ (2 * (s & 3))) << 4));
                }
                if (kb > 0 && kb < 6) ready = mbar_test(bars + 8 * (B_FULLX + kb + 1), 0);
                if (kb == 5) named_sync(9 + wg, 160);
                if (kb == NPIPE) continue;
                const int kc = kb < NPIPE ? kb : kb - 1;
                if (kc == NSQ) { p0 = cS[0][0] + cS[1][0]; p1 = cS[0][2] + cS[1][2]; }
                #pragma unroll
                for (int s = 4 * kc; s < 4 * kc + 4; s++) {
                    mma16816(cS[s & 1], a[s][0], a[s][1], a[s][2], a[s][3], 0x3F803F80u, 0x3F803F80u);
                    if (kc < NSQ) {
                        mma1688(cA[0], a[s][0], a[s][1], a[s][0]); mma1688(cA[1], a[s][2], a[s][3], a[s][2]);
                        mma1688(cB[0], a[s][0], a[s][1], a[s][1]); mma1688(cB[1], a[s][2], a[s][3], a[s][3]);
                    }
                }
            }
            const float m0 = (cS[0][0] + cS[1][0]) * (1.f / D_), m1 = (cS[0][2] + cS[1][2]) * (1.f / D_);
            const uint32_t mm0 = pack_bf16(m0, m0), mm1 = pack_bf16(m1, m1);
            if (lane == 0) mbar_arrive(bars + 8 * B_DONEX);
            auto center = [&](int s) { sub_bf16x2(a[s][0], mm0); sub_bf16x2(a[s][1], mm1); sub_bf16x2(a[s][2], mm0); sub_bf16x2(a[s][3], mm1); };
            uint32_t Ka[8], Kb[8], Kc[8], Va[8], Vb[7], Vc[8];
            float r0, r1, ls0, ls1;
            uint32_t pm, zero;
            uint32_t* od;
            uint4* oh;
            auto kpack = [&](uint32_t (&k)[8], int j, int c, float r) {
                const uint32_t v = pack_bf16(accK[4 * j + c] * r, accK[4 * j + c + 1] * r);
                if (j == 3) { k[3] = t < 2 ? v : 0u; k[4] = t < 2 ? 0u : v; } else k[j + (j > 3)] = v;
            };
            auto batch = [&](auto c0, auto c1) {
                constexpr int n0 = c0.value, n1 = c1.value;
                wg_fence();
                static_for<n0, n1>([&](auto nc) {
                    constexpr int n = nc.value;
                    if (n == 4) { center(4); center(5); center(6); center(7); wg_fence(); }
                    const uint64_t desc = mkdesc(sb + (n < 56 ? slot_kv(n >> 3) + (n & 7) * 2048 : SM_QO + (n - 56) * 2048), 8192, 1024, 1) + wofs;
                    wgmma_rs56<1>(n < 28 ? accK : n < 56 ? accV : accQ, a[n % 28], desc, n % 28 != 0);
                });
                wg_commit();
                if (n0 > 0) wg_wait<1>();
            };
            const uint32_t hs = sb + tid * 16 + warp * 512;
            auto hand_over = [&](const uint32_t (&v)[8], int kv) {
                mbar_wait(bars + 8 * (kv ? B_DONE1 + 5 : B_DONEX), 0);
                sts4(hs + (kv ? SM_HALOV : SM_HALOK), v[0], v[1], v[2], v[3]); sts4(hs + (kv ? SM_HALOV : SM_HALOK) + 512, v[4], v[5], v[6], v[7]);
                if (w == 3) named_arrive(6 + kv, 96);
            };
            auto take_over = [&](uint32_t (&v)[8], int kv) {
                if (w == 0) mbar_wait(bars + 8 * (B_HALO + 2 * kv + wg), 0);
                const uint32_t ad = w ? hs + (kv ? SM_HALOV : SM_HALOK) - 1024 : kv ? sb + lane * 16 + wg * 1024 + SM_HALOV + 8192 : halo_kin(wg, lane);
                const uint4 u0 = lds4(ad), u1 = lds4(ad + (w || kv ? 512 : 16));
                v[0] = u0.x; v[1] = u0.y; v[2] = u0.z; v[3] = u0.w; v[4] = u1.x; v[5] = u1.y; v[6] = u1.z; v[7] = u1.w;
            };
            center(0); center(1); center(2); center(3);
            static_for<0, 7>([&](auto pc) {
                constexpr int p = pc.value;
                mbar_wait(bars + 8 * (B_FULLKV + p), 0);
                if (p == 0 && tid == 0) STAMP(26);
                if (p == 3 && tid == 0) STAMP(27);
                FST(4 + p);
                batch(Int<8 * p>(), Int<8 * p + 8>());
                if (p > 0 && leader) mbar_arrive(bars + 8 * (B_DONE1 + p - 1));
                #pragma unroll
                for (int s = 8 * p + 8; s < 8 * p + 16 && s < 28; s++) center(s);
                if (p == 1) {
                    const float c0 = bf_hi(mm0), c1 = bf_hi(mm1);
                    q0 = fmaf(c0, fmaf(c0, 64.f * NSQ, -2.f * p0), (g & 1) ? cA[0][1] + cA[1][1] : cA[0][0] + cA[1][0]) - D_ * (m0 - c0) * (m0 - c0);
                    q1 = fmaf(c1, fmaf(c1, 64.f * NSQ, -2.f * p1), (g & 1) ? cB[0][3] + cB[1][3] : cB[0][2] + cB[1][2]) - D_ * (m1 - c1) * (m1 - c1);
                    asm("" : "+f"(q0), "+f"(q1));
                    q0 = t == (g >> 1) ? q0 : 0.f; q1 = t == (g >> 1) ? q1 : 0.f;
                    pin2(__float_as_uint(q0), __float_as_uint(q1));
                }
                constexpr int PK = NSQ < 5 ? 5 : 4, NR = 28 - 4 * NSQ;
                if (p >= 2 && p < PK) {
                    #pragma unroll
                    for (int s = 4 * NSQ + NR * (p - 2) / (PK - 2); s < 4 * NSQ + NR * (p - 1) / (PK - 2); s++) { sq(q0, a[s][0]); sq(q1, a[s][1]); sq(q0, a[s][2]); sq(q1, a[s][3]); }
                    pin2(__float_as_uint(q0), __float_as_uint(q1));
                }
                if (p == PK - 1) { q0 = quad_sum(q0); q1 = quad_sum(q1); }
                if (p == PK) {
                    r0 = rsqrt_approx(fmaxf(q0 * (1.f / D_), 0.f) + LN_EPS); r1 = rsqrt_approx(fmaxf(q1 * (1.f / D_), 0.f) + LN_EPS);
                    reg_fence(accK);
                    #pragma unroll
                    for (int j = 0; j < 7; j++) kpack(Kc, j, 2, r1);
                    hand_over(Kc, 0);
                }
                if (p == PK + 1) {
                    #pragma unroll
                    for (int j = 0; j < 7; j++) kpack(Kb, j, 0, r0);
                    #pragma unroll
                    for (int j = 0; j < 8; j += 2) pin2(Kb[j], Kb[j + 1]);
                    ls0 = LOG2E_SCALE * r0; ls1 = LOG2E_SCALE * r1;
                    pm = (2 * t <= g ? 0xFFFFu : 0u) | (2 * t + 1 <= g ? 0xFFFF0000u : 0u);
                    zero = never; asm volatile("" : "+r"(zero));
                    pin2(__float_as_uint(ls0), __float_as_uint(ls1)); pin2(pm, zero);
                }
                if (p == 2) ep = get_tag();
                if (p == 6) {
                    tl = &sc->tiles[ep & 1];
                    const int tt = 2 * tb + (w >> 1);
                    od = tl->o + tt * 14336 + (7 * hp) * 256 + (2 * (2 * (w & 1) + wg)) * 32 + lane;
                    oh = sc->hint_o + (tt * 32 + hp * 4 + (w & 1) * 2 + wg) * 2 + (lane & 1);
                    pin2((uint32_t)(uint64_t)od, (uint32_t)((uint64_t)od >> 32));
                    pin2((uint32_t)(uint64_t)oh, (uint32_t)((uint64_t)oh >> 32));
                }
            });
            if (tid == 0) STAMP(1);
            FST(11);
            mbar_wait(bars + 8 * B_FQ, 0);
            batch(Int<56>(), Int<60>());
            reg_fence(accV);
            if (leader) mbar_arrive(bars + 8 * (B_DONE1 + 6));
            if (tid == 0) STAMP(2);
            FST(12);
            #pragma unroll
            for (int j = 0; j < 7; j++) Vc[j] = movtrans(pack_bf16(accV[4 * j + 2] * r1, accV[4 * j + 3] * r1));
            Vc[7] = Vc[6];
            hand_over(Vc, 1);
            batch(Int<60>(), Int<66>());
            #pragma unroll
            for (int j = 0; j < 7; j++) {
                Vb[j] = movtrans(pack_bf16(accV[4 * j] * r0, accV[4 * j + 1] * r0));
                Vc[j] |= zero;
            }
            batch(Int<66>(), Int<72>());
            #pragma unroll
            for (int j = 0; j < 7; j++) pin2(Vb[j], Vc[j]);
            mbar_wait(bars + 8 * (B_FQ + 1), 0);
            FST(13);
            if (w > 0 && lane < 2) { const uint32_t now = gtime32(); st_relaxed4(oh, ep, now, ep, now); }
            batch(Int<72>(), Int<84>());
            FST(14);
            named_sync(1 + wg, 128);
            take_over(Ka, 0);
            if (tid == 0) STAMP(3);
            wg_wait<0>();
            reg_fence(accQ);
            if (tid == 0) STAMP(4);
            FST(15);
            const bool first = (tb == 0 && w == 0);
            uint32_t pA[2], pB0[2], pB1[2], pC[2], z0[2], z1[2];
            float sA[2][4] = {}, sB[2][4] = {}, sC[2][4] = {}, e[2][4], inv[2][2];
            #pragma unroll
            for (int k = 0; k < 2; k++) {
                #pragma unroll
                for (int h = 0; h < 2; h++) {
                    const float* qq = accQ + 12 * h + 8 * k;
                    uint32_t a2 = pack_bf16(qq[4], qq[5]), a3 = pack_bf16(qq[6], qq[7]);
                    if (h == 0 && k == 1) { a2 |= zero; a3 |= zero; }
                    const uint32_t a0 = pack_bf16(qq[0], qq[1]), a1 = pack_bf16(qq[2], qq[3]);
                    mma16816(sB[h], a0, a1, a2, a3, Kb[4 * h + 2 * k], Kb[4 * h + 2 * k + 1]);
                    mma16816(sA[h], a0, a1, a2, a3, Ka[4 * h + 2 * k], Ka[4 * h + 2 * k + 1]);
                    mma16816(sC[h], a0, a1, a2, a3, Kc[4 * h + 2 * k], Kc[4 * h + 2 * k + 1]);
                }
            }
            if (VTAKE == 0) take_over(Va, 1);
            #pragma unroll
            for (int h = 0; h < 2; h++) {
                const bool n0 = pm & 1, n1 = (int)pm < 0;
                const float l00 = n0 ? sB[h][0] : (first ? -INFINITY : sA[h][0]), l01 = n1 ? sB[h][1] : (first ? -INFINITY : sA[h][1]);
                const float l10 = n0 ? sC[h][2] : sB[h][2], l11 = n1 ? sC[h][3] : sB[h][3];
                const float x0 = -ls0 * quad_max(fmaxf(l00, l01)), x1 = -ls1 * quad_max(fmaxf(l10, l11));
                e[h][0] = ex2(fmaf(l00, ls0, x0)); e[h][1] = ex2(fmaf(l01, ls0, x0)); e[h][2] = ex2(fmaf(l10, ls1, x1)); e[h][3] = ex2(fmaf(l11, ls1, x1));
            }
            if (VTAKE == 1) { pin4(never, e[0][0], e[0][2], e[1][0], e[1][2]); take_over(Va, 1); }
            #pragma unroll
            for (int h = 0; h < 2; h++) {
                inv[h][0] = rcp_approx(quad_sum(e[h][0] + e[h][1])); inv[h][1] = rcp_approx(quad_sum(e[h][2] + e[h][3]));
                const uint32_t P0 = DEFER ? pack_bf16(e[h][0], e[h][1]) : pack_bf16(e[h][0] * inv[h][0], e[h][1] * inv[h][0]);
                const uint32_t P1 = DEFER ? pack_bf16(e[h][2], e[h][3]) : pack_bf16(e[h][2] * inv[h][1], e[h][3] * inv[h][1]);
                pB0[h] = P0 & pm; pA[h] = P0 & ~pm; pC[h] = P1 & pm; pB1[h] = P1 & ~pm; z0[h] = P0 & zero; z1[h] = P1 & zero;
            }
            float o[8][4];
            #pragma unroll
            for (int j = 0; j < 8; j++) {
                o[j][0] = o[j][1] = o[j][2] = o[j][3] = 0.f;
                mma16816(o[j], pB0[j >> 2], pB1[j >> 2], z0[j >> 2], pC[j >> 2], Vb[j - (j >> 2)], Vc[j - (j >> 2)]);
            }
            if (tid == 0) STAMP(12);
            FST(16);
            if (VTAKE == 2) take_over(Va, 1);
            if (tid == 0) STAMP(16);
            #pragma unroll
            for (int j = 0; j < 8; j++) mma1688(o[j], pA[j >> 2], z1[j >> 2], Va[j - (j >> 2)]);
            #pragma unroll
            for (int j = 0; j < 7; j++) {
                float v[4];
                #pragma unroll
                for (int c = 0; c < 4; c++) {
                    v[c] = j < 3 ? o[j][c] : j > 3 ? o[j + 1][c] : (t < 2 ? o[3][c] : o[4][c]);
                    if (DEFER) v[c] *= j < 3 ? inv[0][c >> 1] : j > 3 ? inv[1][c >> 1] : (t < 2 ? inv[0][c >> 1] : inv[1][c >> 1]);
                }
                od[j * 256] = pack_bf16(v[0], v[1]);
                od[j * 256 + 32] = pack_bf16(v[2], v[3]);
            }
            if (lane == 0) mbar_arrive(bars + 8 * B_DONEQ);
            if (tid == 0) STAMP(5);
            FST(17);
        }
        const int z = get_tag() - ep, slot1 = slot + z, tid1 = tid + z, warp1 = warp + z;
        ep += z;
        {
        ASSIGN_WORK(slot1)
        const int tid = tid1, lane = tid & 31, wg = warp1 >> 2, w = warp1 & 3, g = lane >> 2, t = lane & 3;
        tl = &sc->tiles[ep & 1];
        const uint32_t live = wg ^ 1;
        uint32_t rb0, rb1, late[14];
        const unsigned short* pb = (const unsigned short*)(live ? b2 + tt2 * 64 : b1 + ft * 64) + 16 * w + g;
        auto stage_late = [&]() {
            #pragma unroll
            for (int c = 0; c < 14; c++) asm volatile("st.shared.u32 [%0], %1;" :: "r"(sb + SM_H + wg * 8192 + (tid & 127) * 4 + c * 512), "r"(late[c]) : "memory");
            fence_async_smem();
            named_sync(1 + wg, 128);
        };
        auto store_late = [&](bool on, uint32_t* p) {
            #pragma unroll
            for (int c = 0; c < 4; c++)
                if (elect() && on && (c < 3 || w < 2)) bulk_st(p + (4 * c + w) * 256, sb + SM_H + wg * 8192 + (4 * c + w) * 512, 512);
            asm volatile("cp.async.bulk.commit_group;" ::: "memory");
        };
        auto undef = [](float (&v)[56]) {
            #pragma unroll
            for (int i = 0; i < 56; i++) asm volatile("" : "=f"(v[i]));
        };
        {
            float acc[56];
            const int hrow = 32 * (w >> 1) + 2 * ((lane & 7) + (lane & 8)) + (w & 1);
            const uint32_t ha = sb + SM_H + hrow * 128 + (((lane >> 4) ^ (hrow & 7)) << 4);
            uint4* sp = sc->stats + tt2 * 256 + 16 * w + g + 8 * (t & 1);
            uint4* sp_out = sp + q * 64;
            const uint4* sp_in = sp + (t & 2) * 64;
            uint32_t* hd = tl->hn + ((q >> 1) * 32 + (tt2 >> 1)) * 7168 + (q & 1) * 3584 + (tt2 & 1) * 128 + w * 32 + lane;
            pin_ptr(never, sp_out); pin_ptr(never, sp_in); pin_ptr(never, hd);
            float s0 = 0.f, s1 = 0.f, q0 = 0.f, q1 = 0.f, s2 = 0.f, s3 = 0.f, q2 = 0.f, q3 = 0.f;
            auto sums = [&](int j0, int j1) {
                #pragma unroll
                for (int j = j0; j < j1; j++) {
                    s0 += acc[4 * j]; s2 += acc[4 * j + 1]; q0 = fmaf(acc[4 * j], acc[4 * j], q0); q2 = fmaf(acc[4 * j + 1], acc[4 * j + 1], q2);
                    s1 += acc[4 * j + 2]; s3 += acc[4 * j + 3]; q1 = fmaf(acc[4 * j + 2], acc[4 * j + 2], q1); q3 = fmaf(acc[4 * j + 3], acc[4 * j + 3], q3);
                }
            };
            if (live) {
                mbar_wait(bars + 8 * B_FULLWO, 0);
                #pragma unroll
                for (int jp = 0; jp < 7; jp++) {
                    uint32_t xx[4];
                    ldsm4(xx, hcol(ha, jp));
                    #pragma unroll
                    for (int r = 0; r < 4; r++) { acc[8 * jp + 2 * r] = bf_lo(xx[r]); acc[8 * jp + 2 * r + 1] = bf_hi(xx[r]); }
                }
                reg_fence(acc);
                if (SPIN2) { named_sync(12, 256); spin_mma(bars + 8 * B_FULLX, never); }
                auto od_ = [&](int s) { return mkdesc(sb + SM_QO + s * 2048, 1024, 128, 0); };
                auto wd_ = [&](int s) { return mkdesc(sb + slot_wo(s >> 2) + (s & 3) * 2048, 8192, 1024, 1); };
                float accl[32], accr[24];
                #pragma unroll
                for (int i = 0; i < 5; i++) {
                    if (i < 4) mbar_wait(bars + 8 * (B_FULLO + i), 0);
                    if (i == 0 && tid == 0) STAMP(7);
                    if (i == 1) { rb0 = ld_u16(pb); rb1 = ld_u16(pb + 8); }
                    wg_fence();
                    #pragma unroll
                    for (int ss = 0; ss < 7; ss++) {
                        if (i < 3) wgmma_ss112<0, 1>(acc, od_(7 * i + ss), wd_(7 * i + ss));
                        else if (i == 4) wgmma_ss64<0, 1>(accl, od_(21 + ss), wd_(21 + ss));
                        else if (ss == 0) wgmma_ss48<0, 1, 0>(accr, od_(21), wd_(21) + 512);
                        else wgmma_ss48<0, 1>(accr, od_(21 + ss), wd_(21 + ss) + 512);
                    }
                    wg_commit();
                    if (i > 0) {
                        wg_wait<1>();
                        if (i == 3) {
                            reg_fence(acc);
                            #pragma unroll
                            for (int c = 0; c < 32; c++) accl[c] = __uint_as_float(__float_as_uint(acc[c]) | never);
                            reg_fence(accl);
                        }
                        if (i < 4 && leader) mbar_arrive(bars + 8 * (B_DONEO + i - 1));
                    }
                }
                reg_fence(accr);
                #pragma unroll
                for (int c = 0; c < 24; c++) acc[32 + c] += accr[c];
                sums(8, 14);
                pin4(never, s0, s1, s2, s3); pin4(never, q0, q1, q2, q3);
                wg_wait<0>();
                reg_fence(accl);
                #pragma unroll
                for (int c = 0; c < 32; c++) acc[c] = accl[c];
                if (leader) mbar_arrive(bars + 8 * (B_DONEO + 3));
                if (tid == 0) STAMP(8);
            } else { undef(acc); if (SPIN2) named_arrive(12, 256); }
            if (live || (DRY2 && w == 3)) {
            sums(0, 8);
            s0 += s2; s1 += s3; q0 += q2; q1 += q3;
            float sr = ((t & 1) ? s1 : s0) + __shfl_xor_sync(0xffffffffu, (t & 1) ? s0 : s1, 1), qr = ((t & 1) ? q1 : q0) + __shfl_xor_sync(0xffffffffu, (t & 1) ? q0 : q1, 1);
            sr += __shfl_xor_sync(0xffffffffu, sr, 2); qr += __shfl_xor_sync(0xffffffffu, qr, 2);
            st_relaxed4_if(t < 2 * live, sp_out, __float_as_uint(sr), __float_as_uint(qr), ep);
            const uint32_t tp = clock32();
            if (live) named_arrive(5, 256);
            if (tid == 0) STAMP(9);
            #pragma unroll
            for (int jp = 0; jp < 7; jp++)
                stsm4_if(live, hcol(ha, jp), pack_bf16(acc[8 * jp], acc[8 * jp + 1]), pack_bf16(acc[8 * jp + 2], acc[8 * jp + 3]),
                      pack_bf16(acc[8 * jp + 4], acc[8 * jp + 5]), pack_bf16(acc[8 * jp + 6], acc[8 * jp + 7]));
            uint4 v0, v1;
            if (POLL0) { while (clock32() - tp < POLL0) {} __syncwarp(); }
            do { v0 = ld_relaxed4(sp_in); v1 = ld_relaxed4(sp_in + 64); } while (live && __any_sync(0xffffffffu, v0.w != ep || v1.w != ep));
            if (tid == 0) STAMP(10);
            sr = __uint_as_float(v0.x) + __uint_as_float(v1.x); qr = __uint_as_float(v0.y) + __uint_as_float(v1.y);
            sr += __shfl_xor_sync(0xffffffffu, sr, 2); qr += __shfl_xor_sync(0xffffffffu, qr, 2);
            const float m = sr * (1.f / D_), var = fmaxf(qr * (1.f / D_) - m * m, 0.f);
            const float r = rsqrt_approx(fmaf(var, 4.f + 4.f * LN_EPS, 4.f * LN_EPS * LN_EPS)), c = -m * r;
            const float r0 = __shfl_sync(0xffffffffu, r, lane & ~1), c0 = __shfl_sync(0xffffffffu, c, lane & ~1);
            const float r1 = __shfl_sync(0xffffffffu, r, lane | 1), c1 = __shfl_sync(0xffffffffu, c, lane | 1);
            #pragma unroll
            for (int j = 0; j < 14; j++) st_global_if(live, hd + j * 256, pack_bf16(fmaf(acc[4 * j], r0, c0), fmaf(acc[4 * j + 1], r0, c0)));
            if (never) mbar_arrive(bars);
            if (SPIN3) named_arrive_if(live, 3, 256);
            #pragma unroll
            for (int j = 0; j < 14; j++) late[j] = pack_bf16(fmaf(acc[4 * j + 2], r1, c1), fmaf(acc[4 * j + 3], r1, c1));
            if (tid == 0) STAMP(11);
            }
        }
        if (!live) {
            if (w < 2) check_tiles<0>(w, 2, 4, tl->o + tt2 * 14336, false, lane, true);
            rb0 = ld_u16(pb); rb1 = ld_u16(pb + 8);
            auto reset_tiles = [&](int v, int i0, int i1) {
                const int l = slot * 48 + v * 16 + lane / 2;
                #pragma unroll
                for (int i = i0; i < i1; i++)
                    st_relaxed4_if(i < 6 || l < sizeof(Tiles) / 128 - 6 * 6144, (uint4*)&sc->tiles[~ep & 1] + (i * 6144 + l) * 8 + (lane & 7), EMPTY, EMPTY, EMPTY);
            };
            if (CL_N && w < 3) { mbar_wait(bars + 8 * (B_DONEO + CL_P2), 0); reset_tiles(w, 0, CL_N); }
            named_sync(5, 256);
            auto phase3 = [&](auto nc) {
                constexpr int NC = nc.value;
                float acc[4 * NC];
                uint32_t* ud = tl->u + (pr3 * 28 + (ft >> 1) + (NC == 14 ? 4 : 0)) * 7168 + col3 * 256 + (ft & 1) * 128 + w * 32 + lane;
                #pragma unroll
                for (int j = 0; j < 4 * NC; j++) acc[j] = 0.5f * bf_lo((j & 2) ? rb1 : rb0);
                #pragma unroll 1
                for (uint32_t pass = never; pass < 2; pass++) {
                    if (pass) {
                        if (SPIN3) { named_sync(3, 256); spin_mma(bars + 8 * (B_FULLX + 1), never); }
                        mix_mainloop<32>(TSVAL acc, leader);
                        if (leader) STAMP(14);
                    }
                    uint32_t pk[NC];
                    #pragma unroll
                    for (int j = 0; j < NC; j++) {
                        const float k = j < GDEP ? GELU_K1 : __uint_as_float(__float_as_uint(GELU_K1) | (pk[j - GDEP] & never));
                        pk[j] = pack_bf16(gelu_half(acc[4 * j], k), gelu_half(acc[4 * j + 1], k));
                        st_global_if(pass, ud + j * 256, pk[j]);
                    }
                }
                if (leader) STAMP(15);
                #pragma unroll
                for (int j = 0; j < NC; j++) late[j] = pack_bf16(gelu_half(acc[4 * j + 2], GELU_K1), gelu_half(acc[4 * j + 3], GELU_K1));
                if (NC == 14) {
                    stage_late();
                    mbar_wait(bars + 8 * (B_FULLB + LATE_AT4), 1);
                    store_late(true, tl->u + (pr3 * 28 + (ft >> 1) + 14) * 7168 + col3 * 256 + (ft & 1) * 128);
                } else {
                    #pragma unroll
                    for (int c = 0; c < NC; c++) st_global_if(1, ud + 4 * 7168 + c * 256, late[c]);
                    if (SPIN4) named_arrive(13, 256);
                }
            };
            if (early) phase3(Int<10>()); else phase3(Int<14>());
            if (w) {
                if (early && w == 1) fetch_times(TSVAL sc->go, 1, ep, lane);
                check_tiles<2>(CH_U - 1 + w, 3, 28, tl->u + (q >> 1) * 28 * 7168 + (q & 1) * 3584, false, lane, false);
                if (CL_N < 7) { mbar_wait(bars + 8 * (B_DONE + CL_AT), 1); reset_tiles(w - 1, CL_N, 7); }
            }
            if (leader) mbar_wait_wd(bars + 8 * B_END, 0);
            return;
        }
        {
            float acc[56];
            const uint32_t ad = sb + SM_H + (16 * w + (lane & 15)) * 128 + (((lane >> 4) ^ (lane & 7)) << 4);
            const float bb0 = bf_lo(rb0), bb1 = bf_lo(rb1);
            named_sync(1, 128);
            #pragma unroll
            for (int jp = 0; jp < 7; jp++) {
                uint32_t hh[4];
                ldsm4(hh, hcol(ad, jp));
                #pragma unroll
                for (int r = 0; r < 4; r++) { acc[8 * jp + 2 * r] = bf_lo(hh[r]) + ((r & 1) ? bb1 : bb0); acc[8 * jp + 2 * r + 1] = bf_hi(hh[r]) + ((r & 1) ? bb1 : bb0); }
            }
            #pragma unroll 1
            for (uint32_t pass = never; pass < 2; pass++) {
                if (pass) {
                    named_sync(1, 128);
                    stage_late();
                    if (tid == 0) STAMP(39);
                    mbar_wait(bars + 8 * (B_FULLB + LATE_AT), 0);
                    store_late(true, tl->hn + ((q >> 1) * 32 + 16 + (tt2 >> 1)) * 7168 + (q & 1) * 3584 + (tt2 & 1) * 128);
                    check_tiles<1>(CH_H + w, 4, 32, tl->hn + pr3 * 32 * 7168 + col3 * 256, early, lane, false);
                    mbar_wait(bars + 8 * (B_DONE + START4), 0);
                    if (SPIN4 && early) { named_sync(13, 256); spin_mma(bars + 8 * (B_FULLX + 2), never); }
                    mix_mainloop<28>(TSVAL acc, leader);
                    if (leader) mbar_arrive(bars + 8 * B_END);
                    if (tid == 0) STAMP(18);
                }
                #pragma unroll
                for (int jp = 0; jp < 7; jp++)
                    stsm4_if(1, hcol(ad, jp), pack_bf16(acc[8 * jp], acc[8 * jp + 1]), pack_bf16(acc[8 * jp + 2], acc[8 * jp + 3]),
                             pack_bf16(acc[8 * jp + 4], acc[8 * jp + 5]), pack_bf16(acc[8 * jp + 6], acc[8 * jp + 7]));
                fence_async_smem();
                __syncwarp();
            }
            if (elect()) {
                tma2d_store(&tm_out64, c64, tt2 * 64 + 16 * w, sb + SM_H + w * 2048);
                tma2d_store(&tm_out48, c48, tt2 * 64 + 16 * w, sb + SM_H + 8192 + w * 2048);
            }
            asm volatile("cp.async.bulk.commit_group;" ::: "memory");
            asm volatile("cp.async.bulk.wait_group.read 0;" ::: "memory");
            if (tid == 0) { sc->epoch[slot] = ep; STAMP(19); }
        }
        }
    } else {
        asm volatile("setmaxnreg.dec.sync.aligned.u32 56;");
        int warp2; asm("mov.u32 %0, %1;" : "=r"(warp2) : "r"(warp));
        if (warp2 > 8) {
            ASSIGN_WORK(get_slot())
            if (slot >= 128) return;
            uint32_t ep, cl;
            uint4* const oh = sc->hint_o + (2 * tb * 32 + hp * 4) * 2 + (lane & 3);
            uint4* const hu = sc->hint_u + (early ? ech * 8 + ft : 40 + q * 20 + ft) * 2;
            if (warp == 10) {
                post_hint(sc->hint_h + (q * 32 + tt2) * 2, 0, lane);
                post_hint(hu, 0, lane);
            }
            if (warp == 11) {
                ep = ld_volatile(&sc->epoch[slot]) + 1; cl = ld_acquire(&sc->clean);
                post_hint(sc->hint_k + (tb * 8 + hp) * 2, 0, lane);
                if (lane < (tb < 15 ? 4 : 0)) st_relaxed4(oh + 128, 0, 0, 0, 0);
                if (lane < (tb ? 0 : 4)) st_relaxed4(oh, 0, 0, 0, 0);
            }
            if (elect()) {
                if (warp == 9) {
                    #pragma unroll
                    for (int i = B_DONE1; i < B_DONEO; i++) mbar_init(bars + 8 * i, i < B_DONEX ? 2 : i == B_DONEX ? 8 : 9);
                }
                #pragma unroll
                for (int i = 0; i < 54; i++) mbar_init(bars + 8 * (B_DONEO + i) + (warp - 9) * 432, 1);
                asm volatile("fence.mbarrier_init.release.cluster;" ::: "memory");
            }
            named_sync(8, 128);
            if (warp < 11) mbar_expect(sb + SM_RAW + 8 * (tid - 288), early && tid >= 292 && tid < 324 ? 10240 : 14336);
            if (warp == 9) { named_arrive(4, 64); named_arrive(9, 160); named_arrive(10, 160); }
            if (warp < 11) {
                ep = get_tag();
                mbar_wait(bars + 8 * (B_DONE1 + HALO_AT), 0);
                #pragma unroll 1
                for (int kv = 0; kv < 2; kv++) {
                    uint4 v0 = {}, v1 = {}, v2 = {};
                    if (tb > 0) {
                        const uint4* hg = sc->halo + ((((tb - 1) * 8 + hp) * 2 + warp - 9) * 2 + kv) * 96 + lane;
                        if (kv == 0) while (ld_relaxed(sc->hint_k + ((tb - 1) * 8 + hp) * 2) != ep) {}
                        do { v0 = ld_relaxed4(hg); v1 = ld_relaxed4(hg + 32); v2 = ld_relaxed4(hg + 64); } while (!__all_sync(0xffffffffu, v0.w == ep && v1.w == ep && v2.w == ep));
                    }
                    if (kv) mbar_wait(bars + 8 * (B_DONE1 + 5), 0);
                    const uint32_t hs = kv ? sb + lane * 16 + (warp - 9) * 1024 + SM_HALOV + 8192 : halo_kin(warp - 9, lane);
                    sts4(hs, v0.x, v0.y, v0.z, v1.x); sts4(hs + (kv ? 512 : 16), v1.y, v1.z, v2.x, v2.y);
                    __syncwarp();
                    if (lane == 0) mbar_arrive(bars + 8 * (B_HALO + 2 * kv + warp - 9));
                }
                if (tid == 288) STAMP(21);
            } else {
                const long long t0 = clock64();
                while (__any_sync(0xffffffffu, (int)(cl - ep) < 0)) { cl = ld_acquire(&sc->clean); if (clock64() - t0 > WD_CLKS) __trap(); }
                if (lane == 0) { *(volatile uint32_t*)(smem_raw + SM_TAG) = ep; mbar_arrive(bars + 8 * B_CLR); }
                uint4* hg = sc->halo + (tb * 8 + hp) * 384 + lane;
                #pragma unroll 1
                for (int kv = 0; kv < 2; kv++) {
                    const uint32_t hs = sb + lane * 16 + 3072 + (kv ? SM_HALOV : SM_HALOK);
                    named_sync(6 + kv, 96);
                    #pragma unroll
                    for (int p = 0; p < 2; p++) {
                        const uint4 u0 = lds4(hs + p * 4096), u1 = lds4(hs + p * 4096 + 512);
                        st_relaxed4(hg + p * 192, u0.x, u0.y, u0.z, ep); st_relaxed4(hg + p * 192 + 32, u0.w, u1.x, u1.y, ep); st_relaxed4(hg + p * 192 + 64, u1.z, u1.w, ep, ep);
                    }
                    hg += 96;
                    if (kv == 0) {
                        post_hint(sc->hint_k + (tb * 8 + hp) * 2, ep, lane);
                        #pragma unroll
                        for (int j = 0; j < 6; j++) st_relaxed4(hg + j * 32 + (j / 3) * 96, 0, 0, 0, 0);
                    }
                }
                const uint32_t now = gtime32() - LATE_O;
                if (lane < (tb < 15 ? 4 : 0)) st_relaxed4(oh + 128, ep, now, ep, now);
                if (lane < (tb ? 0 : 4)) st_relaxed4(oh, ep, now, ep, now);
                if (lane == 0) STAMP(23);
                if (lane == 0) mbar_arrive(bars + 8 * B_DONEQ);
            }
            if (warp > 9) {
                const Tiles* const tl = &sc->tiles[ep & 1];
                check_tiles<1>(11 - warp, 2, CH_H, tl->hn + pr3 * 32 * 7168 + col3 * 256, early, lane, true);
                if (warp == 10) {
                    mbar_wait(bars + 8 * (B_DONE + (early ? HINT_E : HINT_U)), 0);
                    post_time(hu, ep, lane);
                }
                if (warp == 11) {
                    mbar_wait(bars + 8 * (B_DONE + (early ? POLL_E : POLL_N)), 0);
                    fetch_times(TSVAL sc->go, 0, ep, lane);
                }
                check_tiles<2>(11 - warp, 2, CH_U, tl->u + (q >> 1) * 28 * 7168 + (q & 1) * 3584, false, lane, true);
            } else {
                int aslot = 0;
                if (lane == 0) { prefetch_map(&tm_out64); prefetch_map(&tm_out48); }
                #pragma unroll
                for (int i = 0; i < HINT_F; i++) mbar_wait(bars + 8 * (B_FULLO + i), 0);
                post_time(sc->hint_h + (q * 32 + tt2) * 2, ep, lane);
                #pragma unroll 1
                for (int i = 0; i < 30; i++) {
                    if (i == POLL_I && !early) fetch_times(TSVAL sc->go, 1, ep, lane);
                    int d = 2 * i - 11 + (i >= A4_FROM ? A4_DLY : 0);
                    if (early) d = i < 16 ? 1 + (i - NA_SLOTS) * AE_END / 9 : max(d, AE_W2);
                    mbar_wait(bars + 8 * (i < NA_SLOTS ? B_DONEQ + ((A_SCHED >> (4 * i)) & 15) : B_DONE + (d & 31)), d >= 32);
                    if (elect()) {
                        const uint32_t bar = bars + 8 * (B_FULLA + (i & 15)), dst = sb + SM_ARING + aslot * 16384;
                        mbar_expect(bar, 16384);
                        if (i < 16) tma5d(dst, &tm_w1, ft * 64, (i & 7) * 8, i >> 3, bar);
                        else tma5d(dst, &tm_w2, tt2 * 64, 8 * (i < 20 ? i & 1 : i < 25 ? i - 18 : i - 23), i < 20 ? (i >> 1) & 1 : i >= 25, bar);
                    }
                    aslot = aslot == NA_SLOTS - 1 ? 0 : aslot + 1;
                }
            }
        } else {
            const int slot0 = get_slot(), row0 = (slot0 >> 5) * 256 + (slot0 & 12) * 16;
            if (elect()) {
                prefetch_map(&tm_x);
                #pragma unroll
                for (int i = 0; i < 7; i++) mbar_init(bars + 8 * i, 1);
                asm volatile("fence.mbarrier_init.release.cluster;" ::: "memory");
            }
            named_arrive(0, 288);
            if (elect()) {
                #pragma unroll 1
                for (int kb = 0; kb < 7; kb++) {
                    load_x(kb, row0);
                    if (kb == 0) STAMP(22);
                }
                #pragma unroll
                for (int i = 7; i < B_DONE1; i++) mbar_init(bars + 8 * i, 1);
                asm volatile("fence.mbarrier_init.release.cluster;" ::: "memory");
            }
            named_arrive(8, 128);
            ASSIGN_WORK(get_slot())
            if (slot >= 128) return;
            #pragma unroll 1
            for (int kb = 0; kb < 7; kb++) {
                if (kb == 6) { named_sync(4, 64); mbar_wait(bars + 8 * B_DONEX, 0); }
                if (elect()) {
                    const uint32_t st = sb + slot_kv(kb), bar = bars + 8 * (B_FULLKV + kb);
                    mbar_expect(bar, 16384);
                    #pragma unroll
                    for (int i = 0; i < 2; i++) {
                        const int n = 2 * kb + (i ^ (G & 1));
                        tma2d(st + (n & 1) * 8192, &tm_wqkv, (n < 7 ? 448 : 896) + wcol, (n < 7 ? n : n - 7) * 64, bar);
                    }
                }
            }
            if (elect()) {
                mbar_expect(bars + 8 * B_FQ, 32768);
                mbar_expect(bars + 8 * (B_FQ + 1), 24576);
                #pragma unroll 1
                for (int i = 0; i < 7; i++) { const int j = i == 6 ? i : i ^ (G & 1); tma2d(sb + SM_QO + j * 8192, &tm_wqkv, wcol, j * 64, bars + 8 * (B_FQ + (i >> 2))); }
                mbar_expect(bars + 8 * B_FULLWO, 512 * 112 * 2);
            }
            #pragma unroll 1
            for (int i = 0; i < 7; i++) {
                const int kb = ((q & 1 ? WO_ORD1 : WO_ORD0) >> (4 * i)) & 7;
                if (kb < 5) mbar_wait(bars + 8 * (B_DONE1 + kb), 0);
                if (elect()) {
                    tma2d(sb + slot_wo(kb), &tm_wo64, c64, kb * 64, bars + 8 * B_FULLWO);
                    tma2d(sb + slot_wo(kb) + 8192, &tm_wo48, c48, kb * 64, bars + 8 * B_FULLWO);
                }
            }
            if (elect()) {
                tma2d(sb + SM_H, &tm_xr64, c64, tt2 * 64, bars + 8 * B_FULLWO);
                tma2d(sb + SM_H + 8192, &tm_xr48, c48, tt2 * 64, bars + 8 * B_FULLWO);
            }
            if (smem_u32(smem_raw) != SB) __trap();
            const uint32_t ep = get_tag();
            const Tiles* const tl = &sc->tiles[ep & 1];
            mbar_wait(bars + 8 * (B_DONE1 + 6), 0);
            const uint32_t t_o = last_hint(TSVAL sc->hint_o + (tt2 * 32 + lane) * 2, ep, 38);
            mbar_wait(bars + 8 * B_DONEQ, 0);
            wait_until(t_o + GO_O);
            if (elect()) {
                #pragma unroll
                for (int i = 0; i < 4; i++) {
                    bulk_ld(sb + SM_QO + i * 14336, tl->o + tt2 * 14336 + i * 3584, 14336, sb + SM_RAW + 8 * i);
                }
            }
            if (lane == 0) STAMP(20);
            if (SPIN2) { wait_until(t_o + GO_O + STOP2); if (lane == 0) mbar_arrive(bars + 8 * B_FULLX); }
            mbar_wait(bars + 8 * (B_DONEO + POLL_H), 0);
            const uint32_t* src = tl->hn + pr3 * 32 * 7168 + col3 * 256;
            uint32_t bytes = early ? 10240 : 14336, dst = sb + SM_BRING, top = dst + (early ? NE_SLOTS * 10240 : NB_SLOTS * 14336), raw = sb + SM_RAW + 32;
            auto issue = [&]() {
                if (elect()) bulk_ld(dst, src, bytes, raw);
                src += 7168; raw += 8; dst += bytes;
                if (dst == top) dst = sb + SM_BRING;
            };
            uint2 th;
            do { th = ld_relaxed2((const uint2*)sc->go + (lane & 15)); } while (!__all_sync(0xffffffffu, th.x == ep));
            STAMP(42);
            mbar_wait(bars + 8 * (B_DONEO + 3), 0);
            {
                uint32_t bit = 1, wait = ~1u;
                wait_until(__shfl_sync(0xffffffffu, th.y, 0) + GO_H);
                #pragma unroll 1
                do {
                    while (wait & bit) wait = __ballot_sync(0xffffffffu, (int)(gtime32() - th.y - GO_H) < 0);
                    if (bit == 1) STAMP(29);
                    issue();
                    if (SPIN3 && bit == 1 << STOP3 && lane == 0) mbar_arrive(bars + 8 * (B_FULLX + 1));
                    bit *= 2;
                } while (dst != sb + SM_BRING);
            }
            uint32_t done = bars + 8 * B_DONE;
            #pragma unroll 1
            do { mbar_wait(done, 0); done += 8; issue(); } while (raw != sb + SM_RAW + 288);
            if (early) mbar_wait(bars + 8 * (B_DONE + 31), 0);
            src = tl->u + (q >> 1) * 28 * 7168 + (q & 1) * 3584; bytes = 14336; dst = sb + SM_BRING; top = dst + NB_SLOTS * 14336;
            done = bars + 8 * (B_DONE + 24);
            #pragma unroll 1
            for (uint32_t par = 0; par < 2; par++) {
                mbar_wait(bars + 8 * (B_GO + par), 0);
                const uint32_t ts = *(volatile uint32_t*)(smem_raw + SM_TIME + 128 * par + 4 * lane);
                if (par) done = bars + 8 * B_DONE;
                uint32_t bit = 1, wait = ~1u;
                wait_until(__shfl_sync(0xffffffffu, ts, 0));
                #pragma unroll 1
                do {
                    while (wait & bit) wait = __ballot_sync(0xffffffffu, (int)(gtime32() - ts) < 0);
                    if (bit == 1) STAMP(par ? 36 : 30);
                    mbar_wait(done, par); done += 8;
                    issue();
                    if (SPIN4 && bit == 1 << STOP3 && lane + par == 0) mbar_arrive(bars + 8 * (B_FULLX + 2));
                    bit *= 2;
                } while (bit != (par ? 1 << 20 : 1 << 8));
            }
        }
    }
}

typedef CUresult (*EncodeFn)(CUtensorMap*, CUtensorMapDataType, cuuint32_t, void*, const cuuint64_t*, const cuuint64_t*, const cuuint32_t*,
                             const cuuint32_t*, CUtensorMapInterleave, CUtensorMapSwizzle, CUtensorMapL2promotion, CUtensorMapFloatOOBfill);

void make_map(EncodeFn fn, CUtensorMap* tm, const void* ptr, int rank, const cuuint64_t* dims, const cuuint64_t* strides, const cuuint32_t* box, CUtensorMapSwizzle sw) {
    cuuint32_t es[5] = {1, 1, 1, 1, 1};
    fn(tm, CU_TENSOR_MAP_DATA_TYPE_BFLOAT16, rank, const_cast<void*>(ptr), dims, strides, box, es, CU_TENSOR_MAP_INTERLEAVE_NONE, sw,
       CU_TENSOR_MAP_L2_PROMOTION_NONE, CU_TENSOR_MAP_FLOAT_OOB_FILL_NONE);
}

}

extern "C" void kernel_launch(void* const* d_in, const int* in_sizes, int n_in, void* d_out, int out_size) {
    const __nv_bfloat16* x = (const __nv_bfloat16*)d_in[0];
    const __nv_bfloat16* wqkv = (const __nv_bfloat16*)d_in[1];
    const __nv_bfloat16* wo = (const __nv_bfloat16*)d_in[2];
    const __nv_bfloat16* w1 = (const __nv_bfloat16*)d_in[4];
    const __nv_bfloat16* b1 = (const __nv_bfloat16*)d_in[5];
    const __nv_bfloat16* w2 = (const __nv_bfloat16*)d_in[6];
    const __nv_bfloat16* b2 = (const __nv_bfloat16*)d_in[7];

    void* fnp = nullptr; cudaDriverEntryPointQueryResult qr;
    cudaGetDriverEntryPoint("cuTensorMapEncodeTiled", &fnp, cudaEnableDefault, &qr);
    EncodeFn fn = (EncodeFn)fnp;
    CUtensorMap tx, twqkv, two64, two48, tw1, tw2, txr64, txr48, tout64, tout48;
    { cuuint64_t d[3] = {448, 2, 1024}, s[2] = {896, 1792}; cuuint32_t b[3] = {64, 1, 64}; make_map(fn, &tx, x, 3, d, s, b, CU_TENSOR_MAP_SWIZZLE_128B); }
    { cuuint64_t d[2] = {1344, 448}, s[1] = {2688}; cuuint32_t b[2] = {64, 64}; make_map(fn, &twqkv, wqkv, 2, d, s, b, CU_TENSOR_MAP_SWIZZLE_128B); }
    { cuuint64_t d[2] = {448, 448}, s[1] = {896}; cuuint32_t b[2] = {64, 64}; make_map(fn, &two64, wo, 2, d, s, b, CU_TENSOR_MAP_SWIZZLE_128B); }
    { cuuint64_t d[2] = {448, 448}, s[1] = {896}; cuuint32_t b[2] = {48, 64}; make_map(fn, &two48, wo, 2, d, s, b, CU_TENSOR_MAP_SWIZZLE_128B); }
    { cuuint64_t d[5] = {1792, 8, 2, 64, 2}, s[4] = {2 * 3584, 3584, 32 * 3584, 16 * 3584}; cuuint32_t b[5] = {64, 8, 2, 8, 1}; make_map(fn, &tw1, w1, 5, d, s, b, CU_TENSOR_MAP_SWIZZLE_128B); }
    { cuuint64_t d[5] = {2048, 8, 2, 56, 2}, s[4] = {4096, 16 * 4096, 32 * 4096, 8 * 4096}; cuuint32_t b[5] = {64, 8, 2, 8, 1}; make_map(fn, &tw2, w2, 5, d, s, b, CU_TENSOR_MAP_SWIZZLE_128B); }
    { cuuint64_t d[2] = {448, 2048}, s[1] = {896}; cuuint32_t b[2] = {64, 64}; make_map(fn, &txr64, x, 2, d, s, b, CU_TENSOR_MAP_SWIZZLE_128B); }
    { cuuint64_t d[2] = {448, 2048}, s[1] = {896}; cuuint32_t b[2] = {48, 64}; make_map(fn, &txr48, x, 2, d, s, b, CU_TENSOR_MAP_SWIZZLE_128B); }
    { cuuint64_t d[2] = {448, 2048}, s[1] = {896}; cuuint32_t b[2] = {64, 16}; make_map(fn, &tout64, d_out, 2, d, s, b, CU_TENSOR_MAP_SWIZZLE_128B); }
    { cuuint64_t d[2] = {448, 2048}, s[1] = {896}; cuuint32_t b[2] = {48, 16}; make_map(fn, &tout48, d_out, 2, d, s, b, CU_TENSOR_MAP_SWIZZLE_128B); }

    void* scv = nullptr;
    cudaGetSymbolAddress(&scv, g_scratch);
    Scratch* scp = (Scratch*)scv;
    int dev = 0, sms = 0;
    cudaGetDevice(&dev);
    cudaDeviceGetAttribute(&sms, cudaDevAttrMultiProcessorCount, dev);
    if (sms == 132) {
        cudaFuncSetAttribute(fused_kernel<true>, cudaFuncAttributeMaxDynamicSharedMemorySize, SM_TOTAL);
        fused_kernel<true><<<132, 384, SM_TOTAL>>>(scp, wo, w1, b1, w2, b2, tx, twqkv, two64, two48, tw1, tw2, txr64, txr48, tout64, tout48);
    } else {
        cudaFuncSetAttribute(fused_kernel<false>, cudaFuncAttributeMaxDynamicSharedMemorySize, SM_TOTAL);
        fused_kernel<false><<<132, 384, SM_TOTAL>>>(scp, wo, w1, b1, w2, b2, tx, twqkv, two64, two48, tw1, tw2, txr64, txr48, tout64, tout48);
    }
}
```

```cpp
#include <cuda_runtime.h>
#include <cuda_bf16.h>
#include <cuda.h>
#include <stdint.h>

namespace {

constexpr int D_ = 448;
constexpr float LN_EPS = 1e-5f;
constexpr float LOG2E_SCALE = 0.1889822365046136f * 1.4426950408889634f;

struct Tiles {
    uint32_t o[32 * 57344 / 4];
    uint32_t hn[4 * 32 * 14336 / 4];
    uint32_t u[4 * 28 * 14336 / 4];
};
struct Scratch {
    uint4 halo[128 * 2 * 2 * 3 * 32];
    uint4 stats[32 * 4 * 64];
    uint4 hint_k[128 * 2];
    uint4 hint_o[32 * 32 * 2];
    uint4 hint_h[4 * 32 * 2];
    uint4 hint_u[128 * 2];
    uint4 go[24];
    uint32_t epoch[160];
    uint32_t clean;
    alignas(1024) Tiles tiles[2];
};
__device__ Scratch g_scratch;
#define STAMP(i) do {} while (0)
#define FST(i) do {} while (0)
#define TSARG
#define TSVAL

constexpr uint32_t SB = 1024;
constexpr int SM_SLOT = 16384;
__device__ __forceinline__ constexpr uint32_t slot_x(int kb) { return (kb ? 6 + kb : 0) * SM_SLOT; }
__device__ __forceinline__ constexpr uint32_t slot_kv(int kb) { return (kb < 5 ? 2 + kb : 6 - kb) * SM_SLOT; }
__device__ __forceinline__ constexpr uint32_t slot_wo(int kb) { return (kb < 6 ? 2 + kb : 12) * SM_SLOT; }
constexpr int SM_QO = 8 * SM_SLOT;
constexpr int SM_HALOK = SM_QO + 57344, SM_HALOV = 1 * SM_SLOT;
constexpr int NA_SLOTS = 6, NB_SLOTS = 8;
constexpr int SM_ARING = 0;
constexpr int SM_BRING = NA_SLOTS * 16384;
constexpr int SM_H = 212992;
__device__ __forceinline__ uint32_t halo_kin(int par, int lane) { return SB + SM_H + 8192 + par * 4096 + lane * 128 + ((~lane & 6) << 4); }
constexpr int SM_BAR = 229376;
constexpr int SM_TAG = SM_BAR + 1536;
constexpr int SM_TIME = SM_TAG + 256;
constexpr int SM_TOTAL = SM_TIME + 256;
constexpr int B_FULLX = 0;
constexpr int B_FULLKV = 7;
constexpr int B_FQ = 14;
constexpr int B_DONE1 = 16;
constexpr int B_DONEX = 23;
constexpr int B_DONEQ = 24;
constexpr int B_DONEO = 25;
constexpr int B_FULLO = 29;
constexpr int B_FULLWO = 33;
constexpr int B_END = 34;
constexpr int B_HALO = 35;
constexpr int B_FULLA = 39;
constexpr int B_FULLB = 55;
constexpr int B_DONE = 87;
constexpr int B_GO = 119;
constexpr int B_CLR = 121;
constexpr int SM_RAW = SM_BAR + 8 * 122;

constexpr long long WD_CLKS = 2000000000ll;

template<int N> struct Int { static constexpr int value = N; };
template<int A, int B, class F> __device__ __forceinline__ void static_for(F&& f) { if constexpr (A < B) { f(Int<A>()); static_for<A + 1, B>(f); } }

__device__ __forceinline__ uint32_t smem_u32(const void* p) { return (uint32_t)__cvta_generic_to_shared(p); }
__device__ __forceinline__ void mbar_init(uint32_t bar, uint32_t cnt) { asm volatile("mbarrier.init.shared::cta.b64 [%0], %1;" :: "r"(bar), "r"(cnt) : "memory"); }
__device__ __forceinline__ void mbar_expect(uint32_t bar, uint32_t bytes) { asm volatile("mbarrier.arrive.expect_tx.shared::cta.b64 _, [%0], %1;" :: "r"(bar), "r"(bytes) : "memory"); }
__device__ __forceinline__ void mbar_arrive(uint32_t bar) { asm volatile("mbarrier.arrive.shared::cta.b64 _, [%0];" :: "r"(bar) : "memory"); }
__device__ __forceinline__ bool mbar_try(uint32_t bar, uint32_t parity) {
    uint32_t ok;
    asm volatile("{\n.reg .pred p;\nmbarrier.try_wait.parity.shared::cta.b64 p, [%1], %2;\nselp.u32 %0, 1, 0, p;\n}" : "=r"(ok) : "r"(bar), "r"(parity) : "memory");
    return ok;
}
__device__ __forceinline__ bool mbar_test(uint32_t bar, uint32_t parity) {
    uint32_t ok;
    asm volatile("{\n.reg .pred p;\nmbarrier.test_wait.parity.shared::cta.b64 p, [%1], %2;\nselp.u32 %0, 1, 0, p;\n}" : "=r"(ok) : "r"(bar), "r"(parity) : "memory");
    return ok;
}
__device__ __forceinline__ void mbar_wait(uint32_t bar, uint32_t parity) {
    asm volatile("{\n.reg .pred p;\n"
                 "WAIT_LOOP:\n"
                 "mbarrier.try_wait.parity.shared::cta.b64 p, [%0], %1;\n"
                 "@!p bra WAIT_LOOP;\n}" :: "r"(bar), "r"(parity) : "memory");
}
__device__ __forceinline__ void mbar_wait_unless(uint32_t ready, uint32_t bar, uint32_t parity) {
    asm volatile("{\n.reg .pred p;\nsetp.ne.u32 p, %1, 0;\n@p bra.uni DONE;\n"
                 "WAIT_LOOP:\n"
                 "mbarrier.try_wait.parity.shared::cta.b64 p, [%0], %2;\n"
                 "@!p bra.uni WAIT_LOOP;\nDONE:\n}" :: "r"(bar), "r"(ready), "r"(parity) : "memory");
}
__device__ __forceinline__ void mbar_wait_wd(uint32_t bar, uint32_t parity) {
    asm volatile("{\n.reg .pred p, q;\n.reg .u32 s, t;\nmov.u32 s, %%clock;\n"
                 "WAIT_LOOP:\n"
                 "mbarrier.try_wait.parity.shared::cta.b64 p, [%0], %1;\nmov.u32 t, %%clock;\nsub.u32 t, t, s;\nsetp.lt.and.s32 q, t, 0, !p;\n@q trap;\n"
                 "@!p bra WAIT_LOOP;\n}" :: "r"(bar), "r"(parity) : "memory");
}
__device__ __forceinline__ bool elect() { uint32_t p; asm volatile("{\n.reg .pred P;\nelect.sync _|P, 0xffffffff;\nselp.u32 %0, 1, 0, P;\n}" : "=r"(p)); return p; }
__device__ __forceinline__ void tma2d(uint32_t dst, const CUtensorMap* tm, int c0, int c1, uint32_t bar) {
    asm volatile("cp.async.bulk.tensor.2d.shared::cluster.global.mbarrier::complete_tx::bytes [%0], [%1, {%3, %4}], [%2];" :: "r"(dst), "l"(tm), "r"(bar), "r"(c0), "r"(c1) : "memory");
}
__device__ __forceinline__ void tma3d(uint32_t dst, const CUtensorMap* tm, int c0, int c1, int c2, uint32_t bar) {
    asm volatile("cp.async.bulk.tensor.3d.shared::cluster.global.mbarrier::complete_tx::bytes [%0], [%1, {%3, %4, %5}], [%2];" :: "r"(dst), "l"(tm), "r"(bar), "r"(c0), "r"(c1), "r"(c2) : "memory");
}
__device__ __forceinline__ void tma5d(uint32_t dst, const CUtensorMap* tm, int c0, int c3, int c4, uint32_t bar) {
    asm volatile("cp.async.bulk.tensor.5d.shared::cluster.global.mbarrier::complete_tx::bytes [%0], [%1, {%3, 0, 0, %4, %5}], [%2];" :: "r"(dst), "l"(tm), "r"(bar), "r"(c0), "r"(c3), "r"(c4) : "memory");
}
__device__ __forceinline__ void tma5d_prefetch(const CUtensorMap* tm, int c0, int c3, int c4) {
    asm volatile("cp.async.bulk.prefetch.tensor.5d.L2.global [%0, {%1, 0, 0, %2, %3}];" :: "l"(tm), "r"(c0), "r"(c3), "r"(c4) : "memory");
}
__device__ __forceinline__ void tma2d_store(const CUtensorMap* tm, int c0, int c1, uint32_t src) {
    asm volatile("cp.async.bulk.tensor.2d.global.shared::cta.bulk_group [%0, {%2, %3}], [%1];" :: "l"(tm), "r"(src), "r"(c0), "r"(c1) : "memory");
}
__device__ __forceinline__ void bulk_st(void* dst, uint32_t src, uint32_t bytes) {
    asm volatile("cp.async.bulk.global.shared::cta.bulk_group [%0], [%1], %2;" :: "l"(dst), "r"(src), "r"(bytes) : "memory");
}
__device__ __forceinline__ void bulk_ld(uint32_t dst, const void* src, uint32_t bytes, uint32_t bar) {
    asm volatile("cp.async.bulk.shared::cluster.global.mbarrier::complete_tx::bytes [%0], [%1], %2, [%3];" :: "r"(dst), "l"(src), "r"(bytes), "r"(bar) : "memory");
}
__device__ __forceinline__ void bulk_prefetch(const void* src, uint32_t bytes) { asm volatile("cp.async.bulk.prefetch.L2.global [%0], %1;" :: "l"(src), "r"(bytes) : "memory"); }
__device__ __forceinline__ void prefetch_map(const CUtensorMap* tm) { asm volatile("prefetch.tensormap [%0];" :: "l"(tm) : "memory"); }
__device__ __forceinline__ void st_global_if(uint32_t c, uint32_t* p, uint32_t v) {
    asm volatile("{\n.reg .pred p;\nsetp.ne.u32 p, %2, 0;\n@p st.global.u32 [%0], %1;\n}" :: "l"(p), "r"(v), "r"(c) : "memory");
}
__device__ __forceinline__ void st_relaxed4_if(bool c, uint4* p, uint32_t a, uint32_t b, uint32_t d) {
    asm volatile("{\n.reg .b128 t;\n.reg .b64 a, b;\n.reg .pred p;\nsetp.ne.u32 p, %4, 0;\nmov.b64 a, {%1, %2};\nmov.b64 b, {%3, %3};\nmov.b128 t, {a, b};\n@p st.relaxed.gpu.global.b128 [%0], t;\n}" :: "l"(p), "r"(a), "r"(b), "r"(d), "r"((uint32_t)c) : "memory");
}
__device__ __forceinline__ void pin_ptr(uint32_t never, const void* a) {
    asm volatile("{\n.reg .pred p;\nsetp.ne.u32 p, %1, 0;\n@p st.shared.u64 [%1], %0;\n}" :: "l"(a), "r"(never) : "memory");
}
__device__ __forceinline__ void pin4(uint32_t never, float a, float b, float c, float d) {
    asm volatile("{\n.reg .pred p;\nsetp.ne.u32 p, %4, 0;\n@p st.shared.v4.f32 [%4], {%0,%1,%2,%3};\n}" :: "f"(a), "f"(b), "f"(c), "f"(d), "r"(never) : "memory");
}
__device__ __forceinline__ void fence_async_smem() { asm volatile("fence.proxy.async.shared::cta;" ::: "memory"); }
__device__ __forceinline__ uint32_t ld_acquire(const void* p) { uint32_t v; asm volatile("ld.acquire.gpu.global.u32 %0, [%1];" : "=r"(v) : "l"(p) : "memory"); return v; }
__device__ __forceinline__ void st_release(void* p, uint32_t v) { asm volatile("st.release.gpu.global.u32 [%0], %1;" :: "l"(p), "r"(v) : "memory"); }
__device__ __forceinline__ uint32_t ld_relaxed(const void* p) { uint32_t v; asm volatile("ld.relaxed.gpu.global.u32 %0, [%1];" : "=r"(v) : "l"(p) : "memory"); return v; }
__device__ __forceinline__ uint2 ld_relaxed2(const void* p) {
    uint2 v; asm volatile("{\n.reg .b64 a;\nld.relaxed.gpu.global.b64 a, [%2];\nmov.b64 {%0, %1}, a;\n}" : "=r"(v.x), "=r"(v.y) : "l"(p) : "memory"); return v;
}
__device__ __forceinline__ void st_relaxed2(void* p, uint32_t a, uint32_t b) {
    asm volatile("{\n.reg .b64 a;\nmov.b64 a, {%1, %2};\nst.relaxed.gpu.global.b64 [%0], a;\n}" :: "l"(p), "r"(a), "r"(b) : "memory");
}
__device__ __forceinline__ uint4 ld_relaxed4(const uint4* p) {
    uint4 v;
    asm volatile("{\n.reg .b128 t;\n.reg .b64 a, b;\nld.relaxed.gpu.global.b128 t, [%4];\nmov.b128 {a, b}, t;\nmov.b64 {%0, %1}, a;\nmov.b64 {%2, %3}, b;\n}" : "=r"(v.x), "=r"(v.y), "=r"(v.z), "=r"(v.w) : "l"(p) : "memory");
    return v;
}
__device__ __forceinline__ void st_relaxed4(uint4* p, uint32_t a, uint32_t b, uint32_t c, uint32_t d) {
    asm volatile("{\n.reg .b128 t;\n.reg .b64 a, b;\nmov.b64 a, {%1, %2};\nmov.b64 b, {%3, %4};\nmov.b128 t, {a, b};\nst.relaxed.gpu.global.b128 [%0], t;\n}" :: "l"(p), "r"(a), "r"(b), "r"(c), "r"(d) : "memory");
}
__device__ __forceinline__ uint32_t ld_u16(const unsigned short* p) { uint32_t v; asm volatile("ld.volatile.global.u16 %0, [%1];" : "=r"(v) : "l"(p) : "memory"); return v; }
__device__ __forceinline__ uint32_t ld_volatile(const uint32_t* p) { uint32_t v; asm volatile("ld.volatile.global.u32 %0, [%1];" : "=r"(v) : "l"(p) : "memory"); return v; }
__device__ __forceinline__ void named_arrive(int id, int n) { asm volatile("bar.arrive %0, %1;" :: "r"(id), "r"(n) : "memory"); }
__device__ __forceinline__ void named_sync(int id, int n) { asm volatile("bar.sync %0, %1;" :: "r"(id), "r"(n) : "memory"); }
__device__ __forceinline__ void named_arrive_if(uint32_t c, int id, int n) { asm volatile("{\n.reg .pred p;\nsetp.ne.u32 p, %2, 0;\n@p bar.arrive %0, %1;\n}" :: "r"(id), "r"(n), "r"(c) : "memory"); }
__device__ __forceinline__ bool named_any(int id, int n, bool v) {
    uint32_t r; asm volatile("{\n.reg .pred p, q;\nsetp.ne.u32 p, %3, 0;\nbar.red.or.pred q, %1, %2, p;\nselp.u32 %0, 1, 0, q;\n}" : "=r"(r) : "r"(id), "r"(n), "r"((uint32_t)v) : "memory"); return r;
}
__device__ __forceinline__ void wg_fence() { asm volatile("wgmma.fence.sync.aligned;" ::: "memory"); }
__device__ __forceinline__ void wg_commit() { asm volatile("wgmma.commit_group.sync.aligned;" ::: "memory"); }
template<int N> __device__ __forceinline__ void wg_wait() { asm volatile("wgmma.wait_group.sync.aligned %0;" :: "n"(N) : "memory"); }
template<int N> __device__ __forceinline__ void reg_fence(float (&d)[N]) {
    #pragma unroll
    for (int i = 0; i < N; i++) asm volatile("" : "+f"(d[i]) :: "memory");
}
__device__ __forceinline__ constexpr uint64_t mkdesc(uint32_t addr, uint32_t lbo, uint32_t sbo, uint32_t sw) {
    return (uint64_t)((addr & 0x3FFFF) >> 4) | ((uint64_t)(lbo >> 4) << 16) | ((uint64_t)(sbo >> 4) << 32) | ((uint64_t)sw << 62);
}
__device__ __forceinline__ void ldsm4(uint32_t (&r)[4], uint32_t addr) {
    asm volatile("ldmatrix.sync.aligned.m8n8.x4.shared.b16 {%0,%1,%2,%3}, [%4];" : "=r"(r[0]), "=r"(r[1]), "=r"(r[2]), "=r"(r[3]) : "r"(addr) : "memory");
}
__device__ __forceinline__ void stsm4_if(uint32_t c, uint32_t addr, uint32_t r0, uint32_t r1, uint32_t r2, uint32_t r3) {
    asm volatile("{\n.reg .pred p;\nsetp.ne.u32 p, %5, 0;\n@p stmatrix.sync.aligned.m8n8.x4.shared.b16 [%0], {%1,%2,%3,%4};\n}" :: "r"(addr), "r"(r0), "r"(r1), "r"(r2), "r"(r3), "r"(c) : "memory");
}
__device__ __forceinline__ void sts4(uint32_t a, uint32_t x, uint32_t y, uint32_t z, uint32_t w) { asm volatile("st.shared.v4.u32 [%0], {%1,%2,%3,%4};" :: "r"(a), "r"(x), "r"(y), "r"(z), "r"(w) : "memory"); }
__device__ __forceinline__ uint4 lds4(uint32_t a) { uint4 v; asm volatile("ld.shared.v4.u32 {%0,%1,%2,%3}, [%4];" : "=r"(v.x), "=r"(v.y), "=r"(v.z), "=r"(v.w) : "r"(a) : "memory"); return v; }
__device__ __forceinline__ uint32_t movtrans(uint32_t a) { uint32_t d; asm volatile("movmatrix.sync.aligned.m8n8.trans.b16 %0, %1;" : "=r"(d) : "r"(a)); return d; }
__device__ __forceinline__ uint32_t pack_bf16(float lo, float hi) { uint32_t r; asm("cvt.rn.bf16x2.f32 %0, %1, %2;" : "=r"(r) : "f"(hi), "f"(lo)); return r; }
__device__ __forceinline__ void sub_bf16x2(uint32_t& a, uint32_t b) { asm volatile("sub.rn.bf16x2 %0, %0, %1;" : "+r"(a) : "r"(b)); }
__device__ __forceinline__ float bf_lo(uint32_t v) { return __uint_as_float(v << 16); }
__device__ __forceinline__ float bf_hi(uint32_t v) { return __uint_as_float(v & 0xffff0000u); }
__device__ __forceinline__ void mma16816(float (&c)[4], uint32_t a0, uint32_t a1, uint32_t a2, uint32_t a3, uint32_t b0, uint32_t b1) {
    asm volatile("mma.sync.aligned.m16n8k16.row.col.f32.bf16.bf16.f32 {%0,%1,%2,%3}, {%4,%5,%6,%7}, {%8,%9}, {%0,%1,%2,%3};"
        : "+f"(c[0]), "+f"(c[1]), "+f"(c[2]), "+f"(c[3]) : "r"(a0), "r"(a1), "r"(a2), "r"(a3), "r"(b0), "r"(b1));
}
__device__ __forceinline__ void mma1688(float (&c)[4], uint32_t a0, uint32_t a1, uint32_t b0) {
    asm volatile("mma.sync.aligned.m16n8k8.row.col.f32.bf16.bf16.f32 {%0,%1,%2,%3}, {%4,%5}, {%6}, {%0,%1,%2,%3};"
        : "+f"(c[0]), "+f"(c[1]), "+f"(c[2]), "+f"(c[3]) : "r"(a0), "r"(a1), "r"(b0));
}
__device__ __forceinline__ float quad_sum(float v) { v += __shfl_xor_sync(0xffffffffu, v, 1); v += __shfl_xor_sync(0xffffffffu, v, 2); return v; }
__device__ __forceinline__ float quad_max(float v) { v = fmaxf(v, __shfl_xor_sync(0xffffffffu, v, 1)); v = fmaxf(v, __shfl_xor_sync(0xffffffffu, v, 2)); return v; }
__device__ __forceinline__ float ex2(float x) { float y; asm("ex2.approx.ftz.f32 %0, %1;" : "=f"(y) : "f"(x)); return y; }
__device__ __forceinline__ float rsqrt_approx(float x) { float y; asm("rsqrt.approx.ftz.f32 %0, %1;" : "=f"(y) : "f"(x)); return y; }
__device__ __forceinline__ float rcp_approx(float x) { float y; asm("rcp.approx.ftz.f32 %0, %1;" : "=f"(y) : "f"(x)); return y; }
constexpr float GELU_K1 = 2.f * 0.7978845608028654f;
__device__ __forceinline__ float gelu_half(float hx, float k1) {
    const float z = hx * fmaf(hx * hx, 8.f * 0.044715f * 0.7978845608028654f, k1);
    float t; asm("tanh.approx.f32 %0, %1;" : "=f"(t) : "f"(z));
    return fmaf(hx, t, hx);
}
__device__ __forceinline__ uint32_t gtime32() { uint64_t t; asm volatile("mov.u64 %0, %%globaltimer;" : "=l"(t)); return (uint32_t)t; }
__device__ __forceinline__ uint32_t clock32() { uint32_t t; asm volatile("mov.u32 %0, %%clock;" : "=r"(t)); return t; }
#define PF_PACE 160
#define PF_AT 16500
#define PF_N 192
#define NSQ 6
#define NPIPE 1
#define HALO_AT 3
#define HINT_U 18
#define HINT_E 16
#define SP_AT 2000
#define A_SCHED 0x322188
#define WO_ORD0 0x4321065
#define WO_ORD1 0x3465210
#define CL_AT 23
#define WARM_AT 300
#define GO_H 1730
#define GO_E 1900
#define GO_U 2120
#define GO_O 1280
#define LATE_O 256
#define DRY2 1
#define LATE_AT 0
#define LATE_AT4 0
#define SLACK 0
#define GDEP 4
#define START4 30
#define DEPTH_N 1
#define DEPTH_E 2
#define NE_SLOTS 11
#define POLL_E 26
#define CH_U 28
#define AE_END 18
#define AE_W2 27
#define PF1_AT 12000
#define PF1_N 80
#define PF1_PACE 160
#define GO_E2 300
#define GO_U2 400
#define POLL_I 20
#define POLL_N 19
#define ROLES 0x65431027u
#define POLL0 250
#define A4_FROM 23
#define A4_DLY 2
#define SPIN2 1
#define SPIN_N 2
#define STOP2 150
#define PF0_AT 5000
#define PF0_N 48
#define PF0_PACE 140
#define POLL_H 3
#define CH_H 8
#define HINT_F 2
#define CL_N 4
#define CL_P2 7
#define VTAKE 1
#define DEFER 1
#define DRY3 1
template<int TB> __device__ __forceinline__ void wgmma_rs56(float (&d)[28], const uint32_t (&a)[4], uint64_t db, int sc) {
    asm volatile("{\n.reg .pred p;\nsetp.ne.b32 p, %33, 0;\n"
        "wgmma.mma_async.sync.aligned.m64n56k16.f32.bf16.bf16 {%0, %1, %2, %3, %4, %5, %6, %7, %8, %9, %10, %11, %12, %13, %14, %15, %16, %17, %18, %19, %20, %21, %22, %23, %24, %25, %26, %27}, {%28, %29, %30, %31}, %32, p, 1, 1, %34;\n}\n"
        : "+f"(d[0]), "+f"(d[1]), "+f"(d[2]), "+f"(d[3]), "+f"(d[4]), "+f"(d[5]), "+f"(d[6]), "+f"(d[7]), "+f"(d[8]), "+f"(d[9]), "+f"(d[10]), "+f"(d[11]), "+f"(d[12]), "+f"(d[13]), "+f"(d[14]), "+f"(d[15]), "+f"(d[16]), "+f"(d[17]), "+f"(d[18]), "+f"(d[19]), "+f"(d[20]), "+f"(d[21]), "+f"(d[22]), "+f"(d[23]), "+f"(d[24]), "+f"(d[25]), "+f"(d[26]), "+f"(d[27])
        : "r"(a[0]), "r"(a[1]), "r"(a[2]), "r"(a[3]), "l"(db), "r"(sc), "n"(TB));
}

template<int TA, int TB, int SC = 1> __device__ __forceinline__ void wgmma_ss112(float (&d)[56], uint64_t da, uint64_t db) {
    asm volatile("wgmma.mma_async.sync.aligned.m64n112k16.f32.bf16.bf16 {%0, %1, %2, %3, %4, %5, %6, %7, %8, %9, %10, %11, %12, %13, %14, %15, %16, %17, %18, %19, %20, %21, %22, %23, %24, %25, %26, %27, %28, %29, %30, %31, %32, %33, %34, %35, %36, %37, %38, %39, %40, %41, %42, %43, %44, %45, %46, %47, %48, %49, %50, %51, %52, %53, %54, %55}, %56, %57, %60, 1, 1, %58, %59;\n"
        : "+f"(d[0]), "+f"(d[1]), "+f"(d[2]), "+f"(d[3]), "+f"(d[4]), "+f"(d[5]), "+f"(d[6]), "+f"(d[7]), "+f"(d[8]), "+f"(d[9]), "+f"(d[10]), "+f"(d[11]), "+f"(d[12]), "+f"(d[13]), "+f"(d[14]), "+f"(d[15]), "+f"(d[16]), "+f"(d[17]), "+f"(d[18]), "+f"(d[19]), "+f"(d[20]), "+f"(d[21]), "+f"(d[22]), "+f"(d[23]), "+f"(d[24]), "+f"(d[25]), "+f"(d[26]), "+f"(d[27]), "+f"(d[28]), "+f"(d[29]), "+f"(d[30]), "+f"(d[31]), "+f"(d[32]), "+f"(d[33]), "+f"(d[34]), "+f"(d[35]), "+f"(d[36]), "+f"(d[37]), "+f"(d[38]), "+f"(d[39]), "+f"(d[40]), "+f"(d[41]), "+f"(d[42]), "+f"(d[43]), "+f"(d[44]), "+f"(d[45]), "+f"(d[46]), "+f"(d[47]), "+f"(d[48]), "+f"(d[49]), "+f"(d[50]), "+f"(d[51]), "+f"(d[52]), "+f"(d[53]), "+f"(d[54]), "+f"(d[55])
        : "l"(da), "l"(db), "n"(TA), "n"(TB), "n"(SC));
}

template<int TA, int TB, int SC = 1> __device__ __forceinline__ void wgmma_ss80(float (&d)[40], uint64_t da, uint64_t db) {
    asm volatile("wgmma.mma_async.sync.aligned.m64n80k16.f32.bf16.bf16 {%0, %1, %2, %3, %4, %5, %6, %7, %8, %9, %10, %11, %12, %13, %14, %15, %16, %17, %18, %19, %20, %21, %22, %23, %24, %25, %26, %27, %28, %29, %30, %31, %32, %33, %34, %35, %36, %37, %38, %39}, %40, %41, %44, 1, 1, %42, %43;\n"
        : "+f"(d[0]), "+f"(d[1]), "+f"(d[2]), "+f"(d[3]), "+f"(d[4]), "+f"(d[5]), "+f"(d[6]), "+f"(d[7]), "+f"(d[8]), "+f"(d[9]), "+f"(d[10]), "+f"(d[11]), "+f"(d[12]), "+f"(d[13]), "+f"(d[14]), "+f"(d[15]), "+f"(d[16]), "+f"(d[17]), "+f"(d[18]), "+f"(d[19]), "+f"(d[20]), "+f"(d[21]), "+f"(d[22]), "+f"(d[23]), "+f"(d[24]), "+f"(d[25]), "+f"(d[26]), "+f"(d[27]), "+f"(d[28]), "+f"(d[29]), "+f"(d[30]), "+f"(d[31]), "+f"(d[32]), "+f"(d[33]), "+f"(d[34]), "+f"(d[35]), "+f"(d[36]), "+f"(d[37]), "+f"(d[38]), "+f"(d[39])
        : "l"(da), "l"(db), "n"(TA), "n"(TB), "n"(SC));
}

template<int TA, int TB, int SC = 1> __device__ __forceinline__ void wgmma_ss64(float (&d)[32], uint64_t da, uint64_t db) {
    asm volatile("wgmma.mma_async.sync.aligned.m64n64k16.f32.bf16.bf16 {%0, %1, %2, %3, %4, %5, %6, %7, %8, %9, %10, %11, %12, %13, %14, %15, %16, %17, %18, %19, %20, %21, %22, %23, %24, %25, %26, %27, %28, %29, %30, %31}, %32, %33, %36, 1, 1, %34, %35;\n"
        : "+f"(d[0]), "+f"(d[1]), "+f"(d[2]), "+f"(d[3]), "+f"(d[4]), "+f"(d[5]), "+f"(d[6]), "+f"(d[7]), "+f"(d[8]), "+f"(d[9]), "+f"(d[10]), "+f"(d[11]), "+f"(d[12]), "+f"(d[13]), "+f"(d[14]), "+f"(d[15]), "+f"(d[16]), "+f"(d[17]), "+f"(d[18]), "+f"(d[19]), "+f"(d[20]), "+f"(d[21]), "+f"(d[22]), "+f"(d[23]), "+f"(d[24]), "+f"(d[25]), "+f"(d[26]), "+f"(d[27]), "+f"(d[28]), "+f"(d[29]), "+f"(d[30]), "+f"(d[31])
        : "l"(da), "l"(db), "n"(TA), "n"(TB), "n"(SC));
}

template<int TA, int TB, int SC = 1> __device__ __forceinline__ void wgmma_ss48(float (&d)[24], uint64_t da, uint64_t db) {
    asm volatile("wgmma.mma_async.sync.aligned.m64n48k16.f32.bf16.bf16 {%0, %1, %2, %3, %4, %5, %6, %7, %8, %9, %10, %11, %12, %13, %14, %15, %16, %17, %18, %19, %20, %21, %22, %23}, %24, %25, %28, 1, 1, %26, %27;\n"
        : "+f"(d[0]), "+f"(d[1]), "+f"(d[2]), "+f"(d[3]), "+f"(d[4]), "+f"(d[5]), "+f"(d[6]), "+f"(d[7]), "+f"(d[8]), "+f"(d[9]), "+f"(d[10]), "+f"(d[11]), "+f"(d[12]), "+f"(d[13]), "+f"(d[14]), "+f"(d[15]), "+f"(d[16]), "+f"(d[17]), "+f"(d[18]), "+f"(d[19]), "+f"(d[20]), "+f"(d[21]), "+f"(d[22]), "+f"(d[23])
        : "l"(da), "l"(db), "n"(TA), "n"(TB), "n"(SC));
}

template<int NKB, int NR>
__device__ __forceinline__ void mix_mainloop(TSARG float (&acc)[NR], bool leader) {
    constexpr uint32_t sb = SB, bars = sb + SM_BAR, par = NKB == 28;
    constexpr int A0 = NKB == 32 ? 0 : 16 % NA_SLOTS;
    constexpr int DEPTH = NR == 56 ? DEPTH_N : DEPTH_E;
    int bslot = 0, aslot = A0;
    reg_fence(acc);
    #pragma unroll 1
    for (int i = 0; i < NKB / 2; i++) {
        mbar_wait(bars + 8 * (B_FULLA + i), par);
        const uint64_t adesc = mkdesc(sb + SM_ARING, 8192, 1024, 1) + (uint32_t)(aslot * 1024);
        aslot = aslot == NA_SLOTS - 1 ? 0 : aslot + 1;
        #pragma unroll
        for (int jj = 0; jj < 2; jj++) {
            const int j = 2 * i + jj;
            mbar_wait(bars + 8 * (B_FULLB + j), par);
            const uint64_t bdesc = mkdesc(sb + SM_BRING, 128, 1024, 0) + (uint32_t)(bslot * NR * 16);
            bslot = bslot == (NR == 56 ? NB_SLOTS : NE_SLOTS) - 1 ? 0 : bslot + 1;
            wg_fence();
            #pragma unroll
            for (int s = 0; s < 4; s++) {
                if constexpr (NR == 56) wgmma_ss112<1, 1>(acc, adesc + jj * 512 + s * 128, bdesc + s * 16);
                else wgmma_ss80<1, 1>(acc, adesc + jj * 512 + s * 128, bdesc + s * 16);
            }
            wg_commit();
            wg_wait<DEPTH>();
            if (j >= DEPTH && leader) mbar_arrive(bars + 8 * (B_DONE + j - DEPTH));
        }
    }
    if (DEPTH == 2) { wg_wait<1>(); if (leader) mbar_arrive(bars + 8 * (B_DONE + NKB - 2)); }
    wg_wait<0>();
    reg_fence(acc);
    if (leader) mbar_arrive(bars + 8 * (B_DONE + NKB - 1));
}

__device__ __forceinline__ void spin_mma(uint32_t bar, uint32_t never) {
    float d[56];
    #pragma unroll
    for (int i = 0; i < 56; i++) d[i] = 0.f;
    reg_fence(d);
    #pragma unroll 1
    do {
        wg_fence();
        #pragma unroll
        for (int s = 0; s < SPIN_N; s++) wgmma_ss112<1, 1>(d, mkdesc(SB + 2 * SM_SLOT + s * 2048, 8192, 1024, 1), mkdesc(SB + 3 * SM_SLOT + s * 256, 128, 1024, 0));
        wg_commit();
        wg_wait<1>();
    } while (!named_any(11, 128, mbar_test(bar, 1)));
    wg_wait<0>();
    reg_fence(d);
    pin4(never, d[0], d[1], d[2], d[3]);
}

constexpr uint32_t EMPTY = 0xFFFFFFFFu;
__device__ __forceinline__ void post_hint(uint4* p, uint32_t ep, int lane) { if (lane < 2) st_relaxed4(p + lane, ep, ep, ep, ep); }
__device__ __forceinline__ void post_time(uint4* p, uint32_t ep, int lane) { const uint32_t now = gtime32(); if (lane < 2) st_relaxed4(p + lane, ep, now, ep, now); }

__device__ __forceinline__ uint32_t last_hint(TSARG const uint4* hint, uint32_t ep, int st) {
    uint2 v;
    do { v = ld_relaxed2(hint); } while (!__all_sync(0xffffffffu, v.x == ep));
    const uint32_t t1 = gtime32() + 256;
    if (elect()) STAMP(st);
    return t1 - __reduce_min_sync(0xffffffffu, t1 - v.y);
}
__device__ __forceinline__ uint32_t later(uint32_t a, uint32_t b) { return a + max((int)(b - a), 0); }
__device__ __forceinline__ void fetch_times(TSARG const uint4* go, int k, uint32_t ep, int lane) {
    const uint2* p = (const uint2*)(go + 8 + 8 * k) + (k ? lane % 10 : lane & 3);
    uint2 v;
    do { v = ld_relaxed2(p); } while (!__all_sync(0xffffffffu, v.x == ep));
    v.y += k ? (lane < 10 ? GO_U : GO_U + GO_U2) : (lane < 4 ? GO_E : GO_E + GO_E2);
    asm volatile("st.shared.u32 [%0], %1;" :: "r"(SB + SM_TIME + 128 * k + 4 * lane), "r"(v.y) : "memory");
    __syncwarp();
    if (lane == 0) { mbar_arrive(SB + SM_BAR + 8 * (B_GO + k)); STAMP(k ? 43 : 24); }
    __syncwarp();
}
__device__ __forceinline__ void wait_until(uint32_t t) {
    asm volatile("{\n.reg .pred p;\n.reg .u64 a;\n.reg .u32 l, h;\nWAIT_LOOP:\nmov.u64 a, %%globaltimer;\nmov.b64 {l, h}, a;\nsub.u32 l, l, %0;\nsetp.lt.s32 p, l, 0;\n@p bra.uni WAIT_LOOP;\n}" :: "r"(t) : "memory");
}

__device__ __forceinline__ uint32_t check_tile(uint32_t raw, uint32_t full, uint32_t dst, uint32_t lofs, const uint32_t* src, uint32_t bytes, int lane) {
    uint32_t cnt;
    asm volatile("{\n.reg .pred p, e;\n.reg .u32 a, b, c, d;\nmov.u32 %0, 0;\n"
                 "AGAIN:\nand.b32 a, %0, 1;\n"
                 "WAIT:\nmbarrier.try_wait.parity.shared::cta.b64 p, [%1], a;\n@!p bra.uni WAIT;\n"
                 "ld.shared.u32 a, [%4];\nld.shared.u32 b, [%4+4096];\nld.shared.u32 c, [%5+-8192];\nld.shared.u32 d, [%5+-4096];\n"
                 "add.u32 %0, %0, 1;\nmax.u32 a, a, b;\nmax.u32 c, c, d;\nmax.u32 a, a, c;\nsetp.lt.u32 e, %8, 32;\nsetp.eq.and.u32 p, a, 0xFFFFFFFF, e;\n"
                 "vote.sync.any.pred p, p, 0xffffffff;\nsetp.eq.and.u32 e, %8, 0, !p;\n@e mbarrier.arrive.shared::cta.b64 _, [%2];\n"
                 "elect.sync _|e, 0xffffffff;\nand.pred e, e, p;\n"
                 "@e mbarrier.arrive.expect_tx.shared::cta.b64 _, [%1], %7;\n"
                 "@e cp.async.bulk.shared::cluster.global.mbarrier::complete_tx::bytes [%3], [%6], %7, [%1];\n"
                 "@p bra.uni AGAIN;\n}"
                 : "=&r"(cnt) : "r"(raw), "r"(full), "r"(dst), "r"(dst + lofs), "r"(dst + lofs + bytes), "l"(src), "r"(bytes), "r"(lane) : "memory");
    return cnt;
}

template<int ST>
__device__ __forceinline__ void check_tiles(int j, int step, int n, const uint32_t* src, bool small, int lane, bool dry) {
    const uint32_t bytes = small ? 10240 : 14336, nb = small ? NE_SLOTS : NB_SLOTS, lofs = lane * 128 + (lane & 3) * 32 + (lane >> 2) * 4;
    uint32_t sl = j % nb;
    #pragma unroll 1
    for (int inc = dry ? 0 : step; j < n; j += inc, inc = step) {
        const uint32_t c = check_tile(inc ? SB + SM_RAW + 8 * (j + (ST ? 32 * ST - 28 : 0)) : SB + SM_BAR + 8 * B_CLR, SB + SM_BAR + 8 * (j + (ST ? B_FULLB : B_FULLO)),
                                      SB + (ST ? SM_BRING : SM_QO) + sl * bytes, lofs, src + j * (ST ? 7168 : 3584), bytes, inc ? lane : 32);
        sl += inc;
        if (sl >= nb) sl -= nb;
    }
}

__device__ __forceinline__ uint32_t hcol(uint32_t a, int jp) { return (a ^ ((jp & 3) << 5)) + (jp >> 2) * 8192; }

__device__ __forceinline__ uint32_t get_tag() {
    mbar_wait(SB + SM_BAR + 8 * B_CLR, 0);
    uint32_t v; asm volatile("ld.shared.u32 %0, [%1];" : "=r"(v) : "r"(SB + SM_TAG) : "memory"); return v;
}

template<bool USE_SMID>
__global__ void __launch_bounds__(384, 1)
fused_kernel(Scratch* __restrict__ sc, const __nv_bfloat16* __restrict__ wo,
             const __nv_bfloat16* __restrict__ w1, const __nv_bfloat16* __restrict__ b1,
             const __nv_bfloat16* __restrict__ w2, const __nv_bfloat16* __restrict__ b2,
             const __grid_constant__ CUtensorMap tm_x, const __grid_constant__ CUtensorMap tm_wqkv,
             const __grid_constant__ CUtensorMap tm_wo64, const __grid_constant__ CUtensorMap tm_wo48,
             const __grid_constant__ CUtensorMap tm_w1, const __grid_constant__ CUtensorMap tm_w2,
             const __grid_constant__ CUtensorMap tm_xr64, const __grid_constant__ CUtensorMap tm_xr48,
             const __grid_constant__ CUtensorMap tm_out64, const __grid_constant__ CUtensorMap tm_out48) {
    extern __shared__ __align__(1024) uint8_t smem_raw[];
    constexpr uint32_t sb = SB;
    constexpr uint32_t bars = sb + SM_BAR;
    const int tid = threadIdx.x, lane = tid & 31;
    auto get_slot = [&]() {
        int slot;
    if (USE_SMID) {
        asm volatile("{\n.reg .u32 s, t, u, d, a, b, c;\n.reg .pred p, r;\n"
            "mov.u32 s, %%smid;\nshr.u32 t, s, 1;\nsub.u32 u, t, 32;\nmul.lo.u32 d, u, 37;\nshr.u32 d, d, 8;\n"
            "and.b32 a, t, 7;\nshl.b32 a, a, 3;\nshr.u32 c, t, 3;\nadd.u32 a, a, c;\n"
            "mad.lo.u32 b, d, -55, 12;\nshl.b32 c, u, 3;\nadd.u32 b, b, c;\n"
            "setp.lt.u32 p, t, 32;\nselp.u32 a, a, b, p;\n"
            "setp.lt.u32 r, t, 62;\nselp.s32 c, 4, -58, r;\nadd.u32 c, t, c;\nsetp.lt.u32 p, t, 60;\nselp.u32 a, a, c, p;\n"
            "and.b32 s, s, 1;\nshl.b32 a, a, 1;\nadd.u32 %0, a, s;\n}" : "=r"(slot));
    } else slot = blockIdx.x;
        return slot;
    };
    auto load_x = [&](int kb, int row) {
        const uint32_t st = sb + slot_x(kb), bar = bars + 8 * (B_FULLX + kb);
        mbar_expect(bar, 16384);
        tma3d(st, &tm_x, kb * 64, 0, row, bar); tma3d(st + 8192, &tm_x, kb * 64, 1, row, bar);
    };
    const int warp = __shfl_sync(0xffffffffu, tid >> 5, 0);
#define ASSIGN_WORK(s) \
    const int slot = (s), G = slot >> 4, mi = slot & 15; \
    const int tb = 4 * (G >> 1) + (mi >> 2), hp = 2 * (mi & 3) + (G & 1), wcol = (hp * 56) & ~15; \
    const int q = mi & 3, tt2 = 4 * G + (mi >> 2), c64 = 64 * q, c48 = 256 + 48 * q; \
    const int R = (ROLES >> (4 * G)) & 7; \
    const bool early = R < 3; \
    const int ech = R < 2 ? q : 4 + (mi & 1), ft = R == 2 ? mi >> 1 : 4 * (R - !early) + (mi >> 2); \
    const int pr3 = early ? ech >= 3 : q >> 1, col3 = early ? (ech - 3 * pr3) * 9 : (q & 1) * 14;

    if (warp < 8) {
        ASSIGN_WORK(get_slot())
        if (slot >= 128) {
            const uint32_t ep = ld_volatile(&sc->epoch[slot]) + 1;
            if (mi == 0 && warp > 0) {
                const int k = warp % 3;
                uint2* go = (uint2*)(sc->go + 8 * k) + lane;
                if (warp < 4 && lane < 16) st_relaxed2(go, 0, 0);
                while (ld_relaxed(k ? sc->go : sc->hint_k) != ep) __nanosleep(200);
                __nanosleep(warp * 60);
                const uint4* hint = (k ? sc->hint_u : sc->hint_h) + (k == 2 ? 48 + min(lane, 19) : lane) * 2;
                uint2 v[4];
                do {
                    #pragma unroll
                    for (int i = 0; i < 4; i++) v[i] = ld_relaxed2(hint + (k == 0 ? 64 * i : k == 2 ? 40 * i : 32 * (i & 1)));
                } while (!__all_sync(0xffffffffu, v[0].x == ep && v[1].x == ep && v[2].x == ep && v[3].x == ep));
                uint32_t t = later(later(v[0].y, v[1].y), later(v[2].y, v[3].y));
                t = later(t, __shfl_xor_sync(0xffffffffu, t, 1));
                if (k == 1) { t = later(t, __shfl_xor_sync(0xffffffffu, t, 8)); t = later(t, __shfl_xor_sync(0xffffffffu, t, 16)); }
                if (k == 0) {
                    const uint32_t now = gtime32() + 256;
                    t = later(t, now - __reduce_min_sync(0xffffffffu, now - t) - SLACK);
                }
                t = __shfl_sync(0xffffffffu, t, 2 * lane);
                if (lane < 16) st_relaxed2(go, ep, t);
            }
            if (mi == 1 && warp >= 4 && ld_volatile(&sc->clean) != ep) {
                for (int l = (tid - 128) / 2; l < sizeof(Tiles) / 128; l += 64) st_relaxed4((uint4*)&sc->tiles[ep & 1] + l * 8 + (lane & 7), EMPTY, EMPTY, EMPTY, EMPTY);
                named_sync(1, 128);
                if (tid == 128) st_release(&sc->clean, ep);
            }
            if (tid == 0) {
                const long long t0 = clock64();
                while (clock64() - t0 < SP_AT) {}
                #pragma unroll 1
                for (int i = 0; i < 7; i++) bulk_prefetch((const char*)wo + (i * 4 + mi) * 14336, 14336);
                uint32_t t = (uint32_t)t0 + PF0_AT;
                #pragma unroll 1
                for (int i = 0; i < PF0_N; i++) {
                    while ((int)(clock32() - t) < 0) {}
                    bulk_prefetch((const char*)w1 + i * 114688 + mi * 14336, 14336);
                    t += PF0_PACE;
                }
                if (mi) {
                    t = (uint32_t)t0 + PF1_AT;
                    #pragma unroll 1
                    for (int i = mi - 1; i < PF1_N; i += 3) {
                        while ((int)(clock32() - t) < 0) {}
                        tma5d_prefetch(&tm_w1, (i & 7) * 64, (i + 48) & 56, (i + 48) >> 6);
                        t += PF1_PACE;
                    }
                    t = (uint32_t)t0 + PF_AT;
                    #pragma unroll 1
                    for (int i = mi - 1; i < PF_N; i += 3) {
                        while ((int)(clock32() - t) < 0) {}
                        bulk_prefetch((const char*)w2 + (i < 128 ? i * 16384 : (i - 64 >> 1) * 65536 + (i & 1) * 16384), 16384);
                        t += PF_PACE;
                    }
                }
                while (ld_relaxed(sc->hint_u + 254) != ep) { __nanosleep(500); if (clock64() - t0 > WD_CLKS) __trap(); }
                sc->epoch[slot] = ep;
                if (mi == 1) sc->clean = ep + 1;
            }
            return;
        }
        {
            const int w = warp & 3, wg = warp >> 2, g = lane >> 2, t = lane & 3;
            if (WARM_AT) { const uint32_t t0 = clock32(); while (clock32() - t0 < WARM_AT) {} __syncwarp(); }
            if (w > 0) post_hint(sc->hint_o + ((2 * tb + (w >> 1)) * 32 + hp * 4 + (w & 1) * 2 + wg) * 2, 0, lane);
            if (wg == 0) {
                if (t < 2) st_relaxed4(sc->stats + tt2 * 256 + q * 64 + 16 * w + g + 8 * t, 0, 0, 0, 0);
            }
        }
        named_sync(0, 288);
        asm volatile("setmaxnreg.inc.sync.aligned.u32 224;");
        int tid; asm volatile("mov.u32 %0, %%tid.x;" : "=r"(tid));
        const int lane = tid & 31, warp = __shfl_sync(0xffffffffu, tid >> 5, 0), wg = warp >> 2;
        uint32_t ep;
        Tiles* tl;
        const int w = warp & 3, g = lane >> 2, t = lane & 3;
        const bool leader = (tid & 127) == 0;
        const uint32_t never = gridDim.y - 1;
        {
            uint32_t a[28][4];
            float accK[28], accV[28], accQ[28];
            const int lrow = 16 * w + (lane & 7) + (lane & 8);
            const uint32_t lbase = sb + wg * 8192 + lrow * 128;
            const uint32_t lx = (lane >> 4) ^ (lane & 7);
            const uint32_t wofs = hp & 1;
            auto pin2 = [&](uint32_t x0, uint32_t x1) {
                asm volatile("{\n.reg .pred p;\nsetp.ne.u32 p, %2, 0;\n@p st.shared.v2.b32 [%0], {%0,%1};\n}" :: "r"(x0), "r"(x1), "r"(never) : "memory");
            };
            float cS[2][4] = {}, cA[2][4] = {}, cB[2][4] = {}, q0, q1, p0, p1;
            auto sq = [&](float& acc, uint32_t v) { const float lo = bf_lo(v), hi = bf_hi(v); acc = fmaf(hi, hi, fmaf(lo, lo, acc)); };
            uint32_t ready = 0;
            #pragma unroll
            for (int kb = 0; kb < 8; kb++) {
                if (kb < 7) {
                    mbar_wait_unless(ready, bars + 8 * (B_FULLX + kb), 0);
                    if (kb == 0 && tid == 0) STAMP(0);
                    if (kb == 6 && tid == 0) STAMP(25);
                    if (kb == 0) FST(0); if (kb == 2) FST(1); if (kb == 4) FST(2); if (kb == 6) FST(3);
                    #pragma unroll
                    for (int s = 4 * kb; s < 4 * kb + 4; s++) ldsm4(a[s], lbase + slot_x(kb) + ((lx ^ (2 * (s & 3))) << 4));
                }
                if (kb > 0 && kb < 6) ready = mbar_test(bars + 8 * (B_FULLX + kb + 1), 0);
                if (kb == 5) named_sync(9 + wg, 160);
                if (kb == NPIPE) continue;
                const int kc = kb < NPIPE ? kb : kb - 1;
                if (kc == NSQ) { p0 = cS[0][0] + cS[1][0]; p1 = cS[0][2] + cS[1][2]; }
                #pragma unroll
                for (int s = 4 * kc; s < 4 * kc + 4; s++) {
                    mma16816(cS[s & 1], a[s][0], a[s][1], a[s][2], a[s][3], 0x3F803F80u, 0x3F803F80u);
                    if (kc < NSQ) {
                        mma1688(cA[0], a[s][0], a[s][1], a[s][0]); mma1688(cA[1], a[s][2], a[s][3], a[s][2]);
                        mma1688(cB[0], a[s][0], a[s][1], a[s][1]); mma1688(cB[1], a[s][2], a[s][3], a[s][3]);
                    }
                }
            }
            const float m0 = (cS[0][0] + cS[1][0]) * (1.f / D_), m1 = (cS[0][2] + cS[1][2]) * (1.f / D_);
            const uint32_t mm0 = pack_bf16(m0, m0), mm1 = pack_bf16(m1, m1);
            if (lane == 0) mbar_arrive(bars + 8 * B_DONEX);
            auto center = [&](int s) { sub_bf16x2(a[s][0], mm0); sub_bf16x2(a[s][1], mm1); sub_bf16x2(a[s][2], mm0); sub_bf16x2(a[s][3], mm1); };
            uint32_t Ka[8], Kb[8], Kc[8], Va[8], Vb[7], Vc[8];
            float r0, r1, ls0, ls1;
            uint32_t pm, zero;
            uint32_t* od;
            uint4* oh;
            auto kpack = [&](uint32_t (&k)[8], int j, int c, float r) {
                const uint32_t v = pack_bf16(accK[4 * j + c] * r, accK[4 * j + c + 1] * r);
                if (j == 3) { k[3] = t < 2 ? v : 0u; k[4] = t < 2 ? 0u : v; } else k[j + (j > 3)] = v;
            };
            auto batch = [&](auto c0, auto c1) {
                constexpr int n0 = c0.value, n1 = c1.value;
                wg_fence();
                static_for<n0, n1>([&](auto nc) {
                    constexpr int n = nc.value;
                    if (n == 4) { center(4); center(5); center(6); center(7); wg_fence(); }
                    const uint64_t desc = mkdesc(sb + (n < 56 ? slot_kv(n >> 3) + (n & 7) * 2048 : SM_QO + (n - 56) * 2048), 8192, 1024, 1) + wofs;
                    wgmma_rs56<1>(n < 28 ? accK : n < 56 ? accV : accQ, a[n % 28], desc, n % 28 != 0);
                });
                wg_commit();
                if (n0 > 0) wg_wait<1>();
            };
            const uint32_t hs = sb + tid * 16 + warp * 512;
            auto hand_over = [&](const uint32_t (&v)[8], int kv) {
                mbar_wait(bars + 8 * (kv ? B_DONE1 + 5 : B_DONEX), 0);
                sts4(hs + (kv ? SM_HALOV : SM_HALOK), v[0], v[1], v[2], v[3]); sts4(hs + (kv ? SM_HALOV : SM_HALOK) + 512, v[4], v[5], v[6], v[7]);
                if (w == 3) named_arrive(6 + kv, 96);
            };
            auto take_over = [&](uint32_t (&v)[8], int kv) {
                if (w == 0) mbar_wait(bars + 8 * (B_HALO + 2 * kv + wg), 0);
                const uint32_t ad = w ? hs + (kv ? SM_HALOV : SM_HALOK) - 1024 : kv ? sb + lane * 16 + wg * 1024 + SM_HALOV + 8192 : halo_kin(wg, lane);
                const uint4 u0 = lds4(ad), u1 = lds4(ad + (w || kv ? 512 : 16));
                v[0] = u0.x; v[1] = u0.y; v[2] = u0.z; v[3] = u0.w; v[4] = u1.x; v[5] = u1.y; v[6] = u1.z; v[7] = u1.w;
            };
            center(0); center(1); center(2); center(3);
            static_for<0, 7>([&](auto pc) {
                constexpr int p = pc.value;
                mbar_wait(bars + 8 * (B_FULLKV + p), 0);
                if (p == 0 && tid == 0) STAMP(26);
                if (p == 3 && tid == 0) STAMP(27);
                FST(4 + p);
                batch(Int<8 * p>(), Int<8 * p + 8>());
                if (p > 0 && leader) mbar_arrive(bars + 8 * (B_DONE1 + p - 1));
                #pragma unroll
                for (int s = 8 * p + 8; s < 8 * p + 16 && s < 28; s++) center(s);
                if (p == 1) {
                    const float c0 = bf_hi(mm0), c1 = bf_hi(mm1);
                    q0 = fmaf(c0, fmaf(c0, 64.f * NSQ, -2.f * p0), (g & 1) ? cA[0][1] + cA[1][1] : cA[0][0] + cA[1][0]) - D_ * (m0 - c0) * (m0 - c0);
                    q1 = fmaf(c1, fmaf(c1, 64.f * NSQ, -2.f * p1), (g & 1) ? cB[0][3] + cB[1][3] : cB[0][2] + cB[1][2]) - D_ * (m1 - c1) * (m1 - c1);
                    asm("" : "+f"(q0), "+f"(q1));
                    q0 = t == (g >> 1) ? q0 : 0.f; q1 = t == (g >> 1) ? q1 : 0.f;
                    pin2(__float_as_uint(q0), __float_as_uint(q1));
                }
                constexpr int PK = NSQ < 5 ? 5 : 4, NR = 28 - 4 * NSQ;
                if (p >= 2 && p < PK) {
                    #pragma unroll
                    for (int s = 4 * NSQ + NR * (p - 2) / (PK - 2); s < 4 * NSQ + NR * (p - 1) / (PK - 2); s++) { sq(q0, a[s][0]); sq(q1, a[s][1]); sq(q0, a[s][2]); sq(q1, a[s][3]); }
                    pin2(__float_as_uint(q0), __float_as_uint(q1));
                }
                if (p == PK - 1) { q0 = quad_sum(q0); q1 = quad_sum(q1); }
                if (p == PK) {
                    r0 = rsqrt_approx(fmaxf(q0 * (1.f / D_), 0.f) + LN_EPS); r1 = rsqrt_approx(fmaxf(q1 * (1.f / D_), 0.f) + LN_EPS);
                    reg_fence(accK);
                    #pragma unroll
                    for (int j = 0; j < 7; j++) kpack(Kc, j, 2, r1);
                    hand_over(Kc, 0);
                }
                if (p == PK + 1) {
                    #pragma unroll
                    for (int j = 0; j < 7; j++) kpack(Kb, j, 0, r0);
                    #pragma unroll
                    for (int j = 0; j < 8; j += 2) pin2(Kb[j], Kb[j + 1]);
                    ls0 = LOG2E_SCALE * r0; ls1 = LOG2E_SCALE * r1;
                    pm = (2 * t <= g ? 0xFFFFu : 0u) | (2 * t + 1 <= g ? 0xFFFF0000u : 0u);
                    zero = never; asm volatile("" : "+r"(zero));
                    pin2(__float_as_uint(ls0), __float_as_uint(ls1)); pin2(pm, zero);
                }
                if (p == 2) ep = get_tag();
                if (p == 6) {
                    tl = &sc->tiles[ep & 1];
                    const int tt = 2 * tb + (w >> 1);
                    od = tl->o + tt * 14336 + (7 * hp) * 256 + (2 * (2 * (w & 1) + wg)) * 32 + lane;
                    oh = sc->hint_o + (tt * 32 + hp * 4 + (w & 1) * 2 + wg) * 2 + (lane & 1);
                    pin2((uint32_t)(uint64_t)od, (uint32_t)((uint64_t)od >> 32));
                    pin2((uint32_t)(uint64_t)oh, (uint32_t)((uint64_t)oh >> 32));
                }
            });
            if (tid == 0) STAMP(1);
            FST(11);
            mbar_wait(bars + 8 * B_FQ, 0);
            batch(Int<56>(), Int<60>());
            reg_fence(accV);
            if (leader) mbar_arrive(bars + 8 * (B_DONE1 + 6));
            if (tid == 0) STAMP(2);
            FST(12);
            #pragma unroll
            for (int j = 0; j < 7; j++) Vc[j] = movtrans(pack_bf16(accV[4 * j + 2] * r1, accV[4 * j + 3] * r1));
            Vc[7] = Vc[6];
            hand_over(Vc, 1);
            batch(Int<60>(), Int<66>());
            #pragma unroll
            for (int j = 0; j < 7; j++) {
                Vb[j] = movtrans(pack_bf16(accV[4 * j] * r0, accV[4 * j + 1] * r0));
                Vc[j] |= zero;
            }
            batch(Int<66>(), Int<72>());
            #pragma unroll
            for (int j = 0; j < 7; j++) pin2(Vb[j], Vc[j]);
            mbar_wait(bars + 8 * (B_FQ + 1), 0);
            FST(13);
            if (w > 0 && lane < 2) { const uint32_t now = gtime32(); st_relaxed4(oh, ep, now, ep, now); }
            batch(Int<72>(), Int<84>());
            FST(14);
            named_sync(1 + wg, 128);
            take_over(Ka, 0);
            if (tid == 0) STAMP(3);
            wg_wait<0>();
            reg_fence(accQ);
            if (tid == 0) STAMP(4);
            FST(15);
            const bool first = (tb == 0 && w == 0);
            uint32_t pA[2], pB0[2], pB1[2], pC[2], z0[2], z1[2];
            float sA[2][4] = {}, sB[2][4] = {}, sC[2][4] = {}, e[2][4], inv[2][2];
            #pragma unroll
            for (int k = 0; k < 2; k++) {
                #pragma unroll
                for (int h = 0; h < 2; h++) {
                    const float* qq = accQ + 12 * h + 8 * k;
                    uint32_t a2 = pack_bf16(qq[4], qq[5]), a3 = pack_bf16(qq[6], qq[7]);
                    if (h == 0 && k == 1) { a2 |= zero; a3 |= zero; }
                    const uint32_t a0 = pack_bf16(qq[0], qq[1]), a1 = pack_bf16(qq[2], qq[3]);
                    mma16816(sB[h], a0, a1, a2, a3, Kb[4 * h + 2 * k], Kb[4 * h + 2 * k + 1]);
                    mma16816(sA[h], a0, a1, a2, a3, Ka[4 * h + 2 * k], Ka[4 * h + 2 * k + 1]);
                    mma16816(sC[h], a0, a1, a2, a3, Kc[4 * h + 2 * k], Kc[4 * h + 2 * k + 1]);
                }
            }
            if (VTAKE == 0) take_over(Va, 1);
            #pragma unroll
            for (int h = 0; h < 2; h++) {
                const bool n0 = pm & 1, n1 = (int)pm < 0;
                const float l00 = n0 ? sB[h][0] : (first ? -INFINITY : sA[h][0]), l01 = n1 ? sB[h][1] : (first ? -INFINITY : sA[h][1]);
                const float l10 = n0 ? sC[h][2] : sB[h][2], l11 = n1 ? sC[h][3] : sB[h][3];
                const float x0 = -ls0 * quad_max(fmaxf(l00, l01)), x1 = -ls1 * quad_max(fmaxf(l10, l11));
                e[h][0] = ex2(fmaf(l00, ls0, x0)); e[h][1] = ex2(fmaf(l01, ls0, x0)); e[h][2] = ex2(fmaf(l10, ls1, x1)); e[h][3] = ex2(fmaf(l11, ls1, x1));
            }
            if (VTAKE == 1) { pin4(never, e[0][0], e[0][2], e[1][0], e[1][2]); take_over(Va, 1); }
            #pragma unroll
            for (int h = 0; h < 2; h++) {
                inv[h][0] = rcp_approx(quad_sum(e[h][0] + e[h][1])); inv[h][1] = rcp_approx(quad_sum(e[h][2] + e[h][3]));
                const uint32_t P0 = DEFER ? pack_bf16(e[h][0], e[h][1]) : pack_bf16(e[h][0] * inv[h][0], e[h][1] * inv[h][0]);
                const uint32_t P1 = DEFER ? pack_bf16(e[h][2], e[h][3]) : pack_bf16(e[h][2] * inv[h][1], e[h][3] * inv[h][1]);
                pB0[h] = P0 & pm; pA[h] = P0 & ~pm; pC[h] = P1 & pm; pB1[h] = P1 & ~pm; z0[h] = P0 & zero; z1[h] = P1 & zero;
            }
            float o[8][4];
            #pragma unroll
            for (int j = 0; j < 8; j++) {
                o[j][0] = o[j][1] = o[j][2] = o[j][3] = 0.f;
                mma16816(o[j], pB0[j >> 2], pB1[j >> 2], z0[j >> 2], pC[j >> 2], Vb[j - (j >> 2)], Vc[j - (j >> 2)]);
            }
            if (tid == 0) STAMP(12);
            FST(16);
            if (VTAKE == 2) take_over(Va, 1);
            if (tid == 0) STAMP(16);
            #pragma unroll
            for (int j = 0; j < 8; j++) mma1688(o[j], pA[j >> 2], z1[j >> 2], Va[j - (j >> 2)]);
            #pragma unroll
            for (int j = 0; j < 7; j++) {
                float v[4];
                #pragma unroll
                for (int c = 0; c < 4; c++) {
                    v[c] = j < 3 ? o[j][c] : j > 3 ? o[j + 1][c] : (t < 2 ? o[3][c] : o[4][c]);
                    if (DEFER) v[c] *= j < 3 ? inv[0][c >> 1] : j > 3 ? inv[1][c >> 1] : (t < 2 ? inv[0][c >> 1] : inv[1][c >> 1]);
                }
                od[j * 256] = pack_bf16(v[0], v[1]);
                od[j * 256 + 32] = pack_bf16(v[2], v[3]);
            }
            if (lane == 0) mbar_arrive(bars + 8 * B_DONEQ);
            if (tid == 0) STAMP(5);
            FST(17);
        }
        const int z = get_tag() - ep, slot1 = slot + z, tid1 = tid + z, warp1 = warp + z;
        ep += z;
        {
        ASSIGN_WORK(slot1)
        const int tid = tid1, lane = tid & 31, wg = warp1 >> 2, w = warp1 & 3, g = lane >> 2, t = lane & 3;
        tl = &sc->tiles[ep & 1];
        const uint32_t live = wg ^ 1;
        uint32_t rb0, rb1, late[14];
        const unsigned short* pb = (const unsigned short*)(live ? b2 + tt2 * 64 : b1 + ft * 64) + 16 * w + g;
        auto stage_late = [&]() {
            #pragma unroll
            for (int c = 0; c < 14; c++) asm volatile("st.shared.u32 [%0], %1;" :: "r"(sb + SM_H + wg * 8192 + (tid & 127) * 4 + c * 512), "r"(late[c]) : "memory");
            fence_async_smem();
            named_sync(1 + wg, 128);
        };
        auto store_late = [&](bool on, uint32_t* p) {
            #pragma unroll
            for (int c = 0; c < 4; c++)
                if (elect() && on && (c < 3 || w < 2)) bulk_st(p + (4 * c + w) * 256, sb + SM_H + wg * 8192 + (4 * c + w) * 512, 512);
            asm volatile("cp.async.bulk.commit_group;" ::: "memory");
        };
        auto undef = [](float (&v)[56]) {
            #pragma unroll
            for (int i = 0; i < 56; i++) asm volatile("" : "=f"(v[i]));
        };
        {
            float acc[56];
            const int hrow = 32 * (w >> 1) + 2 * ((lane & 7) + (lane & 8)) + (w & 1);
            const uint32_t ha = sb + SM_H + hrow * 128 + (((lane >> 4) ^ (hrow & 7)) << 4);
            uint4* sp = sc->stats + tt2 * 256 + 16 * w + g + 8 * (t & 1);
            uint4* sp_out = sp + q * 64;
            const uint4* sp_in = sp + (t & 2) * 64;
            uint32_t* hd = tl->hn + ((q >> 1) * 32 + (tt2 >> 1)) * 7168 + (q & 1) * 3584 + (tt2 & 1) * 128 + w * 32 + lane;
            pin_ptr(never, sp_out); pin_ptr(never, sp_in); pin_ptr(never, hd);
            float s0 = 0.f, s1 = 0.f, q0 = 0.f, q1 = 0.f, s2 = 0.f, s3 = 0.f, q2 = 0.f, q3 = 0.f;
            auto sums = [&](int j0, int j1) {
                #pragma unroll
                for (int j = j0; j < j1; j++) {
                    s0 += acc[4 * j]; s2 += acc[4 * j + 1]; q0 = fmaf(acc[4 * j], acc[4 * j], q0); q2 = fmaf(acc[4 * j + 1], acc[4 * j + 1], q2);
                    s1 += acc[4 * j + 2]; s3 += acc[4 * j + 3]; q1 = fmaf(acc[4 * j + 2], acc[4 * j + 2], q1); q3 = fmaf(acc[4 * j + 3], acc[4 * j + 3], q3);
                }
            };
            if (live) {
                mbar_wait(bars + 8 * B_FULLWO, 0);
                #pragma unroll
                for (int jp = 0; jp < 7; jp++) {
                    uint32_t xx[4];
                    ldsm4(xx, hcol(ha, jp));
                    #pragma unroll
                    for (int r = 0; r < 4; r++) { acc[8 * jp + 2 * r] = bf_lo(xx[r]); acc[8 * jp + 2 * r + 1] = bf_hi(xx[r]); }
                }
                reg_fence(acc);
                if (SPIN2) { named_sync(12, 256); spin_mma(bars + 8 * B_FULLX, never); }
                auto od_ = [&](int s) { return mkdesc(sb + SM_QO + s * 2048, 1024, 128, 0); };
                auto wd_ = [&](int s) { return mkdesc(sb + slot_wo(s >> 2) + (s & 3) * 2048, 8192, 1024, 1); };
                float accl[32], accr[24];
                #pragma unroll
                for (int i = 0; i < 5; i++) {
                    if (i < 4) mbar_wait(bars + 8 * (B_FULLO + i), 0);
                    if (i == 0 && tid == 0) STAMP(7);
                    if (i == 1) { rb0 = ld_u16(pb); rb1 = ld_u16(pb + 8); }
                    wg_fence();
                    #pragma unroll
                    for (int ss = 0; ss < 7; ss++) {
                        if (i < 3) wgmma_ss112<0, 1>(acc, od_(7 * i + ss), wd_(7 * i + ss));
                        else if (i == 4) wgmma_ss64<0, 1>(accl, od_(21 + ss), wd_(21 + ss));
                        else if (ss == 0) wgmma_ss48<0, 1, 0>(accr, od_(21), wd_(21) + 512);
                        else wgmma_ss48<0, 1>(accr, od_(21 + ss), wd_(21 + ss) + 512);
                    }
                    wg_commit();
                    if (i > 0) {
                        wg_wait<1>();
                        if (i == 3) {
                            reg_fence(acc);
                            #pragma unroll
                            for (int c = 0; c < 32; c++) accl[c] = __uint_as_float(__float_as_uint(acc[c]) | never);
                            reg_fence(accl);
                        }
                        if (i < 4 && leader) mbar_arrive(bars + 8 * (B_DONEO + i - 1));
                    }
                }
                reg_fence(accr);
                #pragma unroll
                for (int c = 0; c < 24; c++) acc[32 + c] += accr[c];
                sums(8, 14);
                pin4(never, s0, s1, s2, s3); pin4(never, q0, q1, q2, q3);
                wg_wait<0>();
                reg_fence(accl);
                #pragma unroll
                for (int c = 0; c < 32; c++) acc[c] = accl[c];
                if (leader) mbar_arrive(bars + 8 * (B_DONEO + 3));
                if (tid == 0) STAMP(8);
            } else { undef(acc); if (SPIN2) named_arrive(12, 256); }
            if (live || (DRY2 && w == 3)) {
            sums(0, 8);
            s0 += s2; s1 += s3; q0 += q2; q1 += q3;
            float sr = ((t & 1) ? s1 : s0) + __shfl_xor_sync(0xffffffffu, (t & 1) ? s0 : s1, 1), qr = ((t & 1) ? q1 : q0) + __shfl_xor_sync(0xffffffffu, (t & 1) ? q0 : q1, 1);
            sr += __shfl_xor_sync(0xffffffffu, sr, 2); qr += __shfl_xor_sync(0xffffffffu, qr, 2);
            st_relaxed4_if(t < 2 * live, sp_out, __float_as_uint(sr), __float_as_uint(qr), ep);
            const uint32_t tp = clock32();
            if (live) named_arrive(5, 256);
            if (tid == 0) STAMP(9);
            #pragma unroll
            for (int jp = 0; jp < 7; jp++)
                stsm4_if(live, hcol(ha, jp), pack_bf16(acc[8 * jp], acc[8 * jp + 1]), pack_bf16(acc[8 * jp + 2], acc[8 * jp + 3]),
                      pack_bf16(acc[8 * jp + 4], acc[8 * jp + 5]), pack_bf16(acc[8 * jp + 6], acc[8 * jp + 7]));
            uint4 v0, v1;
            if (POLL0) { while (clock32() - tp < POLL0) {} __syncwarp(); }
            do { v0 = ld_relaxed4(sp_in); v1 = ld_relaxed4(sp_in + 64); } while (live && __any_sync(0xffffffffu, v0.w != ep || v1.w != ep));
            if (tid == 0) STAMP(10);
            sr = __uint_as_float(v0.x) + __uint_as_float(v1.x); qr = __uint_as_float(v0.y) + __uint_as_float(v1.y);
            sr += __shfl_xor_sync(0xffffffffu, sr, 2); qr += __shfl_xor_sync(0xffffffffu, qr, 2);
            const float m = sr * (1.f / D_), var = fmaxf(qr * (1.f / D_) - m * m, 0.f);
            const float r = rsqrt_approx(fmaf(var, 4.f + 4.f * LN_EPS, 4.f * LN_EPS * LN_EPS)), c = -m * r;
            const float r0 = __shfl_sync(0xffffffffu, r, lane & ~1), c0 = __shfl_sync(0xffffffffu, c, lane & ~1);
            const float r1 = __shfl_sync(0xffffffffu, r, lane | 1), c1 = __shfl_sync(0xffffffffu, c, lane | 1);
            #pragma unroll
            for (int j = 0; j < 14; j++) st_global_if(live, hd + j * 256, pack_bf16(fmaf(acc[4 * j], r0, c0), fmaf(acc[4 * j + 1], r0, c0)));
            if (never) mbar_arrive(bars);
            #pragma unroll
            for (int j = 0; j < 14; j++) late[j] = pack_bf16(fmaf(acc[4 * j + 2], r1, c1), fmaf(acc[4 * j + 3], r1, c1));
            if (tid == 0) STAMP(11);
            }
        }
        if (!live) {
            if (w < 2) check_tiles<0>(w, 2, 4, tl->o + tt2 * 14336, false, lane, true);
            rb0 = ld_u16(pb); rb1 = ld_u16(pb + 8);
            auto reset_tiles = [&](int v, int i0, int i1) {
                const int l = slot * 48 + v * 16 + lane / 2;
                #pragma unroll
                for (int i = i0; i < i1; i++)
                    st_relaxed4_if(i < 6 || l < sizeof(Tiles) / 128 - 6 * 6144, (uint4*)&sc->tiles[~ep & 1] + (i * 6144 + l) * 8 + (lane & 7), EMPTY, EMPTY, EMPTY);
            };
            if (CL_N && w < 3) { mbar_wait(bars + 8 * (B_DONEO + CL_P2), 0); reset_tiles(w, 0, CL_N); }
            named_sync(5, 256);
            auto phase3 = [&](auto nc) {
                constexpr int NC = nc.value;
                float acc[4 * NC];
                uint32_t* ud = tl->u + (pr3 * 28 + (ft >> 1) + (NC == 14 ? 4 : 0)) * 7168 + col3 * 256 + (ft & 1) * 128 + w * 32 + lane;
                #pragma unroll
                for (int j = 0; j < 4 * NC; j++) acc[j] = 0.5f * bf_lo((j & 2) ? rb1 : rb0);
                #pragma unroll 1
                for (uint32_t pass = DRY3 ? never : 1; pass < 2; pass++) {
                    if (pass) {
                        mix_mainloop<32>(TSVAL acc, leader);
                        if (leader) STAMP(14);
                    }
                    uint32_t pk[NC];
                    #pragma unroll
                    for (int j = 0; j < NC; j++) {
                        const float k = j < GDEP ? GELU_K1 : __uint_as_float(__float_as_uint(GELU_K1) | (pk[j - GDEP] & never));
                        pk[j] = pack_bf16(gelu_half(acc[4 * j], k), gelu_half(acc[4 * j + 1], k));
                        st_global_if(pass, ud + j * 256, pk[j]);
                    }
                }
                if (leader) STAMP(15);
                #pragma unroll
                for (int j = 0; j < NC; j++) late[j] = pack_bf16(gelu_half(acc[4 * j + 2], GELU_K1), gelu_half(acc[4 * j + 3], GELU_K1));
                if (NC == 14) {
                    stage_late();
                    mbar_wait(bars + 8 * (B_FULLB + LATE_AT4), 1);
                    store_late(true, tl->u + (pr3 * 28 + (ft >> 1) + 14) * 7168 + col3 * 256 + (ft & 1) * 128);
                } else {
                    #pragma unroll
                    for (int c = 0; c < NC; c++) st_global_if(1, ud + 4 * 7168 + c * 256, late[c]);
                }
            };
            if (early) phase3(Int<10>()); else phase3(Int<14>());
            if (w) {
                if (early && w == 1) fetch_times(TSVAL sc->go, 1, ep, lane);
                check_tiles<2>(CH_U - 1 + w, 3, 28, tl->u + (q >> 1) * 28 * 7168 + (q & 1) * 3584, false, lane, false);
                if (CL_N < 7) { mbar_wait(bars + 8 * (B_DONE + CL_AT), 1); reset_tiles(w - 1, CL_N, 7); }
            }
            if (leader) mbar_wait_wd(bars + 8 * B_END, 0);
            return;
        }
        {
            float acc[56];
            const uint32_t ad = sb + SM_H + (16 * w + (lane & 15)) * 128 + (((lane >> 4) ^ (lane & 7)) << 4);
            const float bb0 = bf_lo(rb0), bb1 = bf_lo(rb1);
            named_sync(1, 128);
            #pragma unroll
            for (int jp = 0; jp < 7; jp++) {
                uint32_t hh[4];
                ldsm4(hh, hcol(ad, jp));
                #pragma unroll
                for (int r = 0; r < 4; r++) { acc[8 * jp + 2 * r] = bf_lo(hh[r]) + ((r & 1) ? bb1 : bb0); acc[8 * jp + 2 * r + 1] = bf_hi(hh[r]) + ((r & 1) ? bb1 : bb0); }
            }
            named_sync(1, 128);
            stage_late();
            if (tid == 0) STAMP(39);
            mbar_wait(bars + 8 * (B_FULLB + LATE_AT), 0);
            store_late(true, tl->hn + ((q >> 1) * 32 + 16 + (tt2 >> 1)) * 7168 + (q & 1) * 3584 + (tt2 & 1) * 128);
            check_tiles<1>(CH_H + w, 4, 32, tl->hn + pr3 * 32 * 7168 + col3 * 256, early, lane, false);
            mbar_wait(bars + 8 * (B_DONE + START4), 0);
            mix_mainloop<28>(TSVAL acc, leader);
            if (leader) mbar_arrive(bars + 8 * B_END);
            if (tid == 0) STAMP(18);
            #pragma unroll
            for (int jp = 0; jp < 7; jp++)
                stsm4_if(1, hcol(ad, jp), pack_bf16(acc[8 * jp], acc[8 * jp + 1]), pack_bf16(acc[8 * jp + 2], acc[8 * jp + 3]),
                         pack_bf16(acc[8 * jp + 4], acc[8 * jp + 5]), pack_bf16(acc[8 * jp + 6], acc[8 * jp + 7]));
            fence_async_smem();
            __syncwarp();
            if (elect()) {
                tma2d_store(&tm_out64, c64, tt2 * 64 + 16 * w, sb + SM_H + w * 2048);
                tma2d_store(&tm_out48, c48, tt2 * 64 + 16 * w, sb + SM_H + 8192 + w * 2048);
            }
            asm volatile("cp.async.bulk.commit_group;" ::: "memory");
            asm volatile("cp.async.bulk.wait_group.read 0;" ::: "memory");
            if (tid == 0) { sc->epoch[slot] = ep; STAMP(19); }
        }
        }
    } else {
        asm volatile("setmaxnreg.dec.sync.aligned.u32 56;");
        int warp2; asm("mov.u32 %0, %1;" : "=r"(warp2) : "r"(warp));
        if (warp2 > 8) {
            ASSIGN_WORK(get_slot())
            if (slot >= 128) return;
            uint32_t ep, cl;
            uint4* const oh = sc->hint_o + (2 * tb * 32 + hp * 4) * 2 + (lane & 3);
            uint4* const hu = sc->hint_u + (early ? ech * 8 + ft : 40 + q * 20 + ft) * 2;
            if (warp == 10) {
                post_hint(sc->hint_h + (q * 32 + tt2) * 2, 0, lane);
                post_hint(hu, 0, lane);
            }
            if (warp == 11) {
                ep = ld_volatile(&sc->epoch[slot]) + 1; cl = ld_acquire(&sc->clean);
                post_hint(sc->hint_k + (tb * 8 + hp) * 2, 0, lane);
                if (lane < (tb < 15 ? 4 : 0)) st_relaxed4(oh + 128, 0, 0, 0, 0);
                if (lane < (tb ? 0 : 4)) st_relaxed4(oh, 0, 0, 0, 0);
            }
            if (elect()) {
                if (warp == 9) {
                    #pragma unroll
                    for (int i = B_DONE1; i < B_DONEO; i++) mbar_init(bars + 8 * i, i < B_DONEX ? 2 : i == B_DONEX ? 8 : 9);
                }
                #pragma unroll
                for (int i = 0; i < 54; i++) mbar_init(bars + 8 * (B_DONEO + i) + (warp - 9) * 432, 1);
                asm volatile("fence.mbarrier_init.release.cluster;" ::: "memory");
            }
            named_sync(8, 128);
            if (warp < 11) mbar_expect(sb + SM_RAW + 8 * (tid - 288), early && tid >= 292 && tid < 324 ? 10240 : 14336);
            if (warp == 9) { named_arrive(4, 64); named_arrive(9, 160); named_arrive(10, 160); }
            if (warp < 11) {
                ep = get_tag();
                mbar_wait(bars + 8 * (B_DONE1 + HALO_AT), 0);
                #pragma unroll 1
                for (int kv = 0; kv < 2; kv++) {
                    uint4 v0 = {}, v1 = {}, v2 = {};
                    if (tb > 0) {
                        const uint4* hg = sc->halo + ((((tb - 1) * 8 + hp) * 2 + warp - 9) * 2 + kv) * 96 + lane;
                        if (kv == 0) while (ld_relaxed(sc->hint_k + ((tb - 1) * 8 + hp) * 2) != ep) {}
                        do { v0 = ld_relaxed4(hg); v1 = ld_relaxed4(hg + 32); v2 = ld_relaxed4(hg + 64); } while (!__all_sync(0xffffffffu, v0.w == ep && v1.w == ep && v2.w == ep));
                    }
                    if (kv) mbar_wait(bars + 8 * (B_DONE1 + 5), 0);
                    const uint32_t hs = kv ? sb + lane * 16 + (warp - 9) * 1024 + SM_HALOV + 8192 : halo_kin(warp - 9, lane);
                    sts4(hs, v0.x, v0.y, v0.z, v1.x); sts4(hs + (kv ? 512 : 16), v1.y, v1.z, v2.x, v2.y);
                    __syncwarp();
                    if (lane == 0) mbar_arrive(bars + 8 * (B_HALO + 2 * kv + warp - 9));
                }
                if (tid == 288) STAMP(21);
            } else {
                const long long t0 = clock64();
                while (__any_sync(0xffffffffu, (int)(cl - ep) < 0)) { cl = ld_acquire(&sc->clean); if (clock64() - t0 > WD_CLKS) __trap(); }
                if (lane == 0) { *(volatile uint32_t*)(smem_raw + SM_TAG) = ep; mbar_arrive(bars + 8 * B_CLR); }
                uint4* hg = sc->halo + (tb * 8 + hp) * 384 + lane;
                #pragma unroll 1
                for (int kv = 0; kv < 2; kv++) {
                    const uint32_t hs = sb + lane * 16 + 3072 + (kv ? SM_HALOV : SM_HALOK);
                    named_sync(6 + kv, 96);
                    #pragma unroll
                    for (int p = 0; p < 2; p++) {
                        const uint4 u0 = lds4(hs + p * 4096), u1 = lds4(hs + p * 4096 + 512);
                        st_relaxed4(hg + p * 192, u0.x, u0.y, u0.z, ep); st_relaxed4(hg + p * 192 + 32, u0.w, u1.x, u1.y, ep); st_relaxed4(hg + p * 192 + 64, u1.z, u1.w, ep, ep);
                    }
                    hg += 96;
                    if (kv == 0) {
                        post_hint(sc->hint_k + (tb * 8 + hp) * 2, ep, lane);
                        #pragma unroll
                        for (int j = 0; j < 6; j++) st_relaxed4(hg + j * 32 + (j / 3) * 96, 0, 0, 0, 0);
                    }
                }
                const uint32_t now = gtime32() - LATE_O;
                if (lane < (tb < 15 ? 4 : 0)) st_relaxed4(oh + 128, ep, now, ep, now);
                if (lane < (tb ? 0 : 4)) st_relaxed4(oh, ep, now, ep, now);
                if (lane == 0) STAMP(23);
                if (lane == 0) mbar_arrive(bars + 8 * B_DONEQ);
            }
            if (warp > 9) {
                const Tiles* const tl = &sc->tiles[ep & 1];
                check_tiles<1>(11 - warp, 2, CH_H, tl->hn + pr3 * 32 * 7168 + col3 * 256, early, lane, true);
                if (warp == 10) {
                    mbar_wait(bars + 8 * (B_DONE + (early ? HINT_E : HINT_U)), 0);
                    post_time(hu, ep, lane);
                }
                if (warp == 11) {
                    mbar_wait(bars + 8 * (B_DONE + (early ? POLL_E : POLL_N)), 0);
                    fetch_times(TSVAL sc->go, 0, ep, lane);
                }
                check_tiles<2>(11 - warp, 2, CH_U, tl->u + (q >> 1) * 28 * 7168 + (q & 1) * 3584, false, lane, true);
            } else {
                int aslot = 0;
                if (lane == 0) { prefetch_map(&tm_out64); prefetch_map(&tm_out48); }
                #pragma unroll
                for (int i = 0; i < HINT_F; i++) mbar_wait(bars + 8 * (B_FULLO + i), 0);
                post_time(sc->hint_h + (q * 32 + tt2) * 2, ep, lane);
                #pragma unroll 1
                for (int i = 0; i < 30; i++) {
                    if (i == POLL_I && !early) fetch_times(TSVAL sc->go, 1, ep, lane);
                    int d = 2 * i - 11 + (i >= A4_FROM ? A4_DLY : 0);
                    if (early) d = i < 16 ? 1 + (i - NA_SLOTS) * AE_END / 9 : max(d, AE_W2);
                    mbar_wait(bars + 8 * (i < NA_SLOTS ? B_DONEQ + ((A_SCHED >> (4 * i)) & 15) : B_DONE + (d & 31)), d >= 32);
                    if (elect()) {
                        const uint32_t bar = bars + 8 * (B_FULLA + (i & 15)), dst = sb + SM_ARING + aslot * 16384;
                        mbar_expect(bar, 16384);
                        if (i < 16) tma5d(dst, &tm_w1, ft * 64, (i & 7) * 8, i >> 3, bar);
                        else tma5d(dst, &tm_w2, tt2 * 64, 8 * (i < 20 ? i & 1 : i < 25 ? i - 18 : i - 23), i < 20 ? (i >> 1) & 1 : i >= 25, bar);
                    }
                    aslot = aslot == NA_SLOTS - 1 ? 0 : aslot + 1;
                }
            }
        } else {
            const int slot0 = get_slot(), row0 = (slot0 >> 5) * 256 + (slot0 & 12) * 16;
            if (elect()) {
                prefetch_map(&tm_x);
                #pragma unroll
                for (int i = 0; i < 7; i++) mbar_init(bars + 8 * i, 1);
                asm volatile("fence.mbarrier_init.release.cluster;" ::: "memory");
            }
            named_arrive(0, 288);
            if (elect()) {
                #pragma unroll 1
                for (int kb = 0; kb < 7; kb++) {
                    load_x(kb, row0);
                    if (kb == 0) STAMP(22);
                }
                #pragma unroll
                for (int i = 7; i < B_DONE1; i++) mbar_init(bars + 8 * i, 1);
                asm volatile("fence.mbarrier_init.release.cluster;" ::: "memory");
            }
            named_arrive(8, 128);
            ASSIGN_WORK(get_slot())
            if (slot >= 128) return;
            #pragma unroll 1
            for (int kb = 0; kb < 7; kb++) {
                if (kb == 6) { named_sync(4, 64); mbar_wait(bars + 8 * B_DONEX, 0); }
                if (elect()) {
                    const uint32_t st = sb + slot_kv(kb), bar = bars + 8 * (B_FULLKV + kb);
                    mbar_expect(bar, 16384);
                    #pragma unroll
                    for (int i = 0; i < 2; i++) {
                        const int n = 2 * kb + (i ^ (G & 1));
                        tma2d(st + (n & 1) * 8192, &tm_wqkv, (n < 7 ? 448 : 896) + wcol, (n < 7 ? n : n - 7) * 64, bar);
                    }
                }
            }
            if (elect()) {
                mbar_expect(bars + 8 * B_FQ, 32768);
                mbar_expect(bars + 8 * (B_FQ + 1), 24576);
                #pragma unroll 1
                for (int i = 0; i < 7; i++) { const int j = i == 6 ? i : i ^ (G & 1); tma2d(sb + SM_QO + j * 8192, &tm_wqkv, wcol, j * 64, bars + 8 * (B_FQ + (i >> 2))); }
                mbar_expect(bars + 8 * B_FULLWO, 512 * 112 * 2);
            }
            #pragma unroll 1
            for (int i = 0; i < 7; i++) {
                const int kb = ((q & 1 ? WO_ORD1 : WO_ORD0) >> (4 * i)) & 7;
                if (kb < 5) mbar_wait(bars + 8 * (B_DONE1 + kb), 0);
                if (elect()) {
                    tma2d(sb + slot_wo(kb), &tm_wo64, c64, kb * 64, bars + 8 * B_FULLWO);
                    tma2d(sb + slot_wo(kb) + 8192, &tm_wo48, c48, kb * 64, bars + 8 * B_FULLWO);
                }
            }
            if (elect()) {
                tma2d(sb + SM_H, &tm_xr64, c64, tt2 * 64, bars + 8 * B_FULLWO);
                tma2d(sb + SM_H + 8192, &tm_xr48, c48, tt2 * 64, bars + 8 * B_FULLWO);
            }
            if (smem_u32(smem_raw) != SB) __trap();
            const uint32_t ep = get_tag();
            const Tiles* const tl = &sc->tiles[ep & 1];
            mbar_wait(bars + 8 * (B_DONE1 + 6), 0);
            const uint32_t t_o = last_hint(TSVAL sc->hint_o + (tt2 * 32 + lane) * 2, ep, 38);
            mbar_wait(bars + 8 * B_DONEQ, 0);
            wait_until(t_o + GO_O);
            if (elect()) {
                #pragma unroll
                for (int i = 0; i < 4; i++) {
                    bulk_ld(sb + SM_QO + i * 14336, tl->o + tt2 * 14336 + i * 3584, 14336, sb + SM_RAW + 8 * i);
                }
            }
            if (lane == 0) STAMP(20);
            if (SPIN2) { wait_until(t_o + GO_O + STOP2); if (lane == 0) mbar_arrive(bars + 8 * B_FULLX); }
            mbar_wait(bars + 8 * (B_DONEO + POLL_H), 0);
            const uint32_t* src = tl->hn + pr3 * 32 * 7168 + col3 * 256;
            uint32_t bytes = early ? 10240 : 14336, dst = sb + SM_BRING, top = dst + (early ? NE_SLOTS * 10240 : NB_SLOTS * 14336), raw = sb + SM_RAW + 32;
            auto issue = [&]() {
                if (elect()) bulk_ld(dst, src, bytes, raw);
                src += 7168; raw += 8; dst += bytes;
                if (dst == top) dst = sb + SM_BRING;
            };
            uint2 th;
            do { th = ld_relaxed2((const uint2*)sc->go + (lane & 15)); } while (!__all_sync(0xffffffffu, th.x == ep));
            STAMP(42);
            mbar_wait(bars + 8 * (B_DONEO + 3), 0);
            {
                uint32_t bit = 1, wait = ~1u;
                wait_until(__shfl_sync(0xffffffffu, th.y, 0) + GO_H);
                #pragma unroll 1
                do {
                    while (wait & bit) wait = __ballot_sync(0xffffffffu, (int)(gtime32() - th.y - GO_H) < 0);
                    if (bit == 1) STAMP(29);
                    issue();
                    bit *= 2;
                } while (dst != sb + SM_BRING);
            }
            uint32_t done = bars + 8 * B_DONE;
            #pragma unroll 1
            do { mbar_wait(done, 0); done += 8; issue(); } while (raw != sb + SM_RAW + 288);
            if (early) mbar_wait(bars + 8 * (B_DONE + 31), 0);
            src = tl->u + (q >> 1) * 28 * 7168 + (q & 1) * 3584; bytes = 14336; dst = sb + SM_BRING; top = dst + NB_SLOTS * 14336;
            done = bars + 8 * (B_DONE + 24);
            #pragma unroll 1
            for (uint32_t par = 0; par < 2; par++) {
                mbar_wait(bars + 8 * (B_GO + par), 0);
                const uint32_t ts = *(volatile uint32_t*)(smem_raw + SM_TIME + 128 * par + 4 * lane);
                if (par) done = bars + 8 * B_DONE;
                uint32_t bit = 1, wait = ~1u;
                wait_until(__shfl_sync(0xffffffffu, ts, 0));
                #pragma unroll 1
                do {
                    while (wait & bit) wait = __ballot_sync(0xffffffffu, (int)(gtime32() - ts) < 0);
                    if (bit == 1) STAMP(par ? 36 : 30);
                    mbar_wait(done, par); done += 8;
                    issue();
                    bit *= 2;
                } while (bit != (par ? 1 << 20 : 1 << 8));
            }
        }
    }
}

typedef CUresult (*EncodeFn)(CUtensorMap*, CUtensorMapDataType, cuuint32_t, void*, const cuuint64_t*, const cuuint64_t*, const cuuint32_t*,
                             const cuuint32_t*, CUtensorMapInterleave, CUtensorMapSwizzle, CUtensorMapL2promotion, CUtensorMapFloatOOBfill);

void make_map(EncodeFn fn, CUtensorMap* tm, const void* ptr, int rank, const cuuint64_t* dims, const cuuint64_t* strides, const cuuint32_t* box, CUtensorMapSwizzle sw) {
    cuuint32_t es[5] = {1, 1, 1, 1, 1};
    fn(tm, CU_TENSOR_MAP_DATA_TYPE_BFLOAT16, rank, const_cast<void*>(ptr), dims, strides, box, es, CU_TENSOR_MAP_INTERLEAVE_NONE, sw,
       CU_TENSOR_MAP_L2_PROMOTION_NONE, CU_TENSOR_MAP_FLOAT_OOB_FILL_NONE);
}

}

extern "C" void kernel_launch(void* const* d_in, const int* in_sizes, int n_in, void* d_out, int out_size) {
    const __nv_bfloat16* x = (const __nv_bfloat16*)d_in[0];
    const __nv_bfloat16* wqkv = (const __nv_bfloat16*)d_in[1];
    const __nv_bfloat16* wo = (const __nv_bfloat16*)d_in[2];
    const __nv_bfloat16* w1 = (const __nv_bfloat16*)d_in[4];
    const __nv_bfloat16* b1 = (const __nv_bfloat16*)d_in[5];
    const __nv_bfloat16* w2 = (const __nv_bfloat16*)d_in[6];
    const __nv_bfloat16* b2 = (const __nv_bfloat16*)d_in[7];

    void* fnp = nullptr; cudaDriverEntryPointQueryResult qr;
    cudaGetDriverEntryPoint("cuTensorMapEncodeTiled", &fnp, cudaEnableDefault, &qr);
    EncodeFn fn = (EncodeFn)fnp;
    CUtensorMap tx, twqkv, two64, two48, tw1, tw2, txr64, txr48, tout64, tout48;
    { cuuint64_t d[3] = {448, 2, 1024}, s[2] = {896, 1792}; cuuint32_t b[3] = {64, 1, 64}; make_map(fn, &tx, x, 3, d, s, b, CU_TENSOR_MAP_SWIZZLE_128B); }
    { cuuint64_t d[2] = {1344, 448}, s[1] = {2688}; cuuint32_t b[2] = {64, 64}; make_map(fn, &twqkv, wqkv, 2, d, s, b, CU_TENSOR_MAP_SWIZZLE_128B); }
    { cuuint64_t d[2] = {448, 448}, s[1] = {896}; cuuint32_t b[2] = {64, 64}; make_map(fn, &two64, wo, 2, d, s, b, CU_TENSOR_MAP_SWIZZLE_128B); }
    { cuuint64_t d[2] = {448, 448}, s[1] = {896}; cuuint32_t b[2] = {48, 64}; make_map(fn, &two48, wo, 2, d, s, b, CU_TENSOR_MAP_SWIZZLE_128B); }
    { cuuint64_t d[5] = {1792, 8, 2, 64, 2}, s[4] = {2 * 3584, 3584, 32 * 3584, 16 * 3584}; cuuint32_t b[5] = {64, 8, 2, 8, 1}; make_map(fn, &tw1, w1, 5, d, s, b, CU_TENSOR_MAP_SWIZZLE_128B); }
    { cuuint64_t d[5] = {2048, 8, 2, 56, 2}, s[4] = {4096, 16 * 4096, 32 * 4096, 8 * 4096}; cuuint32_t b[5] = {64, 8, 2, 8, 1}; make_map(fn, &tw2, w2, 5, d, s, b, CU_TENSOR_MAP_SWIZZLE_128B); }
    { cuuint64_t d[2] = {448, 2048}, s[1] = {896}; cuuint32_t b[2] = {64, 64}; make_map(fn, &txr64, x, 2, d, s, b, CU_TENSOR_MAP_SWIZZLE_128B); }
    { cuuint64_t d[2] = {448, 2048}, s[1] = {896}; cuuint32_t b[2] = {48, 64}; make_map(fn, &txr48, x, 2, d, s, b, CU_TENSOR_MAP_SWIZZLE_128B); }
    { cuuint64_t d[2] = {448, 2048}, s[1] = {896}; cuuint32_t b[2] = {64, 16}; make_map(fn, &tout64, d_out, 2, d, s, b, CU_TENSOR_MAP_SWIZZLE_128B); }
    { cuuint64_t d[2] = {448, 2048}, s[1] = {896}; cuuint32_t b[2] = {48, 16}; make_map(fn, &tout48, d_out, 2, d, s, b, CU_TENSOR_MAP_SWIZZLE_128B); }

    void* scv = nullptr;
    cudaGetSymbolAddress(&scv, g_scratch);
    Scratch* scp = (Scratch*)scv;
    int dev = 0, sms = 0;
    cudaGetDevice(&dev);
    cudaDeviceGetAttribute(&sms, cudaDevAttrMultiProcessorCount, dev);
    if (sms == 132) {
        cudaFuncSetAttribute(fused_kernel<true>, cudaFuncAttributeMaxDynamicSharedMemorySize, SM_TOTAL);
        fused_kernel<true><<<132, 384, SM_TOTAL>>>(scp, wo, w1, b1, w2, b2, tx, twqkv, two64, two48, tw1, tw2, txr64, txr48, tout64, tout48);
    } else {
        cudaFuncSetAttribute(fused_kernel<false>, cudaFuncAttributeMaxDynamicSharedMemorySize, SM_TOTAL);
        fused_kernel<false><<<132, 384, SM_TOTAL>>>(scp, wo, w1, b1, w2, b2, tx, twqkv, two64, two48, tw1, tw2, txr64, txr48, tout64, tout48);
    }
}
```

```cpp
#include <cuda_runtime.h>
#include <cuda_bf16.h>
#include <cuda.h>
#include <stdint.h>

namespace {

constexpr int D_ = 448;
constexpr float LN_EPS = 1e-5f;
constexpr float LOG2E_SCALE = 0.1889822365046136f * 1.4426950408889634f;

struct Tiles {
    uint32_t o[32 * 57344 / 4];
    uint32_t hn[4 * 32 * 14336 / 4];
    uint32_t u[4 * 28 * 14336 / 4];
};
struct Scratch {
    uint4 halo[128 * 2 * 2 * 3 * 32];
    uint4 stats[32 * 4 * 64];
    uint4 hint_k[128 * 2];
    uint4 hint_o[32 * 32 * 2];
    uint4 hint_h[4 * 32 * 2];
    uint4 hint_u[128 * 2];
    uint4 go[24];
    uint32_t epoch[160];
    uint32_t clean;
    alignas(1024) Tiles tiles[2];
};
__device__ Scratch g_scratch;
#define STAMP(i) do {} while (0)
#define FST(i) do {} while (0)
#define TSARG
#define TSVAL

constexpr uint32_t SB = 1024;
constexpr int SM_SLOT = 16384;
__device__ __forceinline__ constexpr uint32_t slot_x(int kb) { return (kb ? 6 + kb : 0) * SM_SLOT; }
__device__ __forceinline__ constexpr uint32_t slot_kv(int kb) { return (kb < 5 ? 2 + kb : 6 - kb) * SM_SLOT; }
__device__ __forceinline__ constexpr uint32_t slot_wo(int kb) { return (kb < 6 ? 2 + kb : 12) * SM_SLOT; }
constexpr int SM_QO = 8 * SM_SLOT;
constexpr int SM_HALOK = SM_QO + 57344, SM_HALOV = 1 * SM_SLOT;
constexpr int NA_SLOTS = 6, NB_SLOTS = 8;
constexpr int SM_ARING = 0;
constexpr int SM_BRING = NA_SLOTS * 16384;
constexpr int SM_H = 212992;
__device__ __forceinline__ uint32_t halo_kin(int par, int lane) { return SB + SM_H + 8192 + par * 4096 + lane * 128 + ((~lane & 6) << 4); }
constexpr int SM_BAR = 229376;
constexpr int SM_TAG = SM_BAR + 1536;
constexpr int SM_TIME = SM_TAG + 256;
constexpr int SM_TOTAL = SM_TIME + 256;
constexpr int B_FULLX = 0;
constexpr int B_FULLKV = 7;
constexpr int B_FQ = 14;
constexpr int B_DONE1 = 16;
constexpr int B_DONEX = 23;
constexpr int B_DONEQ = 24;
constexpr int B_DONEO = 25;
constexpr int B_FULLO = 29;
constexpr int B_FULLWO = 33;
constexpr int B_END = 34;
constexpr int B_HALO = 35;
constexpr int B_FULLA = 39;
constexpr int B_FULLB = 55;
constexpr int B_DONE = 87;
constexpr int B_GO = 119;
constexpr int B_CLR = 121;
constexpr int SM_RAW = SM_BAR + 8 * 122;

constexpr long long WD_CLKS = 2000000000ll;

template<int N> struct Int { static constexpr int value = N; };
template<int A, int B, class F> __device__ __forceinline__ void static_for(F&& f) { if constexpr (A < B) { f(Int<A>()); static_for<A + 1, B>(f); } }

__device__ __forceinline__ uint32_t smem_u32(const void* p) { return (uint32_t)__cvta_generic_to_shared(p); }
__device__ __forceinline__ void mbar_init(uint32_t bar, uint32_t cnt) { asm volatile("mbarrier.init.shared::cta.b64 [%0], %1;" :: "r"(bar), "r"(cnt) : "memory"); }
__device__ __forceinline__ void mbar_expect(uint32_t bar, uint32_t bytes) { asm volatile("mbarrier.arrive.expect_tx.shared::cta.b64 _, [%0], %1;" :: "r"(bar), "r"(bytes) : "memory"); }
__device__ __forceinline__ void mbar_arrive(uint32_t bar) { asm volatile("mbarrier.arrive.shared::cta.b64 _, [%0];" :: "r"(bar) : "memory"); }
__device__ __forceinline__ bool mbar_try(uint32_t bar, uint32_t parity) {
    uint32_t ok;
    asm volatile("{\n.reg .pred p;\nmbarrier.try_wait.parity.shared::cta.b64 p, [%1], %2;\nselp.u32 %0, 1, 0, p;\n}" : "=r"(ok) : "r"(bar), "r"(parity) : "memory");
    return ok;
}
__device__ __forceinline__ bool mbar_test(uint32_t bar, uint32_t parity) {
    uint32_t ok;
    asm volatile("{\n.reg .pred p;\nmbarrier.test_wait.parity.shared::cta.b64 p, [%1], %2;\nselp.u32 %0, 1, 0, p;\n}" : "=r"(ok) : "r"(bar), "r"(parity) : "memory");
    return ok;
}
__device__ __forceinline__ void mbar_wait(uint32_t bar, uint32_t parity) {
    asm volatile("{\n.reg .pred p;\n"
                 "WAIT_LOOP:\n"
                 "mbarrier.try_wait.parity.shared::cta.b64 p, [%0], %1;\n"
                 "@!p bra WAIT_LOOP;\n}" :: "r"(bar), "r"(parity) : "memory");
}
__device__ __forceinline__ void mbar_wait_unless(uint32_t ready, uint32_t bar, uint32_t parity) {
    asm volatile("{\n.reg .pred p;\nsetp.ne.u32 p, %1, 0;\n@p bra.uni DONE;\n"
                 "WAIT_LOOP:\n"
                 "mbarrier.try_wait.parity.shared::cta.b64 p, [%0], %2;\n"
                 "@!p bra.uni WAIT_LOOP;\nDONE:\n}" :: "r"(bar), "r"(ready), "r"(parity) : "memory");
}
__device__ __forceinline__ void mbar_wait_wd(uint32_t bar, uint32_t parity) {
    asm volatile("{\n.reg .pred p, q;\n.reg .u32 s, t;\nmov.u32 s, %%clock;\n"
                 "WAIT_LOOP:\n"
                 "mbarrier.try_wait.parity.shared::cta.b64 p, [%0], %1;\nmov.u32 t, %%clock;\nsub.u32 t, t, s;\nsetp.lt.and.s32 q, t, 0, !p;\n@q trap;\n"
                 "@!p bra WAIT_LOOP;\n}" :: "r"(bar), "r"(parity) : "memory");
}
__device__ __forceinline__ bool elect() { uint32_t p; asm volatile("{\n.reg .pred P;\nelect.sync _|P, 0xffffffff;\nselp.u32 %0, 1, 0, P;\n}" : "=r"(p)); return p; }
__device__ __forceinline__ void tma2d(uint32_t dst, const CUtensorMap* tm, int c0, int c1, uint32_t bar) {
    asm volatile("cp.async.bulk.tensor.2d.shared::cluster.global.mbarrier::complete_tx::bytes [%0], [%1, {%3, %4}], [%2];" :: "r"(dst), "l"(tm), "r"(bar), "r"(c0), "r"(c1) : "memory");
}
__device__ __forceinline__ void tma3d(uint32_t dst, const CUtensorMap* tm, int c0, int c1, int c2, uint32_t bar) {
    asm volatile("cp.async.bulk.tensor.3d.shared::cluster.global.mbarrier::complete_tx::bytes [%0], [%1, {%3, %4, %5}], [%2];" :: "r"(dst), "l"(tm), "r"(bar), "r"(c0), "r"(c1), "r"(c2) : "memory");
}
__device__ __forceinline__ void tma5d(uint32_t dst, const CUtensorMap* tm, int c0, int c3, int c4, uint32_t bar) {
    asm volatile("cp.async.bulk.tensor.5d.shared::cluster.global.mbarrier::complete_tx::bytes [%0], [%1, {%3, 0, 0, %4, %5}], [%2];" :: "r"(dst), "l"(tm), "r"(bar), "r"(c0), "r"(c3), "r"(c4) : "memory");
}
__device__ __forceinline__ void tma5d_prefetch(const CUtensorMap* tm, int c0, int c3, int c4) {
    asm volatile("cp.async.bulk.prefetch.tensor.5d.L2.global [%0, {%1, 0, 0, %2, %3}];" :: "l"(tm), "r"(c0), "r"(c3), "r"(c4) : "memory");
}
__device__ __forceinline__ void tma2d_store(const CUtensorMap* tm, int c0, int c1, uint32_t src) {
    asm volatile("cp.async.bulk.tensor.2d.global.shared::cta.bulk_group [%0, {%2, %3}], [%1];" :: "l"(tm), "r"(src), "r"(c0), "r"(c1) : "memory");
}
__device__ __forceinline__ void bulk_st(void* dst, uint32_t src, uint32_t bytes) {
    asm volatile("cp.async.bulk.global.shared::cta.bulk_group [%0], [%1], %2;" :: "l"(dst), "r"(src), "r"(bytes) : "memory");
}
__device__ __forceinline__ void bulk_ld(uint32_t dst, const void* src, uint32_t bytes, uint32_t bar) {
    asm volatile("cp.async.bulk.shared::cluster.global.mbarrier::complete_tx::bytes [%0], [%1], %2, [%3];" :: "r"(dst), "l"(src), "r"(bytes), "r"(bar) : "memory");
}
__device__ __forceinline__ void bulk_prefetch(const void* src, uint32_t bytes) { asm volatile("cp.async.bulk.prefetch.L2.global [%0], %1;" :: "l"(src), "r"(bytes) : "memory"); }
__device__ __forceinline__ void prefetch_map(const CUtensorMap* tm) { asm volatile("prefetch.tensormap [%0];" :: "l"(tm) : "memory"); }
__device__ __forceinline__ void st_global_if(uint32_t c, uint32_t* p, uint32_t v) {
    asm volatile("{\n.reg .pred p;\nsetp.ne.u32 p, %2, 0;\n@p st.global.u32 [%0], %1;\n}" :: "l"(p), "r"(v), "r"(c) : "memory");
}
__device__ __forceinline__ void st_relaxed4_if(bool c, uint4* p, uint32_t a, uint32_t b, uint32_t d) {
    asm volatile("{\n.reg .b128 t;\n.reg .b64 a, b;\n.reg .pred p;\nsetp.ne.u32 p, %4, 0;\nmov.b64 a, {%1, %2};\nmov.b64 b, {%3, %3};\nmov.b128 t, {a, b};\n@p st.relaxed.gpu.global.b128 [%0], t;\n}" :: "l"(p), "r"(a), "r"(b), "r"(d), "r"((uint32_t)c) : "memory");
}
__device__ __forceinline__ void pin_ptr(uint32_t never, const void* a) {
    asm volatile("{\n.reg .pred p;\nsetp.ne.u32 p, %1, 0;\n@p st.shared.u64 [%1], %0;\n}" :: "l"(a), "r"(never) : "memory");
}
__device__ __forceinline__ void pin4(uint32_t never, float a, float b, float c, float d) {
    asm volatile("{\n.reg .pred p;\nsetp.ne.u32 p, %4, 0;\n@p st.shared.v4.f32 [%4], {%0,%1,%2,%3};\n}" :: "f"(a), "f"(b), "f"(c), "f"(d), "r"(never) : "memory");
}
__device__ __forceinline__ void fence_async_smem() { asm volatile("fence.proxy.async.shared::cta;" ::: "memory"); }
__device__ __forceinline__ uint32_t ld_acquire(const void* p) { uint32_t v; asm volatile("ld.acquire.gpu.global.u32 %0, [%1];" : "=r"(v) : "l"(p) : "memory"); return v; }
__device__ __forceinline__ void st_release(void* p, uint32_t v) { asm volatile("st.release.gpu.global.u32 [%0], %1;" :: "l"(p), "r"(v) : "memory"); }
__device__ __forceinline__ uint32_t ld_relaxed(const void* p) { uint32_t v; asm volatile("ld.relaxed.gpu.global.u32 %0, [%1];" : "=r"(v) : "l"(p) : "memory"); return v; }
__device__ __forceinline__ uint2 ld_relaxed2(const void* p) {
    uint2 v; asm volatile("{\n.reg .b64 a;\nld.relaxed.gpu.global.b64 a, [%2];\nmov.b64 {%0, %1}, a;\n}" : "=r"(v.x), "=r"(v.y) : "l"(p) : "memory"); return v;
}
__device__ __forceinline__ void st_relaxed2(void* p, uint32_t a, uint32_t b) {
    asm volatile("{\n.reg .b64 a;\nmov.b64 a, {%1, %2};\nst.relaxed.gpu.global.b64 [%0], a;\n}" :: "l"(p), "r"(a), "r"(b) : "memory");
}
__device__ __forceinline__ uint4 ld_relaxed4(const uint4* p) {
    uint4 v;
    asm volatile("{\n.reg .b128 t;\n.reg .b64 a, b;\nld.relaxed.gpu.global.b128 t, [%4];\nmov.b128 {a, b}, t;\nmov.b64 {%0, %1}, a;\nmov.b64 {%2, %3}, b;\n}" : "=r"(v.x), "=r"(v.y), "=r"(v.z), "=r"(v.w) : "l"(p) : "memory");
    return v;
}
__device__ __forceinline__ void st_relaxed4(uint4* p, uint32_t a, uint32_t b, uint32_t c, uint32_t d) {
    asm volatile("{\n.reg .b128 t;\n.reg .b64 a, b;\nmov.b64 a, {%1, %2};\nmov.b64 b, {%3, %4};\nmov.b128 t, {a, b};\nst.relaxed.gpu.global.b128 [%0], t;\n}" :: "l"(p), "r"(a), "r"(b), "r"(c), "r"(d) : "memory");
}
__device__ __forceinline__ uint32_t ld_u16(const unsigned short* p) { uint32_t v; asm volatile("ld.volatile.global.u16 %0, [%1];" : "=r"(v) : "l"(p) : "memory"); return v; }
__device__ __forceinline__ uint32_t ld_volatile(const uint32_t* p) { uint32_t v; asm volatile("ld.volatile.global.u32 %0, [%1];" : "=r"(v) : "l"(p) : "memory"); return v; }
__device__ __forceinline__ void named_arrive(int id, int n) { asm volatile("bar.arrive %0, %1;" :: "r"(id), "r"(n) : "memory"); }
__device__ __forceinline__ void named_sync(int id, int n) { asm volatile("bar.sync %0, %1;" :: "r"(id), "r"(n) : "memory"); }
__device__ __forceinline__ void named_arrive_if(uint32_t c, int id, int n) { asm volatile("{\n.reg .pred p;\nsetp.ne.u32 p, %2, 0;\n@p bar.arrive %0, %1;\n}" :: "r"(id), "r"(n), "r"(c) : "memory"); }
__device__ __forceinline__ bool named_any(int id, int n, bool v) {
    uint32_t r; asm volatile("{\n.reg .pred p, q;\nsetp.ne.u32 p, %3, 0;\nbar.red.or.pred q, %1, %2, p;\nselp.u32 %0, 1, 0, q;\n}" : "=r"(r) : "r"(id), "r"(n), "r"((uint32_t)v) : "memory"); return r;
}
__device__ __forceinline__ void wg_fence() { asm volatile("wgmma.fence.sync.aligned;" ::: "memory"); }
__device__ __forceinline__ void wg_commit() { asm volatile("wgmma.commit_group.sync.aligned;" ::: "memory"); }
template<int N> __device__ __forceinline__ void wg_wait() { asm volatile("wgmma.wait_group.sync.aligned %0;" :: "n"(N) : "memory"); }
template<int N> __device__ __forceinline__ void reg_fence(float (&d)[N]) {
    #pragma unroll
    for (int i = 0; i < N; i++) asm volatile("" : "+f"(d[i]) :: "memory");
}
__device__ __forceinline__ constexpr uint64_t mkdesc(uint32_t addr, uint32_t lbo, uint32_t sbo, uint32_t sw) {
    return (uint64_t)((addr & 0x3FFFF) >> 4) | ((uint64_t)(lbo >> 4) << 16) | ((uint64_t)(sbo >> 4) << 32) | ((uint64_t)sw << 62);
}
__device__ __forceinline__ void ldsm4(uint32_t (&r)[4], uint32_t addr) {
    asm volatile("ldmatrix.sync.aligned.m8n8.x4.shared.b16 {%0,%1,%2,%3}, [%4];" : "=r"(r[0]), "=r"(r[1]), "=r"(r[2]), "=r"(r[3]) : "r"(addr) : "memory");
}
__device__ __forceinline__ void stsm4(uint32_t addr, uint32_t r0, uint32_t r1, uint32_t r2, uint32_t r3) {
    asm volatile("stmatrix.sync.aligned.m8n8.x4.shared.b16 [%0], {%1,%2,%3,%4};" :: "r"(addr), "r"(r0), "r"(r1), "r"(r2), "r"(r3) : "memory");
}
__device__ __forceinline__ void sts4(uint32_t a, uint32_t x, uint32_t y, uint32_t z, uint32_t w) { asm volatile("st.shared.v4.u32 [%0], {%1,%2,%3,%4};" :: "r"(a), "r"(x), "r"(y), "r"(z), "r"(w) : "memory"); }
__device__ __forceinline__ uint4 lds4(uint32_t a) { uint4 v; asm volatile("ld.shared.v4.u32 {%0,%1,%2,%3}, [%4];" : "=r"(v.x), "=r"(v.y), "=r"(v.z), "=r"(v.w) : "r"(a) : "memory"); return v; }
__device__ __forceinline__ uint32_t movtrans(uint32_t a) { uint32_t d; asm volatile("movmatrix.sync.aligned.m8n8.trans.b16 %0, %1;" : "=r"(d) : "r"(a)); return d; }
__device__ __forceinline__ uint32_t pack_bf16(float lo, float hi) { uint32_t r; asm("cvt.rn.bf16x2.f32 %0, %1, %2;" : "=r"(r) : "f"(hi), "f"(lo)); return r; }
__device__ __forceinline__ void sub_bf16x2(uint32_t& a, uint32_t b) { asm volatile("sub.rn.bf16x2 %0, %0, %1;" : "+r"(a) : "r"(b)); }
__device__ __forceinline__ float bf_lo(uint32_t v) { return __uint_as_float(v << 16); }
__device__ __forceinline__ float bf_hi(uint32_t v) { return __uint_as_float(v & 0xffff0000u); }
__device__ __forceinline__ void mma16816(float (&c)[4], uint32_t a0, uint32_t a1, uint32_t a2, uint32_t a3, uint32_t b0, uint32_t b1) {
    asm volatile("mma.sync.aligned.m16n8k16.row.col.f32.bf16.bf16.f32 {%0,%1,%2,%3}, {%4,%5,%6,%7}, {%8,%9}, {%0,%1,%2,%3};"
        : "+f"(c[0]), "+f"(c[1]), "+f"(c[2]), "+f"(c[3]) : "r"(a0), "r"(a1), "r"(a2), "r"(a3), "r"(b0), "r"(b1));
}
__device__ __forceinline__ void mma1688(float (&c)[4], uint32_t a0, uint32_t a1, uint32_t b0) {
    asm volatile("mma.sync.aligned.m16n8k8.row.col.f32.bf16.bf16.f32 {%0,%1,%2,%3}, {%4,%5}, {%6}, {%0,%1,%2,%3};"
        : "+f"(c[0]), "+f"(c[1]), "+f"(c[2]), "+f"(c[3]) : "r"(a0), "r"(a1), "r"(b0));
}
__device__ __forceinline__ float quad_sum(float v) { v += __shfl_xor_sync(0xffffffffu, v, 1); v += __shfl_xor_sync(0xffffffffu, v, 2); return v; }
__device__ __forceinline__ float quad_max(float v) { v = fmaxf(v, __shfl_xor_sync(0xffffffffu, v, 1)); v = fmaxf(v, __shfl_xor_sync(0xffffffffu, v, 2)); return v; }
__device__ __forceinline__ float ex2(float x) { float y; asm("ex2.approx.ftz.f32 %0, %1;" : "=f"(y) : "f"(x)); return y; }
__device__ __forceinline__ float rsqrt_approx(float x) { float y; asm("rsqrt.approx.ftz.f32 %0, %1;" : "=f"(y) : "f"(x)); return y; }
__device__ __forceinline__ float rcp_approx(float x) { float y; asm("rcp.approx.ftz.f32 %0, %1;" : "=f"(y) : "f"(x)); return y; }
constexpr float GELU_K1 = 2.f * 0.7978845608028654f;
__device__ __forceinline__ float gelu_half(float hx, float k1) {
    const float z = hx * fmaf(hx * hx, 8.f * 0.044715f * 0.7978845608028654f, k1);
    float t; asm("tanh.approx.f32 %0, %1;" : "=f"(t) : "f"(z));
    return fmaf(hx, t, hx);
}
__device__ __forceinline__ uint32_t gtime32() { uint64_t t; asm volatile("mov.u64 %0, %%globaltimer;" : "=l"(t)); return (uint32_t)t; }
__device__ __forceinline__ uint32_t clock32() { uint32_t t; asm volatile("mov.u32 %0, %%clock;" : "=r"(t)); return t; }
#define PF_PACE 160
#define PF_AT 16500
#define PF_N 192
#define NSQ 6
#define NPIPE 1
#define HALO_AT 3
#define HINT_U 18
#define HINT_E 16
#define SP_AT 2000
#define A_SCHED 0x322188
#define WO_ORD0 0x4321065
#define WO_ORD1 0x3465210
#define CL_AT 23
#define WARM_AT 300
#define GO_H 1730
#define GO_E 1900
#define GO_U 2120
#define GO_O 1280
#define LATE_O 256
#define LATE_AT 0
#define LATE_AT4 0
#define SLACK 0
#define GDEP 4
#define START4 30
#define NE_SLOTS 11
#define POLL_E 26
#define AE_END 18
#define AE_W2 27
#define PF1_AT 12000
#define PF1_N 80
#define PF1_PACE 160
#define GO_E2 300
#define GO_U2 400
#define POLL_I 20
#define POLL_N 19
#define ROLES 0x65431027u
#define POLL0 250
#define A4_FROM 23
#define A4_DLY 2
#define SPIN_N 3
#define STOP2 150
#define PF0_AT 5000
#define PF0_N 48
#define PF0_PACE 140
#define POLL_H 3
#define CH_H 8
#define HINT_F 2
#define CL_N 4
#define CL_P2 7
#define STOP3 3
template<int TB> __device__ __forceinline__ void wgmma_rs56(float (&d)[28], const uint32_t (&a)[4], uint64_t db, int sc) {
    asm volatile("{\n.reg .pred p;\nsetp.ne.b32 p, %33, 0;\n"
        "wgmma.mma_async.sync.aligned.m64n56k16.f32.bf16.bf16 {%0, %1, %2, %3, %4, %5, %6, %7, %8, %9, %10, %11, %12, %13, %14, %15, %16, %17, %18, %19, %20, %21, %22, %23, %24, %25, %26, %27}, {%28, %29, %30, %31}, %32, p, 1, 1, %34;\n}\n"
        : "+f"(d[0]), "+f"(d[1]), "+f"(d[2]), "+f"(d[3]), "+f"(d[4]), "+f"(d[5]), "+f"(d[6]), "+f"(d[7]), "+f"(d[8]), "+f"(d[9]), "+f"(d[10]), "+f"(d[11]), "+f"(d[12]), "+f"(d[13]), "+f"(d[14]), "+f"(d[15]), "+f"(d[16]), "+f"(d[17]), "+f"(d[18]), "+f"(d[19]), "+f"(d[20]), "+f"(d[21]), "+f"(d[22]), "+f"(d[23]), "+f"(d[24]), "+f"(d[25]), "+f"(d[26]), "+f"(d[27])
        : "r"(a[0]), "r"(a[1]), "r"(a[2]), "r"(a[3]), "l"(db), "r"(sc), "n"(TB));
}

template<int TA, int TB, int SC = 1> __device__ __forceinline__ void wgmma_ss112(float (&d)[56], uint64_t da, uint64_t db) {
    asm volatile("wgmma.mma_async.sync.aligned.m64n112k16.f32.bf16.bf16 {%0, %1, %2, %3, %4, %5, %6, %7, %8, %9, %10, %11, %12, %13, %14, %15, %16, %17, %18, %19, %20, %21, %22, %23, %24, %25, %26, %27, %28, %29, %30, %31, %32, %33, %34, %35, %36, %37, %38, %39, %40, %41, %42, %43, %44, %45, %46, %47, %48, %49, %50, %51, %52, %53, %54, %55}, %56, %57, %60, 1, 1, %58, %59;\n"
        : "+f"(d[0]), "+f"(d[1]), "+f"(d[2]), "+f"(d[3]), "+f"(d[4]), "+f"(d[5]), "+f"(d[6]), "+f"(d[7]), "+f"(d[8]), "+f"(d[9]), "+f"(d[10]), "+f"(d[11]), "+f"(d[12]), "+f"(d[13]), "+f"(d[14]), "+f"(d[15]), "+f"(d[16]), "+f"(d[17]), "+f"(d[18]), "+f"(d[19]), "+f"(d[20]), "+f"(d[21]), "+f"(d[22]), "+f"(d[23]), "+f"(d[24]), "+f"(d[25]), "+f"(d[26]), "+f"(d[27]), "+f"(d[28]), "+f"(d[29]), "+f"(d[30]), "+f"(d[31]), "+f"(d[32]), "+f"(d[33]), "+f"(d[34]), "+f"(d[35]), "+f"(d[36]), "+f"(d[37]), "+f"(d[38]), "+f"(d[39]), "+f"(d[40]), "+f"(d[41]), "+f"(d[42]), "+f"(d[43]), "+f"(d[44]), "+f"(d[45]), "+f"(d[46]), "+f"(d[47]), "+f"(d[48]), "+f"(d[49]), "+f"(d[50]), "+f"(d[51]), "+f"(d[52]), "+f"(d[53]), "+f"(d[54]), "+f"(d[55])
        : "l"(da), "l"(db), "n"(TA), "n"(TB), "n"(SC));
}

template<int TA, int TB, int SC = 1> __device__ __forceinline__ void wgmma_ss80(float (&d)[40], uint64_t da, uint64_t db) {
    asm volatile("wgmma.mma_async.sync.aligned.m64n80k16.f32.bf16.bf16 {%0, %1, %2, %3, %4, %5, %6, %7, %8, %9, %10, %11, %12, %13, %14, %15, %16, %17, %18, %19, %20, %21, %22, %23, %24, %25, %26, %27, %28, %29, %30, %31, %32, %33, %34, %35, %36, %37, %38, %39}, %40, %41, %44, 1, 1, %42, %43;\n"
        : "+f"(d[0]), "+f"(d[1]), "+f"(d[2]), "+f"(d[3]), "+f"(d[4]), "+f"(d[5]), "+f"(d[6]), "+f"(d[7]), "+f"(d[8]), "+f"(d[9]), "+f"(d[10]), "+f"(d[11]), "+f"(d[12]), "+f"(d[13]), "+f"(d[14]), "+f"(d[15]), "+f"(d[16]), "+f"(d[17]), "+f"(d[18]), "+f"(d[19]), "+f"(d[20]), "+f"(d[21]), "+f"(d[22]), "+f"(d[23]), "+f"(d[24]), "+f"(d[25]), "+f"(d[26]), "+f"(d[27]), "+f"(d[28]), "+f"(d[29]), "+f"(d[30]), "+f"(d[31]), "+f"(d[32]), "+f"(d[33]), "+f"(d[34]), "+f"(d[35]), "+f"(d[36]), "+f"(d[37]), "+f"(d[38]), "+f"(d[39])
        : "l"(da), "l"(db), "n"(TA), "n"(TB), "n"(SC));
}

template<int TA, int TB, int SC = 1> __device__ __forceinline__ void wgmma_ss64(float (&d)[32], uint64_t da, uint64_t db) {
    asm volatile("wgmma.mma_async.sync.aligned.m64n64k16.f32.bf16.bf16 {%0, %1, %2, %3, %4, %5, %6, %7, %8, %9, %10, %11, %12, %13, %14, %15, %16, %17, %18, %19, %20, %21, %22, %23, %24, %25, %26, %27, %28, %29, %30, %31}, %32, %33, %36, 1, 1, %34, %35;\n"
        : "+f"(d[0]), "+f"(d[1]), "+f"(d[2]), "+f"(d[3]), "+f"(d[4]), "+f"(d[5]), "+f"(d[6]), "+f"(d[7]), "+f"(d[8]), "+f"(d[9]), "+f"(d[10]), "+f"(d[11]), "+f"(d[12]), "+f"(d[13]), "+f"(d[14]), "+f"(d[15]), "+f"(d[16]), "+f"(d[17]), "+f"(d[18]), "+f"(d[19]), "+f"(d[20]), "+f"(d[21]), "+f"(d[22]), "+f"(d[23]), "+f"(d[24]), "+f"(d[25]), "+f"(d[26]), "+f"(d[27]), "+f"(d[28]), "+f"(d[29]), "+f"(d[30]), "+f"(d[31])
        : "l"(da), "l"(db), "n"(TA), "n"(TB), "n"(SC));
}

template<int TA, int TB, int SC = 1> __device__ __forceinline__ void wgmma_ss48(float (&d)[24], uint64_t da, uint64_t db) {
    asm volatile("wgmma.mma_async.sync.aligned.m64n48k16.f32.bf16.bf16 {%0, %1, %2, %3, %4, %5, %6, %7, %8, %9, %10, %11, %12, %13, %14, %15, %16, %17, %18, %19, %20, %21, %22, %23}, %24, %25, %28, 1, 1, %26, %27;\n"
        : "+f"(d[0]), "+f"(d[1]), "+f"(d[2]), "+f"(d[3]), "+f"(d[4]), "+f"(d[5]), "+f"(d[6]), "+f"(d[7]), "+f"(d[8]), "+f"(d[9]), "+f"(d[10]), "+f"(d[11]), "+f"(d[12]), "+f"(d[13]), "+f"(d[14]), "+f"(d[15]), "+f"(d[16]), "+f"(d[17]), "+f"(d[18]), "+f"(d[19]), "+f"(d[20]), "+f"(d[21]), "+f"(d[22]), "+f"(d[23])
        : "l"(da), "l"(db), "n"(TA), "n"(TB), "n"(SC));
}

template<int NKB, int NR>
__device__ __forceinline__ void mix_mainloop(TSARG float (&acc)[NR], bool leader) {
    constexpr uint32_t sb = SB, bars = sb + SM_BAR, par = NKB == 28;
    constexpr int A0 = NKB == 32 ? 0 : 16 % NA_SLOTS;
    constexpr int DEPTH = NR == 56 ? 1 : 2;
    int bslot = 0, aslot = A0;
    reg_fence(acc);
    #pragma unroll 1
    for (int i = 0; i < NKB / 2; i++) {
        mbar_wait(bars + 8 * (B_FULLA + i), par);
        const uint64_t adesc = mkdesc(sb + SM_ARING, 8192, 1024, 1) + (uint32_t)(aslot * 1024);
        aslot = aslot == NA_SLOTS - 1 ? 0 : aslot + 1;
        #pragma unroll
        for (int jj = 0; jj < 2; jj++) {
            const int j = 2 * i + jj;
            mbar_wait(bars + 8 * (B_FULLB + j), par);
            const uint64_t bdesc = mkdesc(sb + SM_BRING, 128, 1024, 0) + (uint32_t)(bslot * NR * 16);
            bslot = bslot == (NR == 56 ? NB_SLOTS : NE_SLOTS) - 1 ? 0 : bslot + 1;
            wg_fence();
            #pragma unroll
            for (int s = 0; s < 4; s++) {
                if constexpr (NR == 56) wgmma_ss112<1, 1>(acc, adesc + jj * 512 + s * 128, bdesc + s * 16);
                else wgmma_ss80<1, 1>(acc, adesc + jj * 512 + s * 128, bdesc + s * 16);
            }
            wg_commit();
            wg_wait<DEPTH>();
            if (j >= DEPTH && leader) mbar_arrive(bars + 8 * (B_DONE + j - DEPTH));
        }
    }
    if (DEPTH == 2) { wg_wait<1>(); if (leader) mbar_arrive(bars + 8 * (B_DONE + NKB - 2)); }
    wg_wait<0>();
    reg_fence(acc);
    if (leader) mbar_arrive(bars + 8 * (B_DONE + NKB - 1));
}

__device__ __forceinline__ void spin_mma(uint32_t bar, uint32_t never) {
    float d[56];
    #pragma unroll
    for (int i = 0; i < 56; i++) d[i] = 0.f;
    reg_fence(d);
    #pragma unroll 1
    do {
        wg_fence();
        #pragma unroll
        for (int s = 0; s < SPIN_N; s++) wgmma_ss112<1, 1>(d, mkdesc(SB + 2 * SM_SLOT + s * 2048, 8192, 1024, 1), mkdesc(SB + 3 * SM_SLOT + s * 256, 128, 1024, 0));
        wg_commit();
        wg_wait<1>();
    } while (!named_any(11, 128, mbar_test(bar, 1)));
    wg_wait<0>();
    reg_fence(d);
    pin4(never, d[0], d[1], d[2], d[3]);
}

constexpr uint32_t EMPTY = 0xFFFFFFFFu;
__device__ __forceinline__ void post_hint(uint4* p, uint32_t ep, int lane) { if (lane < 2) st_relaxed4(p + lane, ep, ep, ep, ep); }
__device__ __forceinline__ void post_time(uint4* p, uint32_t ep, int lane) { const uint32_t now = gtime32(); if (lane < 2) st_relaxed4(p + lane, ep, now, ep, now); }

__device__ __forceinline__ uint32_t last_hint(TSARG const uint4* hint, uint32_t ep, int st) {
    uint2 v;
    do { v = ld_relaxed2(hint); } while (!__all_sync(0xffffffffu, v.x == ep));
    const uint32_t t1 = gtime32() + 256;
    if (elect()) STAMP(st);
    return t1 - __reduce_min_sync(0xffffffffu, t1 - v.y);
}
__device__ __forceinline__ uint32_t later(uint32_t a, uint32_t b) { return a + max((int)(b - a), 0); }
__device__ __forceinline__ void fetch_times(TSARG const uint4* go, int k, uint32_t ep, int lane) {
    const uint2* p = (const uint2*)(go + 8 + 8 * k) + (k ? lane % 10 : lane & 3);
    uint2 v;
    do { v = ld_relaxed2(p); } while (!__all_sync(0xffffffffu, v.x == ep));
    v.y += k ? (lane < 10 ? GO_U : GO_U + GO_U2) : (lane < 4 ? GO_E : GO_E + GO_E2);
    asm volatile("st.shared.u32 [%0], %1;" :: "r"(SB + SM_TIME + 128 * k + 4 * lane), "r"(v.y) : "memory");
    __syncwarp();
    if (lane == 0) { mbar_arrive(SB + SM_BAR + 8 * (B_GO + k)); STAMP(k ? 43 : 24); }
    __syncwarp();
}
__device__ __forceinline__ void wait_until(uint32_t t) {
    asm volatile("{\n.reg .pred p;\n.reg .u64 a;\n.reg .u32 l, h;\nWAIT_LOOP:\nmov.u64 a, %%globaltimer;\nmov.b64 {l, h}, a;\nsub.u32 l, l, %0;\nsetp.lt.s32 p, l, 0;\n@p bra.uni WAIT_LOOP;\n}" :: "r"(t) : "memory");
}

__device__ __forceinline__ uint32_t check_tile(uint32_t raw, uint32_t full, uint32_t dst, uint32_t lofs, const uint32_t* src, uint32_t bytes, int lane) {
    uint32_t cnt;
    asm volatile("{\n.reg .pred p, e;\n.reg .u32 a, b, c, d;\nmov.u32 %0, 0;\n"
                 "AGAIN:\nand.b32 a, %0, 1;\n"
                 "WAIT:\nmbarrier.try_wait.parity.shared::cta.b64 p, [%1], a;\n@!p bra.uni WAIT;\n"
                 "ld.shared.u32 a, [%4];\nld.shared.u32 b, [%4+4096];\nld.shared.u32 c, [%5+-8192];\nld.shared.u32 d, [%5+-4096];\n"
                 "add.u32 %0, %0, 1;\nmax.u32 a, a, b;\nmax.u32 c, c, d;\nmax.u32 a, a, c;\nsetp.lt.u32 e, %8, 32;\nsetp.eq.and.u32 p, a, 0xFFFFFFFF, e;\n"
                 "vote.sync.any.pred p, p, 0xffffffff;\nsetp.eq.and.u32 e, %8, 0, !p;\n@e mbarrier.arrive.shared::cta.b64 _, [%2];\n"
                 "elect.sync _|e, 0xffffffff;\nand.pred e, e, p;\n"
                 "@e mbarrier.arrive.expect_tx.shared::cta.b64 _, [%1], %7;\n"
                 "@e cp.async.bulk.shared::cluster.global.mbarrier::complete_tx::bytes [%3], [%6], %7, [%1];\n"
                 "@p bra.uni AGAIN;\n}"
                 : "=&r"(cnt) : "r"(raw), "r"(full), "r"(dst), "r"(dst + lofs), "r"(dst + lofs + bytes), "l"(src), "r"(bytes), "r"(lane) : "memory");
    return cnt;
}

template<int ST>
__device__ __forceinline__ void check_tiles(int j, int step, int n, const uint32_t* src, bool small, int lane, bool dry) {
    const uint32_t bytes = small ? 10240 : 14336, nb = small ? NE_SLOTS : NB_SLOTS, lofs = lane * 128 + (lane & 3) * 32 + (lane >> 2) * 4;
    uint32_t sl = j % nb;
    #pragma unroll 1
    for (int inc = dry ? 0 : step; j < n; j += inc, inc = step) {
        const uint32_t c = check_tile(inc ? SB + SM_RAW + 8 * (j + (ST ? 32 * ST - 28 : 0)) : SB + SM_BAR + 8 * B_CLR, SB + SM_BAR + 8 * (j + (ST ? B_FULLB : B_FULLO)),
                                      SB + (ST ? SM_BRING + sl * bytes : SM_QO + max(2 * j - 1, 0) * 8192), lofs, src + (ST ? j * 7168 : max(2 * j - 1, 0) * 2048),
                                      ST ? bytes : j ? 16384 : 8192, inc ? lane : 32);
        sl += inc;
        if (sl >= nb) sl -= nb;
    }
}

__device__ __forceinline__ uint32_t hcol(uint32_t a, int jp) { return (a ^ ((jp & 3) << 5)) + (jp >> 2) * 8192; }

__device__ __forceinline__ uint32_t get_tag() {
    mbar_wait(SB + SM_BAR + 8 * B_CLR, 0);
    uint32_t v; asm volatile("ld.shared.u32 %0, [%1];" : "=r"(v) : "r"(SB + SM_TAG) : "memory"); return v;
}

template<bool USE_SMID>
__global__ void __launch_bounds__(384, 1)
fused_kernel(Scratch* __restrict__ sc, const __nv_bfloat16* __restrict__ wo,
             const __nv_bfloat16* __restrict__ w1, const __nv_bfloat16* __restrict__ b1,
             const __nv_bfloat16* __restrict__ w2, const __nv_bfloat16* __restrict__ b2,
             const __grid_constant__ CUtensorMap tm_x, const __grid_constant__ CUtensorMap tm_wqkv,
             const __grid_constant__ CUtensorMap tm_wo64, const __grid_constant__ CUtensorMap tm_wo48,
             const __grid_constant__ CUtensorMap tm_w1, const __grid_constant__ CUtensorMap tm_w2,
             const __grid_constant__ CUtensorMap tm_xr64, const __grid_constant__ CUtensorMap tm_xr48,
             const __grid_constant__ CUtensorMap tm_out64, const __grid_constant__ CUtensorMap tm_out48) {
    extern __shared__ __align__(1024) uint8_t smem_raw[];
    constexpr uint32_t sb = SB;
    constexpr uint32_t bars = sb + SM_BAR;
    const int tid = threadIdx.x, lane = tid & 31;
    auto get_slot = [&]() {
        int slot;
    if (USE_SMID) {
        asm volatile("{\n.reg .u32 s, t, u, d, a, b, c;\n.reg .pred p, r;\n"
            "mov.u32 s, %%smid;\nshr.u32 t, s, 1;\nsub.u32 u, t, 32;\nmul.lo.u32 d, u, 37;\nshr.u32 d, d, 8;\n"
            "and.b32 a, t, 7;\nshl.b32 a, a, 3;\nshr.u32 c, t, 3;\nadd.u32 a, a, c;\n"
            "mad.lo.u32 b, d, -55, 12;\nshl.b32 c, u, 3;\nadd.u32 b, b, c;\n"
            "setp.lt.u32 p, t, 32;\nselp.u32 a, a, b, p;\n"
            "setp.lt.u32 r, t, 62;\nselp.s32 c, 4, -58, r;\nadd.u32 c, t, c;\nsetp.lt.u32 p, t, 60;\nselp.u32 a, a, c, p;\n"
            "and.b32 s, s, 1;\nshl.b32 a, a, 1;\nadd.u32 %0, a, s;\n}" : "=r"(slot));
    } else slot = blockIdx.x;
        return slot;
    };
    auto load_x = [&](int kb, int row) {
        const uint32_t st = sb + slot_x(kb), bar = bars + 8 * (B_FULLX + kb);
        mbar_expect(bar, 16384);
        tma3d(st, &tm_x, kb * 64, 0, row, bar); tma3d(st + 8192, &tm_x, kb * 64, 1, row, bar);
    };
    const int warp = __shfl_sync(0xffffffffu, tid >> 5, 0);
#define ASSIGN_WORK(s) \
    const int slot = (s), G = slot >> 4, mi = slot & 15; \
    const int tb = 4 * (G >> 1) + (mi >> 2), hp = 2 * (mi & 3) + (G & 1), wcol = (hp * 56) & ~15; \
    const int q = mi & 3, tt2 = 4 * G + (mi >> 2), c64 = 64 * q, c48 = 256 + 48 * q; \
    const int R = (ROLES >> (4 * G)) & 7; \
    const bool early = R < 3; \
    const int ech = R < 2 ? q : 4 + (mi & 1), ft = R == 2 ? mi >> 1 : 4 * (R - !early) + (mi >> 2); \
    const int pr3 = early ? ech >= 3 : q >> 1, col3 = early ? (ech - 3 * pr3) * 9 : (q & 1) * 14;

    if (warp < 8) {
        ASSIGN_WORK(get_slot())
        if (slot >= 128) {
            const uint32_t ep = ld_volatile(&sc->epoch[slot]) + 1;
            if (mi == 0 && warp > 0) {
                const int k = warp % 3;
                uint2* go = (uint2*)(sc->go + 8 * k) + lane;
                if (warp < 4 && lane < 16) st_relaxed2(go, 0, 0);
                while (ld_relaxed(k ? sc->go : sc->hint_k) != ep) __nanosleep(200);
                __nanosleep(warp * 60);
                const uint4* hint = (k ? sc->hint_u : sc->hint_h) + (k == 2 ? 48 + min(lane, 19) : lane) * 2;
                uint2 v[4];
                do {
                    #pragma unroll
                    for (int i = 0; i < 4; i++) v[i] = ld_relaxed2(hint + (k == 0 ? 64 * i : k == 2 ? 40 * i : 32 * (i & 1)));
                } while (!__all_sync(0xffffffffu, v[0].x == ep && v[1].x == ep && v[2].x == ep && v[3].x == ep));
                uint32_t t = later(later(v[0].y, v[1].y), later(v[2].y, v[3].y));
                t = later(t, __shfl_xor_sync(0xffffffffu, t, 1));
                if (k == 1) { t = later(t, __shfl_xor_sync(0xffffffffu, t, 8)); t = later(t, __shfl_xor_sync(0xffffffffu, t, 16)); }
                if (k == 0) {
                    const uint32_t now = gtime32() + 256;
                    t = later(t, now - __reduce_min_sync(0xffffffffu, now - t) - SLACK);
                }
                t = __shfl_sync(0xffffffffu, t, 2 * lane);
                if (lane < 16) st_relaxed2(go, ep, t);
            }
            if (mi == 1 && warp >= 4 && ld_volatile(&sc->clean) != ep) {
                for (int l = (tid - 128) / 2; l < sizeof(Tiles) / 128; l += 64) st_relaxed4((uint4*)&sc->tiles[ep & 1] + l * 8 + (lane & 7), EMPTY, EMPTY, EMPTY, EMPTY);
                named_sync(1, 128);
                if (tid == 128) st_release(&sc->clean, ep);
            }
            if (tid == 0) {
                const long long t0 = clock64();
                while (clock64() - t0 < SP_AT) {}
                #pragma unroll 1
                for (int i = 0; i < 7; i++) bulk_prefetch((const char*)wo + (i * 4 + mi) * 14336, 14336);
                uint32_t t = (uint32_t)t0 + PF0_AT;
                #pragma unroll 1
                for (int i = 0; i < PF0_N; i++) {
                    while ((int)(clock32() - t) < 0) {}
                    bulk_prefetch((const char*)w1 + i * 114688 + mi * 14336, 14336);
                    t += PF0_PACE;
                }
                if (mi) {
                    t = (uint32_t)t0 + PF1_AT;
                    #pragma unroll 1
                    for (int i = mi - 1; i < PF1_N; i += 3) {
                        while ((int)(clock32() - t) < 0) {}
                        tma5d_prefetch(&tm_w1, (i & 7) * 64, (i + 48) & 56, (i + 48) >> 6);
                        t += PF1_PACE;
                    }
                    t = (uint32_t)t0 + PF_AT;
                    #pragma unroll 1
                    for (int i = mi - 1; i < PF_N; i += 3) {
                        while ((int)(clock32() - t) < 0) {}
                        bulk_prefetch((const char*)w2 + (i < 128 ? i * 16384 : (i - 64 >> 1) * 65536 + (i & 1) * 16384), 16384);
                        t += PF_PACE;
                    }
                }
                while (ld_relaxed(sc->hint_u + 254) != ep) { __nanosleep(500); if (clock64() - t0 > WD_CLKS) __trap(); }
                sc->epoch[slot] = ep;
                if (mi == 1) sc->clean = ep + 1;
            }
            return;
        }
        {
            const int w = warp & 3, wg = warp >> 2, g = lane >> 2, t = lane & 3;
            if (WARM_AT) { const uint32_t t0 = clock32(); while (clock32() - t0 < WARM_AT) {} __syncwarp(); }
            if (w > 0) post_hint(sc->hint_o + ((2 * tb + (w >> 1)) * 32 + hp * 4 + (w & 1) * 2 + wg) * 2, 0, lane);
            if (wg == 0) {
                if (t < 2) st_relaxed4(sc->stats + tt2 * 256 + q * 64 + 16 * w + g + 8 * t, 0, 0, 0, 0);
            }
        }
        named_sync(0, 288);
        asm volatile("setmaxnreg.inc.sync.aligned.u32 224;");
        int tid; asm volatile("mov.u32 %0, %%tid.x;" : "=r"(tid));
        const int lane = tid & 31, warp = __shfl_sync(0xffffffffu, tid >> 5, 0), wg = warp >> 2;
        uint32_t ep;
        Tiles* tl;
        const int w = warp & 3, g = lane >> 2, t = lane & 3;
        const bool leader = (tid & 127) == 0;
        const uint32_t never = gridDim.y - 1;
        {
            uint32_t a[28][4];
            float accK[28], accV[28], accQ[28];
            const int lrow = 16 * w + (lane & 7) + (lane & 8);
            const uint32_t lbase = sb + wg * 8192 + lrow * 128;
            const uint32_t lx = (lane >> 4) ^ (lane & 7);
            const uint32_t wofs = hp & 1;
            auto pin2 = [&](uint32_t x0, uint32_t x1) {
                asm volatile("{\n.reg .pred p;\nsetp.ne.u32 p, %2, 0;\n@p st.shared.v2.b32 [%0], {%0,%1};\n}" :: "r"(x0), "r"(x1), "r"(never) : "memory");
            };
            float cS[2][4] = {}, cA[2][4] = {}, cB[2][4] = {}, q0, q1, p0, p1;
            auto sq = [&](float& acc, uint32_t v) { const float lo = bf_lo(v), hi = bf_hi(v); acc = fmaf(hi, hi, fmaf(lo, lo, acc)); };
            uint32_t ready = 0;
            #pragma unroll
            for (int kb = 0; kb < 8; kb++) {
                if (kb < 7) {
                    mbar_wait_unless(ready, bars + 8 * (B_FULLX + kb), 0);
                    if (kb == 0 && tid == 0) STAMP(0);
                    if (kb == 6 && tid == 0) STAMP(25);
                    if (kb == 0) FST(0); if (kb == 2) FST(1); if (kb == 4) FST(2); if (kb == 6) FST(3);
                    #pragma unroll
                    for (int s = 4 * kb; s < 4 * kb + 4; s++) ldsm4(a[s], lbase + slot_x(kb) + ((lx ^ (2 * (s & 3))) << 4));
                }
                if (kb > 0 && kb < 6) ready = mbar_test(bars + 8 * (B_FULLX + kb + 1), 0);
                if (kb == 5) named_sync(9 + wg, 160);
                if (kb == NPIPE) continue;
                const int kc = kb < NPIPE ? kb : kb - 1;
                if (kc == NSQ) { p0 = cS[0][0] + cS[1][0]; p1 = cS[0][2] + cS[1][2]; }
                #pragma unroll
                for (int s = 4 * kc; s < 4 * kc + 4; s++) {
                    mma16816(cS[s & 1], a[s][0], a[s][1], a[s][2], a[s][3], 0x3F803F80u, 0x3F803F80u);
                    if (kc < NSQ) {
                        mma1688(cA[0], a[s][0], a[s][1], a[s][0]); mma1688(cA[1], a[s][2], a[s][3], a[s][2]);
                        mma1688(cB[0], a[s][0], a[s][1], a[s][1]); mma1688(cB[1], a[s][2], a[s][3], a[s][3]);
                    }
                }
            }
            const float m0 = (cS[0][0] + cS[1][0]) * (1.f / D_), m1 = (cS[0][2] + cS[1][2]) * (1.f / D_);
            const uint32_t mm0 = pack_bf16(m0, m0), mm1 = pack_bf16(m1, m1);
            if (lane == 0) mbar_arrive(bars + 8 * B_DONEX);
            auto center = [&](int s) { sub_bf16x2(a[s][0], mm0); sub_bf16x2(a[s][1], mm1); sub_bf16x2(a[s][2], mm0); sub_bf16x2(a[s][3], mm1); };
            uint32_t Ka[8], Kb[8], Kc[8], Va[8], Vb[7], Vc[8];
            float r0, r1, ls0, ls1;
            uint32_t pm, zero;
            uint32_t* od;
            uint4* oh;
            auto kpack = [&](uint32_t (&k)[8], int j, int c, float r) {
                const uint32_t v = pack_bf16(accK[4 * j + c] * r, accK[4 * j + c + 1] * r);
                if (j == 3) { k[3] = t < 2 ? v : 0u; k[4] = t < 2 ? 0u : v; } else k[j + (j > 3)] = v;
            };
            auto batch = [&](auto c0, auto c1) {
                constexpr int n0 = c0.value, n1 = c1.value;
                wg_fence();
                static_for<n0, n1>([&](auto nc) {
                    constexpr int n = nc.value;
                    if (n == 4) { center(4); center(5); center(6); center(7); wg_fence(); }
                    const uint64_t desc = mkdesc(sb + (n < 56 ? slot_kv(n >> 3) + (n & 7) * 2048 : SM_QO + (n - 56) * 2048), 8192, 1024, 1) + wofs;
                    wgmma_rs56<1>(n < 28 ? accK : n < 56 ? accV : accQ, a[n % 28], desc, n % 28 != 0);
                });
                wg_commit();
                if (n0 > 0) wg_wait<1>();
            };
            const uint32_t hs = sb + tid * 16 + warp * 512;
            auto hand_over = [&](const uint32_t (&v)[8], int kv) {
                mbar_wait(bars + 8 * (kv ? B_DONE1 + 5 : B_DONEX), 0);
                sts4(hs + (kv ? SM_HALOV : SM_HALOK), v[0], v[1], v[2], v[3]); sts4(hs + (kv ? SM_HALOV : SM_HALOK) + 512, v[4], v[5], v[6], v[7]);
                if (w == 3) named_arrive(6 + kv, 96);
            };
            auto take_over = [&](uint32_t (&v)[8], int kv) {
                if (w == 0) mbar_wait(bars + 8 * (B_HALO + 2 * kv + wg), 0);
                const uint32_t ad = w ? hs + (kv ? SM_HALOV : SM_HALOK) - 1024 : kv ? sb + lane * 16 + wg * 1024 + SM_HALOV + 8192 : halo_kin(wg, lane);
                const uint4 u0 = lds4(ad), u1 = lds4(ad + (w || kv ? 512 : 16));
                v[0] = u0.x; v[1] = u0.y; v[2] = u0.z; v[3] = u0.w; v[4] = u1.x; v[5] = u1.y; v[6] = u1.z; v[7] = u1.w;
            };
            center(0); center(1); center(2); center(3);
            static_for<0, 7>([&](auto pc) {
                constexpr int p = pc.value;
                mbar_wait(bars + 8 * (B_FULLKV + p), 0);
                if (p == 0 && tid == 0) STAMP(26);
                if (p == 3 && tid == 0) STAMP(27);
                FST(4 + p);
                batch(Int<8 * p>(), Int<8 * p + 8>());
                if (p > 0 && leader) mbar_arrive(bars + 8 * (B_DONE1 + p - 1));
                #pragma unroll
                for (int s = 8 * p + 8; s < 8 * p + 16 && s < 28; s++) center(s);
                if (p == 1) {
                    const float c0 = bf_hi(mm0), c1 = bf_hi(mm1);
                    q0 = fmaf(c0, fmaf(c0, 64.f * NSQ, -2.f * p0), (g & 1) ? cA[0][1] + cA[1][1] : cA[0][0] + cA[1][0]) - D_ * (m0 - c0) * (m0 - c0);
                    q1 = fmaf(c1, fmaf(c1, 64.f * NSQ, -2.f * p1), (g & 1) ? cB[0][3] + cB[1][3] : cB[0][2] + cB[1][2]) - D_ * (m1 - c1) * (m1 - c1);
                    asm("" : "+f"(q0), "+f"(q1));
                    q0 = t == (g >> 1) ? q0 : 0.f; q1 = t == (g >> 1) ? q1 : 0.f;
                    pin2(__float_as_uint(q0), __float_as_uint(q1));
                }
                constexpr int PK = NSQ < 5 ? 5 : 4, NR = 28 - 4 * NSQ;
                if (p >= 2 && p < PK) {
                    #pragma unroll
                    for (int s = 4 * NSQ + NR * (p - 2) / (PK - 2); s < 4 * NSQ + NR * (p - 1) / (PK - 2); s++) { sq(q0, a[s][0]); sq(q1, a[s][1]); sq(q0, a[s][2]); sq(q1, a[s][3]); }
                    pin2(__float_as_uint(q0), __float_as_uint(q1));
                }
                if (p == PK - 1) { q0 = quad_sum(q0); q1 = quad_sum(q1); }
                if (p == PK) {
                    r0 = rsqrt_approx(fmaxf(q0 * (1.f / D_), 0.f) + LN_EPS); r1 = rsqrt_approx(fmaxf(q1 * (1.f / D_), 0.f) + LN_EPS);
                    reg_fence(accK);
                    #pragma unroll
                    for (int j = 0; j < 7; j++) kpack(Kc, j, 2, r1);
                    hand_over(Kc, 0);
                }
                if (p == PK + 1) {
                    #pragma unroll
                    for (int j = 0; j < 7; j++) kpack(Kb, j, 0, r0);
                    #pragma unroll
                    for (int j = 0; j < 8; j += 2) pin2(Kb[j], Kb[j + 1]);
                    ls0 = LOG2E_SCALE * r0; ls1 = LOG2E_SCALE * r1;
                    pm = (2 * t <= g ? 0xFFFFu : 0u) | (2 * t + 1 <= g ? 0xFFFF0000u : 0u);
                    zero = never; asm volatile("" : "+r"(zero));
                    pin2(__float_as_uint(ls0), __float_as_uint(ls1)); pin2(pm, zero);
                }
                if (p == 2) ep = get_tag();
                if (p == 6) {
                    tl = &sc->tiles[ep & 1];
                    const int tt = 2 * tb + (w >> 1);
                    od = tl->o + tt * 14336 + (7 * hp) * 256 + (2 * (2 * (w & 1) + wg)) * 32 + lane;
                    oh = sc->hint_o + (tt * 32 + hp * 4 + (w & 1) * 2 + wg) * 2 + (lane & 1);
                    pin2((uint32_t)(uint64_t)od, (uint32_t)((uint64_t)od >> 32));
                    pin2((uint32_t)(uint64_t)oh, (uint32_t)((uint64_t)oh >> 32));
                }
            });
            if (tid == 0) STAMP(1);
            FST(11);
            mbar_wait(bars + 8 * B_FQ, 0);
            batch(Int<56>(), Int<60>());
            reg_fence(accV);
            if (leader) mbar_arrive(bars + 8 * (B_DONE1 + 6));
            if (tid == 0) STAMP(2);
            FST(12);
            #pragma unroll
            for (int j = 0; j < 7; j++) Vc[j] = movtrans(pack_bf16(accV[4 * j + 2] * r1, accV[4 * j + 3] * r1));
            Vc[7] = Vc[6];
            hand_over(Vc, 1);
            batch(Int<60>(), Int<66>());
            #pragma unroll
            for (int j = 0; j < 7; j++) {
                Vb[j] = movtrans(pack_bf16(accV[4 * j] * r0, accV[4 * j + 1] * r0));
                Vc[j] |= zero;
            }
            batch(Int<66>(), Int<72>());
            #pragma unroll
            for (int j = 0; j < 7; j++) pin2(Vb[j], Vc[j]);
            mbar_wait(bars + 8 * (B_FQ + 1), 0);
            FST(13);
            if (w > 0 && lane < 2) { const uint32_t now = gtime32(); st_relaxed4(oh, ep, now, ep, now); }
            batch(Int<72>(), Int<84>());
            FST(14);
            named_sync(1 + wg, 128);
            take_over(Ka, 0);
            if (tid == 0) STAMP(3);
            wg_wait<0>();
            reg_fence(accQ);
            if (tid == 0) STAMP(4);
            FST(15);
            const bool first = (tb == 0 && w == 0);
            uint32_t pA[2], pB0[2], pB1[2], pC[2], z0[2], z1[2];
            float sA[2][4] = {}, sB[2][4] = {}, sC[2][4] = {}, e[2][4], inv[2][2];
            #pragma unroll
            for (int k = 0; k < 2; k++) {
                #pragma unroll
                for (int h = 0; h < 2; h++) {
                    const float* qq = accQ + 12 * h + 8 * k;
                    uint32_t a2 = pack_bf16(qq[4], qq[5]), a3 = pack_bf16(qq[6], qq[7]);
                    if (h == 0 && k == 1) { a2 |= zero; a3 |= zero; }
                    const uint32_t a0 = pack_bf16(qq[0], qq[1]), a1 = pack_bf16(qq[2], qq[3]);
                    mma16816(sB[h], a0, a1, a2, a3, Kb[4 * h + 2 * k], Kb[4 * h + 2 * k + 1]);
                    mma16816(sA[h], a0, a1, a2, a3, Ka[4 * h + 2 * k], Ka[4 * h + 2 * k + 1]);
                    mma16816(sC[h], a0, a1, a2, a3, Kc[4 * h + 2 * k], Kc[4 * h + 2 * k + 1]);
                }
            }
            #pragma unroll
            for (int h = 0; h < 2; h++) {
                const bool n0 = pm & 1, n1 = (int)pm < 0;
                const float l00 = n0 ? sB[h][0] : (first ? -INFINITY : sA[h][0]), l01 = n1 ? sB[h][1] : (first ? -INFINITY : sA[h][1]);
                const float l10 = n0 ? sC[h][2] : sB[h][2], l11 = n1 ? sC[h][3] : sB[h][3];
                const float x0 = -ls0 * quad_max(fmaxf(l00, l01)), x1 = -ls1 * quad_max(fmaxf(l10, l11));
                e[h][0] = ex2(fmaf(l00, ls0, x0)); e[h][1] = ex2(fmaf(l01, ls0, x0)); e[h][2] = ex2(fmaf(l10, ls1, x1)); e[h][3] = ex2(fmaf(l11, ls1, x1));
            }
            pin4(never, e[0][0], e[0][2], e[1][0], e[1][2]);
            take_over(Va, 1);
            #pragma unroll
            for (int h = 0; h < 2; h++) {
                inv[h][0] = rcp_approx(quad_sum(e[h][0] + e[h][1])); inv[h][1] = rcp_approx(quad_sum(e[h][2] + e[h][3]));
                const uint32_t P0 = pack_bf16(e[h][0], e[h][1]), P1 = pack_bf16(e[h][2], e[h][3]);
                pB0[h] = P0 & pm; pA[h] = P0 & ~pm; pC[h] = P1 & pm; pB1[h] = P1 & ~pm; z0[h] = P0 & zero; z1[h] = P1 & zero;
            }
            float o[8][4];
            #pragma unroll
            for (int j = 0; j < 8; j++) {
                o[j][0] = o[j][1] = o[j][2] = o[j][3] = 0.f;
                mma16816(o[j], pB0[j >> 2], pB1[j >> 2], z0[j >> 2], pC[j >> 2], Vb[j - (j >> 2)], Vc[j - (j >> 2)]);
            }
            if (tid == 0) STAMP(12);
            FST(16);
            if (tid == 0) STAMP(16);
            #pragma unroll
            for (int j = 0; j < 8; j++) mma1688(o[j], pA[j >> 2], z1[j >> 2], Va[j - (j >> 2)]);
            #pragma unroll
            for (int j = 0; j < 7; j++) {
                float v[4];
                #pragma unroll
                for (int c = 0; c < 4; c++) {
                    v[c] = j < 3 ? o[j][c] : j > 3 ? o[j + 1][c] : (t < 2 ? o[3][c] : o[4][c]);
                    v[c] *= j < 3 ? inv[0][c >> 1] : j > 3 ? inv[1][c >> 1] : (t < 2 ? inv[0][c >> 1] : inv[1][c >> 1]);
                }
                od[j * 256] = pack_bf16(v[0], v[1]);
                od[j * 256 + 32] = pack_bf16(v[2], v[3]);
            }
            if (lane == 0) mbar_arrive(bars + 8 * B_DONEQ);
            if (tid == 0) STAMP(5);
            FST(17);
        }
        const int z = get_tag() - ep, slot1 = slot + z, tid1 = tid + z, warp1 = warp + z;
        ep += z;
        {
        ASSIGN_WORK(slot1)
        const int tid = tid1, lane = tid & 31, wg = warp1 >> 2, w = warp1 & 3, g = lane >> 2, t = lane & 3;
        tl = &sc->tiles[ep & 1];
        const uint32_t live = wg ^ 1;
        uint32_t rb0, rb1, late[14];
        const unsigned short* pb = (const unsigned short*)(live ? b2 + tt2 * 64 : b1 + ft * 64) + 16 * w + g;
        auto stage_late = [&]() {
            #pragma unroll
            for (int c = 0; c < 14; c++) asm volatile("st.shared.u32 [%0], %1;" :: "r"(sb + SM_H + wg * 8192 + (tid & 127) * 4 + c * 512), "r"(late[c]) : "memory");
            fence_async_smem();
            named_sync(1 + wg, 128);
        };
        auto store_late = [&](bool on, uint32_t* p) {
            #pragma unroll
            for (int c = 0; c < 4; c++)
                if (elect() && on && (c < 3 || w < 2)) bulk_st(p + (4 * c + w) * 256, sb + SM_H + wg * 8192 + (4 * c + w) * 512, 512);
            asm volatile("cp.async.bulk.commit_group;" ::: "memory");
        };
        if (live) {
            float acc[56];
            const int hrow = 32 * (w >> 1) + 2 * ((lane & 7) + (lane & 8)) + (w & 1);
            const uint32_t ha = sb + SM_H + hrow * 128 + (((lane >> 4) ^ (hrow & 7)) << 4);
            uint4* sp = sc->stats + tt2 * 256 + 16 * w + g + 8 * (t & 1);
            uint4* sp_out = sp + q * 64;
            const uint4* sp_in = sp + (t & 2) * 64;
            uint32_t* hd = tl->hn + ((q >> 1) * 32 + (tt2 >> 1)) * 7168 + (q & 1) * 3584 + (tt2 & 1) * 128 + w * 32 + lane;
            pin_ptr(never, sp_out); pin_ptr(never, sp_in); pin_ptr(never, hd);
            float s0 = 0.f, s1 = 0.f, q0 = 0.f, q1 = 0.f, s2 = 0.f, s3 = 0.f, q2 = 0.f, q3 = 0.f;
            auto sums = [&](int j0, int j1) {
                #pragma unroll
                for (int j = j0; j < j1; j++) {
                    s0 += acc[4 * j]; s2 += acc[4 * j + 1]; q0 = fmaf(acc[4 * j], acc[4 * j], q0); q2 = fmaf(acc[4 * j + 1], acc[4 * j + 1], q2);
                    s1 += acc[4 * j + 2]; s3 += acc[4 * j + 3]; q1 = fmaf(acc[4 * j + 2], acc[4 * j + 2], q1); q3 = fmaf(acc[4 * j + 3], acc[4 * j + 3], q3);
                }
            };
            {
                mbar_wait(bars + 8 * B_FULLWO, 0);
                #pragma unroll
                for (int jp = 0; jp < 7; jp++) {
                    uint32_t xx[4];
                    ldsm4(xx, hcol(ha, jp));
                    #pragma unroll
                    for (int r = 0; r < 4; r++) { acc[8 * jp + 2 * r] = bf_lo(xx[r]); acc[8 * jp + 2 * r + 1] = bf_hi(xx[r]); }
                }
                reg_fence(acc);
                named_sync(12, 256);
                spin_mma(bars + 8 * B_FULLX, never);
                auto od_ = [&](int s) { return mkdesc(sb + SM_QO + s * 2048, 1024, 128, 0); };
                auto wd_ = [&](int s) { return mkdesc(sb + slot_wo(s >> 2) + (s & 3) * 2048, 8192, 1024, 1); };
                float accl[32], accr[24];
                #pragma unroll
                for (int i = 0; i < 5; i++) {
                    if (i < 4) mbar_wait(bars + 8 * (B_FULLO + i), 0);
                    if (i == 0 && tid == 0) STAMP(7);
                    if (i == 1) { rb0 = ld_u16(pb); rb1 = ld_u16(pb + 8); }
                    wg_fence();
                    #pragma unroll
                    for (int ss = i ? 0 : 4; ss < 8; ss++) {
                        if (i < 3) wgmma_ss112<0, 1>(acc, od_(8 * i - 4 + ss), wd_(8 * i - 4 + ss));
                        else if (i == 4) wgmma_ss64<0, 1>(accl, od_(20 + ss), wd_(20 + ss));
                        else if (ss == 0) wgmma_ss48<0, 1, 0>(accr, od_(20), wd_(20) + 512);
                        else wgmma_ss48<0, 1>(accr, od_(20 + ss), wd_(20 + ss) + 512);
                    }
                    wg_commit();
                    if (i > 0) {
                        wg_wait<1>();
                        if (i == 3) {
                            reg_fence(acc);
                            #pragma unroll
                            for (int c = 0; c < 32; c++) accl[c] = __uint_as_float(__float_as_uint(acc[c]) | never);
                            reg_fence(accl);
                        }
                        if (i < 4 && leader) mbar_arrive(bars + 8 * (B_DONEO + i - 1));
                    }
                }
                reg_fence(accr);
                #pragma unroll
                for (int c = 0; c < 24; c++) acc[32 + c] += accr[c];
                sums(8, 14);
                pin4(never, s0, s1, s2, s3); pin4(never, q0, q1, q2, q3);
                wg_wait<0>();
                reg_fence(accl);
                #pragma unroll
                for (int c = 0; c < 32; c++) acc[c] = accl[c];
                if (leader) mbar_arrive(bars + 8 * (B_DONEO + 3));
                if (tid == 0) STAMP(8);
            }
            sums(0, 8);
            s0 += s2; s1 += s3; q0 += q2; q1 += q3;
            float sr = ((t & 1) ? s1 : s0) + __shfl_xor_sync(0xffffffffu, (t & 1) ? s0 : s1, 1), qr = ((t & 1) ? q1 : q0) + __shfl_xor_sync(0xffffffffu, (t & 1) ? q0 : q1, 1);
            sr += __shfl_xor_sync(0xffffffffu, sr, 2); qr += __shfl_xor_sync(0xffffffffu, qr, 2);
            st_relaxed4_if(t < 2, sp_out, __float_as_uint(sr), __float_as_uint(qr), ep);
            const uint32_t tp = clock32();
            named_arrive(5, 256);
            if (tid == 0) STAMP(9);
            #pragma unroll
            for (int jp = 0; jp < 7; jp++)
                stsm4(hcol(ha, jp), pack_bf16(acc[8 * jp], acc[8 * jp + 1]), pack_bf16(acc[8 * jp + 2], acc[8 * jp + 3]),
                      pack_bf16(acc[8 * jp + 4], acc[8 * jp + 5]), pack_bf16(acc[8 * jp + 6], acc[8 * jp + 7]));
            uint4 v0, v1;
            if (POLL0) { while (clock32() - tp < POLL0) {} __syncwarp(); }
            do { v0 = ld_relaxed4(sp_in); v1 = ld_relaxed4(sp_in + 64); } while (__any_sync(0xffffffffu, v0.w != ep || v1.w != ep));
            if (tid == 0) STAMP(10);
            sr = __uint_as_float(v0.x) + __uint_as_float(v1.x); qr = __uint_as_float(v0.y) + __uint_as_float(v1.y);
            sr += __shfl_xor_sync(0xffffffffu, sr, 2); qr += __shfl_xor_sync(0xffffffffu, qr, 2);
            const float m = sr * (1.f / D_), var = fmaxf(qr * (1.f / D_) - m * m, 0.f);
            const float r = rsqrt_approx(fmaf(var, 4.f + 4.f * LN_EPS, 4.f * LN_EPS * LN_EPS)), c = -m * r;
            const float r0 = __shfl_sync(0xffffffffu, r, lane & ~1), c0 = __shfl_sync(0xffffffffu, c, lane & ~1);
            const float r1 = __shfl_sync(0xffffffffu, r, lane | 1), c1 = __shfl_sync(0xffffffffu, c, lane | 1);
            #pragma unroll
            for (int j = 0; j < 14; j++) st_global_if(1, hd + j * 256, pack_bf16(fmaf(acc[4 * j], r0, c0), fmaf(acc[4 * j + 1], r0, c0)));
            if (never) mbar_arrive(bars);
            #pragma unroll
            for (int j = 0; j < 14; j++) late[j] = pack_bf16(fmaf(acc[4 * j + 2], r1, c1), fmaf(acc[4 * j + 3], r1, c1));
            if (tid == 0) STAMP(11);
        } else {
            named_arrive(12, 256);
            check_tiles<0>(w, 4, 4, tl->o + tt2 * 14336, false, lane, true);
            rb0 = ld_u16(pb); rb1 = ld_u16(pb + 8);
            auto reset_tiles = [&](int v, int i0, int i1) {
                const int l = slot * 48 + v * 16 + lane / 2;
                #pragma unroll
                for (int i = i0; i < i1; i++)
                    st_relaxed4_if(i < 6 || l < sizeof(Tiles) / 128 - 6 * 6144, (uint4*)&sc->tiles[~ep & 1] + (i * 6144 + l) * 8 + (lane & 7), EMPTY, EMPTY, EMPTY);
            };
            if (CL_N && w < 3) { mbar_wait(bars + 8 * (B_DONEO + CL_P2), 0); reset_tiles(w, 0, CL_N); }
            named_sync(5, 256);
            auto phase3 = [&](auto nc) {
                constexpr int NC = nc.value;
                float acc[4 * NC];
                uint32_t* ud = tl->u + (pr3 * 28 + (ft >> 1) + (NC == 14 ? 4 : 0)) * 7168 + col3 * 256 + (ft & 1) * 128 + w * 32 + lane;
                #pragma unroll
                for (int j = 0; j < 4 * NC; j++) acc[j] = 0.5f * bf_lo((j & 2) ? rb1 : rb0);
                #pragma unroll 1
                for (uint32_t pass = never; pass < 2; pass++) {
                    if (pass) {
                        mix_mainloop<32>(TSVAL acc, leader);
                        if (leader) STAMP(14);
                    }
                    uint32_t pk[NC];
                    #pragma unroll
                    for (int j = 0; j < NC; j++) {
                        const float k = j < GDEP ? GELU_K1 : __uint_as_float(__float_as_uint(GELU_K1) | (pk[j - GDEP] & never));
                        pk[j] = pack_bf16(gelu_half(acc[4 * j], k), gelu_half(acc[4 * j + 1], k));
                        st_global_if(pass, ud + j * 256, pk[j]);
                    }
                }
                if (leader) STAMP(15);
                #pragma unroll
                for (int j = 0; j < NC; j++) late[j] = pack_bf16(gelu_half(acc[4 * j + 2], GELU_K1), gelu_half(acc[4 * j + 3], GELU_K1));
                if (NC == 14) {
                    stage_late();
                    mbar_wait(bars + 8 * (B_FULLB + LATE_AT4), 1);
                    store_late(true, tl->u + (pr3 * 28 + (ft >> 1) + 14) * 7168 + col3 * 256 + (ft & 1) * 128);
                } else {
                    #pragma unroll
                    for (int c = 0; c < NC; c++) st_global_if(1, ud + 4 * 7168 + c * 256, late[c]);
                }
            };
            if (early) phase3(Int<10>()); else phase3(Int<14>());
            if (w) {
                if (early && w == 1) fetch_times(TSVAL sc->go, 1, ep, lane);
                if (CL_N < 7) { mbar_wait(bars + 8 * (B_DONE + CL_AT), 1); reset_tiles(w - 1, CL_N, 7); }
            }
            if (leader) mbar_wait_wd(bars + 8 * B_END, 0);
            return;
        }
        {
            float acc[56];
            const uint32_t ad = sb + SM_H + (16 * w + (lane & 15)) * 128 + (((lane >> 4) ^ (lane & 7)) << 4);
            const float bb0 = bf_lo(rb0), bb1 = bf_lo(rb1);
            named_sync(1, 128);
            #pragma unroll
            for (int jp = 0; jp < 7; jp++) {
                uint32_t hh[4];
                ldsm4(hh, hcol(ad, jp));
                #pragma unroll
                for (int r = 0; r < 4; r++) { acc[8 * jp + 2 * r] = bf_lo(hh[r]) + ((r & 1) ? bb1 : bb0); acc[8 * jp + 2 * r + 1] = bf_hi(hh[r]) + ((r & 1) ? bb1 : bb0); }
            }
            named_sync(1, 128);
            stage_late();
            if (tid == 0) STAMP(39);
            reg_fence(acc);
            spin_mma(bars + 8 * (B_FULLX + 1), never);
            mbar_wait(bars + 8 * (B_FULLB + LATE_AT), 0);
            store_late(true, tl->hn + ((q >> 1) * 32 + 16 + (tt2 >> 1)) * 7168 + (q & 1) * 3584 + (tt2 & 1) * 128);
            check_tiles<1>(CH_H + w, 4, 32, tl->hn + pr3 * 32 * 7168 + col3 * 256, early, lane, false);
            mbar_wait(bars + 8 * (B_DONE + START4), 0);
            mix_mainloop<28>(TSVAL acc, leader);
            if (leader) mbar_arrive(bars + 8 * B_END);
            if (tid == 0) STAMP(18);
            #pragma unroll
            for (int jp = 0; jp < 7; jp++)
                stsm4(hcol(ad, jp), pack_bf16(acc[8 * jp], acc[8 * jp + 1]), pack_bf16(acc[8 * jp + 2], acc[8 * jp + 3]),
                         pack_bf16(acc[8 * jp + 4], acc[8 * jp + 5]), pack_bf16(acc[8 * jp + 6], acc[8 * jp + 7]));
            fence_async_smem();
            __syncwarp();
            if (elect()) {
                tma2d_store(&tm_out64, c64, tt2 * 64 + 16 * w, sb + SM_H + w * 2048);
                tma2d_store(&tm_out48, c48, tt2 * 64 + 16 * w, sb + SM_H + 8192 + w * 2048);
            }
            asm volatile("cp.async.bulk.commit_group;" ::: "memory");
            asm volatile("cp.async.bulk.wait_group.read 0;" ::: "memory");
            if (tid == 0) { sc->epoch[slot] = ep; STAMP(19); }
        }
        }
    } else {
        asm volatile("setmaxnreg.dec.sync.aligned.u32 56;");
        int warp2; asm("mov.u32 %0, %1;" : "=r"(warp2) : "r"(warp));
        if (warp2 > 8) {
            ASSIGN_WORK(get_slot())
            if (slot >= 128) return;
            uint32_t ep, cl;
            uint4* const oh = sc->hint_o + (2 * tb * 32 + hp * 4) * 2 + (lane & 3);
            uint4* const hu = sc->hint_u + (early ? ech * 8 + ft : 40 + q * 20 + ft) * 2;
            if (warp == 10) {
                post_hint(sc->hint_h + (q * 32 + tt2) * 2, 0, lane);
                post_hint(hu, 0, lane);
            }
            if (warp == 11) {
                ep = ld_volatile(&sc->epoch[slot]) + 1; cl = ld_acquire(&sc->clean);
                post_hint(sc->hint_k + (tb * 8 + hp) * 2, 0, lane);
                if (lane < (tb < 15 ? 4 : 0)) st_relaxed4(oh + 128, 0, 0, 0, 0);
                if (lane < (tb ? 0 : 4)) st_relaxed4(oh, 0, 0, 0, 0);
            }
            if (elect()) {
                if (warp == 9) {
                    #pragma unroll
                    for (int i = B_DONE1; i < B_DONEO; i++) mbar_init(bars + 8 * i, i < B_DONEX ? 2 : i == B_DONEX ? 8 : 9);
                }
                #pragma unroll
                for (int i = 0; i < 54; i++) mbar_init(bars + 8 * (B_DONEO + i) + (warp - 9) * 432, 1);
                asm volatile("fence.mbarrier_init.release.cluster;" ::: "memory");
            }
            named_sync(8, 128);
            if (warp < 11) mbar_expect(sb + SM_RAW + 8 * (tid - 288), tid == 288 ? 8192 : tid < 292 ? 16384 : early && tid < 324 ? 10240 : 14336);
            if (warp == 9) { named_arrive(4, 64); named_arrive(9, 160); named_arrive(10, 160); }
            if (warp < 11) {
                ep = get_tag();
                mbar_wait(bars + 8 * (B_DONE1 + HALO_AT), 0);
                #pragma unroll 1
                for (int kv = 0; kv < 2; kv++) {
                    uint4 v0 = {}, v1 = {}, v2 = {};
                    if (tb > 0) {
                        const uint4* hg = sc->halo + ((((tb - 1) * 8 + hp) * 2 + warp - 9) * 2 + kv) * 96 + lane;
                        if (kv == 0) while (ld_relaxed(sc->hint_k + ((tb - 1) * 8 + hp) * 2) != ep) {}
                        do { v0 = ld_relaxed4(hg); v1 = ld_relaxed4(hg + 32); v2 = ld_relaxed4(hg + 64); } while (!__all_sync(0xffffffffu, v0.w == ep && v1.w == ep && v2.w == ep));
                    }
                    if (kv) mbar_wait(bars + 8 * (B_DONE1 + 5), 0);
                    const uint32_t hs = kv ? sb + lane * 16 + (warp - 9) * 1024 + SM_HALOV + 8192 : halo_kin(warp - 9, lane);
                    sts4(hs, v0.x, v0.y, v0.z, v1.x); sts4(hs + (kv ? 512 : 16), v1.y, v1.z, v2.x, v2.y);
                    __syncwarp();
                    if (lane == 0) mbar_arrive(bars + 8 * (B_HALO + 2 * kv + warp - 9));
                }
                if (tid == 288) STAMP(21);
            } else {
                const long long t0 = clock64();
                while (__any_sync(0xffffffffu, (int)(cl - ep) < 0)) { cl = ld_acquire(&sc->clean); if (clock64() - t0 > WD_CLKS) __trap(); }
                if (lane == 0) { *(volatile uint32_t*)(smem_raw + SM_TAG) = ep; mbar_arrive(bars + 8 * B_CLR); }
                uint4* hg = sc->halo + (tb * 8 + hp) * 384 + lane;
                #pragma unroll 1
                for (int kv = 0; kv < 2; kv++) {
                    const uint32_t hs = sb + lane * 16 + 3072 + (kv ? SM_HALOV : SM_HALOK);
                    named_sync(6 + kv, 96);
                    #pragma unroll
                    for (int p = 0; p < 2; p++) {
                        const uint4 u0 = lds4(hs + p * 4096), u1 = lds4(hs + p * 4096 + 512);
                        st_relaxed4(hg + p * 192, u0.x, u0.y, u0.z, ep); st_relaxed4(hg + p * 192 + 32, u0.w, u1.x, u1.y, ep); st_relaxed4(hg + p * 192 + 64, u1.z, u1.w, ep, ep);
                    }
                    hg += 96;
                    if (kv == 0) {
                        post_hint(sc->hint_k + (tb * 8 + hp) * 2, ep, lane);
                        #pragma unroll
                        for (int j = 0; j < 6; j++) st_relaxed4(hg + j * 32 + (j / 3) * 96, 0, 0, 0, 0);
                    }
                }
                const uint32_t now = gtime32() - LATE_O;
                if (lane < (tb < 15 ? 4 : 0)) st_relaxed4(oh + 128, ep, now, ep, now);
                if (lane < (tb ? 0 : 4)) st_relaxed4(oh, ep, now, ep, now);
                if (lane == 0) STAMP(23);
                if (lane == 0) mbar_arrive(bars + 8 * B_DONEQ);
            }
            if (warp > 9) {
                const Tiles* const tl = &sc->tiles[ep & 1];
                check_tiles<1>(11 - warp, 2, CH_H, tl->hn + pr3 * 32 * 7168 + col3 * 256, early, lane, true);
                if (warp == 10) {
                    mbar_wait(bars + 8 * (B_DONE + (early ? HINT_E : HINT_U)), 0);
                    post_time(hu, ep, lane);
                }
                if (warp == 11) {
                    mbar_wait(bars + 8 * (B_DONE + (early ? POLL_E : POLL_N)), 0);
                    fetch_times(TSVAL sc->go, 0, ep, lane);
                }
                check_tiles<2>(11 - warp, 2, 28, tl->u + (q >> 1) * 28 * 7168 + (q & 1) * 3584, false, lane, true);
            } else {
                int aslot = 0;
                if (lane == 0) { prefetch_map(&tm_out64); prefetch_map(&tm_out48); }
                #pragma unroll
                for (int i = 0; i < HINT_F; i++) mbar_wait(bars + 8 * (B_FULLO + i), 0);
                post_time(sc->hint_h + (q * 32 + tt2) * 2, ep, lane);
                #pragma unroll 1
                for (int i = 0; i < 30; i++) {
                    if (i == POLL_I && !early) fetch_times(TSVAL sc->go, 1, ep, lane);
                    int d = 2 * i - 11 + (i >= A4_FROM ? A4_DLY : 0);
                    if (early) d = i < 16 ? 1 + (i - NA_SLOTS) * AE_END / 9 : max(d, AE_W2);
                    mbar_wait(bars + 8 * (i < NA_SLOTS ? B_DONEQ + ((A_SCHED >> (4 * i)) & 15) : B_DONE + (d & 31)), d >= 32);
                    if (elect()) {
                        const uint32_t bar = bars + 8 * (B_FULLA + (i & 15)), dst = sb + SM_ARING + aslot * 16384;
                        mbar_expect(bar, 16384);
                        if (i < 16) tma5d(dst, &tm_w1, ft * 64, (i & 7) * 8, i >> 3, bar);
                        else tma5d(dst, &tm_w2, tt2 * 64, 8 * (i < 20 ? i & 1 : i < 25 ? i - 18 : i - 23), i < 20 ? (i >> 1) & 1 : i >= 25, bar);
                    }
                    aslot = aslot == NA_SLOTS - 1 ? 0 : aslot + 1;
                }
            }
        } else {
            const int slot0 = get_slot(), row0 = (slot0 >> 5) * 256 + (slot0 & 12) * 16;
            if (elect()) {
                prefetch_map(&tm_x);
                #pragma unroll
                for (int i = 0; i < 7; i++) mbar_init(bars + 8 * i, 1);
                asm volatile("fence.mbarrier_init.release.cluster;" ::: "memory");
            }
            named_arrive(0, 288);
            if (elect()) {
                #pragma unroll 1
                for (int kb = 0; kb < 7; kb++) {
                    load_x(kb, row0);
                    if (kb == 0) STAMP(22);
                }
                #pragma unroll
                for (int i = 7; i < B_DONE1; i++) mbar_init(bars + 8 * i, 1);
                asm volatile("fence.mbarrier_init.release.cluster;" ::: "memory");
            }
            named_arrive(8, 128);
            ASSIGN_WORK(get_slot())
            if (slot >= 128) return;
            #pragma unroll 1
            for (int kb = 0; kb < 7; kb++) {
                if (kb == 6) { named_sync(4, 64); mbar_wait(bars + 8 * B_DONEX, 0); }
                if (elect()) {
                    const uint32_t st = sb + slot_kv(kb), bar = bars + 8 * (B_FULLKV + kb);
                    mbar_expect(bar, 16384);
                    #pragma unroll
                    for (int i = 0; i < 2; i++) {
                        const int n = 2 * kb + (i ^ (G & 1));
                        tma2d(st + (n & 1) * 8192, &tm_wqkv, (n < 7 ? 448 : 896) + wcol, (n < 7 ? n : n - 7) * 64, bar);
                    }
                }
            }
            if (elect()) {
                mbar_expect(bars + 8 * B_FQ, 32768);
                mbar_expect(bars + 8 * (B_FQ + 1), 24576);
                #pragma unroll 1
                for (int i = 0; i < 7; i++) { const int j = i == 6 ? i : i ^ (G & 1); tma2d(sb + SM_QO + j * 8192, &tm_wqkv, wcol, j * 64, bars + 8 * (B_FQ + (i >> 2))); }
                mbar_expect(bars + 8 * B_FULLWO, 512 * 112 * 2);
            }
            #pragma unroll 1
            for (int i = 0; i < 7; i++) {
                const int kb = ((q & 1 ? WO_ORD1 : WO_ORD0) >> (4 * i)) & 7;
                if (kb < 5) mbar_wait(bars + 8 * (B_DONE1 + kb), 0);
                if (elect()) {
                    tma2d(sb + slot_wo(kb), &tm_wo64, c64, kb * 64, bars + 8 * B_FULLWO);
                    tma2d(sb + slot_wo(kb) + 8192, &tm_wo48, c48, kb * 64, bars + 8 * B_FULLWO);
                }
            }
            if (elect()) {
                tma2d(sb + SM_H, &tm_xr64, c64, tt2 * 64, bars + 8 * B_FULLWO);
                tma2d(sb + SM_H + 8192, &tm_xr48, c48, tt2 * 64, bars + 8 * B_FULLWO);
            }
            if (smem_u32(smem_raw) != SB) __trap();
            const uint32_t ep = get_tag();
            const Tiles* const tl = &sc->tiles[ep & 1];
            mbar_wait(bars + 8 * (B_DONE1 + 6), 0);
            const uint32_t t_o = last_hint(TSVAL sc->hint_o + (tt2 * 32 + lane) * 2, ep, 38);
            mbar_wait(bars + 8 * B_DONEQ, 0);
            wait_until(t_o + GO_O);
            if (elect()) {
                #pragma unroll
                for (int i = 0; i < 4; i++) {
                    bulk_ld(sb + SM_QO + max(2 * i - 1, 0) * 8192, tl->o + tt2 * 14336 + max(2 * i - 1, 0) * 2048, i ? 16384 : 8192, sb + SM_RAW + 8 * i);
                }
            }
            if (lane == 0) STAMP(20);
            wait_until(t_o + GO_O + STOP2);
            if (lane == 0) mbar_arrive(bars + 8 * B_FULLX);
            mbar_wait(bars + 8 * (B_DONEO + POLL_H), 0);
            const uint32_t* src = tl->hn + pr3 * 32 * 7168 + col3 * 256;
            uint32_t bytes = early ? 10240 : 14336, dst = sb + SM_BRING, top = dst + (early ? NE_SLOTS * 10240 : NB_SLOTS * 14336), raw = sb + SM_RAW + 32;
            auto issue = [&]() {
                if (elect()) bulk_ld(dst, src, bytes, raw);
                src += 7168; raw += 8; dst += bytes;
                if (dst == top) dst = sb + SM_BRING;
            };
            uint2 th;
            do { th = ld_relaxed2((const uint2*)sc->go + (lane & 15)); } while (!__all_sync(0xffffffffu, th.x == ep));
            STAMP(42);
            mbar_wait(bars + 8 * (B_DONEO + 3), 0);
            {
                uint32_t bit = 1, wait = ~1u;
                wait_until(__shfl_sync(0xffffffffu, th.y, 0) + GO_H);
                #pragma unroll 1
                do {
                    while (wait & bit) wait = __ballot_sync(0xffffffffu, (int)(gtime32() - th.y - GO_H) < 0);
                    if (bit == 1) STAMP(29);
                    issue();
                    if (bit == 1 << STOP3 && lane == 0) mbar_arrive(bars + 8 * (B_FULLX + 1));
                    bit *= 2;
                } while (dst != sb + SM_BRING);
            }
            uint32_t done = bars + 8 * B_DONE;
            #pragma unroll 1
            do { mbar_wait(done, 0); done += 8; issue(); } while (raw != sb + SM_RAW + 288);
            if (early) mbar_wait(bars + 8 * (B_DONE + 31), 0);
            src = tl->u + (q >> 1) * 28 * 7168 + (q & 1) * 3584; bytes = 14336; dst = sb + SM_BRING; top = dst + NB_SLOTS * 14336;
            done = bars + 8 * (B_DONE + 24);
            #pragma unroll 1
            for (uint32_t par = 0; par < 2; par++) {
                mbar_wait(bars + 8 * (B_GO + par), 0);
                const uint32_t ts = *(volatile uint32_t*)(smem_raw + SM_TIME + 128 * par + 4 * lane);
                if (par) done = bars + 8 * B_DONE;
                uint32_t bit = 1, wait = ~1u;
                wait_until(__shfl_sync(0xffffffffu, ts, 0));
                #pragma unroll 1
                do {
                    while (wait & bit) wait = __ballot_sync(0xffffffffu, (int)(gtime32() - ts) < 0);
                    if (bit == 1) STAMP(par ? 36 : 30);
                    mbar_wait(done, par); done += 8;
                    issue();
                    bit *= 2;
                } while (bit != (par ? 1 << 20 : 1 << 8));
            }
        }
    }
}

typedef CUresult (*EncodeFn)(CUtensorMap*, CUtensorMapDataType, cuuint32_t, void*, const cuuint64_t*, const cuuint64_t*, const cuuint32_t*,
                             const cuuint32_t*, CUtensorMapInterleave, CUtensorMapSwizzle, CUtensorMapL2promotion, CUtensorMapFloatOOBfill);

void make_map(EncodeFn fn, CUtensorMap* tm, const void* ptr, int rank, const cuuint64_t* dims, const cuuint64_t* strides, const cuuint32_t* box, CUtensorMapSwizzle sw) {
    cuuint32_t es[5] = {1, 1, 1, 1, 1};
    fn(tm, CU_TENSOR_MAP_DATA_TYPE_BFLOAT16, rank, const_cast<void*>(ptr), dims, strides, box, es, CU_TENSOR_MAP_INTERLEAVE_NONE, sw,
       CU_TENSOR_MAP_L2_PROMOTION_NONE, CU_TENSOR_MAP_FLOAT_OOB_FILL_NONE);
}

}

extern "C" void kernel_launch(void* const* d_in, const int* in_sizes, int n_in, void* d_out, int out_size) {
    const __nv_bfloat16* x = (const __nv_bfloat16*)d_in[0];
    const __nv_bfloat16* wqkv = (const __nv_bfloat16*)d_in[1];
    const __nv_bfloat16* wo = (const __nv_bfloat16*)d_in[2];
    const __nv_bfloat16* w1 = (const __nv_bfloat16*)d_in[4];
    const __nv_bfloat16* b1 = (const __nv_bfloat16*)d_in[5];
    const __nv_bfloat16* w2 = (const __nv_bfloat16*)d_in[6];
    const __nv_bfloat16* b2 = (const __nv_bfloat16*)d_in[7];

    void* fnp = nullptr; cudaDriverEntryPointQueryResult qr;
    cudaGetDriverEntryPoint("cuTensorMapEncodeTiled", &fnp, cudaEnableDefault, &qr);
    EncodeFn fn = (EncodeFn)fnp;
    CUtensorMap tx, twqkv, two64, two48, tw1, tw2, txr64, txr48, tout64, tout48;
    { cuuint64_t d[3] = {448, 2, 1024}, s[2] = {896, 1792}; cuuint32_t b[3] = {64, 1, 64}; make_map(fn, &tx, x, 3, d, s, b, CU_TENSOR_MAP_SWIZZLE_128B); }
    { cuuint64_t d[2] = {1344, 448}, s[1] = {2688}; cuuint32_t b[2] = {64, 64}; make_map(fn, &twqkv, wqkv, 2, d, s, b, CU_TENSOR_MAP_SWIZZLE_128B); }
    { cuuint64_t d[2] = {448, 448}, s[1] = {896}; cuuint32_t b[2] = {64, 64}; make_map(fn, &two64, wo, 2, d, s, b, CU_TENSOR_MAP_SWIZZLE_128B); }
    { cuuint64_t d[2] = {448, 448}, s[1] = {896}; cuuint32_t b[2] = {48, 64}; make_map(fn, &two48, wo, 2, d, s, b, CU_TENSOR_MAP_SWIZZLE_128B); }
    { cuuint64_t d[5] = {1792, 8, 2, 64, 2}, s[4] = {2 * 3584, 3584, 32 * 3584, 16 * 3584}; cuuint32_t b[5] = {64, 8, 2, 8, 1}; make_map(fn, &tw1, w1, 5, d, s, b, CU_TENSOR_MAP_SWIZZLE_128B); }
    { cuuint64_t d[5] = {2048, 8, 2, 56, 2}, s[4] = {4096, 16 * 4096, 32 * 4096, 8 * 4096}; cuuint32_t b[5] = {64, 8, 2, 8, 1}; make_map(fn, &tw2, w2, 5, d, s, b, CU_TENSOR_MAP_SWIZZLE_128B); }
    { cuuint64_t d[2] = {448, 2048}, s[1] = {896}; cuuint32_t b[2] = {64, 64}; make_map(fn, &txr64, x, 2, d, s, b, CU_TENSOR_MAP_SWIZZLE_128B); }
    { cuuint64_t d[2] = {448, 2048}, s[1] = {896}; cuuint32_t b[2] = {48, 64}; make_map(fn, &txr48, x, 2, d, s, b, CU_TENSOR_MAP_SWIZZLE_128B); }
    { cuuint64_t d[2] = {448, 2048}, s[1] = {896}; cuuint32_t b[2] = {64, 16}; make_map(fn, &tout64, d_out, 2, d, s, b, CU_TENSOR_MAP_SWIZZLE_128B); }
    { cuuint64_t d[2] = {448, 2048}, s[1] = {896}; cuuint32_t b[2] = {48, 16}; make_map(fn, &tout48, d_out, 2, d, s, b, CU_TENSOR_MAP_SWIZZLE_128B); }

    void* scv = nullptr;
    cudaGetSymbolAddress(&scv, g_scratch);
    Scratch* scp = (Scratch*)scv;
    int dev = 0, sms = 0;
    cudaGetDevice(&dev);
    cudaDeviceGetAttribute(&sms, cudaDevAttrMultiProcessorCount, dev);
    if (sms == 132) {
        cudaFuncSetAttribute(fused_kernel<true>, cudaFuncAttributeMaxDynamicSharedMemorySize, SM_TOTAL);
        fused_kernel<true><<<132, 384, SM_TOTAL>>>(scp, wo, w1, b1, w2, b2, tx, twqkv, two64, two48, tw1, tw2, txr64, txr48, tout64, tout48);
    } else {
        cudaFuncSetAttribute(fused_kernel<false>, cudaFuncAttributeMaxDynamicSharedMemorySize, SM_TOTAL);
        fused_kernel<false><<<132, 384, SM_TOTAL>>>(scp, wo, w1, b1, w2, b2, tx, twqkv, two64, two48, tw1, tw2, txr64, txr48, tout64, tout48);
    }
}
```

```cpp
#include <cuda_runtime.h>
#include <cuda_bf16.h>
#include <cuda.h>
#include <stdint.h>

namespace {

constexpr int D_ = 448;
constexpr float LN_EPS = 1e-5f;
constexpr float LOG2E_SCALE = 0.1889822365046136f * 1.4426950408889634f;

struct Tiles {
    uint32_t o[32 * 57344 / 4];
    uint32_t hn[4 * 32 * 14336 / 4];
    uint32_t u[4 * 28 * 14336 / 4];
};
struct Scratch {
    uint4 halo[128 * 2 * 2 * 3 * 32];
    uint4 stats[32 * 4 * 64];
    uint4 hint_k[128 * 2];
    uint4 hint_o[32 * 32 * 2];
    uint4 hint_h[4 * 32 * 2];
    uint4 hint_u[128 * 2];
    uint4 go[24];
    uint32_t epoch[160];
    uint32_t clean;
    alignas(1024) Tiles tiles[2];
};
__device__ Scratch g_scratch;
#define STAMP(i) do {} while (0)
#define FST(i) do {} while (0)
#define TSARG
#define TSVAL

constexpr uint32_t SB = 1024;
constexpr int SM_SLOT = 16384;
__device__ __forceinline__ constexpr uint32_t slot_x(int kb) { return (kb ? 6 + kb : 0) * SM_SLOT; }
__device__ __forceinline__ constexpr uint32_t slot_kv(int kb) { return (kb < 5 ? 2 + kb : 6 - kb) * SM_SLOT; }
__device__ __forceinline__ constexpr uint32_t slot_wo(int kb) { return (kb < 6 ? 2 + kb : 12) * SM_SLOT; }
constexpr int SM_QO = 8 * SM_SLOT;
constexpr int SM_HALOK = SM_QO + 57344, SM_HALOV = 1 * SM_SLOT;
constexpr int NA_SLOTS = 6, NB_SLOTS = 8;
constexpr int SM_ARING = 0;
constexpr int SM_BRING = NA_SLOTS * 16384;
constexpr int SM_H = 212992;
__device__ __forceinline__ uint32_t halo_kin(int par, int lane) { return SB + SM_H + 8192 + par * 4096 + lane * 128 + ((~lane & 6) << 4); }
constexpr int SM_BAR = 229376;
constexpr int SM_TAG = SM_BAR + 1536;
constexpr int SM_TIME = SM_TAG + 256;
constexpr int SM_TOTAL = SM_TIME + 256;
constexpr int B_FULLX = 0;
constexpr int B_FULLKV = 7;
constexpr int B_FQ = 14;
constexpr int B_DONE1 = 16;
constexpr int B_DONEX = 23;
constexpr int B_DONEQ = 24;
constexpr int B_DONEO = 25;
constexpr int B_FULLO = 29;
constexpr int B_FULLWO = 33;
constexpr int B_END = 34;
constexpr int B_HALO = 35;
constexpr int B_FULLA = 39;
constexpr int B_FULLB = 55;
constexpr int B_DONE = 87;
constexpr int B_GO = 119;
constexpr int B_CLR = 121;
constexpr int SM_RAW = SM_BAR + 8 * 122;

constexpr long long WD_CLKS = 2000000000ll;

template<int N> struct Int { static constexpr int value = N; };
template<int A, int B, class F> __device__ __forceinline__ void static_for(F&& f) { if constexpr (A < B) { f(Int<A>()); static_for<A + 1, B>(f); } }

__device__ __forceinline__ uint32_t smem_u32(const void* p) { return (uint32_t)__cvta_generic_to_shared(p); }
__device__ __forceinline__ void mbar_init(uint32_t bar, uint32_t cnt) { asm volatile("mbarrier.init.shared::cta.b64 [%0], %1;" :: "r"(bar), "r"(cnt) : "memory"); }
__device__ __forceinline__ void mbar_expect(uint32_t bar, uint32_t bytes) { asm volatile("mbarrier.arrive.expect_tx.shared::cta.b64 _, [%0], %1;" :: "r"(bar), "r"(bytes) : "memory"); }
__device__ __forceinline__ void mbar_arrive(uint32_t bar) { asm volatile("mbarrier.arrive.shared::cta.b64 _, [%0];" :: "r"(bar) : "memory"); }
__device__ __forceinline__ bool mbar_try(uint32_t bar, uint32_t parity) {
    uint32_t ok;
    asm volatile("{\n.reg .pred p;\nmbarrier.try_wait.parity.shared::cta.b64 p, [%1], %2;\nselp.u32 %0, 1, 0, p;\n}" : "=r"(ok) : "r"(bar), "r"(parity) : "memory");
    return ok;
}
__device__ __forceinline__ bool mbar_test(uint32_t bar, uint32_t parity) {
    uint32_t ok;
    asm volatile("{\n.reg .pred p;\nmbarrier.test_wait.parity.shared::cta.b64 p, [%1], %2;\nselp.u32 %0, 1, 0, p;\n}" : "=r"(ok) : "r"(bar), "r"(parity) : "memory");
    return ok;
}
__device__ __forceinline__ void mbar_wait(uint32_t bar, uint32_t parity) {
    asm volatile("{\n.reg .pred p;\n"
                 "WAIT_LOOP:\n"
                 "mbarrier.try_wait.parity.shared::cta.b64 p, [%0], %1;\n"
                 "@!p bra WAIT_LOOP;\n}" :: "r"(bar), "r"(parity) : "memory");
}
__device__ __forceinline__ void mbar_wait_unless(uint32_t ready, uint32_t bar, uint32_t parity) {
    asm volatile("{\n.reg .pred p;\nsetp.ne.u32 p, %1, 0;\n@p bra.uni DONE;\n"
                 "WAIT_LOOP:\n"
                 "mbarrier.try_wait.parity.shared::cta.b64 p, [%0], %2;\n"
                 "@!p bra.uni WAIT_LOOP;\nDONE:\n}" :: "r"(bar), "r"(ready), "r"(parity) : "memory");
}
__device__ __forceinline__ void mbar_wait_wd(uint32_t bar, uint32_t parity) {
    asm volatile("{\n.reg .pred p, q;\n.reg .u32 s, t;\nmov.u32 s, %%clock;\n"
                 "WAIT_LOOP:\n"
                 "mbarrier.try_wait.parity.shared::cta.b64 p, [%0], %1;\nmov.u32 t, %%clock;\nsub.u32 t, t, s;\nsetp.lt.and.s32 q, t, 0, !p;\n@q trap;\n"
                 "@!p bra WAIT_LOOP;\n}" :: "r"(bar), "r"(parity) : "memory");
}
__device__ __forceinline__ bool elect() { uint32_t p; asm volatile("{\n.reg .pred P;\nelect.sync _|P, 0xffffffff;\nselp.u32 %0, 1, 0, P;\n}" : "=r"(p)); return p; }
__device__ __forceinline__ void tma2d(uint32_t dst, const CUtensorMap* tm, int c0, int c1, uint32_t bar) {
    asm volatile("cp.async.bulk.tensor.2d.shared::cluster.global.mbarrier::complete_tx::bytes [%0], [%1, {%3, %4}], [%2];" :: "r"(dst), "l"(tm), "r"(bar), "r"(c0), "r"(c1) : "memory");
}
__device__ __forceinline__ void tma3d(uint32_t dst, const CUtensorMap* tm, int c0, int c1, int c2, uint32_t bar) {
    asm volatile("cp.async.bulk.tensor.3d.shared::cluster.global.mbarrier::complete_tx::bytes [%0], [%1, {%3, %4, %5}], [%2];" :: "r"(dst), "l"(tm), "r"(bar), "r"(c0), "r"(c1), "r"(c2) : "memory");
}
__device__ __forceinline__ void tma5d(uint32_t dst, const CUtensorMap* tm, int c0, int c3, int c4, uint32_t bar) {
    asm volatile("cp.async.bulk.tensor.5d.shared::cluster.global.mbarrier::complete_tx::bytes [%0], [%1, {%3, 0, 0, %4, %5}], [%2];" :: "r"(dst), "l"(tm), "r"(bar), "r"(c0), "r"(c3), "r"(c4) : "memory");
}
__device__ __forceinline__ void tma5d_prefetch(const CUtensorMap* tm, int c0, int c3, int c4) {
    asm volatile("cp.async.bulk.prefetch.tensor.5d.L2.global [%0, {%1, 0, 0, %2, %3}];" :: "l"(tm), "r"(c0), "r"(c3), "r"(c4) : "memory");
}
__device__ __forceinline__ void tma2d_store(const CUtensorMap* tm, int c0, int c1, uint32_t src) {
    asm volatile("cp.async.bulk.tensor.2d.global.shared::cta.bulk_group [%0, {%2, %3}], [%1];" :: "l"(tm), "r"(src), "r"(c0), "r"(c1) : "memory");
}
__device__ __forceinline__ void bulk_st(void* dst, uint32_t src, uint32_t bytes) {
    asm volatile("cp.async.bulk.global.shared::cta.bulk_group [%0], [%1], %2;" :: "l"(dst), "r"(src), "r"(bytes) : "memory");
}
__device__ __forceinline__ void bulk_ld(uint32_t dst, const void* src, uint32_t bytes, uint32_t bar) {
    asm volatile("cp.async.bulk.shared::cluster.global.mbarrier::complete_tx::bytes [%0], [%1], %2, [%3];" :: "r"(dst), "l"(src), "r"(bytes), "r"(bar) : "memory");
}
__device__ __forceinline__ void bulk_prefetch(const void* src, uint32_t bytes) { asm volatile("cp.async.bulk.prefetch.L2.global [%0], %1;" :: "l"(src), "r"(bytes) : "memory"); }
__device__ __forceinline__ void prefetch_map(const CUtensorMap* tm) { asm volatile("prefetch.tensormap [%0];" :: "l"(tm) : "memory"); }
__device__ __forceinline__ void st_global_if(uint32_t c, uint32_t* p, uint32_t v) {
    asm volatile("{\n.reg .pred p;\nsetp.ne.u32 p, %2, 0;\n@p st.global.u32 [%0], %1;\n}" :: "l"(p), "r"(v), "r"(c) : "memory");
}
__device__ __forceinline__ void st_relaxed4_if(bool c, uint4* p, uint32_t a, uint32_t b, uint32_t d) {
    asm volatile("{\n.reg .b128 t;\n.reg .b64 a, b;\n.reg .pred p;\nsetp.ne.u32 p, %4, 0;\nmov.b64 a, {%1, %2};\nmov.b64 b, {%3, %3};\nmov.b128 t, {a, b};\n@p st.relaxed.gpu.global.b128 [%0], t;\n}" :: "l"(p), "r"(a), "r"(b), "r"(d), "r"((uint32_t)c) : "memory");
}
__device__ __forceinline__ void pin_ptr(uint32_t never, const void* a) {
    asm volatile("{\n.reg .pred p;\nsetp.ne.u32 p, %1, 0;\n@p st.shared.u64 [%1], %0;\n}" :: "l"(a), "r"(never) : "memory");
}
__device__ __forceinline__ void pin4(uint32_t never, float a, float b, float c, float d) {
    asm volatile("{\n.reg .pred p;\nsetp.ne.u32 p, %4, 0;\n@p st.shared.v4.f32 [%4], {%0,%1,%2,%3};\n}" :: "f"(a), "f"(b), "f"(c), "f"(d), "r"(never) : "memory");
}
__device__ __forceinline__ void fence_async_smem() { asm volatile("fence.proxy.async.shared::cta;" ::: "memory"); }
__device__ __forceinline__ uint32_t ld_acquire(const void* p) { uint32_t v; asm volatile("ld.acquire.gpu.global.u32 %0, [%1];" : "=r"(v) : "l"(p) : "memory"); return v; }
__device__ __forceinline__ void st_release(void* p, uint32_t v) { asm volatile("st.release.gpu.global.u32 [%0], %1;" :: "l"(p), "r"(v) : "memory"); }
__device__ __forceinline__ uint32_t ld_relaxed(const void* p) { uint32_t v; asm volatile("ld.relaxed.gpu.global.u32 %0, [%1];" : "=r"(v) : "l"(p) : "memory"); return v; }
__device__ __forceinline__ uint2 ld_relaxed2(const void* p) {
    uint2 v; asm volatile("{\n.reg .b64 a;\nld.relaxed.gpu.global.b64 a, [%2];\nmov.b64 {%0, %1}, a;\n}" : "=r"(v.x), "=r"(v.y) : "l"(p) : "memory"); return v;
}
__device__ __forceinline__ void st_relaxed2(void* p, uint32_t a, uint32_t b) {
    asm volatile("{\n.reg .b64 a;\nmov.b64 a, {%1, %2};\nst.relaxed.gpu.global.b64 [%0], a;\n}" :: "l"(p), "r"(a), "r"(b) : "memory");
}
__device__ __forceinline__ uint4 ld_relaxed4(const uint4* p) {
    uint4 v;
    asm volatile("{\n.reg .b128 t;\n.reg .b64 a, b;\nld.relaxed.gpu.global.b128 t, [%4];\nmov.b128 {a, b}, t;\nmov.b64 {%0, %1}, a;\nmov.b64 {%2, %3}, b;\n}" : "=r"(v.x), "=r"(v.y), "=r"(v.z), "=r"(v.w) : "l"(p) : "memory");
    return v;
}
__device__ __forceinline__ void st_relaxed4(uint4* p, uint32_t a, uint32_t b, uint32_t c, uint32_t d) {
    asm volatile("{\n.reg .b128 t;\n.reg .b64 a, b;\nmov.b64 a, {%1, %2};\nmov.b64 b, {%3, %4};\nmov.b128 t, {a, b};\nst.relaxed.gpu.global.b128 [%0], t;\n}" :: "l"(p), "r"(a), "r"(b), "r"(c), "r"(d) : "memory");
}
__device__ __forceinline__ uint32_t ld_u16(const unsigned short* p) { uint32_t v; asm volatile("ld.volatile.global.u16 %0, [%1];" : "=r"(v) : "l"(p) : "memory"); return v; }
__device__ __forceinline__ uint32_t ld_volatile(const uint32_t* p) { uint32_t v; asm volatile("ld.volatile.global.u32 %0, [%1];" : "=r"(v) : "l"(p) : "memory"); return v; }
__device__ __forceinline__ void named_arrive(int id, int n) { asm volatile("bar.arrive %0, %1;" :: "r"(id), "r"(n) : "memory"); }
__device__ __forceinline__ void named_sync(int id, int n) { asm volatile("bar.sync %0, %1;" :: "r"(id), "r"(n) : "memory"); }
__device__ __forceinline__ void named_arrive_if(uint32_t c, int id, int n) { asm volatile("{\n.reg .pred p;\nsetp.ne.u32 p, %2, 0;\n@p bar.arrive %0, %1;\n}" :: "r"(id), "r"(n), "r"(c) : "memory"); }
__device__ __forceinline__ bool named_any(int id, int n, bool v) {
    uint32_t r; asm volatile("{\n.reg .pred p, q;\nsetp.ne.u32 p, %3, 0;\nbar.red.or.pred q, %1, %2, p;\nselp.u32 %0, 1, 0, q;\n}" : "=r"(r) : "r"(id), "r"(n), "r"((uint32_t)v) : "memory"); return r;
}
__device__ __forceinline__ void wg_fence() { asm volatile("wgmma.fence.sync.aligned;" ::: "memory"); }
__device__ __forceinline__ void wg_commit() { asm volatile("wgmma.commit_group.sync.aligned;" ::: "memory"); }
template<int N> __device__ __forceinline__ void wg_wait() { asm volatile("wgmma.wait_group.sync.aligned %0;" :: "n"(N) : "memory"); }
template<int N> __device__ __forceinline__ void reg_fence(float (&d)[N]) {
    #pragma unroll
    for (int i = 0; i < N; i++) asm volatile("" : "+f"(d[i]) :: "memory");
}
__device__ __forceinline__ constexpr uint64_t mkdesc(uint32_t addr, uint32_t lbo, uint32_t sbo, uint32_t sw) {
    return (uint64_t)((addr & 0x3FFFF) >> 4) | ((uint64_t)(lbo >> 4) << 16) | ((uint64_t)(sbo >> 4) << 32) | ((uint64_t)sw << 62);
}
__device__ __forceinline__ void ldsm4(uint32_t (&r)[4], uint32_t addr) {
    asm volatile("ldmatrix.sync.aligned.m8n8.x4.shared.b16 {%0,%1,%2,%3}, [%4];" : "=r"(r[0]), "=r"(r[1]), "=r"(r[2]), "=r"(r[3]) : "r"(addr) : "memory");
}
__device__ __forceinline__ void stsm4(uint32_t addr, uint32_t r0, uint32_t r1, uint32_t r2, uint32_t r3) {
    asm volatile("stmatrix.sync.aligned.m8n8.x4.shared.b16 [%0], {%1,%2,%3,%4};" :: "r"(addr), "r"(r0), "r"(r1), "r"(r2), "r"(r3) : "memory");
}
__device__ __forceinline__ void sts4(uint32_t a, uint32_t x, uint32_t y, uint32_t z, uint32_t w) { asm volatile("st.shared.v4.u32 [%0], {%1,%2,%3,%4};" :: "r"(a), "r"(x), "r"(y), "r"(z), "r"(w) : "memory"); }
__device__ __forceinline__ uint4 lds4(uint32_t a) { uint4 v; asm volatile("ld.shared.v4.u32 {%0,%1,%2,%3}, [%4];" : "=r"(v.x), "=r"(v.y), "=r"(v.z), "=r"(v.w) : "r"(a) : "memory"); return v; }
__device__ __forceinline__ uint32_t movtrans(uint32_t a) { uint32_t d; asm volatile("movmatrix.sync.aligned.m8n8.trans.b16 %0, %1;" : "=r"(d) : "r"(a)); return d; }
__device__ __forceinline__ uint32_t pack_bf16(float lo, float hi) { uint32_t r; asm("cvt.rn.bf16x2.f32 %0, %1, %2;" : "=r"(r) : "f"(hi), "f"(lo)); return r; }
__device__ __forceinline__ void sub_bf16x2(uint32_t& a, uint32_t b) { asm volatile("sub.rn.bf16x2 %0, %0, %1;" : "+r"(a) : "r"(b)); }
__device__ __forceinline__ float bf_lo(uint32_t v) { return __uint_as_float(v << 16); }
__device__ __forceinline__ float bf_hi(uint32_t v) { return __uint_as_float(v & 0xffff0000u); }
__device__ __forceinline__ void mma16816(float (&c)[4], uint32_t a0, uint32_t a1, uint32_t a2, uint32_t a3, uint32_t b0, uint32_t b1) {
    asm volatile("mma.sync.aligned.m16n8k16.row.col.f32.bf16.bf16.f32 {%0,%1,%2,%3}, {%4,%5,%6,%7}, {%8,%9}, {%0,%1,%2,%3};"
        : "+f"(c[0]), "+f"(c[1]), "+f"(c[2]), "+f"(c[3]) : "r"(a0), "r"(a1), "r"(a2), "r"(a3), "r"(b0), "r"(b1));
}
__device__ __forceinline__ void mma1688(float (&c)[4], uint32_t a0, uint32_t a1, uint32_t b0) {
    asm volatile("mma.sync.aligned.m16n8k8.row.col.f32.bf16.bf16.f32 {%0,%1,%2,%3}, {%4,%5}, {%6}, {%0,%1,%2,%3};"
        : "+f"(c[0]), "+f"(c[1]), "+f"(c[2]), "+f"(c[3]) : "r"(a0), "r"(a1), "r"(b0));
}
__device__ __forceinline__ float quad_sum(float v) { v += __shfl_xor_sync(0xffffffffu, v, 1); v += __shfl_xor_sync(0xffffffffu, v, 2); return v; }
__device__ __forceinline__ float quad_max(float v) { v = fmaxf(v, __shfl_xor_sync(0xffffffffu, v, 1)); v = fmaxf(v, __shfl_xor_sync(0xffffffffu, v, 2)); return v; }
__device__ __forceinline__ float ex2(float x) { float y; asm("ex2.approx.ftz.f32 %0, %1;" : "=f"(y) : "f"(x)); return y; }
__device__ __forceinline__ float rsqrt_approx(float x) { float y; asm("rsqrt.approx.ftz.f32 %0, %1;" : "=f"(y) : "f"(x)); return y; }
__device__ __forceinline__ float rcp_approx(float x) { float y; asm("rcp.approx.ftz.f32 %0, %1;" : "=f"(y) : "f"(x)); return y; }
constexpr float GELU_K1 = 2.f * 0.7978845608028654f;
__device__ __forceinline__ float gelu_half(float hx, float k1) {
    const float z = hx * fmaf(hx * hx, 8.f * 0.044715f * 0.7978845608028654f, k1);
    float t; asm("tanh.approx.f32 %0, %1;" : "=f"(t) : "f"(z));
    return fmaf(hx, t, hx);
}
__device__ __forceinline__ uint32_t gtime32() { uint64_t t; asm volatile("mov.u64 %0, %%globaltimer;" : "=l"(t)); return (uint32_t)t; }
__device__ __forceinline__ uint32_t clock32() { uint32_t t; asm volatile("mov.u32 %0, %%clock;" : "=r"(t)); return t; }
#define PF_PACE 160
#define PF_AT 14500
#define PF_N 240
#define NSQ 6
#define NPIPE 1
#define HALO_AT 3
#define HINT_U 18
#define HINT_E 16
#define SP_AT 2000
#define A_SCHED 0x322188
#define WO_ORD0 0x4321065
#define WO_ORD1 0x3465210
#define CL_AT 23
#define WARM_AT 300
#define GO_H 1600
#define GO_E 1950
#define GO_U 2050
#define GO_O 1312
#define LATE_O 256
#define LATE_AT 0
#define LATE_AT4 0
#define SLACK 0
#define GDEP 4
#define START4 30
#define NE_SLOTS 11
#define POLL_E 26
#define AE_END 18
#define AE_W2 27
#define PF1_AT 11000
#define PF1_N 80
#define PF1_PACE 160
#define GO_E2 300
#define GO_U2 400
#define POLL_I 20
#define POLL_N 19
#define ROLES 0x65431027u
#define A4_FROM 23
#define A4_DLY 2
#define SPIN_N 3
#define STOP2 150
#define PF0_AT 4500
#define PF0_N 48
#define PF0_PACE 140
#define POLL_H 3
#define CH_H 8
#define HINT_F 4
#define CL_N 4
#define CL_P2 7
#define STOP3 3
#define PF_OFS 0
#define PFC_AT 0
#define PFC_E 0
#define PFC_N 16
#define PFW_AT 6
#define PFW_0 10
#define PFW_N 14
template<int TB> __device__ __forceinline__ void wgmma_rs56(float (&d)[28], const uint32_t (&a)[4], uint64_t db, int sc) {
    asm volatile("{\n.reg .pred p;\nsetp.ne.b32 p, %33, 0;\n"
        "wgmma.mma_async.sync.aligned.m64n56k16.f32.bf16.bf16 {%0, %1, %2, %3, %4, %5, %6, %7, %8, %9, %10, %11, %12, %13, %14, %15, %16, %17, %18, %19, %20, %21, %22, %23, %24, %25, %26, %27}, {%28, %29, %30, %31}, %32, p, 1, 1, %34;\n}\n"
        : "+f"(d[0]), "+f"(d[1]), "+f"(d[2]), "+f"(d[3]), "+f"(d[4]), "+f"(d[5]), "+f"(d[6]), "+f"(d[7]), "+f"(d[8]), "+f"(d[9]), "+f"(d[10]), "+f"(d[11]), "+f"(d[12]), "+f"(d[13]), "+f"(d[14]), "+f"(d[15]), "+f"(d[16]), "+f"(d[17]), "+f"(d[18]), "+f"(d[19]), "+f"(d[20]), "+f"(d[21]), "+f"(d[22]), "+f"(d[23]), "+f"(d[24]), "+f"(d[25]), "+f"(d[26]), "+f"(d[27])
        : "r"(a[0]), "r"(a[1]), "r"(a[2]), "r"(a[3]), "l"(db), "r"(sc), "n"(TB));
}

template<int TA, int TB, int SC = 1> __device__ __forceinline__ void wgmma_ss112(float (&d)[56], uint64_t da, uint64_t db) {
    asm volatile("wgmma.mma_async.sync.aligned.m64n112k16.f32.bf16.bf16 {%0, %1, %2, %3, %4, %5, %6, %7, %8, %9, %10, %11, %12, %13, %14, %15, %16, %17, %18, %19, %20, %21, %22, %23, %24, %25, %26, %27, %28, %29, %30, %31, %32, %33, %34, %35, %36, %37, %38, %39, %40, %41, %42, %43, %44, %45, %46, %47, %48, %49, %50, %51, %52, %53, %54, %55}, %56, %57, %60, 1, 1, %58, %59;\n"
        : "+f"(d[0]), "+f"(d[1]), "+f"(d[2]), "+f"(d[3]), "+f"(d[4]), "+f"(d[5]), "+f"(d[6]), "+f"(d[7]), "+f"(d[8]), "+f"(d[9]), "+f"(d[10]), "+f"(d[11]), "+f"(d[12]), "+f"(d[13]), "+f"(d[14]), "+f"(d[15]), "+f"(d[16]), "+f"(d[17]), "+f"(d[18]), "+f"(d[19]), "+f"(d[20]), "+f"(d[21]), "+f"(d[22]), "+f"(d[23]), "+f"(d[24]), "+f"(d[25]), "+f"(d[26]), "+f"(d[27]), "+f"(d[28]), "+f"(d[29]), "+f"(d[30]), "+f"(d[31]), "+f"(d[32]), "+f"(d[33]), "+f"(d[34]), "+f"(d[35]), "+f"(d[36]), "+f"(d[37]), "+f"(d[38]), "+f"(d[39]), "+f"(d[40]), "+f"(d[41]), "+f"(d[42]), "+f"(d[43]), "+f"(d[44]), "+f"(d[45]), "+f"(d[46]), "+f"(d[47]), "+f"(d[48]), "+f"(d[49]), "+f"(d[50]), "+f"(d[51]), "+f"(d[52]), "+f"(d[53]), "+f"(d[54]), "+f"(d[55])
        : "l"(da), "l"(db), "n"(TA), "n"(TB), "n"(SC));
}

template<int TA, int TB, int SC = 1> __device__ __forceinline__ void wgmma_ss80(float (&d)[40], uint64_t da, uint64_t db) {
    asm volatile("wgmma.mma_async.sync.aligned.m64n80k16.f32.bf16.bf16 {%0, %1, %2, %3, %4, %5, %6, %7, %8, %9, %10, %11, %12, %13, %14, %15, %16, %17, %18, %19, %20, %21, %22, %23, %24, %25, %26, %27, %28, %29, %30, %31, %32, %33, %34, %35, %36, %37, %38, %39}, %40, %41, %44, 1, 1, %42, %43;\n"
        : "+f"(d[0]), "+f"(d[1]), "+f"(d[2]), "+f"(d[3]), "+f"(d[4]), "+f"(d[5]), "+f"(d[6]), "+f"(d[7]), "+f"(d[8]), "+f"(d[9]), "+f"(d[10]), "+f"(d[11]), "+f"(d[12]), "+f"(d[13]), "+f"(d[14]), "+f"(d[15]), "+f"(d[16]), "+f"(d[17]), "+f"(d[18]), "+f"(d[19]), "+f"(d[20]), "+f"(d[21]), "+f"(d[22]), "+f"(d[23]), "+f"(d[24]), "+f"(d[25]), "+f"(d[26]), "+f"(d[27]), "+f"(d[28]), "+f"(d[29]), "+f"(d[30]), "+f"(d[31]), "+f"(d[32]), "+f"(d[33]), "+f"(d[34]), "+f"(d[35]), "+f"(d[36]), "+f"(d[37]), "+f"(d[38]), "+f"(d[39])
        : "l"(da), "l"(db), "n"(TA), "n"(TB), "n"(SC));
}

template<int TA, int TB, int SC = 1> __device__ __forceinline__ void wgmma_ss64(float (&d)[32], uint64_t da, uint64_t db) {
    asm volatile("wgmma.mma_async.sync.aligned.m64n64k16.f32.bf16.bf16 {%0, %1, %2, %3, %4, %5, %6, %7, %8, %9, %10, %11, %12, %13, %14, %15, %16, %17, %18, %19, %20, %21, %22, %23, %24, %25, %26, %27, %28, %29, %30, %31}, %32, %33, %36, 1, 1, %34, %35;\n"
        : "+f"(d[0]), "+f"(d[1]), "+f"(d[2]), "+f"(d[3]), "+f"(d[4]), "+f"(d[5]), "+f"(d[6]), "+f"(d[7]), "+f"(d[8]), "+f"(d[9]), "+f"(d[10]), "+f"(d[11]), "+f"(d[12]), "+f"(d[13]), "+f"(d[14]), "+f"(d[15]), "+f"(d[16]), "+f"(d[17]), "+f"(d[18]), "+f"(d[19]), "+f"(d[20]), "+f"(d[21]), "+f"(d[22]), "+f"(d[23]), "+f"(d[24]), "+f"(d[25]), "+f"(d[26]), "+f"(d[27]), "+f"(d[28]), "+f"(d[29]), "+f"(d[30]), "+f"(d[31])
        : "l"(da), "l"(db), "n"(TA), "n"(TB), "n"(SC));
}

template<int TA, int TB, int SC = 1> __device__ __forceinline__ void wgmma_ss48(float (&d)[24], uint64_t da, uint64_t db) {
    asm volatile("wgmma.mma_async.sync.aligned.m64n48k16.f32.bf16.bf16 {%0, %1, %2, %3, %4, %5, %6, %7, %8, %9, %10, %11, %12, %13, %14, %15, %16, %17, %18, %19, %20, %21, %22, %23}, %24, %25, %28, 1, 1, %26, %27;\n"
        : "+f"(d[0]), "+f"(d[1]), "+f"(d[2]), "+f"(d[3]), "+f"(d[4]), "+f"(d[5]), "+f"(d[6]), "+f"(d[7]), "+f"(d[8]), "+f"(d[9]), "+f"(d[10]), "+f"(d[11]), "+f"(d[12]), "+f"(d[13]), "+f"(d[14]), "+f"(d[15]), "+f"(d[16]), "+f"(d[17]), "+f"(d[18]), "+f"(d[19]), "+f"(d[20]), "+f"(d[21]), "+f"(d[22]), "+f"(d[23])
        : "l"(da), "l"(db), "n"(TA), "n"(TB), "n"(SC));
}

template<int NKB, int NR>
__device__ __forceinline__ void mix_mainloop(TSARG float (&acc)[NR], bool leader) {
    constexpr uint32_t sb = SB, bars = sb + SM_BAR, par = NKB == 28;
    constexpr int A0 = NKB == 32 ? 0 : 16 % NA_SLOTS;
    constexpr int DEPTH = NR == 56 ? 1 : 2;
    int bslot = 0, aslot = A0;
    reg_fence(acc);
    #pragma unroll 1
    for (int i = 0; i < NKB / 2; i++) {
        mbar_wait(bars + 8 * (B_FULLA + i), par);
        const uint64_t adesc = mkdesc(sb + SM_ARING, 8192, 1024, 1) + (uint32_t)(aslot * 1024);
        aslot = aslot == NA_SLOTS - 1 ? 0 : aslot + 1;
        #pragma unroll
        for (int jj = 0; jj < 2; jj++) {
            const int j = 2 * i + jj;
            mbar_wait(bars + 8 * (B_FULLB + j), par);
            const uint64_t bdesc = mkdesc(sb + SM_BRING, 128, 1024, 0) + (uint32_t)(bslot * NR * 16);
            bslot = bslot == (NR == 56 ? NB_SLOTS : NE_SLOTS) - 1 ? 0 : bslot + 1;
            wg_fence();
            #pragma unroll
            for (int s = 0; s < 4; s++) {
                if constexpr (NR == 56) wgmma_ss112<1, 1>(acc, adesc + jj * 512 + s * 128, bdesc + s * 16);
                else wgmma_ss80<1, 1>(acc, adesc + jj * 512 + s * 128, bdesc + s * 16);
            }
            wg_commit();
            wg_wait<DEPTH>();
            if (j >= DEPTH && leader) mbar_arrive(bars + 8 * (B_DONE + j - DEPTH));
        }
    }
    if (DEPTH == 2) { wg_wait<1>(); if (leader) mbar_arrive(bars + 8 * (B_DONE + NKB - 2)); }
    wg_wait<0>();
    reg_fence(acc);
    if (leader) mbar_arrive(bars + 8 * (B_DONE + NKB - 1));
}

__device__ __forceinline__ void spin_mma(uint32_t bar, uint32_t never) {
    float d[56];
    #pragma unroll
    for (int i = 0; i < 56; i++) d[i] = 0.f;
    reg_fence(d);
    #pragma unroll 1
    do {
        wg_fence();
        #pragma unroll
        for (int s = 0; s < SPIN_N; s++) wgmma_ss112<1, 1>(d, mkdesc(SB + 2 * SM_SLOT + s * 2048, 8192, 1024, 1), mkdesc(SB + 3 * SM_SLOT + s * 256, 128, 1024, 0));
        wg_commit();
        wg_wait<1>();
    } while (!named_any(11, 128, mbar_test(bar, 1)));
    wg_wait<0>();
    reg_fence(d);
    pin4(never, d[0], d[1], d[2], d[3]);
}

constexpr uint32_t EMPTY = 0xFFFFFFFFu;
__device__ __forceinline__ void post_hint(uint4* p, uint32_t ep, int lane) { if (lane < 2) st_relaxed4(p + lane, ep, ep, ep, ep); }
__device__ __forceinline__ void post_time(uint4* p, uint32_t ep, int lane) { const uint32_t now = gtime32(); if (lane < 2) st_relaxed4(p + lane, ep, now, ep, now); }

__device__ __forceinline__ uint32_t last_hint(TSARG const uint4* hint, uint32_t ep, int st) {
    uint2 v;
    do { v = ld_relaxed2(hint); } while (!__all_sync(0xffffffffu, v.x == ep));
    const uint32_t t1 = gtime32() + 256;
    if (elect()) STAMP(st);
    return t1 - __reduce_min_sync(0xffffffffu, t1 - v.y);
}
__device__ __forceinline__ uint32_t later(uint32_t a, uint32_t b) { return a + max((int)(b - a), 0); }
__device__ __forceinline__ void fetch_times(TSARG const uint4* go, int k, uint32_t ep, int lane) {
    const uint2* p = (const uint2*)(go + 8 + 8 * k) + (k ? lane % 10 : lane & 3);
    uint2 v;
    do { v = ld_relaxed2(p); } while (!__all_sync(0xffffffffu, v.x == ep));
    v.y += k ? (lane < 10 ? GO_U : GO_U + GO_U2) : (lane < 4 ? GO_E : GO_E + GO_E2);
    asm volatile("st.shared.u32 [%0], %1;" :: "r"(SB + SM_TIME + 128 * k + 4 * lane), "r"(v.y) : "memory");
    __syncwarp();
    if (lane == 0) { mbar_arrive(SB + SM_BAR + 8 * (B_GO + k)); STAMP(k ? 43 : 24); }
    __syncwarp();
}
__device__ __forceinline__ void wait_until(uint32_t t) {
    asm volatile("{\n.reg .pred p;\n.reg .u64 a;\n.reg .u32 l, h;\nWAIT_LOOP:\nmov.u64 a, %%globaltimer;\nmov.b64 {l, h}, a;\nsub.u32 l, l, %0;\nsetp.lt.s32 p, l, 0;\n@p bra.uni WAIT_LOOP;\n}" :: "r"(t) : "memory");
}

__device__ __forceinline__ uint32_t check_tile(uint32_t raw, uint32_t full, uint32_t dst, uint32_t lofs, const uint32_t* src, uint32_t bytes, int lane) {
    uint32_t cnt;
    asm volatile("{\n.reg .pred p, e;\n.reg .u32 a, b, c, d;\nmov.u32 %0, 0;\n"
                 "AGAIN:\nand.b32 a, %0, 1;\n"
                 "WAIT:\nmbarrier.try_wait.parity.shared::cta.b64 p, [%1], a;\n@!p bra.uni WAIT;\n"
                 "ld.shared.u32 a, [%4];\nld.shared.u32 b, [%4+4096];\nld.shared.u32 c, [%5+-8192];\nld.shared.u32 d, [%5+-4096];\n"
                 "add.u32 %0, %0, 1;\nmax.u32 a, a, b;\nmax.u32 c, c, d;\nmax.u32 a, a, c;\nsetp.lt.u32 e, %8, 32;\nsetp.eq.and.u32 p, a, 0xFFFFFFFF, e;\n"
                 "vote.sync.any.pred p, p, 0xffffffff;\nsetp.eq.and.u32 e, %8, 0, !p;\n@e mbarrier.arrive.shared::cta.b64 _, [%2];\n"
                 "elect.sync _|e, 0xffffffff;\nand.pred e, e, p;\n"
                 "@e mbarrier.arrive.expect_tx.shared::cta.b64 _, [%1], %7;\n"
                 "@e cp.async.bulk.shared::cluster.global.mbarrier::complete_tx::bytes [%3], [%6], %7, [%1];\n"
                 "@p bra.uni AGAIN;\n}"
                 : "=&r"(cnt) : "r"(raw), "r"(full), "r"(dst), "r"(dst + lofs), "r"(dst + lofs + bytes), "l"(src), "r"(bytes), "r"(lane) : "memory");
    return cnt;
}

template<int ST>
__device__ __forceinline__ void check_tiles(int j, int step, int n, const uint32_t* src, bool small, int lane, bool dry) {
    const uint32_t bytes = small ? 10240 : 14336, nb = small ? NE_SLOTS : NB_SLOTS, lofs = lane * 128 + (lane & 3) * 32 + (lane >> 2) * 4;
    uint32_t sl = j % nb;
    #pragma unroll 1
    for (int inc = dry ? 0 : step; j < n; j += inc, inc = step) {
        const uint32_t c = check_tile(inc ? SB + SM_RAW + 8 * (j + (ST ? 32 * ST - 28 : 0)) : SB + SM_BAR + 8 * B_CLR, SB + SM_BAR + 8 * (j + (ST ? B_FULLB : B_FULLO)),
                                      SB + (ST ? SM_BRING + sl * bytes : SM_QO + max(2 * j - 1, 0) * 8192), lofs, src + (ST ? j * 7168 : max(2 * j - 1, 0) * 2048),
                                      ST ? bytes : j ? 16384 : 8192, inc ? lane : 32);
        sl += inc;
        if (sl >= nb) sl -= nb;
    }
}

__device__ __forceinline__ uint32_t hcol(uint32_t a, int jp) { return (a ^ ((jp & 3) << 5)) + (jp >> 2) * 8192; }

__device__ __forceinline__ uint32_t get_tag() {
    mbar_wait(SB + SM_BAR + 8 * B_CLR, 0);
    uint32_t v; asm volatile("ld.shared.u32 %0, [%1];" : "=r"(v) : "r"(SB + SM_TAG) : "memory"); return v;
}

template<bool USE_SMID>
__global__ void __launch_bounds__(384, 1)
fused_kernel(Scratch* __restrict__ sc, const __nv_bfloat16* __restrict__ wo,
             const __nv_bfloat16* __restrict__ w1, const __nv_bfloat16* __restrict__ b1,
             const __nv_bfloat16* __restrict__ w2, const __nv_bfloat16* __restrict__ b2,
             const __grid_constant__ CUtensorMap tm_x, const __grid_constant__ CUtensorMap tm_wqkv,
             const __grid_constant__ CUtensorMap tm_wo64, const __grid_constant__ CUtensorMap tm_wo48,
             const __grid_constant__ CUtensorMap tm_w1, const __grid_constant__ CUtensorMap tm_w2,
             const __grid_constant__ CUtensorMap tm_xr64, const __grid_constant__ CUtensorMap tm_xr48,
             const __grid_constant__ CUtensorMap tm_out64, const __grid_constant__ CUtensorMap tm_out48) {
    extern __shared__ __align__(1024) uint8_t smem_raw[];
    constexpr uint32_t sb = SB;
    constexpr uint32_t bars = sb + SM_BAR;
    const int tid = threadIdx.x, lane = tid & 31;
    auto get_slot = [&]() {
        int slot;
    if (USE_SMID) {
        asm volatile("{\n.reg .u32 s, t, u, d, a, b, c;\n.reg .pred p, r;\n"
            "mov.u32 s, %%smid;\nshr.u32 t, s, 1;\nsub.u32 u, t, 32;\nmul.lo.u32 d, u, 37;\nshr.u32 d, d, 8;\n"
            "and.b32 a, t, 7;\nshl.b32 a, a, 3;\nshr.u32 c, t, 3;\nadd.u32 a, a, c;\n"
            "mad.lo.u32 b, d, -55, 12;\nshl.b32 c, u, 3;\nadd.u32 b, b, c;\n"
            "setp.lt.u32 p, t, 32;\nselp.u32 a, a, b, p;\n"
            "setp.lt.u32 r, t, 62;\nselp.s32 c, 4, -58, r;\nadd.u32 c, t, c;\nsetp.lt.u32 p, t, 60;\nselp.u32 a, a, c, p;\n"
            "and.b32 s, s, 1;\nshl.b32 a, a, 1;\nadd.u32 %0, a, s;\n}" : "=r"(slot));
    } else slot = blockIdx.x;
        return slot;
    };
    auto load_x = [&](int kb, int row) {
        const uint32_t st = sb + slot_x(kb), bar = bars + 8 * (B_FULLX + kb);
        mbar_expect(bar, 16384);
        tma3d(st, &tm_x, kb * 64, 0, row, bar); tma3d(st + 8192, &tm_x, kb * 64, 1, row, bar);
    };
    const int warp = __shfl_sync(0xffffffffu, tid >> 5, 0);
#define ASSIGN_WORK(s) \
    const int slot = (s), G = slot >> 4, mi = slot & 15; \
    const int tb = 4 * (G >> 1) + (mi >> 2), hp = 2 * (mi & 3) + (G & 1), wcol = (hp * 56) & ~15; \
    const int q = mi & 3, tt2 = 4 * G + (mi >> 2), c64 = 64 * q, c48 = 256 + 48 * q; \
    const int R = (ROLES >> (4 * G)) & 7; \
    const bool early = R < 3; \
    const int ech = R < 2 ? q : 4 + (mi & 1), ft = R == 2 ? mi >> 1 : 4 * (R - !early) + (mi >> 2); \
    const int pr3 = early ? ech >= 3 : q >> 1, col3 = early ? (ech - 3 * pr3) * 9 : (q & 1) * 14;

    if (warp < 8) {
        ASSIGN_WORK(get_slot())
        if (slot >= 128) {
            const uint32_t ep = ld_volatile(&sc->epoch[slot]) + 1;
            if (mi == 0 && warp > 0) {
                const int k = warp % 3;
                uint2* go = (uint2*)(sc->go + 8 * k) + lane;
                if (warp < 4 && lane < 16) st_relaxed2(go, 0, 0);
                while (ld_relaxed(k ? sc->go : sc->hint_k) != ep) __nanosleep(200);
                __nanosleep(warp * 60);
                const uint4* hint = (k ? sc->hint_u : sc->hint_h) + (k == 2 ? 48 + min(lane, 19) : lane) * 2;
                uint2 v[4];
                do {
                    #pragma unroll
                    for (int i = 0; i < 4; i++) v[i] = ld_relaxed2(hint + (k == 0 ? 64 * i : k == 2 ? 40 * i : 32 * (i & 1)));
                } while (!__all_sync(0xffffffffu, v[0].x == ep && v[1].x == ep && v[2].x == ep && v[3].x == ep));
                uint32_t t = later(later(v[0].y, v[1].y), later(v[2].y, v[3].y));
                t = later(t, __shfl_xor_sync(0xffffffffu, t, 1));
                if (k == 1) { t = later(t, __shfl_xor_sync(0xffffffffu, t, 8)); t = later(t, __shfl_xor_sync(0xffffffffu, t, 16)); }
                if (k == 0) {
                    const uint32_t now = gtime32() + 256;
                    t = later(t, now - __reduce_min_sync(0xffffffffu, now - t) - SLACK);
                }
                t = __shfl_sync(0xffffffffu, t, 2 * lane);
                if (lane < 16) st_relaxed2(go, ep, t);
            }
            if (mi == 1 && warp >= 4 && ld_volatile(&sc->clean) != ep) {
                for (int l = (tid - 128) / 2; l < sizeof(Tiles) / 128; l += 64) st_relaxed4((uint4*)&sc->tiles[ep & 1] + l * 8 + (lane & 7), EMPTY, EMPTY, EMPTY, EMPTY);
                named_sync(1, 128);
                if (tid == 128) st_release(&sc->clean, ep);
            }
            if (tid == 0) {
                const long long t0 = clock64();
                while (clock64() - t0 < SP_AT) {}
                #pragma unroll 1
                for (int i = 0; i < 7; i++) bulk_prefetch((const char*)wo + (i * 4 + mi) * 14336, 14336);
                uint32_t t = (uint32_t)t0 + PF0_AT;
                #pragma unroll 1
                for (int i = 0; i < PF0_N; i++) {
                    while ((int)(clock32() - t) < 0) {}
                    bulk_prefetch((const char*)w1 + i * 114688 + mi * 14336, 14336);
                    t += PF0_PACE;
                }
                if (mi) {
                    t = (uint32_t)t0 + PF1_AT;
                    #pragma unroll 1
                    for (int i = mi - 1; i < PF1_N; i += 3) {
                        while ((int)(clock32() - t) < 0) {}
                        tma5d_prefetch(&tm_w1, (i & 7) * 64, (i + 48) & 56, (i + 48) >> 6);
                        t += PF1_PACE;
                    }
                    t = (uint32_t)t0 + PF_AT;
                    #pragma unroll 1
                    for (int i = PF_OFS + mi - 1; i < PF_N; i += 3) {
                        while ((int)(clock32() - t) < 0) {}
                        bulk_prefetch((const char*)w2 + (i < 128 ? i * 16384 : i < 288 ? (i - 64 >> 1) * 65536 + (i & 1) * 16384 : (i - 224 >> 1) * 65536 + (i & 1) * 16384 + 32768), 16384);
                        t += PF_PACE;
                    }
                }
                while (ld_relaxed(sc->hint_u + 254) != ep) { __nanosleep(500); if (clock64() - t0 > WD_CLKS) __trap(); }
                sc->epoch[slot] = ep;
                if (mi == 1) sc->clean = ep + 1;
            }
            return;
        }
        {
            const int w = warp & 3, wg = warp >> 2, g = lane >> 2, t = lane & 3;
            if (WARM_AT) { const uint32_t t0 = clock32(); while (clock32() - t0 < WARM_AT) {} __syncwarp(); }
            if (w > 0) post_hint(sc->hint_o + ((2 * tb + (w >> 1)) * 32 + hp * 4 + (w & 1) * 2 + wg) * 2, 0, lane);
            if (wg == 0) {
                if (t < 2) st_relaxed4(sc->stats + tt2 * 256 + q * 64 + 16 * w + g + 8 * t, 0, 0, 0, 0);
            }
        }
        named_sync(0, 288);
        asm volatile("setmaxnreg.inc.sync.aligned.u32 224;");
        int tid; asm volatile("mov.u32 %0, %%tid.x;" : "=r"(tid));
        const int lane = tid & 31, warp = __shfl_sync(0xffffffffu, tid >> 5, 0), wg = warp >> 2;
        uint32_t ep;
        Tiles* tl;
        const int w = warp & 3, g = lane >> 2, t = lane & 3;
        const bool leader = (tid & 127) == 0;
        const uint32_t never = gridDim.y - 1;
        {
            uint32_t a[28][4];
            float accK[28], accV[28], accQ[28];
            const int lrow = 16 * w + (lane & 7) + (lane & 8);
            const uint32_t lbase = sb + wg * 8192 + lrow * 128;
            const uint32_t lx = (lane >> 4) ^ (lane & 7);
            const uint32_t wofs = hp & 1;
            auto pin2 = [&](uint32_t x0, uint32_t x1) {
                asm volatile("{\n.reg .pred p;\nsetp.ne.u32 p, %2, 0;\n@p st.shared.v2.b32 [%0], {%0,%1};\n}" :: "r"(x0), "r"(x1), "r"(never) : "memory");
            };
            float cS[2][4] = {}, cA[2][4] = {}, cB[2][4] = {}, q0, q1, p0, p1;
            auto sq = [&](float& acc, uint32_t v) { const float lo = bf_lo(v), hi = bf_hi(v); acc = fmaf(hi, hi, fmaf(lo, lo, acc)); };
            uint32_t ready = 0;
            #pragma unroll
            for (int kb = 0; kb < 8; kb++) {
                if (kb < 7) {
                    mbar_wait_unless(ready, bars + 8 * (B_FULLX + kb), 0);
                    if (kb == 0 && tid == 0) STAMP(0);
                    if (kb == 6 && tid == 0) STAMP(25);
                    if (kb == 0) FST(0); if (kb == 2) FST(1); if (kb == 4) FST(2); if (kb == 6) FST(3);
                    #pragma unroll
                    for (int s = 4 * kb; s < 4 * kb + 4; s++) ldsm4(a[s], lbase + slot_x(kb) + ((lx ^ (2 * (s & 3))) << 4));
                }
                if (kb > 0 && kb < 6) ready = mbar_test(bars + 8 * (B_FULLX + kb + 1), 0);
                if (kb == 5) named_sync(9 + wg, 160);
                if (kb == NPIPE) continue;
                const int kc = kb < NPIPE ? kb : kb - 1;
                if (kc == NSQ) { p0 = cS[0][0] + cS[1][0]; p1 = cS[0][2] + cS[1][2]; }
                #pragma unroll
                for (int s = 4 * kc; s < 4 * kc + 4; s++) {
                    mma16816(cS[s & 1], a[s][0], a[s][1], a[s][2], a[s][3], 0x3F803F80u, 0x3F803F80u);
                    if (kc < NSQ) {
                        mma1688(cA[0], a[s][0], a[s][1], a[s][0]); mma1688(cA[1], a[s][2], a[s][3], a[s][2]);
                        mma1688(cB[0], a[s][0], a[s][1], a[s][1]); mma1688(cB[1], a[s][2], a[s][3], a[s][3]);
                    }
                }
            }
            const float m0 = (cS[0][0] + cS[1][0]) * (1.f / D_), m1 = (cS[0][2] + cS[1][2]) * (1.f / D_);
            const uint32_t mm0 = pack_bf16(m0, m0), mm1 = pack_bf16(m1, m1);
            if (lane == 0) mbar_arrive(bars + 8 * B_DONEX);
            auto center = [&](int s) { sub_bf16x2(a[s][0], mm0); sub_bf16x2(a[s][1], mm1); sub_bf16x2(a[s][2], mm0); sub_bf16x2(a[s][3], mm1); };
            uint32_t Ka[8], Kb[8], Kc[8], Va[8], Vb[7], Vc[8];
            float r0, r1, ls0, ls1;
            uint32_t pm, zero;
            uint32_t* od;
            uint4* oh;
            auto kpack = [&](uint32_t (&k)[8], int j, int c, float r) {
                const uint32_t v = pack_bf16(accK[4 * j + c] * r, accK[4 * j + c + 1] * r);
                if (j == 3) { k[3] = t < 2 ? v : 0u; k[4] = t < 2 ? 0u : v; } else k[j + (j > 3)] = v;
            };
            auto batch = [&](auto c0, auto c1) {
                constexpr int n0 = c0.value, n1 = c1.value;
                wg_fence();
                static_for<n0, n1>([&](auto nc) {
                    constexpr int n = nc.value;
                    if (n == 4) { center(4); center(5); center(6); center(7); wg_fence(); }
                    const uint64_t desc = mkdesc(sb + (n < 56 ? slot_kv(n >> 3) + (n & 7) * 2048 : SM_QO + (n - 56) * 2048), 8192, 1024, 1) + wofs;
                    wgmma_rs56<1>(n < 28 ? accK : n < 56 ? accV : accQ, a[n % 28], desc, n % 28 != 0);
                });
                wg_commit();
                if (n0 > 0) wg_wait<1>();
            };
            const uint32_t hs = sb + tid * 16 + warp * 512;
            auto hand_over = [&](const uint32_t (&v)[8], int kv) {
                mbar_wait(bars + 8 * (kv ? B_DONE1 + 5 : B_DONEX), 0);
                sts4(hs + (kv ? SM_HALOV : SM_HALOK), v[0], v[1], v[2], v[3]); sts4(hs + (kv ? SM_HALOV : SM_HALOK) + 512, v[4], v[5], v[6], v[7]);
                if (w == 3) named_arrive(6 + kv, 96);
            };
            auto take_over = [&](uint32_t (&v)[8], int kv) {
                if (w == 0) mbar_wait(bars + 8 * (B_HALO + 2 * kv + wg), 0);
                const uint32_t ad = w ? hs + (kv ? SM_HALOV : SM_HALOK) - 1024 : kv ? sb + lane * 16 + wg * 1024 + SM_HALOV + 8192 : halo_kin(wg, lane);
                const uint4 u0 = lds4(ad), u1 = lds4(ad + (w || kv ? 512 : 16));
                v[0] = u0.x; v[1] = u0.y; v[2] = u0.z; v[3] = u0.w; v[4] = u1.x; v[5] = u1.y; v[6] = u1.z; v[7] = u1.w;
            };
            center(0); center(1); center(2); center(3);
            static_for<0, 7>([&](auto pc) {
                constexpr int p = pc.value;
                mbar_wait(bars + 8 * (B_FULLKV + p), 0);
                if (p == 0 && tid == 0) STAMP(26);
                if (p == 3 && tid == 0) STAMP(27);
                FST(4 + p);
                batch(Int<8 * p>(), Int<8 * p + 8>());
                if (p > 0 && leader) mbar_arrive(bars + 8 * (B_DONE1 + p - 1));
                #pragma unroll
                for (int s = 8 * p + 8; s < 8 * p + 16 && s < 28; s++) center(s);
                if (p == 1) {
                    const float c0 = bf_hi(mm0), c1 = bf_hi(mm1);
                    q0 = fmaf(c0, fmaf(c0, 64.f * NSQ, -2.f * p0), (g & 1) ? cA[0][1] + cA[1][1] : cA[0][0] + cA[1][0]) - D_ * (m0 - c0) * (m0 - c0);
                    q1 = fmaf(c1, fmaf(c1, 64.f * NSQ, -2.f * p1), (g & 1) ? cB[0][3] + cB[1][3] : cB[0][2] + cB[1][2]) - D_ * (m1 - c1) * (m1 - c1);
                    asm("" : "+f"(q0), "+f"(q1));
                    q0 = t == (g >> 1) ? q0 : 0.f; q1 = t == (g >> 1) ? q1 : 0.f;
                    pin2(__float_as_uint(q0), __float_as_uint(q1));
                }
                constexpr int PK = NSQ < 5 ? 5 : 4, NR = 28 - 4 * NSQ;
                if (p >= 2 && p < PK) {
                    #pragma unroll
                    for (int s = 4 * NSQ + NR * (p - 2) / (PK - 2); s < 4 * NSQ + NR * (p - 1) / (PK - 2); s++) { sq(q0, a[s][0]); sq(q1, a[s][1]); sq(q0, a[s][2]); sq(q1, a[s][3]); }
                    pin2(__float_as_uint(q0), __float_as_uint(q1));
                }
                if (p == PK - 1) { q0 = quad_sum(q0); q1 = quad_sum(q1); }
                if (p == PK) {
                    r0 = rsqrt_approx(fmaxf(q0 * (1.f / D_), 0.f) + LN_EPS); r1 = rsqrt_approx(fmaxf(q1 * (1.f / D_), 0.f) + LN_EPS);
                    reg_fence(accK);
                    #pragma unroll
                    for (int j = 0; j < 7; j++) kpack(Kc, j, 2, r1);
                    hand_over(Kc, 0);
                }
                if (p == PK + 1) {
                    #pragma unroll
                    for (int j = 0; j < 7; j++) kpack(Kb, j, 0, r0);
                    #pragma unroll
                    for (int j = 0; j < 8; j += 2) pin2(Kb[j], Kb[j + 1]);
                    ls0 = LOG2E_SCALE * r0; ls1 = LOG2E_SCALE * r1;
                    pm = (2 * t <= g ? 0xFFFFu : 0u) | (2 * t + 1 <= g ? 0xFFFF0000u : 0u);
                    zero = never; asm volatile("" : "+r"(zero));
                    pin2(__float_as_uint(ls0), __float_as_uint(ls1)); pin2(pm, zero);
                }
                if (p == 2) ep = get_tag();
                if (p == 6) {
                    tl = &sc->tiles[ep & 1];
                    const int tt = 2 * tb + (w >> 1);
                    od = tl->o + tt * 14336 + (7 * hp) * 256 + (2 * (2 * (w & 1) + wg)) * 32 + lane;
                    oh = sc->hint_o + (tt * 32 + hp * 4 + (w & 1) * 2 + wg) * 2 + (lane & 1);
                    pin2((uint32_t)(uint64_t)od, (uint32_t)((uint64_t)od >> 32));
                    pin2((uint32_t)(uint64_t)oh, (uint32_t)((uint64_t)oh >> 32));
                }
            });
            if (tid == 0) STAMP(1);
            FST(11);
            mbar_wait(bars + 8 * B_FQ, 0);
            batch(Int<56>(), Int<60>());
            reg_fence(accV);
            if (leader) mbar_arrive(bars + 8 * (B_DONE1 + 6));
            if (tid == 0) STAMP(2);
            FST(12);
            #pragma unroll
            for (int j = 0; j < 7; j++) Vc[j] = movtrans(pack_bf16(accV[4 * j + 2] * r1, accV[4 * j + 3] * r1));
            Vc[7] = Vc[6];
            hand_over(Vc, 1);
            batch(Int<60>(), Int<66>());
            #pragma unroll
            for (int j = 0; j < 7; j++) {
                Vb[j] = movtrans(pack_bf16(accV[4 * j] * r0, accV[4 * j + 1] * r0));
                Vc[j] |= zero;
            }
            batch(Int<66>(), Int<72>());
            #pragma unroll
            for (int j = 0; j < 7; j++) pin2(Vb[j], Vc[j]);
            mbar_wait(bars + 8 * (B_FQ + 1), 0);
            FST(13);
            if (w > 0 && lane < 2) { const uint32_t now = gtime32(); st_relaxed4(oh, ep, now, ep, now); }
            batch(Int<72>(), Int<84>());
            FST(14);
            named_sync(1 + wg, 128);
            take_over(Ka, 0);
            if (tid == 0) STAMP(3);
            wg_wait<0>();
            reg_fence(accQ);
            if (tid == 0) STAMP(4);
            FST(15);
            const bool first = (tb == 0 && w == 0);
            uint32_t pA[2], pB0[2], pB1[2], pC[2], z0[2], z1[2];
            float sA[2][4] = {}, sB[2][4] = {}, sC[2][4] = {}, e[2][4], inv[2][2];
            #pragma unroll
            for (int k = 0; k < 2; k++) {
                #pragma unroll
                for (int h = 0; h < 2; h++) {
                    const float* qq = accQ + 12 * h + 8 * k;
                    uint32_t a2 = pack_bf16(qq[4], qq[5]), a3 = pack_bf16(qq[6], qq[7]);
                    if (h == 0 && k == 1) { a2 |= zero; a3 |= zero; }
                    const uint32_t a0 = pack_bf16(qq[0], qq[1]), a1 = pack_bf16(qq[2], qq[3]);
                    mma16816(sB[h], a0, a1, a2, a3, Kb[4 * h + 2 * k], Kb[4 * h + 2 * k + 1]);
                    mma16816(sA[h], a0, a1, a2, a3, Ka[4 * h + 2 * k], Ka[4 * h + 2 * k + 1]);
                    mma16816(sC[h], a0, a1, a2, a3, Kc[4 * h + 2 * k], Kc[4 * h + 2 * k + 1]);
                }
            }
            #pragma unroll
            for (int h = 0; h < 2; h++) {
                const bool n0 = pm & 1, n1 = (int)pm < 0;
                const float l00 = n0 ? sB[h][0] : (first ? -INFINITY : sA[h][0]), l01 = n1 ? sB[h][1] : (first ? -INFINITY : sA[h][1]);
                const float l10 = n0 ? sC[h][2] : sB[h][2], l11 = n1 ? sC[h][3] : sB[h][3];
                const float x0 = -ls0 * quad_max(fmaxf(l00, l01)), x1 = -ls1 * quad_max(fmaxf(l10, l11));
                e[h][0] = ex2(fmaf(l00, ls0, x0)); e[h][1] = ex2(fmaf(l01, ls0, x0)); e[h][2] = ex2(fmaf(l10, ls1, x1)); e[h][3] = ex2(fmaf(l11, ls1, x1));
            }
            pin4(never, e[0][0], e[0][2], e[1][0], e[1][2]);
            take_over(Va, 1);
            #pragma unroll
            for (int h = 0; h < 2; h++) {
                inv[h][0] = rcp_approx(quad_sum(e[h][0] + e[h][1])); inv[h][1] = rcp_approx(quad_sum(e[h][2] + e[h][3]));
                const uint32_t P0 = pack_bf16(e[h][0], e[h][1]), P1 = pack_bf16(e[h][2], e[h][3]);
                pB0[h] = P0 & pm; pA[h] = P0 & ~pm; pC[h] = P1 & pm; pB1[h] = P1 & ~pm; z0[h] = P0 & zero; z1[h] = P1 & zero;
            }
            float o[8][4];
            #pragma unroll
            for (int j = 0; j < 8; j++) {
                o[j][0] = o[j][1] = o[j][2] = o[j][3] = 0.f;
                mma16816(o[j], pB0[j >> 2], pB1[j >> 2], z0[j >> 2], pC[j >> 2], Vb[j - (j >> 2)], Vc[j - (j >> 2)]);
            }
            if (tid == 0) STAMP(12);
            FST(16);
            if (tid == 0) STAMP(16);
            #pragma unroll
            for (int j = 0; j < 8; j++) mma1688(o[j], pA[j >> 2], z1[j >> 2], Va[j - (j >> 2)]);
            #pragma unroll
            for (int j = 0; j < 7; j++) {
                float v[4];
                #pragma unroll
                for (int c = 0; c < 4; c++) {
                    v[c] = j < 3 ? o[j][c] : j > 3 ? o[j + 1][c] : (t < 2 ? o[3][c] : o[4][c]);
                    v[c] *= j < 3 ? inv[0][c >> 1] : j > 3 ? inv[1][c >> 1] : (t < 2 ? inv[0][c >> 1] : inv[1][c >> 1]);
                }
                od[j * 256] = pack_bf16(v[0], v[1]);
                od[j * 256 + 32] = pack_bf16(v[2], v[3]);
            }
            if (lane == 0) mbar_arrive(bars + 8 * B_DONEQ);
            if (tid == 0) STAMP(5);
            FST(17);
        }
        const int z = get_tag() - ep, slot1 = slot + z, tid1 = tid + z, warp1 = warp + z;
        ep += z;
        {
        ASSIGN_WORK(slot1)
        const int tid = tid1, lane = tid & 31, wg = warp1 >> 2, w = warp1 & 3, g = lane >> 2, t = lane & 3;
        tl = &sc->tiles[ep & 1];
        const uint32_t live = wg ^ 1;
        uint32_t rb0, rb1, late[14];
        const unsigned short* pb = (const unsigned short*)(live ? b2 + tt2 * 64 : b1 + ft * 64) + 16 * w + g;
        auto stage_late = [&]() {
            #pragma unroll
            for (int c = 0; c < 14; c++) asm volatile("st.shared.u32 [%0], %1;" :: "r"(sb + SM_H + wg * 8192 + (tid & 127) * 4 + c * 512), "r"(late[c]) : "memory");
            fence_async_smem();
            named_sync(1 + wg, 128);
        };
        auto store_late = [&](bool on, uint32_t* p) {
            #pragma unroll
            for (int c = 0; c < 4; c++)
                if (elect() && on && (c < 3 || w < 2)) bulk_st(p + (4 * c + w) * 256, sb + SM_H + wg * 8192 + (4 * c + w) * 512, 512);
            asm volatile("cp.async.bulk.commit_group;" ::: "memory");
        };
        if (live) {
            float acc[56];
            const int hrow = 32 * (w >> 1) + 2 * ((lane & 7) + (lane & 8)) + (w & 1);
            const uint32_t ha = sb + SM_H + hrow * 128 + (((lane >> 4) ^ (hrow & 7)) << 4);
            uint4* sp = sc->stats + tt2 * 256 + 16 * w + g + 8 * (t & 1);
            uint4* sp_out = sp + q * 64;
            const uint4* sp_in = sp + (t & 2) * 64;
            uint32_t* hd = tl->hn + ((q >> 1) * 32 + (tt2 >> 1)) * 7168 + (q & 1) * 3584 + (tt2 & 1) * 128 + w * 32 + lane;
            pin_ptr(never, sp_out); pin_ptr(never, sp_in); pin_ptr(never, hd);
            float s0 = 0.f, s1 = 0.f, q0 = 0.f, q1 = 0.f, s2 = 0.f, s3 = 0.f, q2 = 0.f, q3 = 0.f;
            auto sums = [&](int j0, int j1) {
                #pragma unroll
                for (int j = j0; j < j1; j++) {
                    s0 += acc[4 * j]; s2 += acc[4 * j + 1]; q0 = fmaf(acc[4 * j], acc[4 * j], q0); q2 = fmaf(acc[4 * j + 1], acc[4 * j + 1], q2);
                    s1 += acc[4 * j + 2]; s3 += acc[4 * j + 3]; q1 = fmaf(acc[4 * j + 2], acc[4 * j + 2], q1); q3 = fmaf(acc[4 * j + 3], acc[4 * j + 3], q3);
                }
            };
            {
                mbar_wait(bars + 8 * B_FULLWO, 0);
                #pragma unroll
                for (int jp = 0; jp < 7; jp++) {
                    uint32_t xx[4];
                    ldsm4(xx, hcol(ha, jp));
                    #pragma unroll
                    for (int r = 0; r < 4; r++) { acc[8 * jp + 2 * r] = bf_lo(xx[r]); acc[8 * jp + 2 * r + 1] = bf_hi(xx[r]); }
                }
                reg_fence(acc);
                named_sync(12, 256);
                spin_mma(bars + 8 * B_FULLX, never);
                auto od_ = [&](int s) { return mkdesc(sb + SM_QO + s * 2048, 1024, 128, 0); };
                auto wd_ = [&](int s) { return mkdesc(sb + slot_wo(s >> 2) + (s & 3) * 2048, 8192, 1024, 1); };
                float accl[32], accr[24];
                #pragma unroll
                for (int i = 0; i < 5; i++) {
                    if (i < 4) mbar_wait(bars + 8 * (B_FULLO + i), 0);
                    if (i == 0 && tid == 0) STAMP(7);
                    if (i == 1) { rb0 = ld_u16(pb); rb1 = ld_u16(pb + 8); }
                    wg_fence();
                    #pragma unroll
                    for (int ss = i ? 0 : 4; ss < 8; ss++) {
                        if (i < 3) wgmma_ss112<0, 1>(acc, od_(8 * i - 4 + ss), wd_(8 * i - 4 + ss));
                        else if (i == 4) wgmma_ss64<0, 1>(accl, od_(20 + ss), wd_(20 + ss));
                        else if (ss == 0) wgmma_ss48<0, 1, 0>(accr, od_(20), wd_(20) + 512);
                        else wgmma_ss48<0, 1>(accr, od_(20 + ss), wd_(20 + ss) + 512);
                    }
                    wg_commit();
                    if (i > 0) {
                        wg_wait<1>();
                        if (i == 3) {
                            reg_fence(acc);
                            #pragma unroll
                            for (int c = 0; c < 32; c++) accl[c] = __uint_as_float(__float_as_uint(acc[c]) | never);
                            reg_fence(accl);
                        }
                        if (i < 4 && leader) mbar_arrive(bars + 8 * (B_DONEO + i - 1));
                    }
                }
                reg_fence(accr);
                #pragma unroll
                for (int c = 0; c < 24; c++) acc[32 + c] += accr[c];
                sums(8, 14);
                pin4(never, s0, s1, s2, s3); pin4(never, q0, q1, q2, q3);
                wg_wait<0>();
                reg_fence(accl);
                #pragma unroll
                for (int c = 0; c < 32; c++) acc[c] = accl[c];
                if (leader) mbar_arrive(bars + 8 * (B_DONEO + 3));
                if (tid == 0) STAMP(8);
            }
            sums(0, 8);
            s0 += s2; s1 += s3; q0 += q2; q1 += q3;
            float sr = ((t & 1) ? s1 : s0) + __shfl_xor_sync(0xffffffffu, (t & 1) ? s0 : s1, 1), qr = ((t & 1) ? q1 : q0) + __shfl_xor_sync(0xffffffffu, (t & 1) ? q0 : q1, 1);
            sr += __shfl_xor_sync(0xffffffffu, sr, 2); qr += __shfl_xor_sync(0xffffffffu, qr, 2);
            st_relaxed4_if(t < 2, sp_out, __float_as_uint(sr), __float_as_uint(qr), ep);
            named_arrive(5, 256);
            if (tid == 0) STAMP(9);
            #pragma unroll
            for (int jp = 0; jp < 7; jp++)
                stsm4(hcol(ha, jp), pack_bf16(acc[8 * jp], acc[8 * jp + 1]), pack_bf16(acc[8 * jp + 2], acc[8 * jp + 3]),
                      pack_bf16(acc[8 * jp + 4], acc[8 * jp + 5]), pack_bf16(acc[8 * jp + 6], acc[8 * jp + 7]));
            uint4 v0, v1;
            do { v0 = ld_relaxed4(sp_in); v1 = ld_relaxed4(sp_in + 64); } while (__any_sync(0xffffffffu, v0.w != ep || v1.w != ep));
            if (tid == 0) STAMP(10);
            sr = __uint_as_float(v0.x) + __uint_as_float(v1.x); qr = __uint_as_float(v0.y) + __uint_as_float(v1.y);
            sr += __shfl_xor_sync(0xffffffffu, sr, 2); qr += __shfl_xor_sync(0xffffffffu, qr, 2);
            const float m = sr * (1.f / D_), var = fmaxf(qr * (1.f / D_) - m * m, 0.f);
            const float r = rsqrt_approx(fmaf(var, 4.f + 4.f * LN_EPS, 4.f * LN_EPS * LN_EPS)), c = -m * r;
            const float r0 = __shfl_sync(0xffffffffu, r, lane & ~1), c0 = __shfl_sync(0xffffffffu, c, lane & ~1);
            const float r1 = __shfl_sync(0xffffffffu, r, lane | 1), c1 = __shfl_sync(0xffffffffu, c, lane | 1);
            #pragma unroll
            for (int j = 0; j < 14; j++) st_global_if(1, hd + j * 256, pack_bf16(fmaf(acc[4 * j], r0, c0), fmaf(acc[4 * j + 1], r0, c0)));
            if (never) mbar_arrive(bars);
            #pragma unroll
            for (int j = 0; j < 14; j++) late[j] = pack_bf16(fmaf(acc[4 * j + 2], r1, c1), fmaf(acc[4 * j + 3], r1, c1));
            if (tid == 0) STAMP(11);
        } else {
            named_arrive(12, 256);
            check_tiles<0>(w, 4, 4, tl->o + tt2 * 14336, false, lane, true);
            rb0 = ld_u16(pb); rb1 = ld_u16(pb + 8);
            auto reset_tiles = [&](int v, int i0, int i1) {
                const int l = slot * 48 + v * 16 + lane / 2;
                #pragma unroll
                for (int i = i0; i < i1; i++)
                    st_relaxed4_if(i < 6 || l < sizeof(Tiles) / 128 - 6 * 6144, (uint4*)&sc->tiles[~ep & 1] + (i * 6144 + l) * 8 + (lane & 7), EMPTY, EMPTY, EMPTY);
            };
            if (CL_N && w < 3) { mbar_wait(bars + 8 * (B_DONEO + CL_P2), 0); reset_tiles(w, 0, CL_N); }
            named_sync(5, 256);
            auto phase3 = [&](auto nc) {
                constexpr int NC = nc.value;
                float acc[4 * NC];
                uint32_t* ud = tl->u + (pr3 * 28 + (ft >> 1) + (NC == 14 ? 4 : 0)) * 7168 + col3 * 256 + (ft & 1) * 128 + w * 32 + lane;
                #pragma unroll
                for (int j = 0; j < 4 * NC; j++) acc[j] = 0.5f * bf_lo((j & 2) ? rb1 : rb0);
                #pragma unroll 1
                for (uint32_t pass = never; pass < 2; pass++) {
                    if (pass) {
                        mix_mainloop<32>(TSVAL acc, leader);
                        if (leader) STAMP(14);
                    }
                    uint32_t pk[NC];
                    #pragma unroll
                    for (int j = 0; j < NC; j++) {
                        const float k = j < GDEP ? GELU_K1 : __uint_as_float(__float_as_uint(GELU_K1) | (pk[j - GDEP] & never));
                        pk[j] = pack_bf16(gelu_half(acc[4 * j], k), gelu_half(acc[4 * j + 1], k));
                        st_global_if(pass, ud + j * 256, pk[j]);
                    }
                }
                if (leader) STAMP(15);
                #pragma unroll
                for (int j = 0; j < NC; j++) late[j] = pack_bf16(gelu_half(acc[4 * j + 2], GELU_K1), gelu_half(acc[4 * j + 3], GELU_K1));
                if (NC == 14) {
                    stage_late();
                    mbar_wait(bars + 8 * (B_FULLB + LATE_AT4), 1);
                    store_late(true, tl->u + (pr3 * 28 + (ft >> 1) + 14) * 7168 + col3 * 256 + (ft & 1) * 128);
                } else {
                    #pragma unroll
                    for (int c = 0; c < NC; c++) st_global_if(1, ud + 4 * 7168 + c * 256, late[c]);
                }
            };
            if (early) phase3(Int<10>()); else phase3(Int<14>());
            if (w) {
                if (early && w == 1) fetch_times(TSVAL sc->go, 1, ep, lane);
                if (CL_N < 7) { mbar_wait(bars + 8 * (B_DONE + CL_AT), 1); reset_tiles(w - 1, CL_N, 7); }
            }
            if (leader) mbar_wait_wd(bars + 8 * B_END, 0);
            return;
        }
        {
            float acc[56];
            const uint32_t ad = sb + SM_H + (16 * w + (lane & 15)) * 128 + (((lane >> 4) ^ (lane & 7)) << 4);
            const float bb0 = bf_lo(rb0), bb1 = bf_lo(rb1);
            named_sync(1, 128);
            #pragma unroll
            for (int jp = 0; jp < 7; jp++) {
                uint32_t hh[4];
                ldsm4(hh, hcol(ad, jp));
                #pragma unroll
                for (int r = 0; r < 4; r++) { acc[8 * jp + 2 * r] = bf_lo(hh[r]) + ((r & 1) ? bb1 : bb0); acc[8 * jp + 2 * r + 1] = bf_hi(hh[r]) + ((r & 1) ? bb1 : bb0); }
            }
            named_sync(1, 128);
            stage_late();
            if (tid == 0) STAMP(39);
            reg_fence(acc);
            spin_mma(bars + 8 * (B_FULLX + 1), never);
            mbar_wait(bars + 8 * (B_FULLB + LATE_AT), 0);
            store_late(true, tl->hn + ((q >> 1) * 32 + 16 + (tt2 >> 1)) * 7168 + (q & 1) * 3584 + (tt2 & 1) * 128);
            check_tiles<1>(CH_H + w, 4, 32, tl->hn + pr3 * 32 * 7168 + col3 * 256, early, lane, false);
            mbar_wait(bars + 8 * (B_DONE + START4), 0);
            mix_mainloop<28>(TSVAL acc, leader);
            if (leader) mbar_arrive(bars + 8 * B_END);
            if (tid == 0) STAMP(18);
            #pragma unroll
            for (int jp = 0; jp < 7; jp++)
                stsm4(hcol(ad, jp), pack_bf16(acc[8 * jp], acc[8 * jp + 1]), pack_bf16(acc[8 * jp + 2], acc[8 * jp + 3]),
                         pack_bf16(acc[8 * jp + 4], acc[8 * jp + 5]), pack_bf16(acc[8 * jp + 6], acc[8 * jp + 7]));
            fence_async_smem();
            __syncwarp();
            if (elect()) {
                tma2d_store(&tm_out64, c64, tt2 * 64 + 16 * w, sb + SM_H + w * 2048);
                tma2d_store(&tm_out48, c48, tt2 * 64 + 16 * w, sb + SM_H + 8192 + w * 2048);
            }
            asm volatile("cp.async.bulk.commit_group;" ::: "memory");
            asm volatile("cp.async.bulk.wait_group.read 0;" ::: "memory");
            if (tid == 0) { sc->epoch[slot] = ep; STAMP(19); }
        }
        }
    } else {
        asm volatile("setmaxnreg.dec.sync.aligned.u32 56;");
        int warp2; asm("mov.u32 %0, %1;" : "=r"(warp2) : "r"(warp));
        if (warp2 > 8) {
            ASSIGN_WORK(get_slot())
            if (slot >= 128) return;
            uint32_t ep, cl;
            uint4* const oh = sc->hint_o + (2 * tb * 32 + hp * 4) * 2 + (lane & 3);
            uint4* const hu = sc->hint_u + (early ? ech * 8 + ft : 40 + q * 20 + ft) * 2;
            if (warp == 10) {
                post_hint(sc->hint_h + (q * 32 + tt2) * 2, 0, lane);
                post_hint(hu, 0, lane);
            }
            if (warp == 11) {
                ep = ld_volatile(&sc->epoch[slot]) + 1; cl = ld_acquire(&sc->clean);
                post_hint(sc->hint_k + (tb * 8 + hp) * 2, 0, lane);
                if (lane < (tb < 15 ? 4 : 0)) st_relaxed4(oh + 128, 0, 0, 0, 0);
                if (lane < (tb ? 0 : 4)) st_relaxed4(oh, 0, 0, 0, 0);
            }
            if (elect()) {
                if (warp == 9) {
                    #pragma unroll
                    for (int i = B_DONE1; i < B_DONEO; i++) mbar_init(bars + 8 * i, i < B_DONEX ? 2 : i == B_DONEX ? 8 : 9);
                }
                #pragma unroll
                for (int i = 0; i < 54; i++) mbar_init(bars + 8 * (B_DONEO + i) + (warp - 9) * 432, 1);
                asm volatile("fence.mbarrier_init.release.cluster;" ::: "memory");
            }
            named_sync(8, 128);
            if (warp < 11) mbar_expect(sb + SM_RAW + 8 * (tid - 288), tid == 288 ? 8192 : tid < 292 ? 16384 : early && tid < 324 ? 10240 : 14336);
            if (warp == 9) { named_arrive(4, 64); named_arrive(9, 160); named_arrive(10, 160); }
            if (warp < 11) {
                ep = get_tag();
                mbar_wait(bars + 8 * (B_DONE1 + HALO_AT), 0);
                #pragma unroll 1
                for (int kv = 0; kv < 2; kv++) {
                    uint4 v0 = {}, v1 = {}, v2 = {};
                    if (tb > 0) {
                        const uint4* hg = sc->halo + ((((tb - 1) * 8 + hp) * 2 + warp - 9) * 2 + kv) * 96 + lane;
                        if (kv == 0) while (ld_relaxed(sc->hint_k + ((tb - 1) * 8 + hp) * 2) != ep) {}
                        do { v0 = ld_relaxed4(hg); v1 = ld_relaxed4(hg + 32); v2 = ld_relaxed4(hg + 64); } while (!__all_sync(0xffffffffu, v0.w == ep && v1.w == ep && v2.w == ep));
                    }
                    if (kv) mbar_wait(bars + 8 * (B_DONE1 + 5), 0);
                    const uint32_t hs = kv ? sb + lane * 16 + (warp - 9) * 1024 + SM_HALOV + 8192 : halo_kin(warp - 9, lane);
                    sts4(hs, v0.x, v0.y, v0.z, v1.x); sts4(hs + (kv ? 512 : 16), v1.y, v1.z, v2.x, v2.y);
                    __syncwarp();
                    if (lane == 0) mbar_arrive(bars + 8 * (B_HALO + 2 * kv + warp - 9));
                }
                if (tid == 288) STAMP(21);
            } else {
                const long long t0 = clock64();
                while (__any_sync(0xffffffffu, (int)(cl - ep) < 0)) { cl = ld_acquire(&sc->clean); if (clock64() - t0 > WD_CLKS) __trap(); }
                if (lane == 0) { *(volatile uint32_t*)(smem_raw + SM_TAG) = ep; mbar_arrive(bars + 8 * B_CLR); }
                uint4* hg = sc->halo + (tb * 8 + hp) * 384 + lane;
                #pragma unroll 1
                for (int kv = 0; kv < 2; kv++) {
                    const uint32_t hs = sb + lane * 16 + 3072 + (kv ? SM_HALOV : SM_HALOK);
                    named_sync(6 + kv, 96);
                    #pragma unroll
                    for (int p = 0; p < 2; p++) {
                        const uint4 u0 = lds4(hs + p * 4096), u1 = lds4(hs + p * 4096 + 512);
                        st_relaxed4(hg + p * 192, u0.x, u0.y, u0.z, ep); st_relaxed4(hg + p * 192 + 32, u0.w, u1.x, u1.y, ep); st_relaxed4(hg + p * 192 + 64, u1.z, u1.w, ep, ep);
                    }
                    hg += 96;
                    if (kv == 0) {
                        post_hint(sc->hint_k + (tb * 8 + hp) * 2, ep, lane);
                        #pragma unroll
                        for (int j = 0; j < 6; j++) st_relaxed4(hg + j * 32 + (j / 3) * 96, 0, 0, 0, 0);
                    }
                }
                const uint32_t now = gtime32() - LATE_O;
                if (lane < (tb < 15 ? 4 : 0)) st_relaxed4(oh + 128, ep, now, ep, now);
                if (lane < (tb ? 0 : 4)) st_relaxed4(oh, ep, now, ep, now);
                if (lane == 0) STAMP(23);
                if (lane == 0) mbar_arrive(bars + 8 * B_DONEQ);
            }
            if (warp > 9) {
                const Tiles* const tl = &sc->tiles[ep & 1];
                check_tiles<1>(11 - warp, 2, CH_H, tl->hn + pr3 * 32 * 7168 + col3 * 256, early, lane, true);
                if (warp == 10) {
                    mbar_wait(bars + 8 * (B_DONE + (early ? HINT_E : HINT_U)), 0);
                    post_time(hu, ep, lane);
                }
                if (warp == 11) {
                    mbar_wait(bars + 8 * (B_DONE + (early ? POLL_E : POLL_N)), 0);
                    fetch_times(TSVAL sc->go, 0, ep, lane);
                }
                check_tiles<2>(11 - warp, 2, 28, tl->u + (q >> 1) * 28 * 7168 + (q & 1) * 3584, false, lane, true);
            } else {
                int aslot = 0;
                if (lane == 0) { prefetch_map(&tm_out64); prefetch_map(&tm_out48); }
                #pragma unroll
                for (int i = 0; i < HINT_F; i++) mbar_wait(bars + 8 * (B_FULLO + i), 0);
                post_time(sc->hint_h + (q * 32 + tt2) * 2, ep, lane);
                #pragma unroll 1
                for (int i = 0; i < 30; i++) {
                    if (i == POLL_I && !early) fetch_times(TSVAL sc->go, 1, ep, lane);
                    int d = 2 * i - 11 + (i >= A4_FROM ? A4_DLY : 0);
                    if (early) d = i < 16 ? 1 + (i - NA_SLOTS) * AE_END / 9 : max(d, AE_W2);
                    mbar_wait(bars + 8 * (i < NA_SLOTS ? B_DONEQ + ((A_SCHED >> (4 * i)) & 15) : B_DONE + (d & 31)), d >= 32);
                    if (elect()) {
                        const uint32_t bar = bars + 8 * (B_FULLA + (i & 15)), dst = sb + SM_ARING + aslot * 16384;
                        mbar_expect(bar, 16384);
                        if (i < 16) tma5d(dst, &tm_w1, ft * 64, (i & 7) * 8, i >> 3, bar);
                        else tma5d(dst, &tm_w2, tt2 * 64, 8 * (i < 20 ? i & 1 : i < 25 ? i - 18 : i - 23), i < 20 ? (i >> 1) & 1 : i >= 25, bar);
                    }
                    aslot = aslot == NA_SLOTS - 1 ? 0 : aslot + 1;
                }
            }
        } else {
            const int slot0 = get_slot(), row0 = (slot0 >> 5) * 256 + (slot0 & 12) * 16;
            if (elect()) {
                prefetch_map(&tm_x);
                #pragma unroll
                for (int i = 0; i < 7; i++) mbar_init(bars + 8 * i, 1);
                asm volatile("fence.mbarrier_init.release.cluster;" ::: "memory");
            }
            named_arrive(0, 288);
            if (elect()) {
                #pragma unroll 1
                for (int kb = 0; kb < 7; kb++) {
                    load_x(kb, row0);
                    if (kb == 0) STAMP(22);
                }
                #pragma unroll
                for (int i = 7; i < B_DONE1; i++) mbar_init(bars + 8 * i, 1);
                asm volatile("fence.mbarrier_init.release.cluster;" ::: "memory");
            }
            named_arrive(8, 128);
            ASSIGN_WORK(get_slot())
            if (slot >= 128) return;
            #pragma unroll 1
            for (int kb = 0; kb < 7; kb++) {
                if (kb == 6) { named_sync(4, 64); mbar_wait(bars + 8 * B_DONEX, 0); }
                if (elect()) {
                    const uint32_t st = sb + slot_kv(kb), bar = bars + 8 * (B_FULLKV + kb);
                    mbar_expect(bar, 16384);
                    #pragma unroll
                    for (int i = 0; i < 2; i++) {
                        const int n = 2 * kb + (i ^ (G & 1));
                        tma2d(st + (n & 1) * 8192, &tm_wqkv, (n < 7 ? 448 : 896) + wcol, (n < 7 ? n : n - 7) * 64, bar);
                    }
                }
            }
            if (elect()) {
                mbar_expect(bars + 8 * B_FQ, 32768);
                mbar_expect(bars + 8 * (B_FQ + 1), 24576);
                #pragma unroll 1
                for (int i = 0; i < 7; i++) { const int j = i == 6 ? i : i ^ (G & 1); tma2d(sb + SM_QO + j * 8192, &tm_wqkv, wcol, j * 64, bars + 8 * (B_FQ + (i >> 2))); }
                mbar_expect(bars + 8 * B_FULLWO, 512 * 112 * 2);
            }
            #pragma unroll 1
            for (int i = 0; i < 7; i++) {
                if (i == PFC_AT && elect()) {
                    #pragma unroll 1
                    for (int k = NA_SLOTS + (early ? ech : q); k < (early ? PFC_E : PFC_N); k += early ? 6 : 4) tma5d_prefetch(&tm_w1, ft * 64, (k & 7) * 8, k >> 3);
                }
                if (i == PFW_AT && elect()) {
                    #pragma unroll 1
                    for (int k = PFW_0 + q; k < PFW_N; k += 4) tma5d_prefetch(&tm_w2, tt2 * 64, 8 * (k < 4 ? k & 1 : k < 9 ? k - 2 : k - 7), k < 4 ? k >> 1 : k >= 9);
                }
                const int kb = ((q & 1 ? WO_ORD1 : WO_ORD0) >> (4 * i)) & 7;
                if (kb < 5) mbar_wait(bars + 8 * (B_DONE1 + kb), 0);
                if (elect()) {
                    tma2d(sb + slot_wo(kb), &tm_wo64, c64, kb * 64, bars + 8 * B_FULLWO);
                    tma2d(sb + slot_wo(kb) + 8192, &tm_wo48, c48, kb * 64, bars + 8 * B_FULLWO);
                }
            }
            if (elect()) {
                tma2d(sb + SM_H, &tm_xr64, c64, tt2 * 64, bars + 8 * B_FULLWO);
                tma2d(sb + SM_H + 8192, &tm_xr48, c48, tt2 * 64, bars + 8 * B_FULLWO);
            }
            if (smem_u32(smem_raw) != SB) __trap();
            const uint32_t ep = get_tag();
            const Tiles* const tl = &sc->tiles[ep & 1];
            mbar_wait(bars + 8 * (B_DONE1 + 6), 0);
            const uint32_t t_o = last_hint(TSVAL sc->hint_o + (tt2 * 32 + lane) * 2, ep, 38);
            mbar_wait(bars + 8 * B_DONEQ, 0);
            wait_until(t_o + GO_O);
            if (elect()) {
                #pragma unroll
                for (int i = 0; i < 4; i++) {
                    bulk_ld(sb + SM_QO + max(2 * i - 1, 0) * 8192, tl->o + tt2 * 14336 + max(2 * i - 1, 0) * 2048, i ? 16384 : 8192, sb + SM_RAW + 8 * i);
                }
            }
            if (lane == 0) STAMP(20);
            wait_until(t_o + GO_O + STOP2);
            if (lane == 0) mbar_arrive(bars + 8 * B_FULLX);
            mbar_wait(bars + 8 * (B_DONEO + POLL_H), 0);
            const uint32_t* src = tl->hn + pr3 * 32 * 7168 + col3 * 256;
            uint32_t bytes = early ? 10240 : 14336, dst = sb + SM_BRING, top = dst + (early ? NE_SLOTS * 10240 : NB_SLOTS * 14336), raw = sb + SM_RAW + 32;
            auto issue = [&]() {
                if (elect()) bulk_ld(dst, src, bytes, raw);
                src += 7168; raw += 8; dst += bytes;
                if (dst == top) dst = sb + SM_BRING;
            };
            uint2 th;
            do { th = ld_relaxed2((const uint2*)sc->go + (lane & 15)); } while (!__all_sync(0xffffffffu, th.x == ep));
            STAMP(42);
            mbar_wait(bars + 8 * (B_DONEO + 3), 0);
            {
                uint32_t bit = 1, wait = ~1u;
                wait_until(__shfl_sync(0xffffffffu, th.y, 0) + GO_H);
                #pragma unroll 1
                do {
                    while (wait & bit) wait = __ballot_sync(0xffffffffu, (int)(gtime32() - th.y - GO_H) < 0);
                    if (bit == 1) STAMP(29);
                    issue();
                    if (bit == 1 << STOP3 && lane == 0) mbar_arrive(bars + 8 * (B_FULLX + 1));
                    bit *= 2;
                } while (dst != sb + SM_BRING);
            }
            uint32_t done = bars + 8 * B_DONE;
            #pragma unroll 1
            do { mbar_wait(done, 0); done += 8; issue(); } while (raw != sb + SM_RAW + 288);
            if (early) mbar_wait(bars + 8 * (B_DONE + 31), 0);
            src = tl->u + (q >> 1) * 28 * 7168 + (q & 1) * 3584; bytes = 14336; dst = sb + SM_BRING; top = dst + NB_SLOTS * 14336;
            done = bars + 8 * (B_DONE + 24);
            #pragma unroll 1
            for (uint32_t par = 0; par < 2; par++) {
                mbar_wait(bars + 8 * (B_GO + par), 0);
                const uint32_t ts = *(volatile uint32_t*)(smem_raw + SM_TIME + 128 * par + 4 * lane);
                if (par) done = bars + 8 * B_DONE;
                uint32_t bit = 1, wait = ~1u;
                wait_until(__shfl_sync(0xffffffffu, ts, 0));
                #pragma unroll 1
                do {
                    while (wait & bit) wait = __ballot_sync(0xffffffffu, (int)(gtime32() - ts) < 0);
                    if (bit == 1) STAMP(par ? 36 : 30);
                    mbar_wait(done, par); done += 8;
                    issue();
                    bit *= 2;
                } while (bit != (par ? 1 << 20 : 1 << 8));
            }
        }
    }
}

typedef CUresult (*EncodeFn)(CUtensorMap*, CUtensorMapDataType, cuuint32_t, void*, const cuuint64_t*, const cuuint64_t*, const cuuint32_t*,
                             const cuuint32_t*, CUtensorMapInterleave, CUtensorMapSwizzle, CUtensorMapL2promotion, CUtensorMapFloatOOBfill);

void make_map(EncodeFn fn, CUtensorMap* tm, const void* ptr, int rank, const cuuint64_t* dims, const cuuint64_t* strides, const cuuint32_t* box, CUtensorMapSwizzle sw) {
    cuuint32_t es[5] = {1, 1, 1, 1, 1};
    fn(tm, CU_TENSOR_MAP_DATA_TYPE_BFLOAT16, rank, const_cast<void*>(ptr), dims, strides, box, es, CU_TENSOR_MAP_INTERLEAVE_NONE, sw,
       CU_TENSOR_MAP_L2_PROMOTION_NONE, CU_TENSOR_MAP_FLOAT_OOB_FILL_NONE);
}

}

extern "C" void kernel_launch(void* const* d_in, const int* in_sizes, int n_in, void* d_out, int out_size) {
    const __nv_bfloat16* x = (const __nv_bfloat16*)d_in[0];
    const __nv_bfloat16* wqkv = (const __nv_bfloat16*)d_in[1];
    const __nv_bfloat16* wo = (const __nv_bfloat16*)d_in[2];
    const __nv_bfloat16* w1 = (const __nv_bfloat16*)d_in[4];
    const __nv_bfloat16* b1 = (const __nv_bfloat16*)d_in[5];
    const __nv_bfloat16* w2 = (const __nv_bfloat16*)d_in[6];
    const __nv_bfloat16* b2 = (const __nv_bfloat16*)d_in[7];

    void* fnp = nullptr; cudaDriverEntryPointQueryResult qr;
    cudaGetDriverEntryPoint("cuTensorMapEncodeTiled", &fnp, cudaEnableDefault, &qr);
    EncodeFn fn = (EncodeFn)fnp;
    CUtensorMap tx, twqkv, two64, two48, tw1, tw2, txr64, txr48, tout64, tout48;
    { cuuint64_t d[3] = {448, 2, 1024}, s[2] = {896, 1792}; cuuint32_t b[3] = {64, 1, 64}; make_map(fn, &tx, x, 3, d, s, b, CU_TENSOR_MAP_SWIZZLE_128B); }
    { cuuint64_t d[2] = {1344, 448}, s[1] = {2688}; cuuint32_t b[2] = {64, 64}; make_map(fn, &twqkv, wqkv, 2, d, s, b, CU_TENSOR_MAP_SWIZZLE_128B); }
    { cuuint64_t d[2] = {448, 448}, s[1] = {896}; cuuint32_t b[2] = {64, 64}; make_map(fn, &two64, wo, 2, d, s, b, CU_TENSOR_MAP_SWIZZLE_128B); }
    { cuuint64_t d[2] = {448, 448}, s[1] = {896}; cuuint32_t b[2] = {48, 64}; make_map(fn, &two48, wo, 2, d, s, b, CU_TENSOR_MAP_SWIZZLE_128B); }
    { cuuint64_t d[5] = {1792, 8, 2, 64, 2}, s[4] = {2 * 3584, 3584, 32 * 3584, 16 * 3584}; cuuint32_t b[5] = {64, 8, 2, 8, 1}; make_map(fn, &tw1, w1, 5, d, s, b, CU_TENSOR_MAP_SWIZZLE_128B); }
    { cuuint64_t d[5] = {2048, 8, 2, 56, 2}, s[4] = {4096, 16 * 4096, 32 * 4096, 8 * 4096}; cuuint32_t b[5] = {64, 8, 2, 8, 1}; make_map(fn, &tw2, w2, 5, d, s, b, CU_TENSOR_MAP_SWIZZLE_128B); }
    { cuuint64_t d[2] = {448, 2048}, s[1] = {896}; cuuint32_t b[2] = {64, 64}; make_map(fn, &txr64, x, 2, d, s, b, CU_TENSOR_MAP_SWIZZLE_128B); }
    { cuuint64_t d[2] = {448, 2048}, s[1] = {896}; cuuint32_t b[2] = {48, 64}; make_map(fn, &txr48, x, 2, d, s, b, CU_TENSOR_MAP_SWIZZLE_128B); }
    { cuuint64_t d[2] = {448, 2048}, s[1] = {896}; cuuint32_t b[2] = {64, 16}; make_map(fn, &tout64, d_out, 2, d, s, b, CU_TENSOR_MAP_SWIZZLE_128B); }
    { cuuint64_t d[2] = {448, 2048}, s[1] = {896}; cuuint32_t b[2] = {48, 16}; make_map(fn, &tout48, d_out, 2, d, s, b, CU_TENSOR_MAP_SWIZZLE_128B); }

    void* scv = nullptr;
    cudaGetSymbolAddress(&scv, g_scratch);
    Scratch* scp = (Scratch*)scv;
    int dev = 0, sms = 0;
    cudaGetDevice(&dev);
    cudaDeviceGetAttribute(&sms, cudaDevAttrMultiProcessorCount, dev);
    if (sms == 132) {
        cudaFuncSetAttribute(fused_kernel<true>, cudaFuncAttributeMaxDynamicSharedMemorySize, SM_TOTAL);
        fused_kernel<true><<<132, 384, SM_TOTAL>>>(scp, wo, w1, b1, w2, b2, tx, twqkv, two64, two48, tw1, tw2, txr64, txr48, tout64, tout48);
    } else {
        cudaFuncSetAttribute(fused_kernel<false>, cudaFuncAttributeMaxDynamicSharedMemorySize, SM_TOTAL);
        fused_kernel<false><<<132, 384, SM_TOTAL>>>(scp, wo, w1, b1, w2, b2, tx, twqkv, two64, two48, tw1, tw2, txr64, txr48, tout64, tout48);
    }
}
```

```cpp
#include <cuda_runtime.h>
#include <cuda_bf16.h>
#include <cuda.h>
#include <stdint.h>

namespace {

constexpr int D_ = 448;
constexpr float LN_EPS = 1e-5f;
constexpr float LOG2E_SCALE = 0.1889822365046136f * 1.4426950408889634f;

struct Tiles {
    uint32_t o[32 * 57344 / 4];
    uint32_t hn[4 * 32 * 14336 / 4];
    uint32_t u[4 * 28 * 14336 / 4];
};
struct Scratch {
    uint4 halo[128 * 2 * 2 * 3 * 32];
    uint4 stats[32 * 4 * 64];
    uint4 hint_k[128 * 2];
    uint4 hint_o[32 * 32 * 2];
    uint4 hint_h[4 * 32 * 2];
    uint4 hint_u[128 * 2];
    uint4 go[24];
    uint32_t epoch[160];
    uint32_t clean;
    alignas(1024) Tiles tiles[2];
};
__device__ Scratch g_scratch;
#define STAMP(i) do {} while (0)
#define FST(i) do {} while (0)
#define TSARG
#define TSVAL

constexpr uint32_t SB = 1024;
constexpr int SM_SLOT = 16384;
__device__ __forceinline__ constexpr uint32_t slot_x(int kb) { return (kb ? 6 + kb : 0) * SM_SLOT; }
__device__ __forceinline__ constexpr uint32_t slot_kv(int kb) { return (kb < 5 ? 2 + kb : 6 - kb) * SM_SLOT; }
__device__ __forceinline__ constexpr uint32_t slot_wo(int kb) { return (kb < 6 ? 2 + kb : 12) * SM_SLOT; }
constexpr int SM_QO = 8 * SM_SLOT;
constexpr int SM_HALOK = SM_QO + 57344, SM_HALOV = 1 * SM_SLOT;
constexpr int NA_SLOTS = 6, NB_SLOTS = 8;
constexpr int SM_ARING = 0;
constexpr int SM_BRING = NA_SLOTS * 16384;
constexpr int SM_H = 212992;
__device__ __forceinline__ uint32_t halo_kin(int par, int lane) { return SB + SM_H + 8192 + par * 4096 + lane * 128 + ((~lane & 6) << 4); }
constexpr int SM_BAR = 229376;
constexpr int SM_TAG = SM_BAR + 1536;
constexpr int SM_TIME = SM_TAG + 256;
constexpr int SM_TOTAL = SM_TIME + 256;
constexpr int B_FULLX = 0;
constexpr int B_FULLKV = 7;
constexpr int B_FQ = 14;
constexpr int B_DONE1 = 16;
constexpr int B_DONEX = 23;
constexpr int B_DONEQ = 24;
constexpr int B_DONEO = 25;
constexpr int B_FULLO = 29;
constexpr int B_FULLWO = 33;
constexpr int B_END = 34;
constexpr int B_HALO = 35;
constexpr int B_FULLA = 39;
constexpr int B_FULLB = 55;
constexpr int B_DONE = 87;
constexpr int B_GO = 119;
constexpr int B_CLR = 121;
constexpr int SM_RAW = SM_BAR + 8 * 124;

constexpr long long WD_CLKS = 2000000000ll;

template<int N> struct Int { static constexpr int value = N; };
template<int A, int B, class F> __device__ __forceinline__ void static_for(F&& f) { if constexpr (A < B) { f(Int<A>()); static_for<A + 1, B>(f); } }

__device__ __forceinline__ uint32_t smem_u32(const void* p) { return (uint32_t)__cvta_generic_to_shared(p); }
__device__ __forceinline__ void mbar_init(uint32_t bar, uint32_t cnt) { asm volatile("mbarrier.init.shared::cta.b64 [%0], %1;" :: "r"(bar), "r"(cnt) : "memory"); }
__device__ __forceinline__ void mbar_expect(uint32_t bar, uint32_t bytes) { asm volatile("mbarrier.arrive.expect_tx.shared::cta.b64 _, [%0], %1;" :: "r"(bar), "r"(bytes) : "memory"); }
__device__ __forceinline__ void mbar_arrive(uint32_t bar) { asm volatile("mbarrier.arrive.shared::cta.b64 _, [%0];" :: "r"(bar) : "memory"); }
__device__ __forceinline__ bool mbar_try(uint32_t bar, uint32_t parity) {
    uint32_t ok;
    asm volatile("{\n.reg .pred p;\nmbarrier.try_wait.parity.shared::cta.b64 p, [%1], %2;\nselp.u32 %0, 1, 0, p;\n}" : "=r"(ok) : "r"(bar), "r"(parity) : "memory");
    return ok;
}
__device__ __forceinline__ bool mbar_test(uint32_t bar, uint32_t parity) {
    uint32_t ok;
    asm volatile("{\n.reg .pred p;\nmbarrier.test_wait.parity.shared::cta.b64 p, [%1], %2;\nselp.u32 %0, 1, 0, p;\n}" : "=r"(ok) : "r"(bar), "r"(parity) : "memory");
    return ok;
}
__device__ __forceinline__ void mbar_wait(uint32_t bar, uint32_t parity) {
    asm volatile("{\n.reg .pred p;\n"
                 "WAIT_LOOP:\n"
                 "mbarrier.try_wait.parity.shared::cta.b64 p, [%0], %1;\n"
                 "@!p bra WAIT_LOOP;\n}" :: "r"(bar), "r"(parity) : "memory");
}
__device__ __forceinline__ void mbar_wait_unless(uint32_t ready, uint32_t bar, uint32_t parity) {
    asm volatile("{\n.reg .pred p;\nsetp.ne.u32 p, %1, 0;\n@p bra.uni DONE;\n"
                 "WAIT_LOOP:\n"
                 "mbarrier.try_wait.parity.shared::cta.b64 p, [%0], %2;\n"
                 "@!p bra.uni WAIT_LOOP;\nDONE:\n}" :: "r"(bar), "r"(ready), "r"(parity) : "memory");
}
__device__ __forceinline__ void mbar_wait_wd(uint32_t bar, uint32_t parity) {
    asm volatile("{\n.reg .pred p, q;\n.reg .u32 s, t;\nmov.u32 s, %%clock;\n"
                 "WAIT_LOOP:\n"
                 "mbarrier.try_wait.parity.shared::cta.b64 p, [%0], %1;\nmov.u32 t, %%clock;\nsub.u32 t, t, s;\nsetp.lt.and.s32 q, t, 0, !p;\n@q trap;\n"
                 "@!p bra WAIT_LOOP;\n}" :: "r"(bar), "r"(parity) : "memory");
}
__device__ __forceinline__ bool elect() { uint32_t p; asm volatile("{\n.reg .pred P;\nelect.sync _|P, 0xffffffff;\nselp.u32 %0, 1, 0, P;\n}" : "=r"(p)); return p; }
__device__ __forceinline__ void tma2d(uint32_t dst, const CUtensorMap* tm, int c0, int c1, uint32_t bar) {
    asm volatile("cp.async.bulk.tensor.2d.shared::cluster.global.mbarrier::complete_tx::bytes [%0], [%1, {%3, %4}], [%2];" :: "r"(dst), "l"(tm), "r"(bar), "r"(c0), "r"(c1) : "memory");
}
__device__ __forceinline__ void tma3d(uint32_t dst, const CUtensorMap* tm, int c0, int c1, int c2, uint32_t bar) {
    asm volatile("cp.async.bulk.tensor.3d.shared::cluster.global.mbarrier::complete_tx::bytes [%0], [%1, {%3, %4, %5}], [%2];" :: "r"(dst), "l"(tm), "r"(bar), "r"(c0), "r"(c1), "r"(c2) : "memory");
}
__device__ __forceinline__ void tma5d(uint32_t dst, const CUtensorMap* tm, int c0, int c3, int c4, uint32_t bar) {
    asm volatile("cp.async.bulk.tensor.5d.shared::cluster.global.mbarrier::complete_tx::bytes [%0], [%1, {%3, 0, 0, %4, %5}], [%2];" :: "r"(dst), "l"(tm), "r"(bar), "r"(c0), "r"(c3), "r"(c4) : "memory");
}
__device__ __forceinline__ void tma5d_prefetch(const CUtensorMap* tm, int c0, int c3, int c4) {
    asm volatile("cp.async.bulk.prefetch.tensor.5d.L2.global [%0, {%1, 0, 0, %2, %3}];" :: "l"(tm), "r"(c0), "r"(c3), "r"(c4) : "memory");
}
__device__ __forceinline__ void tma2d_store(const CUtensorMap* tm, int c0, int c1, uint32_t src) {
    asm volatile("cp.async.bulk.tensor.2d.global.shared::cta.bulk_group [%0, {%2, %3}], [%1];" :: "l"(tm), "r"(src), "r"(c0), "r"(c1) : "memory");
}
__device__ __forceinline__ void bulk_st(void* dst, uint32_t src, uint32_t bytes) {
    asm volatile("cp.async.bulk.global.shared::cta.bulk_group [%0], [%1], %2;" :: "l"(dst), "r"(src), "r"(bytes) : "memory");
}
__device__ __forceinline__ void bulk_ld(uint32_t dst, const void* src, uint32_t bytes, uint32_t bar) {
    asm volatile("cp.async.bulk.shared::cluster.global.mbarrier::complete_tx::bytes [%0], [%1], %2, [%3];" :: "r"(dst), "l"(src), "r"(bytes), "r"(bar) : "memory");
}
__device__ __forceinline__ void bulk_prefetch(const void* src, uint32_t bytes) { asm volatile("cp.async.bulk.prefetch.L2.global [%0], %1;" :: "l"(src), "r"(bytes) : "memory"); }
__device__ __forceinline__ void prefetch_map(const CUtensorMap* tm) { asm volatile("prefetch.tensormap [%0];" :: "l"(tm) : "memory"); }
__device__ __forceinline__ void st_global_if(uint32_t c, uint32_t* p, uint32_t v) {
    asm volatile("{\n.reg .pred p;\nsetp.ne.u32 p, %2, 0;\n@p st.global.u32 [%0], %1;\n}" :: "l"(p), "r"(v), "r"(c) : "memory");
}
__device__ __forceinline__ void st_relaxed4_if(bool c, uint4* p, uint32_t a, uint32_t b, uint32_t d) {
    asm volatile("{\n.reg .b128 t;\n.reg .b64 a, b;\n.reg .pred p;\nsetp.ne.u32 p, %4, 0;\nmov.b64 a, {%1, %2};\nmov.b64 b, {%3, %3};\nmov.b128 t, {a, b};\n@p st.relaxed.gpu.global.b128 [%0], t;\n}" :: "l"(p), "r"(a), "r"(b), "r"(d), "r"((uint32_t)c) : "memory");
}
__device__ __forceinline__ void pin_ptr(uint32_t never, const void* a) {
    asm volatile("{\n.reg .pred p;\nsetp.ne.u32 p, %1, 0;\n@p st.shared.u64 [%1], %0;\n}" :: "l"(a), "r"(never) : "memory");
}
__device__ __forceinline__ void pin4(uint32_t never, float a, float b, float c, float d) {
    asm volatile("{\n.reg .pred p;\nsetp.ne.u32 p, %4, 0;\n@p st.shared.v4.f32 [%4], {%0,%1,%2,%3};\n}" :: "f"(a), "f"(b), "f"(c), "f"(d), "r"(never) : "memory");
}
__device__ __forceinline__ void fence_async_smem() { asm volatile("fence.proxy.async.shared::cta;" ::: "memory"); }
__device__ __forceinline__ uint32_t ld_acquire(const void* p) { uint32_t v; asm volatile("ld.acquire.gpu.global.u32 %0, [%1];" : "=r"(v) : "l"(p) : "memory"); return v; }
__device__ __forceinline__ void st_release(void* p, uint32_t v) { asm volatile("st.release.gpu.global.u32 [%0], %1;" :: "l"(p), "r"(v) : "memory"); }
__device__ __forceinline__ uint32_t ld_relaxed(const void* p) { uint32_t v; asm volatile("ld.relaxed.gpu.global.u32 %0, [%1];" : "=r"(v) : "l"(p) : "memory"); return v; }
__device__ __forceinline__ uint2 ld_relaxed2(const void* p) {
    uint2 v; asm volatile("{\n.reg .b64 a;\nld.relaxed.gpu.global.b64 a, [%2];\nmov.b64 {%0, %1}, a;\n}" : "=r"(v.x), "=r"(v.y) : "l"(p) : "memory"); return v;
}
__device__ __forceinline__ void st_relaxed2(void* p, uint32_t a, uint32_t b) {
    asm volatile("{\n.reg .b64 a;\nmov.b64 a, {%1, %2};\nst.relaxed.gpu.global.b64 [%0], a;\n}" :: "l"(p), "r"(a), "r"(b) : "memory");
}
__device__ __forceinline__ uint4 ld_relaxed4(const uint4* p) {
    uint4 v;
    asm volatile("{\n.reg .b128 t;\n.reg .b64 a, b;\nld.relaxed.gpu.global.b128 t, [%4];\nmov.b128 {a, b}, t;\nmov.b64 {%0, %1}, a;\nmov.b64 {%2, %3}, b;\n}" : "=r"(v.x), "=r"(v.y), "=r"(v.z), "=r"(v.w) : "l"(p) : "memory");
    return v;
}
__device__ __forceinline__ void st_relaxed4(uint4* p, uint32_t a, uint32_t b, uint32_t c, uint32_t d) {
    asm volatile("{\n.reg .b128 t;\n.reg .b64 a, b;\nmov.b64 a, {%1, %2};\nmov.b64 b, {%3, %4};\nmov.b128 t, {a, b};\nst.relaxed.gpu.global.b128 [%0], t;\n}" :: "l"(p), "r"(a), "r"(b), "r"(c), "r"(d) : "memory");
}
__device__ __forceinline__ uint32_t ld_u16(const unsigned short* p) { uint32_t v; asm volatile("ld.volatile.global.u16 %0, [%1];" : "=r"(v) : "l"(p) : "memory"); return v; }
__device__ __forceinline__ uint32_t ld_volatile(const uint32_t* p) { uint32_t v; asm volatile("ld.volatile.global.u32 %0, [%1];" : "=r"(v) : "l"(p) : "memory"); return v; }
__device__ __forceinline__ void named_arrive(int id, int n) { asm volatile("bar.arrive %0, %1;" :: "r"(id), "r"(n) : "memory"); }
__device__ __forceinline__ void named_sync(int id, int n) { asm volatile("bar.sync %0, %1;" :: "r"(id), "r"(n) : "memory"); }
__device__ __forceinline__ void named_arrive_if(uint32_t c, int id, int n) { asm volatile("{\n.reg .pred p;\nsetp.ne.u32 p, %2, 0;\n@p bar.arrive %0, %1;\n}" :: "r"(id), "r"(n), "r"(c) : "memory"); }
__device__ __forceinline__ bool named_any(int id, int n, bool v) {
    uint32_t r; asm volatile("{\n.reg .pred p, q;\nsetp.ne.u32 p, %3, 0;\nbar.red.or.pred q, %1, %2, p;\nselp.u32 %0, 1, 0, q;\n}" : "=r"(r) : "r"(id), "r"(n), "r"((uint32_t)v) : "memory"); return r;
}
__device__ __forceinline__ void wg_fence() { asm volatile("wgmma.fence.sync.aligned;" ::: "memory"); }
__device__ __forceinline__ void wg_commit() { asm volatile("wgmma.commit_group.sync.aligned;" ::: "memory"); }
template<int N> __device__ __forceinline__ void wg_wait() { asm volatile("wgmma.wait_group.sync.aligned %0;" :: "n"(N) : "memory"); }
template<int N> __device__ __forceinline__ void reg_fence(float (&d)[N]) {
    #pragma unroll
    for (int i = 0; i < N; i++) asm volatile("" : "+f"(d[i]) :: "memory");
}
__device__ __forceinline__ constexpr uint64_t mkdesc(uint32_t addr, uint32_t lbo, uint32_t sbo, uint32_t sw) {
    return (uint64_t)((addr & 0x3FFFF) >> 4) | ((uint64_t)(lbo >> 4) << 16) | ((uint64_t)(sbo >> 4) << 32) | ((uint64_t)sw << 62);
}
__device__ __forceinline__ void ldsm4(uint32_t (&r)[4], uint32_t addr) {
    asm volatile("ldmatrix.sync.aligned.m8n8.x4.shared.b16 {%0,%1,%2,%3}, [%4];" : "=r"(r[0]), "=r"(r[1]), "=r"(r[2]), "=r"(r[3]) : "r"(addr) : "memory");
}
__device__ __forceinline__ void stsm4(uint32_t addr, uint32_t r0, uint32_t r1, uint32_t r2, uint32_t r3) {
    asm volatile("stmatrix.sync.aligned.m8n8.x4.shared.b16 [%0], {%1,%2,%3,%4};" :: "r"(addr), "r"(r0), "r"(r1), "r"(r2), "r"(r3) : "memory");
}
__device__ __forceinline__ void sts4(uint32_t a, uint32_t x, uint32_t y, uint32_t z, uint32_t w) { asm volatile("st.shared.v4.u32 [%0], {%1,%2,%3,%4};" :: "r"(a), "r"(x), "r"(y), "r"(z), "r"(w) : "memory"); }
__device__ __forceinline__ uint4 lds4(uint32_t a) { uint4 v; asm volatile("ld.shared.v4.u32 {%0,%1,%2,%3}, [%4];" : "=r"(v.x), "=r"(v.y), "=r"(v.z), "=r"(v.w) : "r"(a) : "memory"); return v; }
__device__ __forceinline__ uint32_t movtrans(uint32_t a) { uint32_t d; asm volatile("movmatrix.sync.aligned.m8n8.trans.b16 %0, %1;" : "=r"(d) : "r"(a)); return d; }
__device__ __forceinline__ uint32_t pack_bf16(float lo, float hi) { uint32_t r; asm("cvt.rn.bf16x2.f32 %0, %1, %2;" : "=r"(r) : "f"(hi), "f"(lo)); return r; }
__device__ __forceinline__ void sub_bf16x2(uint32_t& a, uint32_t b) { asm volatile("sub.rn.bf16x2 %0, %0, %1;" : "+r"(a) : "r"(b)); }
__device__ __forceinline__ float bf_lo(uint32_t v) { return __uint_as_float(v << 16); }
__device__ __forceinline__ float bf_hi(uint32_t v) { return __uint_as_float(v & 0xffff0000u); }
__device__ __forceinline__ void mma16816(float (&c)[4], uint32_t a0, uint32_t a1, uint32_t a2, uint32_t a3, uint32_t b0, uint32_t b1) {
    asm volatile("mma.sync.aligned.m16n8k16.row.col.f32.bf16.bf16.f32 {%0,%1,%2,%3}, {%4,%5,%6,%7}, {%8,%9}, {%0,%1,%2,%3};"
        : "+f"(c[0]), "+f"(c[1]), "+f"(c[2]), "+f"(c[3]) : "r"(a0), "r"(a1), "r"(a2), "r"(a3), "r"(b0), "r"(b1));
}
__device__ __forceinline__ void mma1688(float (&c)[4], uint32_t a0, uint32_t a1, uint32_t b0) {
    asm volatile("mma.sync.aligned.m16n8k8.row.col.f32.bf16.bf16.f32 {%0,%1,%2,%3}, {%4,%5}, {%6}, {%0,%1,%2,%3};"
        : "+f"(c[0]), "+f"(c[1]), "+f"(c[2]), "+f"(c[3]) : "r"(a0), "r"(a1), "r"(b0));
}
__device__ __forceinline__ float quad_sum(float v) { v += __shfl_xor_sync(0xffffffffu, v, 1); v += __shfl_xor_sync(0xffffffffu, v, 2); return v; }
__device__ __forceinline__ float quad_max(float v) { v = fmaxf(v, __shfl_xor_sync(0xffffffffu, v, 1)); v = fmaxf(v, __shfl_xor_sync(0xffffffffu, v, 2)); return v; }
__device__ __forceinline__ float ex2(float x) { float y; asm("ex2.approx.ftz.f32 %0, %1;" : "=f"(y) : "f"(x)); return y; }
__device__ __forceinline__ float rsqrt_approx(float x) { float y; asm("rsqrt.approx.ftz.f32 %0, %1;" : "=f"(y) : "f"(x)); return y; }
__device__ __forceinline__ float rcp_approx(float x) { float y; asm("rcp.approx.ftz.f32 %0, %1;" : "=f"(y) : "f"(x)); return y; }
constexpr float GELU_K1 = 2.f * 0.7978845608028654f;
__device__ __forceinline__ float gelu_half(float hx, float k1) {
    const float z = hx * fmaf(hx * hx, 8.f * 0.044715f * 0.7978845608028654f, k1);
    float t; asm("tanh.approx.f32 %0, %1;" : "=f"(t) : "f"(z));
    return fmaf(hx, t, hx);
}
__device__ __forceinline__ uint32_t gtime32() { uint64_t t; asm volatile("mov.u64 %0, %%globaltimer;" : "=l"(t)); return (uint32_t)t; }
__device__ __forceinline__ uint32_t clock32() { uint32_t t; asm volatile("mov.u32 %0, %%clock;" : "=r"(t)); return t; }
#define PF_PACE 160
#define PF_AT 14500
#define PF_N 240
#define NSQ 6
#define NPIPE 2
#define HALO_AT 3
#define HINT_U 18
#define HINT_E 16
#define SP_AT 2000
#define A_SCHED 0x322188
#define WO_ORD0 0x4321065
#define WO_ORD1 0x3465210
#define CL_AT 23
#define WARM_AT 300
#define GO_H 1600
#define GO_E 1950
#define GO_U 2050
#define GO_O 1312
#define LATE_O 256
#define LATE_AT 0
#define LATE_AT4 0
#define SLACK 0
#define GDEP 4
#define START4 30
#define NE_SLOTS 11
#define POLL_E 26
#define AE_END 18
#define AE_W2 27
#define PF1_AT 11000
#define PF1_N 80
#define PF1_PACE 160
#define GO_E2 300
#define GO_U2 400
#define POLL_I 20
#define POLL_N 19
#define ROLES 0x65431027u
#define A4_FROM 23
#define A4_DLY 2
#define SPIN_N 3
#define STOP2 150
#define PF0_AT 4500
#define PF0_N 48
#define PF0_PACE 140
#define POLL_H 3
#define CH_H 8
#define HINT_F 4
#define CL_N 4
#define CL_P2 7
#define STOP3 3
#define PF_OFS 0
#define PFC_AT 0
#define PFC_E 0
#define PFC_N 16
#define PFW_AT 6
#define PFW_0 10
#define PFW_N 14
template<int TB> __device__ __forceinline__ void wgmma_rs56(float (&d)[28], const uint32_t (&a)[4], uint64_t db, int sc) {
    asm volatile("{\n.reg .pred p;\nsetp.ne.b32 p, %33, 0;\n"
        "wgmma.mma_async.sync.aligned.m64n56k16.f32.bf16.bf16 {%0, %1, %2, %3, %4, %5, %6, %7, %8, %9, %10, %11, %12, %13, %14, %15, %16, %17, %18, %19, %20, %21, %22, %23, %24, %25, %26, %27}, {%28, %29, %30, %31}, %32, p, 1, 1, %34;\n}\n"
        : "+f"(d[0]), "+f"(d[1]), "+f"(d[2]), "+f"(d[3]), "+f"(d[4]), "+f"(d[5]), "+f"(d[6]), "+f"(d[7]), "+f"(d[8]), "+f"(d[9]), "+f"(d[10]), "+f"(d[11]), "+f"(d[12]), "+f"(d[13]), "+f"(d[14]), "+f"(d[15]), "+f"(d[16]), "+f"(d[17]), "+f"(d[18]), "+f"(d[19]), "+f"(d[20]), "+f"(d[21]), "+f"(d[22]), "+f"(d[23]), "+f"(d[24]), "+f"(d[25]), "+f"(d[26]), "+f"(d[27])
        : "r"(a[0]), "r"(a[1]), "r"(a[2]), "r"(a[3]), "l"(db), "r"(sc), "n"(TB));
}

template<int TA, int TB, int SC = 1> __device__ __forceinline__ void wgmma_ss112(float (&d)[56], uint64_t da, uint64_t db) {
    asm volatile("wgmma.mma_async.sync.aligned.m64n112k16.f32.bf16.bf16 {%0, %1, %2, %3, %4, %5, %6, %7, %8, %9, %10, %11, %12, %13, %14, %15, %16, %17, %18, %19, %20, %21, %22, %23, %24, %25, %26, %27, %28, %29, %30, %31, %32, %33, %34, %35, %36, %37, %38, %39, %40, %41, %42, %43, %44, %45, %46, %47, %48, %49, %50, %51, %52, %53, %54, %55}, %56, %57, %60, 1, 1, %58, %59;\n"
        : "+f"(d[0]), "+f"(d[1]), "+f"(d[2]), "+f"(d[3]), "+f"(d[4]), "+f"(d[5]), "+f"(d[6]), "+f"(d[7]), "+f"(d[8]), "+f"(d[9]), "+f"(d[10]), "+f"(d[11]), "+f"(d[12]), "+f"(d[13]), "+f"(d[14]), "+f"(d[15]), "+f"(d[16]), "+f"(d[17]), "+f"(d[18]), "+f"(d[19]), "+f"(d[20]), "+f"(d[21]), "+f"(d[22]), "+f"(d[23]), "+f"(d[24]), "+f"(d[25]), "+f"(d[26]), "+f"(d[27]), "+f"(d[28]), "+f"(d[29]), "+f"(d[30]), "+f"(d[31]), "+f"(d[32]), "+f"(d[33]), "+f"(d[34]), "+f"(d[35]), "+f"(d[36]), "+f"(d[37]), "+f"(d[38]), "+f"(d[39]), "+f"(d[40]), "+f"(d[41]), "+f"(d[42]), "+f"(d[43]), "+f"(d[44]), "+f"(d[45]), "+f"(d[46]), "+f"(d[47]), "+f"(d[48]), "+f"(d[49]), "+f"(d[50]), "+f"(d[51]), "+f"(d[52]), "+f"(d[53]), "+f"(d[54]), "+f"(d[55])
        : "l"(da), "l"(db), "n"(TA), "n"(TB), "n"(SC));
}

template<int TA, int TB, int SC = 1> __device__ __forceinline__ void wgmma_ss80(float (&d)[40], uint64_t da, uint64_t db) {
    asm volatile("wgmma.mma_async.sync.aligned.m64n80k16.f32.bf16.bf16 {%0, %1, %2, %3, %4, %5, %6, %7, %8, %9, %10, %11, %12, %13, %14, %15, %16, %17, %18, %19, %20, %21, %22, %23, %24, %25, %26, %27, %28, %29, %30, %31, %32, %33, %34, %35, %36, %37, %38, %39}, %40, %41, %44, 1, 1, %42, %43;\n"
        : "+f"(d[0]), "+f"(d[1]), "+f"(d[2]), "+f"(d[3]), "+f"(d[4]), "+f"(d[5]), "+f"(d[6]), "+f"(d[7]), "+f"(d[8]), "+f"(d[9]), "+f"(d[10]), "+f"(d[11]), "+f"(d[12]), "+f"(d[13]), "+f"(d[14]), "+f"(d[15]), "+f"(d[16]), "+f"(d[17]), "+f"(d[18]), "+f"(d[19]), "+f"(d[20]), "+f"(d[21]), "+f"(d[22]), "+f"(d[23]), "+f"(d[24]), "+f"(d[25]), "+f"(d[26]), "+f"(d[27]), "+f"(d[28]), "+f"(d[29]), "+f"(d[30]), "+f"(d[31]), "+f"(d[32]), "+f"(d[33]), "+f"(d[34]), "+f"(d[35]), "+f"(d[36]), "+f"(d[37]), "+f"(d[38]), "+f"(d[39])
        : "l"(da), "l"(db), "n"(TA), "n"(TB), "n"(SC));
}

template<int TA, int TB, int SC = 1> __device__ __forceinline__ void wgmma_ss64(float (&d)[32], uint64_t da, uint64_t db) {
    asm volatile("wgmma.mma_async.sync.aligned.m64n64k16.f32.bf16.bf16 {%0, %1, %2, %3, %4, %5, %6, %7, %8, %9, %10, %11, %12, %13, %14, %15, %16, %17, %18, %19, %20, %21, %22, %23, %24, %25, %26, %27, %28, %29, %30, %31}, %32, %33, %36, 1, 1, %34, %35;\n"
        : "+f"(d[0]), "+f"(d[1]), "+f"(d[2]), "+f"(d[3]), "+f"(d[4]), "+f"(d[5]), "+f"(d[6]), "+f"(d[7]), "+f"(d[8]), "+f"(d[9]), "+f"(d[10]), "+f"(d[11]), "+f"(d[12]), "+f"(d[13]), "+f"(d[14]), "+f"(d[15]), "+f"(d[16]), "+f"(d[17]), "+f"(d[18]), "+f"(d[19]), "+f"(d[20]), "+f"(d[21]), "+f"(d[22]), "+f"(d[23]), "+f"(d[24]), "+f"(d[25]), "+f"(d[26]), "+f"(d[27]), "+f"(d[28]), "+f"(d[29]), "+f"(d[30]), "+f"(d[31])
        : "l"(da), "l"(db), "n"(TA), "n"(TB), "n"(SC));
}

template<int TA, int TB, int SC = 1> __device__ __forceinline__ void wgmma_ss48(float (&d)[24], uint64_t da, uint64_t db) {
    asm volatile("wgmma.mma_async.sync.aligned.m64n48k16.f32.bf16.bf16 {%0, %1, %2, %3, %4, %5, %6, %7, %8, %9, %10, %11, %12, %13, %14, %15, %16, %17, %18, %19, %20, %21, %22, %23}, %24, %25, %28, 1, 1, %26, %27;\n"
        : "+f"(d[0]), "+f"(d[1]), "+f"(d[2]), "+f"(d[3]), "+f"(d[4]), "+f"(d[5]), "+f"(d[6]), "+f"(d[7]), "+f"(d[8]), "+f"(d[9]), "+f"(d[10]), "+f"(d[11]), "+f"(d[12]), "+f"(d[13]), "+f"(d[14]), "+f"(d[15]), "+f"(d[16]), "+f"(d[17]), "+f"(d[18]), "+f"(d[19]), "+f"(d[20]), "+f"(d[21]), "+f"(d[22]), "+f"(d[23])
        : "l"(da), "l"(db), "n"(TA), "n"(TB), "n"(SC));
}

template<int NKB, int NR>
__device__ __forceinline__ void mix_mainloop(TSARG float (&acc)[NR], bool leader) {
    constexpr uint32_t sb = SB, bars = sb + SM_BAR, par = NKB == 28;
    constexpr int A0 = NKB == 32 ? 0 : 16 % NA_SLOTS;
    constexpr int DEPTH = NR == 56 ? 1 : 2;
    int bslot = 0, aslot = A0;
    reg_fence(acc);
    #pragma unroll 1
    for (int i = 0; i < NKB / 2; i++) {
        mbar_wait(bars + 8 * (B_FULLA + i), par);
        const uint64_t adesc = mkdesc(sb + SM_ARING, 8192, 1024, 1) + (uint32_t)(aslot * 1024);
        aslot = aslot == NA_SLOTS - 1 ? 0 : aslot + 1;
        #pragma unroll
        for (int jj = 0; jj < 2; jj++) {
            const int j = 2 * i + jj;
            mbar_wait(bars + 8 * (B_FULLB + j), par);
            const uint64_t bdesc = mkdesc(sb + SM_BRING, 128, 1024, 0) + (uint32_t)(bslot * NR * 16);
            bslot = bslot == (NR == 56 ? NB_SLOTS : NE_SLOTS) - 1 ? 0 : bslot + 1;
            wg_fence();
            #pragma unroll
            for (int s = 0; s < 4; s++) {
                if constexpr (NR == 56) wgmma_ss112<1, 1>(acc, adesc + jj * 512 + s * 128, bdesc + s * 16);
                else wgmma_ss80<1, 1>(acc, adesc + jj * 512 + s * 128, bdesc + s * 16);
            }
            wg_commit();
            wg_wait<DEPTH>();
            if (j >= DEPTH && leader) mbar_arrive(bars + 8 * (B_DONE + j - DEPTH));
        }
    }
    if (DEPTH == 2) { wg_wait<1>(); if (leader) mbar_arrive(bars + 8 * (B_DONE + NKB - 2)); }
    wg_wait<0>();
    reg_fence(acc);
    if (leader) mbar_arrive(bars + 8 * (B_DONE + NKB - 1));
}

__device__ __forceinline__ void spin_mma(uint32_t bar, uint32_t never) {
    float d[56];
    #pragma unroll
    for (int i = 0; i < 56; i++) d[i] = 0.f;
    reg_fence(d);
    #pragma unroll 1
    do {
        wg_fence();
        #pragma unroll
        for (int s = 0; s < SPIN_N; s++) wgmma_ss112<1, 1>(d, mkdesc(SB + 2 * SM_SLOT + s * 2048, 8192, 1024, 1), mkdesc(SB + 3 * SM_SLOT + s * 256, 128, 1024, 0));
        wg_commit();
        wg_wait<1>();
    } while (!named_any(11, 128, mbar_test(bar, 1)));
    wg_wait<0>();
    reg_fence(d);
    pin4(never, d[0], d[1], d[2], d[3]);
}

constexpr uint32_t EMPTY = 0xFFFFFFFFu;
__device__ __forceinline__ void post_hint(uint4* p, uint32_t ep, int lane) { if (lane < 2) st_relaxed4(p + lane, ep, ep, ep, ep); }
__device__ __forceinline__ void post_time(uint4* p, uint32_t ep, int lane) { const uint32_t now = gtime32(); if (lane < 2) st_relaxed4(p + lane, ep, now, ep, now); }

__device__ __forceinline__ uint32_t last_hint(TSARG const uint4* hint, uint32_t ep, int st) {
    uint2 v;
    do { v = ld_relaxed2(hint); } while (!__all_sync(0xffffffffu, v.x == ep));
    const uint32_t t1 = gtime32() + 256;
    if (elect()) STAMP(st);
    return t1 - __reduce_min_sync(0xffffffffu, t1 - v.y);
}
__device__ __forceinline__ uint32_t later(uint32_t a, uint32_t b) { return a + max((int)(b - a), 0); }
__device__ __forceinline__ void fetch_times(TSARG const uint4* go, int k, uint32_t ep, int lane) {
    const uint2* p = (const uint2*)(go + 8 + 8 * k) + (k ? lane % 10 : lane & 3);
    uint2 v;
    do { v = ld_relaxed2(p); } while (!__all_sync(0xffffffffu, v.x == ep));
    v.y += k ? (lane < 10 ? GO_U : GO_U + GO_U2) : (lane < 4 ? GO_E : GO_E + GO_E2);
    asm volatile("st.shared.u32 [%0], %1;" :: "r"(SB + SM_TIME + 128 * k + 4 * lane), "r"(v.y) : "memory");
    __syncwarp();
    if (lane == 0) { mbar_arrive(SB + SM_BAR + 8 * (B_GO + k)); STAMP(k ? 43 : 24); }
    __syncwarp();
}
__device__ __forceinline__ void wait_until(uint32_t t) {
    asm volatile("{\n.reg .pred p;\n.reg .u64 a;\n.reg .u32 l, h;\nWAIT_LOOP:\nmov.u64 a, %%globaltimer;\nmov.b64 {l, h}, a;\nsub.u32 l, l, %0;\nsetp.lt.s32 p, l, 0;\n@p bra.uni WAIT_LOOP;\n}" :: "r"(t) : "memory");
}

__device__ __forceinline__ uint32_t check_tile(uint32_t raw, uint32_t full, uint32_t dst, uint32_t lofs, const uint32_t* src, uint32_t bytes, int lane) {
    uint32_t cnt;
    asm volatile("{\n.reg .pred p, e;\n.reg .u32 a, b, c, d;\nmov.u32 %0, 0;\n"
                 "AGAIN:\nand.b32 a, %0, 1;\n"
                 "WAIT:\nmbarrier.try_wait.parity.shared::cta.b64 p, [%1], a;\n@!p bra.uni WAIT;\n"
                 "ld.shared.u32 a, [%4];\nld.shared.u32 b, [%4+4096];\nld.shared.u32 c, [%5+-8192];\nld.shared.u32 d, [%5+-4096];\n"
                 "add.u32 %0, %0, 1;\nmax.u32 a, a, b;\nmax.u32 c, c, d;\nmax.u32 a, a, c;\nsetp.lt.u32 e, %8, 32;\nsetp.eq.and.u32 p, a, 0xFFFFFFFF, e;\n"
                 "vote.sync.any.pred p, p, 0xffffffff;\nsetp.eq.and.u32 e, %8, 0, !p;\n@e mbarrier.arrive.shared::cta.b64 _, [%2];\n"
                 "elect.sync _|e, 0xffffffff;\nand.pred e, e, p;\n"
                 "@e mbarrier.arrive.expect_tx.shared::cta.b64 _, [%1], %7;\n"
                 "@e cp.async.bulk.shared::cluster.global.mbarrier::complete_tx::bytes [%3], [%6], %7, [%1];\n"
                 "@p bra.uni AGAIN;\n}"
                 : "=&r"(cnt) : "r"(raw), "r"(full), "r"(dst), "r"(dst + lofs), "r"(dst + lofs + bytes), "l"(src), "r"(bytes), "r"(lane) : "memory");
    return cnt;
}

template<int ST>
__device__ __forceinline__ void check_tiles(int j, int step, int n, const uint32_t* src, bool small, int lane, bool dry) {
    const uint32_t bytes = small ? 10240 : 14336, nb = small ? NE_SLOTS : NB_SLOTS, lofs = lane * 128 + (lane & 3) * 32 + (lane >> 2) * 4;
    uint32_t sl = j % nb;
    #pragma unroll 1
    for (int inc = dry ? 0 : step; j < n; j += inc, inc = step) {
        const uint32_t c = check_tile(inc ? SB + SM_RAW + 8 * (j + (ST ? 32 * ST - 28 : 0)) : SB + SM_BAR + 8 * B_CLR, SB + SM_BAR + 8 * (j + (ST ? B_FULLB : B_FULLO)),
                                      SB + (ST ? SM_BRING + sl * bytes : SM_QO + max(2 * j - 1, 0) * 8192), lofs, src + (ST ? j * 7168 : max(2 * j - 1, 0) * 2048),
                                      ST ? bytes : j ? 16384 : 8192, inc ? lane : 32);
        sl += inc;
        if (sl >= nb) sl -= nb;
    }
}

__device__ __forceinline__ uint32_t hcol(uint32_t a, int jp) { return (a ^ ((jp & 3) << 5)) + (jp >> 2) * 8192; }

__device__ __forceinline__ uint32_t get_tag() {
    mbar_wait(SB + SM_BAR + 8 * B_CLR, 0);
    uint32_t v; asm volatile("ld.shared.u32 %0, [%1];" : "=r"(v) : "r"(SB + SM_TAG) : "memory"); return v;
}

template<bool USE_SMID>
__global__ void __launch_bounds__(384, 1)
fused_kernel(Scratch* __restrict__ sc, const __nv_bfloat16* __restrict__ wo,
             const __nv_bfloat16* __restrict__ w1, const __nv_bfloat16* __restrict__ b1,
             const __nv_bfloat16* __restrict__ w2, const __nv_bfloat16* __restrict__ b2,
             const __grid_constant__ CUtensorMap tm_x, const __grid_constant__ CUtensorMap tm_wqkv,
             const __grid_constant__ CUtensorMap tm_wo64, const __grid_constant__ CUtensorMap tm_wo48,
             const __grid_constant__ CUtensorMap tm_w1, const __grid_constant__ CUtensorMap tm_w2,
             const __grid_constant__ CUtensorMap tm_xr64, const __grid_constant__ CUtensorMap tm_xr48,
             const __grid_constant__ CUtensorMap tm_out64, const __grid_constant__ CUtensorMap tm_out48) {
    extern __shared__ __align__(1024) uint8_t smem_raw[];
    constexpr uint32_t sb = SB;
    constexpr uint32_t bars = sb + SM_BAR;
    const int tid = threadIdx.x, lane = tid & 31;
    auto get_slot = [&]() {
        int slot;
    if (USE_SMID) {
        asm volatile("{\n.reg .u32 s, t, u, d, a, b, c;\n.reg .pred p, r;\n"
            "mov.u32 s, %%smid;\nshr.u32 t, s, 1;\nsub.u32 u, t, 32;\nmul.lo.u32 d, u, 37;\nshr.u32 d, d, 8;\n"
            "and.b32 a, t, 7;\nshl.b32 a, a, 3;\nshr.u32 c, t, 3;\nadd.u32 a, a, c;\n"
            "mad.lo.u32 b, d, -55, 12;\nshl.b32 c, u, 3;\nadd.u32 b, b, c;\n"
            "setp.lt.u32 p, t, 32;\nselp.u32 a, a, b, p;\n"
            "setp.lt.u32 r, t, 62;\nselp.s32 c, 4, -58, r;\nadd.u32 c, t, c;\nsetp.lt.u32 p, t, 60;\nselp.u32 a, a, c, p;\n"
            "and.b32 s, s, 1;\nshl.b32 a, a, 1;\nadd.u32 %0, a, s;\n}" : "=r"(slot));
    } else slot = blockIdx.x;
        return slot;
    };
    auto load_x = [&](int kb, int row) {
        const uint32_t st = sb + slot_x(kb), bar = bars + 8 * (B_FULLX + kb);
        mbar_expect(bar, 16384);
        tma3d(st, &tm_x, kb * 64, 0, row, bar); tma3d(st + 8192, &tm_x, kb * 64, 1, row, bar);
    };
    const int warp = __shfl_sync(0xffffffffu, tid >> 5, 0);
#define ASSIGN_WORK(s) \
    const int slot = (s), G = slot >> 4, mi = slot & 15; \
    const int tb = 4 * (G >> 1) + (mi >> 2), hp = 2 * (mi & 3) + (G & 1), wcol = (hp * 56) & ~15; \
    const int q = mi & 3, tt2 = 4 * G + (mi >> 2), c64 = 64 * q, c48 = 256 + 48 * q; \
    const int R = (ROLES >> (4 * G)) & 7; \
    const bool early = R < 3; \
    const int ech = R < 2 ? q : 4 + (mi & 1), ft = R == 2 ? mi >> 1 : 4 * (R - !early) + (mi >> 2); \
    const int pr3 = early ? ech >= 3 : q >> 1, col3 = early ? (ech - 3 * pr3) * 9 : (q & 1) * 14;

    if (warp < 8) {
        ASSIGN_WORK(get_slot())
        if (slot >= 128) {
            const uint32_t ep = ld_volatile(&sc->epoch[slot]) + 1;
            if (mi == 0 && warp > 0) {
                const int k = warp % 3;
                uint2* go = (uint2*)(sc->go + 8 * k) + lane;
                if (warp < 4 && lane < 16) st_relaxed2(go, 0, 0);
                while (ld_relaxed(k ? sc->go : sc->hint_k) != ep) __nanosleep(200);
                __nanosleep(warp * 60);
                const uint4* hint = (k ? sc->hint_u : sc->hint_h) + (k == 2 ? 48 + min(lane, 19) : lane) * 2;
                uint2 v[4];
                do {
                    #pragma unroll
                    for (int i = 0; i < 4; i++) v[i] = ld_relaxed2(hint + (k == 0 ? 64 * i : k == 2 ? 40 * i : 32 * (i & 1)));
                } while (!__all_sync(0xffffffffu, v[0].x == ep && v[1].x == ep && v[2].x == ep && v[3].x == ep));
                uint32_t t = later(later(v[0].y, v[1].y), later(v[2].y, v[3].y));
                t = later(t, __shfl_xor_sync(0xffffffffu, t, 1));
                if (k == 1) { t = later(t, __shfl_xor_sync(0xffffffffu, t, 8)); t = later(t, __shfl_xor_sync(0xffffffffu, t, 16)); }
                if (k == 0) {
                    const uint32_t now = gtime32() + 256;
                    t = later(t, now - __reduce_min_sync(0xffffffffu, now - t) - SLACK);
                }
                t = __shfl_sync(0xffffffffu, t, 2 * lane);
                if (lane < 16) st_relaxed2(go, ep, t);
            }
            if (mi == 1 && warp >= 4 && ld_volatile(&sc->clean) != ep) {
                for (int l = (tid - 128) / 2; l < sizeof(Tiles) / 128; l += 64) st_relaxed4((uint4*)&sc->tiles[ep & 1] + l * 8 + (lane & 7), EMPTY, EMPTY, EMPTY, EMPTY);
                named_sync(1, 128);
                if (tid == 128) st_release(&sc->clean, ep);
            }
            if (tid == 0) {
                const long long t0 = clock64();
                while (clock64() - t0 < SP_AT) {}
                #pragma unroll 1
                for (int i = 0; i < 7; i++) bulk_prefetch((const char*)wo + (i * 4 + mi) * 14336, 14336);
                uint32_t t = (uint32_t)t0 + PF0_AT;
                #pragma unroll 1
                for (int i = 0; i < PF0_N; i++) {
                    while ((int)(clock32() - t) < 0) {}
                    bulk_prefetch((const char*)w1 + i * 114688 + mi * 14336, 14336);
                    t += PF0_PACE;
                }
                if (mi) {
                    t = (uint32_t)t0 + PF1_AT;
                    #pragma unroll 1
                    for (int i = mi - 1; i < PF1_N; i += 3) {
                        while ((int)(clock32() - t) < 0) {}
                        tma5d_prefetch(&tm_w1, (i & 7) * 64, (i + 48) & 56, (i + 48) >> 6);
                        t += PF1_PACE;
                    }
                    t = (uint32_t)t0 + PF_AT;
                    #pragma unroll 1
                    for (int i = PF_OFS + mi - 1; i < PF_N; i += 3) {
                        while ((int)(clock32() - t) < 0) {}
                        bulk_prefetch((const char*)w2 + (i < 128 ? i * 16384 : i < 288 ? (i - 64 >> 1) * 65536 + (i & 1) * 16384 : (i - 224 >> 1) * 65536 + (i & 1) * 16384 + 32768), 16384);
                        t += PF_PACE;
                    }
                }
                while (ld_relaxed(sc->hint_u + 254) != ep) { __nanosleep(500); if (clock64() - t0 > WD_CLKS) __trap(); }
                sc->epoch[slot] = ep;
                if (mi == 1) sc->clean = ep + 1;
            }
            return;
        }
        {
            const int w = warp & 3, wg = warp >> 2, g = lane >> 2, t = lane & 3;
            if (WARM_AT) { const uint32_t t0 = clock32(); while (clock32() - t0 < WARM_AT) {} __syncwarp(); }
            if (w > 0) post_hint(sc->hint_o + ((2 * tb + (w >> 1)) * 32 + hp * 4 + (w & 1) * 2 + wg) * 2, 0, lane);
            if (wg == 0) {
                if (t < 2) st_relaxed4(sc->stats + tt2 * 256 + q * 64 + 16 * w + g + 8 * t, 0, 0, 0, 0);
            }
        }
        named_sync(0, 288);
        asm volatile("setmaxnreg.inc.sync.aligned.u32 224;");
        int tid; asm volatile("mov.u32 %0, %%tid.x;" : "=r"(tid));
        const int lane = tid & 31, warp = __shfl_sync(0xffffffffu, tid >> 5, 0), wg = warp >> 2;
        uint32_t ep;
        Tiles* tl;
        const int w = warp & 3, g = lane >> 2, t = lane & 3;
        const bool leader = (tid & 127) == 0;
        const uint32_t never = gridDim.y - 1;
        {
            uint32_t a[28][4];
            float accK[28], accV[28], accQ[28];
            const int lrow = 16 * w + (lane & 7) + (lane & 8);
            const uint32_t lbase = sb + wg * 8192 + lrow * 128;
            const uint32_t lx = (lane >> 4) ^ (lane & 7);
            const uint32_t wofs = hp & 1;
            auto pin2 = [&](uint32_t x0, uint32_t x1) {
                asm volatile("{\n.reg .pred p;\nsetp.ne.u32 p, %2, 0;\n@p st.shared.v2.b32 [%0], {%0,%1};\n}" :: "r"(x0), "r"(x1), "r"(never) : "memory");
            };
            float cS[2][4] = {}, cA[2][4] = {}, cB[2][4] = {}, q0, q1, p0, p1;
            auto sq = [&](float& acc, uint32_t v) { const float lo = bf_lo(v), hi = bf_hi(v); acc = fmaf(hi, hi, fmaf(lo, lo, acc)); };
            uint32_t ready = 0;
            #pragma unroll
            for (int kb = 0; kb < 8; kb++) {
                if (kb < 7) {
                    mbar_wait_unless(ready, bars + 8 * (B_FULLX + kb), 0);
                    if (kb == 0 && tid == 0) STAMP(0);
                    if (kb == 6 && tid == 0) STAMP(25);
                    if (kb == 0) FST(0); if (kb == 2) FST(1); if (kb == 4) FST(2); if (kb == 6) FST(3);
                    #pragma unroll
                    for (int s = 4 * kb; s < 4 * kb + 4; s++) ldsm4(a[s], lbase + slot_x(kb) + ((lx ^ (2 * (s & 3))) << 4));
                }
                if (kb > 0 && kb < 6) ready = mbar_test(bars + 8 * (B_FULLX + kb + 1), 0);
                if (kb == 5) named_sync(9 + wg, 160);
                if (kb == NPIPE) continue;
                const int kc = kb < NPIPE ? kb : kb - 1;
                if (kc == NSQ) { p0 = cS[0][0] + cS[1][0]; p1 = cS[0][2] + cS[1][2]; }
                #pragma unroll
                for (int s = 4 * kc; s < 4 * kc + 4; s++) {
                    mma16816(cS[s & 1], a[s][0], a[s][1], a[s][2], a[s][3], 0x3F803F80u, 0x3F803F80u);
                    if (kc < NSQ) {
                        mma1688(cA[0], a[s][0], a[s][1], a[s][0]); mma1688(cA[1], a[s][2], a[s][3], a[s][2]);
                        mma1688(cB[0], a[s][0], a[s][1], a[s][1]); mma1688(cB[1], a[s][2], a[s][3], a[s][3]);
                    }
                }
            }
            const float m0 = (cS[0][0] + cS[1][0]) * (1.f / D_), m1 = (cS[0][2] + cS[1][2]) * (1.f / D_);
            const uint32_t mm0 = pack_bf16(m0, m0), mm1 = pack_bf16(m1, m1);
            if (lane == 0) mbar_arrive(bars + 8 * B_DONEX);
            auto center = [&](int s) { sub_bf16x2(a[s][0], mm0); sub_bf16x2(a[s][1], mm1); sub_bf16x2(a[s][2], mm0); sub_bf16x2(a[s][3], mm1); };
            uint32_t Ka[8], Kb[8], Kc[8], Va[8], Vb[7], Vc[8];
            float r0, r1, ls0, ls1;
            uint32_t pm, zero;
            uint32_t* od;
            uint4* oh;
            auto kpack = [&](uint32_t (&k)[8], int j, int c, float r) {
                const uint32_t v = pack_bf16(accK[4 * j + c] * r, accK[4 * j + c + 1] * r);
                if (j == 3) { k[3] = t < 2 ? v : 0u; k[4] = t < 2 ? 0u : v; } else k[j + (j > 3)] = v;
            };
            auto batch = [&](auto c0, auto c1) {
                constexpr int n0 = c0.value, n1 = c1.value;
                wg_fence();
                static_for<n0, n1>([&](auto nc) {
                    constexpr int n = nc.value;
                    if (n == 4) { center(4); center(5); center(6); center(7); wg_fence(); }
                    const uint64_t desc = mkdesc(sb + (n < 56 ? slot_kv(n >> 3) + (n & 7) * 2048 : SM_QO + (n - 56) * 2048), 8192, 1024, 1) + wofs;
                    wgmma_rs56<1>(n < 28 ? accK : n < 56 ? accV : accQ, a[n % 28], desc, n % 28 != 0);
                });
                wg_commit();
                if (n0 > 0) wg_wait<1>();
            };
            const uint32_t hs = sb + tid * 16 + warp * 512;
            auto hand_over = [&](const uint32_t (&v)[8], int kv) {
                mbar_wait(bars + 8 * (kv ? B_DONE1 + 5 : B_DONEX), 0);
                sts4(hs + (kv ? SM_HALOV : SM_HALOK), v[0], v[1], v[2], v[3]); sts4(hs + (kv ? SM_HALOV : SM_HALOK) + 512, v[4], v[5], v[6], v[7]);
                if (w == 3) named_arrive(6 + kv, 96);
            };
            auto take_over = [&](uint32_t (&v)[8], int kv) {
                if (w == 0) mbar_wait(bars + 8 * (B_HALO + 2 * kv + wg), 0);
                const uint32_t ad = w ? hs + (kv ? SM_HALOV : SM_HALOK) - 1024 : kv ? sb + lane * 16 + wg * 1024 + SM_HALOV + 8192 : halo_kin(wg, lane);
                const uint4 u0 = lds4(ad), u1 = lds4(ad + (w || kv ? 512 : 16));
                v[0] = u0.x; v[1] = u0.y; v[2] = u0.z; v[3] = u0.w; v[4] = u1.x; v[5] = u1.y; v[6] = u1.z; v[7] = u1.w;
            };
            center(0); center(1); center(2); center(3);
            static_for<0, 7>([&](auto pc) {
                constexpr int p = pc.value;
                mbar_wait(bars + 8 * (B_FULLKV + p), 0);
                if (p == 0 && tid == 0) STAMP(26);
                if (p == 3 && tid == 0) STAMP(27);
                FST(4 + p);
                batch(Int<8 * p>(), Int<8 * p + 8>());
                if (p > 0 && leader) mbar_arrive(bars + 8 * (B_DONE1 + p - 1));
                #pragma unroll
                for (int s = 8 * p + 8; s < 8 * p + 16 && s < 28; s++) center(s);
                if (p == 1) {
                    const float c0 = bf_hi(mm0), c1 = bf_hi(mm1);
                    q0 = fmaf(c0, fmaf(c0, 64.f * NSQ, -2.f * p0), (g & 1) ? cA[0][1] + cA[1][1] : cA[0][0] + cA[1][0]) - D_ * (m0 - c0) * (m0 - c0);
                    q1 = fmaf(c1, fmaf(c1, 64.f * NSQ, -2.f * p1), (g & 1) ? cB[0][3] + cB[1][3] : cB[0][2] + cB[1][2]) - D_ * (m1 - c1) * (m1 - c1);
                    asm("" : "+f"(q0), "+f"(q1));
                    q0 = t == (g >> 1) ? q0 : 0.f; q1 = t == (g >> 1) ? q1 : 0.f;
                    pin2(__float_as_uint(q0), __float_as_uint(q1));
                }
                constexpr int PK = NSQ < 5 ? 5 : 4, NR = 28 - 4 * NSQ;
                if (p >= 2 && p < PK) {
                    #pragma unroll
                    for (int s = 4 * NSQ + NR * (p - 2) / (PK - 2); s < 4 * NSQ + NR * (p - 1) / (PK - 2); s++) { sq(q0, a[s][0]); sq(q1, a[s][1]); sq(q0, a[s][2]); sq(q1, a[s][3]); }
                    pin2(__float_as_uint(q0), __float_as_uint(q1));
                }
                if (p == PK - 1) { q0 = quad_sum(q0); q1 = quad_sum(q1); }
                if (p == PK) {
                    r0 = rsqrt_approx(fmaxf(q0 * (1.f / D_), 0.f) + LN_EPS); r1 = rsqrt_approx(fmaxf(q1 * (1.f / D_), 0.f) + LN_EPS);
                    reg_fence(accK);
                    #pragma unroll
                    for (int j = 0; j < 7; j++) kpack(Kc, j, 2, r1);
                    hand_over(Kc, 0);
                }
                if (p == PK + 1) {
                    #pragma unroll
                    for (int j = 0; j < 7; j++) kpack(Kb, j, 0, r0);
                    #pragma unroll
                    for (int j = 0; j < 8; j += 2) pin2(Kb[j], Kb[j + 1]);
                    ls0 = LOG2E_SCALE * r0; ls1 = LOG2E_SCALE * r1;
                    pm = (2 * t <= g ? 0xFFFFu : 0u) | (2 * t + 1 <= g ? 0xFFFF0000u : 0u);
                    zero = never; asm volatile("" : "+r"(zero));
                    pin2(__float_as_uint(ls0), __float_as_uint(ls1)); pin2(pm, zero);
                }
                if (p == 2) ep = get_tag();
                if (p == 6) {
                    tl = &sc->tiles[ep & 1];
                    const int tt = 2 * tb + (w >> 1);
                    od = tl->o + tt * 14336 + (7 * hp) * 256 + (2 * (2 * (w & 1) + wg)) * 32 + lane;
                    oh = sc->hint_o + (tt * 32 + hp * 4 + (w & 1) * 2 + wg) * 2 + (lane & 1);
                    pin2((uint32_t)(uint64_t)od, (uint32_t)((uint64_t)od >> 32));
                    pin2((uint32_t)(uint64_t)oh, (uint32_t)((uint64_t)oh >> 32));
                }
            });
            if (tid == 0) STAMP(1);
            FST(11);
            mbar_wait(bars + 8 * B_FQ, 0);
            batch(Int<56>(), Int<60>());
            reg_fence(accV);
            if (leader) mbar_arrive(bars + 8 * (B_DONE1 + 6));
            if (tid == 0) STAMP(2);
            FST(12);
            #pragma unroll
            for (int j = 0; j < 7; j++) Vc[j] = movtrans(pack_bf16(accV[4 * j + 2] * r1, accV[4 * j + 3] * r1));
            Vc[7] = Vc[6];
            hand_over(Vc, 1);
            batch(Int<60>(), Int<66>());
            #pragma unroll
            for (int j = 0; j < 7; j++) {
                Vb[j] = movtrans(pack_bf16(accV[4 * j] * r0, accV[4 * j + 1] * r0));
                Vc[j] |= zero;
            }
            batch(Int<66>(), Int<72>());
            #pragma unroll
            for (int j = 0; j < 7; j++) pin2(Vb[j], Vc[j]);
            mbar_wait(bars + 8 * (B_FQ + 1), 0);
            FST(13);
            if (w > 0 && lane < 2) { const uint32_t now = gtime32(); st_relaxed4(oh, ep, now, ep, now); }
            batch(Int<72>(), Int<84>());
            FST(14);
            named_sync(1 + wg, 128);
            take_over(Ka, 0);
            if (tid == 0) STAMP(3);
            wg_wait<0>();
            reg_fence(accQ);
            if (tid == 0) STAMP(4);
            FST(15);
            const bool first = (tb == 0 && w == 0);
            uint32_t pA[2], pB0[2], pB1[2], pC[2], z0[2], z1[2];
            float sA[2][4] = {}, sB[2][4] = {}, sC[2][4] = {}, e[2][4], inv[2][2];
            #pragma unroll
            for (int k = 0; k < 2; k++) {
                #pragma unroll
                for (int h = 0; h < 2; h++) {
                    const float* qq = accQ + 12 * h + 8 * k;
                    uint32_t a2 = pack_bf16(qq[4], qq[5]), a3 = pack_bf16(qq[6], qq[7]);
                    if (h == 0 && k == 1) { a2 |= zero; a3 |= zero; }
                    const uint32_t a0 = pack_bf16(qq[0], qq[1]), a1 = pack_bf16(qq[2], qq[3]);
                    mma16816(sB[h], a0, a1, a2, a3, Kb[4 * h + 2 * k], Kb[4 * h + 2 * k + 1]);
                    mma16816(sA[h], a0, a1, a2, a3, Ka[4 * h + 2 * k], Ka[4 * h + 2 * k + 1]);
                    mma16816(sC[h], a0, a1, a2, a3, Kc[4 * h + 2 * k], Kc[4 * h + 2 * k + 1]);
                }
            }
            #pragma unroll
            for (int h = 0; h < 2; h++) {
                const bool n0 = pm & 1, n1 = (int)pm < 0;
                const float l00 = n0 ? sB[h][0] : (first ? -INFINITY : sA[h][0]), l01 = n1 ? sB[h][1] : (first ? -INFINITY : sA[h][1]);
                const float l10 = n0 ? sC[h][2] : sB[h][2], l11 = n1 ? sC[h][3] : sB[h][3];
                const float x0 = -ls0 * quad_max(fmaxf(l00, l01)), x1 = -ls1 * quad_max(fmaxf(l10, l11));
                e[h][0] = ex2(fmaf(l00, ls0, x0)); e[h][1] = ex2(fmaf(l01, ls0, x0)); e[h][2] = ex2(fmaf(l10, ls1, x1)); e[h][3] = ex2(fmaf(l11, ls1, x1));
            }
            pin4(never, e[0][0], e[0][2], e[1][0], e[1][2]);
            take_over(Va, 1);
            #pragma unroll
            for (int h = 0; h < 2; h++) {
                inv[h][0] = rcp_approx(quad_sum(e[h][0] + e[h][1])); inv[h][1] = rcp_approx(quad_sum(e[h][2] + e[h][3]));
                const uint32_t P0 = pack_bf16(e[h][0], e[h][1]), P1 = pack_bf16(e[h][2], e[h][3]);
                pB0[h] = P0 & pm; pA[h] = P0 & ~pm; pC[h] = P1 & pm; pB1[h] = P1 & ~pm; z0[h] = P0 & zero; z1[h] = P1 & zero;
            }
            float o[8][4];
            #pragma unroll
            for (int j = 0; j < 8; j++) {
                o[j][0] = o[j][1] = o[j][2] = o[j][3] = 0.f;
                mma16816(o[j], pB0[j >> 2], pB1[j >> 2], z0[j >> 2], pC[j >> 2], Vb[j - (j >> 2)], Vc[j - (j >> 2)]);
            }
            if (tid == 0) STAMP(12);
            FST(16);
            if (tid == 0) STAMP(16);
            #pragma unroll
            for (int j = 0; j < 8; j++) mma1688(o[j], pA[j >> 2], z1[j >> 2], Va[j - (j >> 2)]);
            #pragma unroll
            for (int j = 0; j < 7; j++) {
                float v[4];
                #pragma unroll
                for (int c = 0; c < 4; c++) {
                    v[c] = j < 3 ? o[j][c] : j > 3 ? o[j + 1][c] : (t < 2 ? o[3][c] : o[4][c]);
                    v[c] *= j < 3 ? inv[0][c >> 1] : j > 3 ? inv[1][c >> 1] : (t < 2 ? inv[0][c >> 1] : inv[1][c >> 1]);
                }
                od[j * 256] = pack_bf16(v[0], v[1]);
                od[j * 256 + 32] = pack_bf16(v[2], v[3]);
            }
            if (lane == 0) mbar_arrive(bars + 8 * B_DONEQ);
            if (tid == 0) STAMP(5);
            FST(17);
        }
        const int z = get_tag() - ep, slot1 = slot + z, tid1 = tid + z, warp1 = warp + z;
        ep += z;
        {
        ASSIGN_WORK(slot1)
        const int tid = tid1, lane = tid & 31, wg = warp1 >> 2, w = warp1 & 3, g = lane >> 2, t = lane & 3;
        tl = &sc->tiles[ep & 1];
        const uint32_t live = wg ^ 1;
        uint32_t rb0, rb1, late[14];
        const unsigned short* pb = (const unsigned short*)(live ? b2 + tt2 * 64 : b1 + ft * 64) + 16 * w + g;
        auto stage_late = [&]() {
            #pragma unroll
            for (int c = 0; c < 14; c++) asm volatile("st.shared.u32 [%0], %1;" :: "r"(sb + SM_H + wg * 8192 + (tid & 127) * 4 + c * 512), "r"(late[c]) : "memory");
            fence_async_smem();
            named_sync(1 + wg, 128);
        };
        auto store_late = [&](bool on, uint32_t* p) {
            #pragma unroll
            for (int c = 0; c < 4; c++)
                if (elect() && on && (c < 3 || w < 2)) bulk_st(p + (4 * c + w) * 256, sb + SM_H + wg * 8192 + (4 * c + w) * 512, 512);
            asm volatile("cp.async.bulk.commit_group;" ::: "memory");
        };
        if (live) {
            float acc[56];
            const int hrow = 32 * (w >> 1) + 2 * ((lane & 7) + (lane & 8)) + (w & 1);
            const uint32_t ha = sb + SM_H + hrow * 128 + (((lane >> 4) ^ (hrow & 7)) << 4);
            uint4* sp = sc->stats + tt2 * 256 + 16 * w + g + 8 * (t & 1);
            uint4* sp_out = sp + q * 64;
            const uint4* sp_in = sp + (t & 2) * 64;
            uint32_t* hd = tl->hn + ((q >> 1) * 32 + (tt2 >> 1)) * 7168 + (q & 1) * 3584 + (tt2 & 1) * 128 + w * 32 + lane;
            pin_ptr(never, sp_out); pin_ptr(never, sp_in); pin_ptr(never, hd);
            float s0 = 0.f, s1 = 0.f, q0 = 0.f, q1 = 0.f, s2 = 0.f, s3 = 0.f, q2 = 0.f, q3 = 0.f;
            auto sums = [&](int j0, int j1) {
                #pragma unroll
                for (int j = j0; j < j1; j++) {
                    s0 += acc[4 * j]; s2 += acc[4 * j + 1]; q0 = fmaf(acc[4 * j], acc[4 * j], q0); q2 = fmaf(acc[4 * j + 1], acc[4 * j + 1], q2);
                    s1 += acc[4 * j + 2]; s3 += acc[4 * j + 3]; q1 = fmaf(acc[4 * j + 2], acc[4 * j + 2], q1); q3 = fmaf(acc[4 * j + 3], acc[4 * j + 3], q3);
                }
            };
            {
                mbar_wait(bars + 8 * B_FULLWO, 0);
                #pragma unroll
                for (int jp = 0; jp < 7; jp++) {
                    uint32_t xx[4];
                    ldsm4(xx, hcol(ha, jp));
                    #pragma unroll
                    for (int r = 0; r < 4; r++) { acc[8 * jp + 2 * r] = bf_lo(xx[r]); acc[8 * jp + 2 * r + 1] = bf_hi(xx[r]); }
                }
                reg_fence(acc);
                named_sync(12, 256);
                spin_mma(bars + 8 * B_FULLX, never);
                auto od_ = [&](int s) { return mkdesc(sb + SM_QO + s * 2048, 1024, 128, 0); };
                auto wd_ = [&](int s) { return mkdesc(sb + slot_wo(s >> 2) + (s & 3) * 2048, 8192, 1024, 1); };
                float accl[32], accr[24];
                #pragma unroll
                for (int i = 0; i < 5; i++) {
                    if (i < 4) mbar_wait(bars + 8 * (B_FULLO + i), 0);
                    if (i == 0 && tid == 0) STAMP(7);
                    if (i == 1) { rb0 = ld_u16(pb); rb1 = ld_u16(pb + 8); }
                    wg_fence();
                    #pragma unroll
                    for (int ss = i ? 0 : 4; ss < 8; ss++) {
                        if (i < 3) wgmma_ss112<0, 1>(acc, od_(8 * i - 4 + ss), wd_(8 * i - 4 + ss));
                        else if (i == 4) wgmma_ss64<0, 1>(accl, od_(20 + ss), wd_(20 + ss));
                        else if (ss == 0) wgmma_ss48<0, 1, 0>(accr, od_(20), wd_(20) + 512);
                        else wgmma_ss48<0, 1>(accr, od_(20 + ss), wd_(20 + ss) + 512);
                    }
                    wg_commit();
                    if (i > 0) {
                        wg_wait<1>();
                        if (i == 3) {
                            reg_fence(acc);
                            #pragma unroll
                            for (int c = 0; c < 32; c++) accl[c] = __uint_as_float(__float_as_uint(acc[c]) | never);
                            reg_fence(accl);
                        }
                        if (i < 4 && leader) mbar_arrive(bars + 8 * (B_DONEO + i - 1));
                    }
                }
                reg_fence(accr);
                #pragma unroll
                for (int c = 0; c < 24; c++) acc[32 + c] += accr[c];
                sums(8, 14);
                pin4(never, s0, s1, s2, s3); pin4(never, q0, q1, q2, q3);
                wg_wait<0>();
                reg_fence(accl);
                #pragma unroll
                for (int c = 0; c < 32; c++) acc[c] = accl[c];
                if (leader) mbar_arrive(bars + 8 * (B_DONEO + 3));
                if (tid == 0) STAMP(8);
            }
            sums(0, 8);
            s0 += s2; s1 += s3; q0 += q2; q1 += q3;
            float sr = ((t & 1) ? s1 : s0) + __shfl_xor_sync(0xffffffffu, (t & 1) ? s0 : s1, 1), qr = ((t & 1) ? q1 : q0) + __shfl_xor_sync(0xffffffffu, (t & 1) ? q0 : q1, 1);
            sr += __shfl_xor_sync(0xffffffffu, sr, 2); qr += __shfl_xor_sync(0xffffffffu, qr, 2);
            st_relaxed4_if(t < 2, sp_out, __float_as_uint(sr), __float_as_uint(qr), ep);
            named_arrive(5, 256);
            if (tid == 0) STAMP(9);
            #pragma unroll
            for (int jp = 0; jp < 7; jp++)
                stsm4(hcol(ha, jp), pack_bf16(acc[8 * jp], acc[8 * jp + 1]), pack_bf16(acc[8 * jp + 2], acc[8 * jp + 3]),
                      pack_bf16(acc[8 * jp + 4], acc[8 * jp + 5]), pack_bf16(acc[8 * jp + 6], acc[8 * jp + 7]));
            uint4 v0, v1;
            do { v0 = ld_relaxed4(sp_in); v1 = ld_relaxed4(sp_in + 64); } while (__any_sync(0xffffffffu, v0.w != ep || v1.w != ep));
            if (tid == 0) STAMP(10);
            sr = __uint_as_float(v0.x) + __uint_as_float(v1.x); qr = __uint_as_float(v0.y) + __uint_as_float(v1.y);
            sr += __shfl_xor_sync(0xffffffffu, sr, 2); qr += __shfl_xor_sync(0xffffffffu, qr, 2);
            const float m = sr * (1.f / D_), var = fmaxf(qr * (1.f / D_) - m * m, 0.f);
            const float r = rsqrt_approx(fmaf(var, 4.f + 4.f * LN_EPS, 4.f * LN_EPS * LN_EPS)), c = -m * r;
            const float r0 = __shfl_sync(0xffffffffu, r, lane & ~1), c0 = __shfl_sync(0xffffffffu, c, lane & ~1);
            const float r1 = __shfl_sync(0xffffffffu, r, lane | 1), c1 = __shfl_sync(0xffffffffu, c, lane | 1);
            #pragma unroll
            for (int j = 0; j < 14; j++) st_global_if(1, hd + j * 256, pack_bf16(fmaf(acc[4 * j], r0, c0), fmaf(acc[4 * j + 1], r0, c0)));
            if (never) mbar_arrive(bars);
            #pragma unroll
            for (int j = 0; j < 14; j++) late[j] = pack_bf16(fmaf(acc[4 * j + 2], r1, c1), fmaf(acc[4 * j + 3], r1, c1));
            if (tid == 0) STAMP(11);
        } else {
            named_arrive(12, 256);
            check_tiles<0>(w, 4, 4, tl->o + tt2 * 14336, false, lane, true);
            rb0 = ld_u16(pb); rb1 = ld_u16(pb + 8);
            auto reset_tiles = [&](int v, int i0, int i1) {
                const int l = slot * 48 + v * 16 + lane / 2;
                #pragma unroll
                for (int i = i0; i < i1; i++)
                    st_relaxed4_if(i < 6 || l < sizeof(Tiles) / 128 - 6 * 6144, (uint4*)&sc->tiles[~ep & 1] + (i * 6144 + l) * 8 + (lane & 7), EMPTY, EMPTY, EMPTY);
            };
            if (CL_N && w < 3) { mbar_wait(bars + 8 * (B_DONEO + CL_P2), 0); reset_tiles(w, 0, CL_N); }
            named_sync(5, 256);
            auto phase3 = [&](auto nc) {
                constexpr int NC = nc.value;
                float acc[4 * NC];
                uint32_t* ud = tl->u + (pr3 * 28 + (ft >> 1) + (NC == 14 ? 4 : 0)) * 7168 + col3 * 256 + (ft & 1) * 128 + w * 32 + lane;
                #pragma unroll
                for (int j = 0; j < 4 * NC; j++) acc[j] = 0.5f * bf_lo((j & 2) ? rb1 : rb0);
                #pragma unroll 1
                for (uint32_t pass = never; pass < 2; pass++) {
                    if (pass) {
                        mix_mainloop<32>(TSVAL acc, leader);
                        if (leader) STAMP(14);
                    }
                    uint32_t pk[NC];
                    #pragma unroll
                    for (int j = 0; j < NC; j++) {
                        const float k = j < GDEP ? GELU_K1 : __uint_as_float(__float_as_uint(GELU_K1) | (pk[j - GDEP] & never));
                        pk[j] = pack_bf16(gelu_half(acc[4 * j], k), gelu_half(acc[4 * j + 1], k));
                        st_global_if(pass, ud + j * 256, pk[j]);
                    }
                }
                if (leader) STAMP(15);
                #pragma unroll
                for (int j = 0; j < NC; j++) late[j] = pack_bf16(gelu_half(acc[4 * j + 2], GELU_K1), gelu_half(acc[4 * j + 3], GELU_K1));
                if (NC == 14) {
                    stage_late();
                    mbar_wait(bars + 8 * (B_FULLB + LATE_AT4), 1);
                    store_late(true, tl->u + (pr3 * 28 + (ft >> 1) + 14) * 7168 + col3 * 256 + (ft & 1) * 128);
                } else {
                    #pragma unroll
                    for (int c = 0; c < NC; c++) st_global_if(1, ud + 4 * 7168 + c * 256, late[c]);
                }
            };
            if (early) phase3(Int<10>()); else phase3(Int<14>());
            if (w) {
                if (early && w == 1) fetch_times(TSVAL sc->go, 1, ep, lane);
                if (CL_N < 7) { mbar_wait(bars + 8 * (B_DONE + CL_AT), 1); reset_tiles(w - 1, CL_N, 7); }
            }
            if (leader) mbar_wait_wd(bars + 8 * B_END, 0);
            return;
        }
        {
            float acc[56];
            const uint32_t ad = sb + SM_H + (16 * w + (lane & 15)) * 128 + (((lane >> 4) ^ (lane & 7)) << 4);
            const float bb0 = bf_lo(rb0), bb1 = bf_lo(rb1);
            named_sync(1, 128);
            #pragma unroll
            for (int jp = 0; jp < 7; jp++) {
                uint32_t hh[4];
                ldsm4(hh, hcol(ad, jp));
                #pragma unroll
                for (int r = 0; r < 4; r++) { acc[8 * jp + 2 * r] = bf_lo(hh[r]) + ((r & 1) ? bb1 : bb0); acc[8 * jp + 2 * r + 1] = bf_hi(hh[r]) + ((r & 1) ? bb1 : bb0); }
            }
            named_sync(1, 128);
            stage_late();
            if (tid == 0) STAMP(39);
            reg_fence(acc);
            spin_mma(bars + 8 * (B_FULLX + 1), never);
            mbar_wait(bars + 8 * (B_FULLB + LATE_AT), 0);
            store_late(true, tl->hn + ((q >> 1) * 32 + 16 + (tt2 >> 1)) * 7168 + (q & 1) * 3584 + (tt2 & 1) * 128);
            check_tiles<1>(CH_H + w, 4, 32, tl->hn + pr3 * 32 * 7168 + col3 * 256, early, lane, false);
            mbar_wait(bars + 8 * (B_DONE + START4), 0);
            mix_mainloop<28>(TSVAL acc, leader);
            if (leader) mbar_arrive(bars + 8 * B_END);
            if (tid == 0) STAMP(18);
            #pragma unroll
            for (int jp = 0; jp < 7; jp++)
                stsm4(hcol(ad, jp), pack_bf16(acc[8 * jp], acc[8 * jp + 1]), pack_bf16(acc[8 * jp + 2], acc[8 * jp + 3]),
                         pack_bf16(acc[8 * jp + 4], acc[8 * jp + 5]), pack_bf16(acc[8 * jp + 6], acc[8 * jp + 7]));
            fence_async_smem();
            __syncwarp();
            if (elect()) {
                tma2d_store(&tm_out64, c64, tt2 * 64 + 16 * w, sb + SM_H + w * 2048);
                tma2d_store(&tm_out48, c48, tt2 * 64 + 16 * w, sb + SM_H + 8192 + w * 2048);
            }
            asm volatile("cp.async.bulk.commit_group;" ::: "memory");
            asm volatile("cp.async.bulk.wait_group.read 0;" ::: "memory");
            if (tid == 0) { sc->epoch[slot] = ep; STAMP(19); }
        }
        }
    } else {
        asm volatile("setmaxnreg.dec.sync.aligned.u32 56;");
        int warp2; asm("mov.u32 %0, %1;" : "=r"(warp2) : "r"(warp));
        if (warp2 > 8) {
            ASSIGN_WORK(get_slot())
            if (slot >= 128) return;
            uint32_t ep, cl;
            uint4* const oh = sc->hint_o + (2 * tb * 32 + hp * 4) * 2 + (lane & 3);
            if (warp == 11) ep = ld_volatile(&sc->epoch[slot]) + 1;
            if (elect()) {
                #pragma unroll
                for (int i = 0; i < 33; i++) mbar_init(bars + 8 * (B_DONEO + i) + (warp - 9) * 264, 1);
                if (warp == 11) {
                    #pragma unroll
                    for (int i = B_DONE1; i < B_DONEO; i++) mbar_init(bars + 8 * i, i < B_DONEX ? 2 : i == B_DONEX ? 8 : 9);
                } else {
                    #pragma unroll
                    for (int i = 0; i < 32; i++) mbar_init(sb + SM_RAW + 8 * i + (warp - 9) * 256, 1);
                }
                asm volatile("fence.mbarrier_init.release.cluster;" ::: "memory");
            }
            __syncwarp();
            if (warp < 11) mbar_expect(sb + SM_RAW + 8 * (tid - 288), tid == 288 ? 8192 : tid < 292 ? 16384 : early && tid < 324 ? 10240 : 14336);
            uint4* const hu = sc->hint_u + (early ? ech * 8 + ft : 40 + q * 20 + ft) * 2;
            if (warp == 10) {
                post_hint(sc->hint_h + (q * 32 + tt2) * 2, 0, lane);
                post_hint(hu, 0, lane);
            }
            if (warp == 11) {
                post_hint(sc->hint_k + (tb * 8 + hp) * 2, 0, lane);
                if (lane < (tb < 15 ? 4 : 0)) st_relaxed4(oh + 128, 0, 0, 0, 0);
                if (lane < (tb ? 0 : 4)) st_relaxed4(oh, 0, 0, 0, 0);
                cl = ld_acquire(&sc->clean);
            }
            named_sync(8, 128);
            if (warp == 9) { named_arrive(4, 64); named_arrive(9, 160); named_arrive(10, 160); }
            if (warp < 11) {
                ep = get_tag();
                mbar_wait(bars + 8 * (B_DONE1 + HALO_AT), 0);
                #pragma unroll 1
                for (int kv = 0; kv < 2; kv++) {
                    uint4 v0 = {}, v1 = {}, v2 = {};
                    if (tb > 0) {
                        const uint4* hg = sc->halo + ((((tb - 1) * 8 + hp) * 2 + warp - 9) * 2 + kv) * 96 + lane;
                        if (kv == 0) while (ld_relaxed(sc->hint_k + ((tb - 1) * 8 + hp) * 2) != ep) {}
                        do { v0 = ld_relaxed4(hg); v1 = ld_relaxed4(hg + 32); v2 = ld_relaxed4(hg + 64); } while (!__all_sync(0xffffffffu, v0.w == ep && v1.w == ep && v2.w == ep));
                    }
                    if (kv) mbar_wait(bars + 8 * (B_DONE1 + 5), 0);
                    const uint32_t hs = kv ? sb + lane * 16 + (warp - 9) * 1024 + SM_HALOV + 8192 : halo_kin(warp - 9, lane);
                    sts4(hs, v0.x, v0.y, v0.z, v1.x); sts4(hs + (kv ? 512 : 16), v1.y, v1.z, v2.x, v2.y);
                    __syncwarp();
                    if (lane == 0) mbar_arrive(bars + 8 * (B_HALO + 2 * kv + warp - 9));
                }
                if (tid == 288) STAMP(21);
            } else {
                const long long t0 = clock64();
                while (__any_sync(0xffffffffu, (int)(cl - ep) < 0)) { cl = ld_acquire(&sc->clean); if (clock64() - t0 > WD_CLKS) __trap(); }
                if (lane == 0) { *(volatile uint32_t*)(smem_raw + SM_TAG) = ep; mbar_arrive(bars + 8 * B_CLR); }
                uint4* hg = sc->halo + (tb * 8 + hp) * 384 + lane;
                #pragma unroll 1
                for (int kv = 0; kv < 2; kv++) {
                    const uint32_t hs = sb + lane * 16 + 3072 + (kv ? SM_HALOV : SM_HALOK);
                    named_sync(6 + kv, 96);
                    #pragma unroll
                    for (int p = 0; p < 2; p++) {
                        const uint4 u0 = lds4(hs + p * 4096), u1 = lds4(hs + p * 4096 + 512);
                        st_relaxed4(hg + p * 192, u0.x, u0.y, u0.z, ep); st_relaxed4(hg + p * 192 + 32, u0.w, u1.x, u1.y, ep); st_relaxed4(hg + p * 192 + 64, u1.z, u1.w, ep, ep);
                    }
                    hg += 96;
                    if (kv == 0) {
                        post_hint(sc->hint_k + (tb * 8 + hp) * 2, ep, lane);
                        #pragma unroll
                        for (int j = 0; j < 6; j++) st_relaxed4(hg + j * 32 + (j / 3) * 96, 0, 0, 0, 0);
                    }
                }
                const uint32_t now = gtime32() - LATE_O;
                if (lane < (tb < 15 ? 4 : 0)) st_relaxed4(oh + 128, ep, now, ep, now);
                if (lane < (tb ? 0 : 4)) st_relaxed4(oh, ep, now, ep, now);
                if (lane == 0) STAMP(23);
                if (lane == 0) mbar_arrive(bars + 8 * B_DONEQ);
            }
            if (warp > 9) {
                const Tiles* const tl = &sc->tiles[ep & 1];
                check_tiles<1>(11 - warp, 2, CH_H, tl->hn + pr3 * 32 * 7168 + col3 * 256, early, lane, true);
                if (warp == 10) {
                    mbar_wait(bars + 8 * (B_DONE + (early ? HINT_E : HINT_U)), 0);
                    post_time(hu, ep, lane);
                }
                if (warp == 11) {
                    mbar_wait(bars + 8 * (B_DONE + (early ? POLL_E : POLL_N)), 0);
                    fetch_times(TSVAL sc->go, 0, ep, lane);
                }
                check_tiles<2>(11 - warp, 2, 28, tl->u + (q >> 1) * 28 * 7168 + (q & 1) * 3584, false, lane, true);
            } else {
                int aslot = 0;
                if (lane == 0) { prefetch_map(&tm_out64); prefetch_map(&tm_out48); }
                #pragma unroll
                for (int i = 0; i < HINT_F; i++) mbar_wait(bars + 8 * (B_FULLO + i), 0);
                post_time(sc->hint_h + (q * 32 + tt2) * 2, ep, lane);
                #pragma unroll 1
                for (int i = 0; i < 30; i++) {
                    if (i == POLL_I && !early) fetch_times(TSVAL sc->go, 1, ep, lane);
                    int d = 2 * i - 11 + (i >= A4_FROM ? A4_DLY : 0);
                    if (early) d = i < 16 ? 1 + (i - NA_SLOTS) * AE_END / 9 : max(d, AE_W2);
                    mbar_wait(bars + 8 * (i < NA_SLOTS ? B_DONEQ + ((A_SCHED >> (4 * i)) & 15) : B_DONE + (d & 31)), d >= 32);
                    if (elect()) {
                        const uint32_t bar = bars + 8 * (B_FULLA + (i & 15)), dst = sb + SM_ARING + aslot * 16384;
                        mbar_expect(bar, 16384);
                        if (i < 16) tma5d(dst, &tm_w1, ft * 64, (i & 7) * 8, i >> 3, bar);
                        else tma5d(dst, &tm_w2, tt2 * 64, 8 * (i < 20 ? i & 1 : i < 25 ? i - 18 : i - 23), i < 20 ? (i >> 1) & 1 : i >= 25, bar);
                    }
                    aslot = aslot == NA_SLOTS - 1 ? 0 : aslot + 1;
                }
            }
        } else {
            const int slot0 = get_slot(), row0 = (slot0 >> 5) * 256 + (slot0 & 12) * 16;
            if (elect()) {
                prefetch_map(&tm_x);
                #pragma unroll
                for (int i = 0; i < 7; i++) mbar_init(bars + 8 * i, 1);
                asm volatile("fence.mbarrier_init.release.cluster;" ::: "memory");
            }
            named_arrive(0, 288);
            if (elect()) {
                #pragma unroll 1
                for (int kb = 0; kb < 7; kb++) {
                    load_x(kb, row0);
                    if (kb == 0) STAMP(22);
                }
                #pragma unroll
                for (int i = 7; i < B_DONE1; i++) mbar_init(bars + 8 * i, 1);
                asm volatile("fence.mbarrier_init.release.cluster;" ::: "memory");
            }
            named_arrive(8, 128);
            ASSIGN_WORK(get_slot())
            if (slot >= 128) return;
            #pragma unroll 1
            for (int kb = 0; kb < 7; kb++) {
                if (kb == 6) { named_sync(4, 64); mbar_wait(bars + 8 * B_DONEX, 0); }
                if (elect()) {
                    const uint32_t st = sb + slot_kv(kb), bar = bars + 8 * (B_FULLKV + kb);
                    mbar_expect(bar, 16384);
                    #pragma unroll
                    for (int i = 0; i < 2; i++) {
                        const int n = 2 * kb + (i ^ (G & 1));
                        tma2d(st + (n & 1) * 8192, &tm_wqkv, (n < 7 ? 448 : 896) + wcol, (n < 7 ? n : n - 7) * 64, bar);
                    }
                }
            }
            if (elect()) {
                mbar_expect(bars + 8 * B_FQ, 32768);
                mbar_expect(bars + 8 * (B_FQ + 1), 24576);
                #pragma unroll 1
                for (int i = 0; i < 7; i++) { const int j = i == 6 ? i : i ^ (G & 1); tma2d(sb + SM_QO + j * 8192, &tm_wqkv, wcol, j * 64, bars + 8 * (B_FQ + (i >> 2))); }
                mbar_expect(bars + 8 * B_FULLWO, 512 * 112 * 2);
            }
            #pragma unroll 1
            for (int i = 0; i < 7; i++) {
                if (i == PFC_AT && elect()) {
                    #pragma unroll 1
                    for (int k = NA_SLOTS + (early ? ech : q); k < (early ? PFC_E : PFC_N); k += early ? 6 : 4) tma5d_prefetch(&tm_w1, ft * 64, (k & 7) * 8, k >> 3);
                }
                if (i == PFW_AT && elect()) {
                    #pragma unroll 1
                    for (int k = PFW_0 + q; k < PFW_N; k += 4) tma5d_prefetch(&tm_w2, tt2 * 64, 8 * (k < 4 ? k & 1 : k < 9 ? k - 2 : k - 7), k < 4 ? k >> 1 : k >= 9);
                }
                const int kb = ((q & 1 ? WO_ORD1 : WO_ORD0) >> (4 * i)) & 7;
                if (kb < 5) mbar_wait(bars + 8 * (B_DONE1 + kb), 0);
                if (elect()) {
                    tma2d(sb + slot_wo(kb), &tm_wo64, c64, kb * 64, bars + 8 * B_FULLWO);
                    tma2d(sb + slot_wo(kb) + 8192, &tm_wo48, c48, kb * 64, bars + 8 * B_FULLWO);
                }
            }
            if (elect()) {
                tma2d(sb + SM_H, &tm_xr64, c64, tt2 * 64, bars + 8 * B_FULLWO);
                tma2d(sb + SM_H + 8192, &tm_xr48, c48, tt2 * 64, bars + 8 * B_FULLWO);
            }
            if (smem_u32(smem_raw) != SB) __trap();
            const uint32_t ep = get_tag();
            const Tiles* const tl = &sc->tiles[ep & 1];
            mbar_wait(bars + 8 * (B_DONE1 + 6), 0);
            const uint32_t t_o = last_hint(TSVAL sc->hint_o + (tt2 * 32 + lane) * 2, ep, 38);
            mbar_wait(bars + 8 * B_DONEQ, 0);
            wait_until(t_o + GO_O);
            if (elect()) {
                #pragma unroll
                for (int i = 0; i < 4; i++) {
                    bulk_ld(sb + SM_QO + max(2 * i - 1, 0) * 8192, tl->o + tt2 * 14336 + max(2 * i - 1, 0) * 2048, i ? 16384 : 8192, sb + SM_RAW + 8 * i);
                }
            }
            if (lane == 0) STAMP(20);
            wait_until(t_o + GO_O + STOP2);
            if (lane == 0) mbar_arrive(bars + 8 * B_FULLX);
            mbar_wait(bars + 8 * (B_DONEO + POLL_H), 0);
            const uint32_t* src = tl->hn + pr3 * 32 * 7168 + col3 * 256;
            uint32_t bytes = early ? 10240 : 14336, dst = sb + SM_BRING, top = dst + (early ? NE_SLOTS * 10240 : NB_SLOTS * 14336), raw = sb + SM_RAW + 32;
            auto issue = [&]() {
                if (elect()) bulk_ld(dst, src, bytes, raw);
                src += 7168; raw += 8; dst += bytes;
                if (dst == top) dst = sb + SM_BRING;
            };
            uint2 th;
            do { th = ld_relaxed2((const uint2*)sc->go + (lane & 15)); } while (!__all_sync(0xffffffffu, th.x == ep));
            STAMP(42);
            mbar_wait(bars + 8 * (B_DONEO + 3), 0);
            {
                uint32_t bit = 1, wait = ~1u;
                wait_until(__shfl_sync(0xffffffffu, th.y, 0) + GO_H);
                #pragma unroll 1
                do {
                    while (wait & bit) wait = __ballot_sync(0xffffffffu, (int)(gtime32() - th.y - GO_H) < 0);
                    if (bit == 1) STAMP(29);
                    issue();
                    if (bit == 1 << STOP3 && lane == 0) mbar_arrive(bars + 8 * (B_FULLX + 1));
                    bit *= 2;
                } while (dst != sb + SM_BRING);
            }
            uint32_t done = bars + 8 * B_DONE;
            #pragma unroll 1
            do { mbar_wait(done, 0); done += 8; issue(); } while (raw != sb + SM_RAW + 288);
            if (early) mbar_wait(bars + 8 * (B_DONE + 31), 0);
            src = tl->u + (q >> 1) * 28 * 7168 + (q & 1) * 3584; bytes = 14336; dst = sb + SM_BRING; top = dst + NB_SLOTS * 14336;
            done = bars + 8 * (B_DONE + 24);
            #pragma unroll 1
            for (uint32_t par = 0; par < 2; par++) {
                mbar_wait(bars + 8 * (B_GO + par), 0);
                const uint32_t ts = *(volatile uint32_t*)(smem_raw + SM_TIME + 128 * par + 4 * lane);
                if (par) done = bars + 8 * B_DONE;
                uint32_t bit = 1, wait = ~1u;
                wait_until(__shfl_sync(0xffffffffu, ts, 0));
                #pragma unroll 1
                do {
                    while (wait & bit) wait = __ballot_sync(0xffffffffu, (int)(gtime32() - ts) < 0);
                    if (bit == 1) STAMP(par ? 36 : 30);
                    mbar_wait(done, par); done += 8;
                    issue();
                    bit *= 2;
                } while (bit != (par ? 1 << 20 : 1 << 8));
            }
        }
    }
}

typedef CUresult (*EncodeFn)(CUtensorMap*, CUtensorMapDataType, cuuint32_t, void*, const cuuint64_t*, const cuuint64_t*, const cuuint32_t*,
                             const cuuint32_t*, CUtensorMapInterleave, CUtensorMapSwizzle, CUtensorMapL2promotion, CUtensorMapFloatOOBfill);

void make_map(EncodeFn fn, CUtensorMap* tm, const void* ptr, int rank, const cuuint64_t* dims, const cuuint64_t* strides, const cuuint32_t* box, CUtensorMapSwizzle sw) {
    cuuint32_t es[5] = {1, 1, 1, 1, 1};
    fn(tm, CU_TENSOR_MAP_DATA_TYPE_BFLOAT16, rank, const_cast<void*>(ptr), dims, strides, box, es, CU_TENSOR_MAP_INTERLEAVE_NONE, sw,
       CU_TENSOR_MAP_L2_PROMOTION_NONE, CU_TENSOR_MAP_FLOAT_OOB_FILL_NONE);
}

}

extern "C" void kernel_launch(void* const* d_in, const int* in_sizes, int n_in, void* d_out, int out_size) {
    const __nv_bfloat16* x = (const __nv_bfloat16*)d_in[0];
    const __nv_bfloat16* wqkv = (const __nv_bfloat16*)d_in[1];
    const __nv_bfloat16* wo = (const __nv_bfloat16*)d_in[2];
    const __nv_bfloat16* w1 = (const __nv_bfloat16*)d_in[4];
    const __nv_bfloat16* b1 = (const __nv_bfloat16*)d_in[5];
    const __nv_bfloat16* w2 = (const __nv_bfloat16*)d_in[6];
    const __nv_bfloat16* b2 = (const __nv_bfloat16*)d_in[7];

    void* fnp = nullptr; cudaDriverEntryPointQueryResult qr;
    cudaGetDriverEntryPoint("cuTensorMapEncodeTiled", &fnp, cudaEnableDefault, &qr);
    EncodeFn fn = (EncodeFn)fnp;
    CUtensorMap tx, twqkv, two64, two48, tw1, tw2, txr64, txr48, tout64, tout48;
    { cuuint64_t d[3] = {448, 2, 1024}, s[2] = {896, 1792}; cuuint32_t b[3] = {64, 1, 64}; make_map(fn, &tx, x, 3, d, s, b, CU_TENSOR_MAP_SWIZZLE_128B); }
    { cuuint64_t d[2] = {1344, 448}, s[1] = {2688}; cuuint32_t b[2] = {64, 64}; make_map(fn, &twqkv, wqkv, 2, d, s, b, CU_TENSOR_MAP_SWIZZLE_128B); }
    { cuuint64_t d[2] = {448, 448}, s[1] = {896}; cuuint32_t b[2] = {64, 64}; make_map(fn, &two64, wo, 2, d, s, b, CU_TENSOR_MAP_SWIZZLE_128B); }
    { cuuint64_t d[2] = {448, 448}, s[1] = {896}; cuuint32_t b[2] = {48, 64}; make_map(fn, &two48, wo, 2, d, s, b, CU_TENSOR_MAP_SWIZZLE_128B); }
    { cuuint64_t d[5] = {1792, 8, 2, 64, 2}, s[4] = {2 * 3584, 3584, 32 * 3584, 16 * 3584}; cuuint32_t b[5] = {64, 8, 2, 8, 1}; make_map(fn, &tw1, w1, 5, d, s, b, CU_TENSOR_MAP_SWIZZLE_128B); }
    { cuuint64_t d[5] = {2048, 8, 2, 56, 2}, s[4] = {4096, 16 * 4096, 32 * 4096, 8 * 4096}; cuuint32_t b[5] = {64, 8, 2, 8, 1}; make_map(fn, &tw2, w2, 5, d, s, b, CU_TENSOR_MAP_SWIZZLE_128B); }
    { cuuint64_t d[2] = {448, 2048}, s[1] = {896}; cuuint32_t b[2] = {64, 64}; make_map(fn, &txr64, x, 2, d, s, b, CU_TENSOR_MAP_SWIZZLE_128B); }
    { cuuint64_t d[2] = {448, 2048}, s[1] = {896}; cuuint32_t b[2] = {48, 64}; make_map(fn, &txr48, x, 2, d, s, b, CU_TENSOR_MAP_SWIZZLE_128B); }
    { cuuint64_t d[2] = {448, 2048}, s[1] = {896}; cuuint32_t b[2] = {64, 16}; make_map(fn, &tout64, d_out, 2, d, s, b, CU_TENSOR_MAP_SWIZZLE_128B); }
    { cuuint64_t d[2] = {448, 2048}, s[1] = {896}; cuuint32_t b[2] = {48, 16}; make_map(fn, &tout48, d_out, 2, d, s, b, CU_TENSOR_MAP_SWIZZLE_128B); }

    void* scv = nullptr;
    cudaGetSymbolAddress(&scv, g_scratch);
    Scratch* scp = (Scratch*)scv;
    int dev = 0, sms = 0;
    cudaGetDevice(&dev);
    cudaDeviceGetAttribute(&sms, cudaDevAttrMultiProcessorCount, dev);
    if (sms == 132) {
        cudaFuncSetAttribute(fused_kernel<true>, cudaFuncAttributeMaxDynamicSharedMemorySize, SM_TOTAL);
        fused_kernel<true><<<132, 384, SM_TOTAL>>>(scp, wo, w1, b1, w2, b2, tx, twqkv, two64, two48, tw1, tw2, txr64, txr48, tout64, tout48);
    } else {
        cudaFuncSetAttribute(fused_kernel<false>, cudaFuncAttributeMaxDynamicSharedMemorySize, SM_TOTAL);
        fused_kernel<false><<<132, 384, SM_TOTAL>>>(scp, wo, w1, b1, w2, b2, tx, twqkv, two64, two48, tw1, tw2, txr64, txr48, tout64, tout48);
    }
}
```

```cpp
#include <cuda_runtime.h>
#include <cuda_bf16.h>
#include <cuda.h>
#include <stdint.h>

namespace {

constexpr int D_ = 448;
constexpr float LN_EPS = 1e-5f;
constexpr float LOG2E_SCALE = 0.1889822365046136f * 1.4426950408889634f;

struct Tiles {
    uint32_t o[32 * 57344 / 4];
    uint32_t hn[4 * 32 * 14336 / 4];
    uint32_t u[4 * 28 * 14336 / 4];
};
struct Scratch {
    uint4 halo[128 * 2 * 2 * 3 * 32];
    uint4 stats[32 * 4 * 64];
    uint4 hint_k[128 * 2];
    uint4 hint_o[32 * 32 * 2];
    uint4 hint_h[4 * 32 * 2];
    uint4 hint_u[128 * 2];
    uint4 go[24];
    uint32_t epoch[160];
    uint32_t clean;
    alignas(1024) Tiles tiles[2];
};
__device__ Scratch g_scratch;
#define STAMP(i) do {} while (0)
#define FST(i) do {} while (0)
#define TSARG
#define TSVAL

constexpr uint32_t SB = 1024;
constexpr int SM_SLOT = 16384;
__device__ __forceinline__ constexpr uint32_t slot_x(int kb) { return (kb ? 6 + kb : 0) * SM_SLOT; }
__device__ __forceinline__ constexpr uint32_t slot_kv(int kb) { return (kb < 5 ? 2 + kb : 6 - kb) * SM_SLOT; }
__device__ __forceinline__ constexpr uint32_t slot_wo(int kb) { return (kb < 6 ? 2 + kb : 12) * SM_SLOT; }
constexpr int SM_QO = 8 * SM_SLOT;
constexpr int SM_HALOK = SM_QO + 57344, SM_HALOV = 1 * SM_SLOT;
constexpr int NA_SLOTS = 6, NB_SLOTS = 8;
constexpr int SM_ARING = 0;
constexpr int SM_BRING = NA_SLOTS * 16384;
constexpr int SM_H = 212992;
__device__ __forceinline__ uint32_t halo_kin(int par, int lane) { return SB + SM_H + 8192 + par * 4096 + lane * 128 + ((~lane & 6) << 4); }
constexpr int SM_BAR = 229376;
constexpr int SM_TAG = SM_BAR + 1536;
constexpr int SM_TIME = SM_TAG + 256;
constexpr int SM_TOTAL = SM_TIME + 256;
constexpr int B_FULLX = 0;
constexpr int B_FULLKV = 7;
constexpr int B_FQ = 14;
constexpr int B_DONE1 = 16;
constexpr int B_DONEX = 23;
constexpr int B_DONEQ = 24;
constexpr int B_DONEO = 25;
constexpr int B_FULLO = 29;
constexpr int B_FULLWO = 33;
constexpr int B_END = 34;
constexpr int B_HALO = 35;
constexpr int B_FULLA = 39;
constexpr int B_FULLB = 55;
constexpr int B_DONE = 87;
constexpr int B_GO = 119;
constexpr int B_CLR = 121;
constexpr int SM_RAW = SM_BAR + 8 * 124;

constexpr long long WD_CLKS = 2000000000ll;

template<int N> struct Int { static constexpr int value = N; };
template<int A, int B, class F> __device__ __forceinline__ void static_for(F&& f) { if constexpr (A < B) { f(Int<A>()); static_for<A + 1, B>(f); } }

__device__ __forceinline__ uint32_t smem_u32(const void* p) { return (uint32_t)__cvta_generic_to_shared(p); }
__device__ __forceinline__ void mbar_init(uint32_t bar, uint32_t cnt) { asm volatile("mbarrier.init.shared::cta.b64 [%0], %1;" :: "r"(bar), "r"(cnt) : "memory"); }
__device__ __forceinline__ void mbar_expect(uint32_t bar, uint32_t bytes) { asm volatile("mbarrier.arrive.expect_tx.shared::cta.b64 _, [%0], %1;" :: "r"(bar), "r"(bytes) : "memory"); }
__device__ __forceinline__ void mbar_arrive(uint32_t bar) { asm volatile("mbarrier.arrive.shared::cta.b64 _, [%0];" :: "r"(bar) : "memory"); }
__device__ __forceinline__ bool mbar_test(uint32_t bar, uint32_t parity) {
    uint32_t ok;
    asm volatile("{\n.reg .pred p;\nmbarrier.test_wait.parity.shared::cta.b64 p, [%1], %2;\nselp.u32 %0, 1, 0, p;\n}" : "=r"(ok) : "r"(bar), "r"(parity) : "memory");
    return ok;
}
__device__ __forceinline__ void mbar_wait(uint32_t bar, uint32_t parity) {
    asm volatile("{\n.reg .pred p;\n"
                 "WAIT_LOOP:\n"
                 "mbarrier.try_wait.parity.shared::cta.b64 p, [%0], %1;\n"
                 "@!p bra WAIT_LOOP;\n}" :: "r"(bar), "r"(parity) : "memory");
}
__device__ __forceinline__ void mbar_wait_unless(uint32_t ready, uint32_t bar, uint32_t parity) {
    asm volatile("{\n.reg .pred p;\nsetp.ne.u32 p, %1, 0;\n@p bra.uni DONE;\n"
                 "WAIT_LOOP:\n"
                 "mbarrier.try_wait.parity.shared::cta.b64 p, [%0], %2;\n"
                 "@!p bra.uni WAIT_LOOP;\nDONE:\n}" :: "r"(bar), "r"(ready), "r"(parity) : "memory");
}
__device__ __forceinline__ void mbar_wait_wd(uint32_t bar, uint32_t parity) {
    asm volatile("{\n.reg .pred p, q;\n.reg .u32 s, t;\nmov.u32 s, %%clock;\n"
                 "WAIT_LOOP:\n"
                 "mbarrier.try_wait.parity.shared::cta.b64 p, [%0], %1;\nmov.u32 t, %%clock;\nsub.u32 t, t, s;\nsetp.lt.and.s32 q, t, 0, !p;\n@q trap;\n"
                 "@!p bra WAIT_LOOP;\n}" :: "r"(bar), "r"(parity) : "memory");
}
__device__ __forceinline__ bool elect() { uint32_t p; asm volatile("{\n.reg .pred P;\nelect.sync _|P, 0xffffffff;\nselp.u32 %0, 1, 0, P;\n}" : "=r"(p)); return p; }
__device__ __forceinline__ void tma2d(uint32_t dst, const CUtensorMap* tm, int c0, int c1, uint32_t bar) {
    asm volatile("cp.async.bulk.tensor.2d.shared::cluster.global.mbarrier::complete_tx::bytes [%0], [%1, {%3, %4}], [%2];" :: "r"(dst), "l"(tm), "r"(bar), "r"(c0), "r"(c1) : "memory");
}
__device__ __forceinline__ void tma3d(uint32_t dst, const CUtensorMap* tm, int c0, int c1, int c2, uint32_t bar) {
    asm volatile("cp.async.bulk.tensor.3d.shared::cluster.global.mbarrier::complete_tx::bytes [%0], [%1, {%3, %4, %5}], [%2];" :: "r"(dst), "l"(tm), "r"(bar), "r"(c0), "r"(c1), "r"(c2) : "memory");
}
__device__ __forceinline__ void tma5d(uint32_t dst, const CUtensorMap* tm, int c0, int c3, int c4, uint32_t bar) {
    asm volatile("cp.async.bulk.tensor.5d.shared::cluster.global.mbarrier::complete_tx::bytes [%0], [%1, {%3, 0, 0, %4, %5}], [%2];" :: "r"(dst), "l"(tm), "r"(bar), "r"(c0), "r"(c3), "r"(c4) : "memory");
}
__device__ __forceinline__ void tma5d_prefetch(const CUtensorMap* tm, int c0, int c3, int c4) {
    asm volatile("cp.async.bulk.prefetch.tensor.5d.L2.global [%0, {%1, 0, 0, %2, %3}];" :: "l"(tm), "r"(c0), "r"(c3), "r"(c4) : "memory");
}
__device__ __forceinline__ void tma2d_store(const CUtensorMap* tm, int c0, int c1, uint32_t src) {
    asm volatile("cp.async.bulk.tensor.2d.global.shared::cta.bulk_group [%0, {%2, %3}], [%1];" :: "l"(tm), "r"(src), "r"(c0), "r"(c1) : "memory");
}
__device__ __forceinline__ void bulk_st(void* dst, uint32_t src, uint32_t bytes) {
    asm volatile("cp.async.bulk.global.shared::cta.bulk_group [%0], [%1], %2;" :: "l"(dst), "r"(src), "r"(bytes) : "memory");
}
__device__ __forceinline__ void bulk_ld(uint32_t dst, const void* src, uint32_t bytes, uint32_t bar) {
    asm volatile("cp.async.bulk.shared::cluster.global.mbarrier::complete_tx::bytes [%0], [%1], %2, [%3];" :: "r"(dst), "l"(src), "r"(bytes), "r"(bar) : "memory");
}
__device__ __forceinline__ void bulk_prefetch(const void* src, uint32_t bytes) { asm volatile("cp.async.bulk.prefetch.L2.global [%0], %1;" :: "l"(src), "r"(bytes) : "memory"); }
__device__ __forceinline__ void prefetch_map(const CUtensorMap* tm) { asm volatile("prefetch.tensormap [%0];" :: "l"(tm) : "memory"); }
__device__ __forceinline__ void st_global_if(uint32_t c, uint32_t* p, uint32_t v) {
    asm volatile("{\n.reg .pred p;\nsetp.ne.u32 p, %2, 0;\n@p st.global.u32 [%0], %1;\n}" :: "l"(p), "r"(v), "r"(c) : "memory");
}
__device__ __forceinline__ void st_relaxed4_if(bool c, uint4* p, uint32_t a, uint32_t b, uint32_t d) {
    asm volatile("{\n.reg .b128 t;\n.reg .b64 a, b;\n.reg .pred p;\nsetp.ne.u32 p, %4, 0;\nmov.b64 a, {%1, %2};\nmov.b64 b, {%3, %3};\nmov.b128 t, {a, b};\n@p st.relaxed.gpu.global.b128 [%0], t;\n}" :: "l"(p), "r"(a), "r"(b), "r"(d), "r"((uint32_t)c) : "memory");
}
__device__ __forceinline__ void pin_ptr(uint32_t never, const void* a) {
    asm volatile("{\n.reg .pred p;\nsetp.ne.u32 p, %1, 0;\n@p st.shared.u64 [%1], %0;\n}" :: "l"(a), "r"(never) : "memory");
}
__device__ __forceinline__ void pin4(uint32_t never, float a, float b, float c, float d) {
    asm volatile("{\n.reg .pred p;\nsetp.ne.u32 p, %4, 0;\n@p st.shared.v4.f32 [%4], {%0,%1,%2,%3};\n}" :: "f"(a), "f"(b), "f"(c), "f"(d), "r"(never) : "memory");
}
__device__ __forceinline__ void fence_async_smem() { asm volatile("fence.proxy.async.shared::cta;" ::: "memory"); }
__device__ __forceinline__ uint32_t ld_acquire(const void* p) { uint32_t v; asm volatile("ld.acquire.gpu.global.u32 %0, [%1];" : "=r"(v) : "l"(p) : "memory"); return v; }
__device__ __forceinline__ void st_release(void* p, uint32_t v) { asm volatile("st.release.gpu.global.u32 [%0], %1;" :: "l"(p), "r"(v) : "memory"); }
__device__ __forceinline__ uint32_t ld_relaxed(const void* p) { uint32_t v; asm volatile("ld.relaxed.gpu.global.u32 %0, [%1];" : "=r"(v) : "l"(p) : "memory"); return v; }
__device__ __forceinline__ uint2 ld_relaxed2(const void* p) {
    uint2 v; asm volatile("{\n.reg .b64 a;\nld.relaxed.gpu.global.b64 a, [%2];\nmov.b64 {%0, %1}, a;\n}" : "=r"(v.x), "=r"(v.y) : "l"(p) : "memory"); return v;
}
__device__ __forceinline__ void st_relaxed2(void* p, uint32_t a, uint32_t b) {
    asm volatile("{\n.reg .b64 a;\nmov.b64 a, {%1, %2};\nst.relaxed.gpu.global.b64 [%0], a;\n}" :: "l"(p), "r"(a), "r"(b) : "memory");
}
__device__ __forceinline__ uint4 ld_relaxed4(const uint4* p) {
    uint4 v;
    asm volatile("{\n.reg .b128 t;\n.reg .b64 a, b;\nld.relaxed.gpu.global.b128 t, [%4];\nmov.b128 {a, b}, t;\nmov.b64 {%0, %1}, a;\nmov.b64 {%2, %3}, b;\n}" : "=r"(v.x), "=r"(v.y), "=r"(v.z), "=r"(v.w) : "l"(p) : "memory");
    return v;
}
__device__ __forceinline__ void st_relaxed4(uint4* p, uint32_t a, uint32_t b, uint32_t c, uint32_t d) {
    asm volatile("{\n.reg .b128 t;\n.reg .b64 a, b;\nmov.b64 a, {%1, %2};\nmov.b64 b, {%3, %4};\nmov.b128 t, {a, b};\nst.relaxed.gpu.global.b128 [%0], t;\n}" :: "l"(p), "r"(a), "r"(b), "r"(c), "r"(d) : "memory");
}
__device__ __forceinline__ uint32_t ld_u16(const unsigned short* p) { uint32_t v; asm volatile("ld.volatile.global.u16 %0, [%1];" : "=r"(v) : "l"(p) : "memory"); return v; }
__device__ __forceinline__ uint32_t ld_volatile(const uint32_t* p) { uint32_t v; asm volatile("ld.volatile.global.u32 %0, [%1];" : "=r"(v) : "l"(p) : "memory"); return v; }
__device__ __forceinline__ void named_arrive(int id, int n) { asm volatile("bar.arrive %0, %1;" :: "r"(id), "r"(n) : "memory"); }
__device__ __forceinline__ void named_sync(int id, int n) { asm volatile("bar.sync %0, %1;" :: "r"(id), "r"(n) : "memory"); }
__device__ __forceinline__ bool named_any(int id, int n, bool v) {
    uint32_t r; asm volatile("{\n.reg .pred p, q;\nsetp.ne.u32 p, %3, 0;\nbar.red.or.pred q, %1, %2, p;\nselp.u32 %0, 1, 0, q;\n}" : "=r"(r) : "r"(id), "r"(n), "r"((uint32_t)v) : "memory"); return r;
}
__device__ __forceinline__ void wg_fence() { asm volatile("wgmma.fence.sync.aligned;" ::: "memory"); }
__device__ __forceinline__ void wg_commit() { asm volatile("wgmma.commit_group.sync.aligned;" ::: "memory"); }
template<int N> __device__ __forceinline__ void wg_wait() { asm volatile("wgmma.wait_group.sync.aligned %0;" :: "n"(N) : "memory"); }
template<int N> __device__ __forceinline__ void reg_fence(float (&d)[N]) {
    #pragma unroll
    for (int i = 0; i < N; i++) asm volatile("" : "+f"(d[i]) :: "memory");
}
__device__ __forceinline__ constexpr uint64_t mkdesc(uint32_t addr, uint32_t lbo, uint32_t sbo, uint32_t sw) {
    return (uint64_t)((addr & 0x3FFFF) >> 4) | ((uint64_t)(lbo >> 4) << 16) | ((uint64_t)(sbo >> 4) << 32) | ((uint64_t)sw << 62);
}
__device__ __forceinline__ void ldsm4(uint32_t (&r)[4], uint32_t addr) {
    asm volatile("ldmatrix.sync.aligned.m8n8.x4.shared.b16 {%0,%1,%2,%3}, [%4];" : "=r"(r[0]), "=r"(r[1]), "=r"(r[2]), "=r"(r[3]) : "r"(addr) : "memory");
}
__device__ __forceinline__ void stsm4(uint32_t addr, uint32_t r0, uint32_t r1, uint32_t r2, uint32_t r3) {
    asm volatile("stmatrix.sync.aligned.m8n8.x4.shared.b16 [%0], {%1,%2,%3,%4};" :: "r"(addr), "r"(r0), "r"(r1), "r"(r2), "r"(r3) : "memory");
}
__device__ __forceinline__ void sts4(uint32_t a, uint32_t x, uint32_t y, uint32_t z, uint32_t w) { asm volatile("st.shared.v4.u32 [%0], {%1,%2,%3,%4};" :: "r"(a), "r"(x), "r"(y), "r"(z), "r"(w) : "memory"); }
__device__ __forceinline__ uint4 lds4(uint32_t a) { uint4 v; asm volatile("ld.shared.v4.u32 {%0,%1,%2,%3}, [%4];" : "=r"(v.x), "=r"(v.y), "=r"(v.z), "=r"(v.w) : "r"(a) : "memory"); return v; }
__device__ __forceinline__ uint32_t movtrans(uint32_t a) { uint32_t d; asm volatile("movmatrix.sync.aligned.m8n8.trans.b16 %0, %1;" : "=r"(d) : "r"(a)); return d; }
__device__ __forceinline__ uint32_t pack_bf16(float lo, float hi) { uint32_t r; asm("cvt.rn.bf16x2.f32 %0, %1, %2;" : "=r"(r) : "f"(hi), "f"(lo)); return r; }
__device__ __forceinline__ void sub_bf16x2(uint32_t& a, uint32_t b) { asm volatile("sub.rn.bf16x2 %0, %0, %1;" : "+r"(a) : "r"(b)); }
__device__ __forceinline__ float bf_lo(uint32_t v) { return __uint_as_float(v << 16); }
__device__ __forceinline__ float bf_hi(uint32_t v) { return __uint_as_float(v & 0xffff0000u); }
__device__ __forceinline__ void mma16816(float (&c)[4], uint32_t a0, uint32_t a1, uint32_t a2, uint32_t a3, uint32_t b0, uint32_t b1) {
    asm volatile("mma.sync.aligned.m16n8k16.row.col.f32.bf16.bf16.f32 {%0,%1,%2,%3}, {%4,%5,%6,%7}, {%8,%9}, {%0,%1,%2,%3};"
        : "+f"(c[0]), "+f"(c[1]), "+f"(c[2]), "+f"(c[3]) : "r"(a0), "r"(a1), "r"(a2), "r"(a3), "r"(b0), "r"(b1));
}
__device__ __forceinline__ void mma1688(float (&c)[4], uint32_t a0, uint32_t a1, uint32_t b0) {
    asm volatile("mma.sync.aligned.m16n8k8.row.col.f32.bf16.bf16.f32 {%0,%1,%2,%3}, {%4,%5}, {%6}, {%0,%1,%2,%3};"
        : "+f"(c[0]), "+f"(c[1]), "+f"(c[2]), "+f"(c[3]) : "r"(a0), "r"(a1), "r"(b0));
}
__device__ __forceinline__ float quad_sum(float v) { v += __shfl_xor_sync(0xffffffffu, v, 1); v += __shfl_xor_sync(0xffffffffu, v, 2); return v; }
__device__ __forceinline__ float quad_max(float v) { v = fmaxf(v, __shfl_xor_sync(0xffffffffu, v, 1)); v = fmaxf(v, __shfl_xor_sync(0xffffffffu, v, 2)); return v; }
__device__ __forceinline__ float ex2(float x) { float y; asm("ex2.approx.ftz.f32 %0, %1;" : "=f"(y) : "f"(x)); return y; }
__device__ __forceinline__ float rsqrt_approx(float x) { float y; asm("rsqrt.approx.ftz.f32 %0, %1;" : "=f"(y) : "f"(x)); return y; }
__device__ __forceinline__ float rcp_approx(float x) { float y; asm("rcp.approx.ftz.f32 %0, %1;" : "=f"(y) : "f"(x)); return y; }
constexpr float GELU_K1 = 2.f * 0.7978845608028654f;
__device__ __forceinline__ float gelu_half(float hx, float k1) {
    const float z = hx * fmaf(hx * hx, 8.f * 0.044715f * 0.7978845608028654f, k1);
    float t; asm("tanh.approx.f32 %0, %1;" : "=f"(t) : "f"(z));
    return fmaf(hx, t, hx);
}
__device__ __forceinline__ uint32_t gtime32() { uint64_t t; asm volatile("mov.u64 %0, %%globaltimer;" : "=l"(t)); return (uint32_t)t; }
__device__ __forceinline__ uint32_t clock32() { uint32_t t; asm volatile("mov.u32 %0, %%clock;" : "=r"(t)); return t; }
#define PF_PACE 160
#define PF_AT 14500
#define PF_N 240
#define NSQ 6
#define NPIPE 2
#define HALO_AT 3
#define HINT_U 18
#define HINT_E 16
#define SP_AT 2000
#define A_SCHED 0x322188
#define WO_ORD0 0x4321065
#define WO_ORD1 0x3465210
#define CL_AT 23
#define WARM_AT 300
#define GO_H 1632
#define GO_E 1950
#define GO_U 2050
#define GO_O 1312
#define LATE_O 256
#define LATE_AT 0
#define LATE_AT4 0
#define GDEP 4
#define START4 30
#define NE_SLOTS 11
#define POLL_E 26
#define AE_END 18
#define AE_W2 27
#define PF1_AT 11000
#define PF1_N 80
#define PF1_PACE 160
#define GO_E2 400
#define GO_U2 400
#define POLL_I 20
#define POLL_N 19
#define ROLES 0x65431027u
#define A4_FROM 23
#define A4_DLY 2
#define SPIN_N 3
#define STOP2 150
#define PF0_AT 4500
#define PF0_N 48
#define PF0_PACE 140
#define POLL_H 3
#define CH_H 8
#define HINT_F 4
#define CL_N 4
#define CL_P2 7
#define STOP3 3
#define PF_OFS 0
#define PFC_AT 0
#define PFC_E 0
#define PFC_N 16
#define PFW_AT 6
#define PFW_0 10
#define PFW_N 14
template<int TB> __device__ __forceinline__ void wgmma_rs56(float (&d)[28], const uint32_t (&a)[4], uint64_t db, int sc) {
    asm volatile("{\n.reg .pred p;\nsetp.ne.b32 p, %33, 0;\n"
        "wgmma.mma_async.sync.aligned.m64n56k16.f32.bf16.bf16 {%0, %1, %2, %3, %4, %5, %6, %7, %8, %9, %10, %11, %12, %13, %14, %15, %16, %17, %18, %19, %20, %21, %22, %23, %24, %25, %26, %27}, {%28, %29, %30, %31}, %32, p, 1, 1, %34;\n}\n"
        : "+f"(d[0]), "+f"(d[1]), "+f"(d[2]), "+f"(d[3]), "+f"(d[4]), "+f"(d[5]), "+f"(d[6]), "+f"(d[7]), "+f"(d[8]), "+f"(d[9]), "+f"(d[10]), "+f"(d[11]), "+f"(d[12]), "+f"(d[13]), "+f"(d[14]), "+f"(d[15]), "+f"(d[16]), "+f"(d[17]), "+f"(d[18]), "+f"(d[19]), "+f"(d[20]), "+f"(d[21]), "+f"(d[22]), "+f"(d[23]), "+f"(d[24]), "+f"(d[25]), "+f"(d[26]), "+f"(d[27])
        : "r"(a[0]), "r"(a[1]), "r"(a[2]), "r"(a[3]), "l"(db), "r"(sc), "n"(TB));
}

template<int TA, int TB, int SC = 1> __device__ __forceinline__ void wgmma_ss112(float (&d)[56], uint64_t da, uint64_t db) {
    asm volatile("wgmma.mma_async.sync.aligned.m64n112k16.f32.bf16.bf16 {%0, %1, %2, %3, %4, %5, %6, %7, %8, %9, %10, %11, %12, %13, %14, %15, %16, %17, %18, %19, %20, %21, %22, %23, %24, %25, %26, %27, %28, %29, %30, %31, %32, %33, %34, %35, %36, %37, %38, %39, %40, %41, %42, %43, %44, %45, %46, %47, %48, %49, %50, %51, %52, %53, %54, %55}, %56, %57, %60, 1, 1, %58, %59;\n"
        : "+f"(d[0]), "+f"(d[1]), "+f"(d[2]), "+f"(d[3]), "+f"(d[4]), "+f"(d[5]), "+f"(d[6]), "+f"(d[7]), "+f"(d[8]), "+f"(d[9]), "+f"(d[10]), "+f"(d[11]), "+f"(d[12]), "+f"(d[13]), "+f"(d[14]), "+f"(d[15]), "+f"(d[16]), "+f"(d[17]), "+f"(d[18]), "+f"(d[19]), "+f"(d[20]), "+f"(d[21]), "+f"(d[22]), "+f"(d[23]), "+f"(d[24]), "+f"(d[25]), "+f"(d[26]), "+f"(d[27]), "+f"(d[28]), "+f"(d[29]), "+f"(d[30]), "+f"(d[31]), "+f"(d[32]), "+f"(d[33]), "+f"(d[34]), "+f"(d[35]), "+f"(d[36]), "+f"(d[37]), "+f"(d[38]), "+f"(d[39]), "+f"(d[40]), "+f"(d[41]), "+f"(d[42]), "+f"(d[43]), "+f"(d[44]), "+f"(d[45]), "+f"(d[46]), "+f"(d[47]), "+f"(d[48]), "+f"(d[49]), "+f"(d[50]), "+f"(d[51]), "+f"(d[52]), "+f"(d[53]), "+f"(d[54]), "+f"(d[55])
        : "l"(da), "l"(db), "n"(TA), "n"(TB), "n"(SC));
}

template<int TA, int TB, int SC = 1> __device__ __forceinline__ void wgmma_ss80(float (&d)[40], uint64_t da, uint64_t db) {
    asm volatile("wgmma.mma_async.sync.aligned.m64n80k16.f32.bf16.bf16 {%0, %1, %2, %3, %4, %5, %6, %7, %8, %9, %10, %11, %12, %13, %14, %15, %16, %17, %18, %19, %20, %21, %22, %23, %24, %25, %26, %27, %28, %29, %30, %31, %32, %33, %34, %35, %36, %37, %38, %39}, %40, %41, %44, 1, 1, %42, %43;\n"
        : "+f"(d[0]), "+f"(d[1]), "+f"(d[2]), "+f"(d[3]), "+f"(d[4]), "+f"(d[5]), "+f"(d[6]), "+f"(d[7]), "+f"(d[8]), "+f"(d[9]), "+f"(d[10]), "+f"(d[11]), "+f"(d[12]), "+f"(d[13]), "+f"(d[14]), "+f"(d[15]), "+f"(d[16]), "+f"(d[17]), "+f"(d[18]), "+f"(d[19]), "+f"(d[20]), "+f"(d[21]), "+f"(d[22]), "+f"(d[23]), "+f"(d[24]), "+f"(d[25]), "+f"(d[26]), "+f"(d[27]), "+f"(d[28]), "+f"(d[29]), "+f"(d[30]), "+f"(d[31]), "+f"(d[32]), "+f"(d[33]), "+f"(d[34]), "+f"(d[35]), "+f"(d[36]), "+f"(d[37]), "+f"(d[38]), "+f"(d[39])
        : "l"(da), "l"(db), "n"(TA), "n"(TB), "n"(SC));
}

template<int TA, int TB, int SC = 1> __device__ __forceinline__ void wgmma_ss64(float (&d)[32], uint64_t da, uint64_t db) {
    asm volatile("wgmma.mma_async.sync.aligned.m64n64k16.f32.bf16.bf16 {%0, %1, %2, %3, %4, %5, %6, %7, %8, %9, %10, %11, %12, %13, %14, %15, %16, %17, %18, %19, %20, %21, %22, %23, %24, %25, %26, %27, %28, %29, %30, %31}, %32, %33, %36, 1, 1, %34, %35;\n"
        : "+f"(d[0]), "+f"(d[1]), "+f"(d[2]), "+f"(d[3]), "+f"(d[4]), "+f"(d[5]), "+f"(d[6]), "+f"(d[7]), "+f"(d[8]), "+f"(d[9]), "+f"(d[10]), "+f"(d[11]), "+f"(d[12]), "+f"(d[13]), "+f"(d[14]), "+f"(d[15]), "+f"(d[16]), "+f"(d[17]), "+f"(d[18]), "+f"(d[19]), "+f"(d[20]), "+f"(d[21]), "+f"(d[22]), "+f"(d[23]), "+f"(d[24]), "+f"(d[25]), "+f"(d[26]), "+f"(d[27]), "+f"(d[28]), "+f"(d[29]), "+f"(d[30]), "+f"(d[31])
        : "l"(da), "l"(db), "n"(TA), "n"(TB), "n"(SC));
}

template<int TA, int TB, int SC = 1> __device__ __forceinline__ void wgmma_ss48(float (&d)[24], uint64_t da, uint64_t db) {
    asm volatile("wgmma.mma_async.sync.aligned.m64n48k16.f32.bf16.bf16 {%0, %1, %2, %3, %4, %5, %6, %7, %8, %9, %10, %11, %12, %13, %14, %15, %16, %17, %18, %19, %20, %21, %22, %23}, %24, %25, %28, 1, 1, %26, %27;\n"
        : "+f"(d[0]), "+f"(d[1]), "+f"(d[2]), "+f"(d[3]), "+f"(d[4]), "+f"(d[5]), "+f"(d[6]), "+f"(d[7]), "+f"(d[8]), "+f"(d[9]), "+f"(d[10]), "+f"(d[11]), "+f"(d[12]), "+f"(d[13]), "+f"(d[14]), "+f"(d[15]), "+f"(d[16]), "+f"(d[17]), "+f"(d[18]), "+f"(d[19]), "+f"(d[20]), "+f"(d[21]), "+f"(d[22]), "+f"(d[23])
        : "l"(da), "l"(db), "n"(TA), "n"(TB), "n"(SC));
}

template<int NKB, int NR>
__device__ __forceinline__ void mix_mainloop(TSARG float (&acc)[NR], bool leader) {
    constexpr uint32_t sb = SB, bars = sb + SM_BAR, par = NKB == 28;
    constexpr int A0 = NKB == 32 ? 0 : 16 % NA_SLOTS;
    constexpr int DEPTH = NR == 56 ? 1 : 2;
    int bslot = 0, aslot = A0;
    reg_fence(acc);
    #pragma unroll 1
    for (int i = 0; i < NKB / 2; i++) {
        mbar_wait(bars + 8 * (B_FULLA + i), par);
        const uint64_t adesc = mkdesc(sb + SM_ARING, 8192, 1024, 1) + (uint32_t)(aslot * 1024);
        aslot = aslot == NA_SLOTS - 1 ? 0 : aslot + 1;
        #pragma unroll
        for (int jj = 0; jj < 2; jj++) {
            const int j = 2 * i + jj;
            mbar_wait(bars + 8 * (B_FULLB + j), par);
            const uint64_t bdesc = mkdesc(sb + SM_BRING, 128, 1024, 0) + (uint32_t)(bslot * NR * 16);
            bslot = bslot == (NR == 56 ? NB_SLOTS : NE_SLOTS) - 1 ? 0 : bslot + 1;
            wg_fence();
            #pragma unroll
            for (int s = 0; s < 4; s++) {
                if constexpr (NR == 56) wgmma_ss112<1, 1>(acc, adesc + jj * 512 + s * 128, bdesc + s * 16);
                else wgmma_ss80<1, 1>(acc, adesc + jj * 512 + s * 128, bdesc + s * 16);
            }
            wg_commit();
            wg_wait<DEPTH>();
            if (j >= DEPTH && leader) mbar_arrive(bars + 8 * (B_DONE + j - DEPTH));
        }
    }
    if (DEPTH == 2) { wg_wait<1>(); if (leader) mbar_arrive(bars + 8 * (B_DONE + NKB - 2)); }
    wg_wait<0>();
    reg_fence(acc);
    if (leader) mbar_arrive(bars + 8 * (B_DONE + NKB - 1));
}

__device__ __forceinline__ void spin_mma(uint32_t bar, uint32_t never) {
    float d[56];
    #pragma unroll
    for (int i = 0; i < 56; i++) d[i] = 0.f;
    reg_fence(d);
    #pragma unroll 1
    do {
        wg_fence();
        #pragma unroll
        for (int s = 0; s < SPIN_N; s++) wgmma_ss112<1, 1>(d, mkdesc(SB + 2 * SM_SLOT + s * 2048, 8192, 1024, 1), mkdesc(SB + 3 * SM_SLOT + s * 256, 128, 1024, 0));
        wg_commit();
        wg_wait<1>();
    } while (!named_any(11, 128, mbar_test(bar, 1)));
    wg_wait<0>();
    reg_fence(d);
    pin4(never, d[0], d[1], d[2], d[3]);
}

constexpr uint32_t EMPTY = 0xFFFFFFFFu;
__device__ __forceinline__ void post_hint(uint4* p, uint32_t ep, int lane) { if (lane < 2) st_relaxed4(p + lane, ep, ep, ep, ep); }
__device__ __forceinline__ void post_time(uint4* p, uint32_t ep, int lane) { const uint32_t now = gtime32(); if (lane < 2) st_relaxed4(p + lane, ep, now, ep, now); }

__device__ __forceinline__ uint32_t last_hint(TSARG const uint4* hint, uint32_t ep, int st) {
    uint2 v;
    do { v = ld_relaxed2(hint); } while (!__all_sync(0xffffffffu, v.x == ep));
    const uint32_t t1 = gtime32() + 256;
    if (elect()) STAMP(st);
    return t1 - __reduce_min_sync(0xffffffffu, t1 - v.y);
}
__device__ __forceinline__ uint32_t later(uint32_t a, uint32_t b) { return a + max((int)(b - a), 0); }
__device__ __forceinline__ void fetch_times(TSARG const uint4* go, int k, uint32_t ep, int lane) {
    const uint2* p = (const uint2*)(go + 8 + 8 * k) + (k ? lane % 10 : lane & 3);
    uint2 v;
    do { v = ld_relaxed2(p); } while (!__all_sync(0xffffffffu, v.x == ep));
    v.y += k ? (lane < 10 ? GO_U : GO_U + GO_U2) : (lane < 4 ? GO_E : GO_E + GO_E2);
    asm volatile("st.shared.u32 [%0], %1;" :: "r"(SB + SM_TIME + 128 * k + 4 * lane), "r"(v.y) : "memory");
    __syncwarp();
    if (lane == 0) { mbar_arrive(SB + SM_BAR + 8 * (B_GO + k)); STAMP(k ? 43 : 24); }
    __syncwarp();
}
__device__ __forceinline__ void wait_until(uint32_t t) {
    asm volatile("{\n.reg .pred p;\n.reg .u64 a;\n.reg .u32 l, h;\nWAIT_LOOP:\nmov.u64 a, %%globaltimer;\nmov.b64 {l, h}, a;\nsub.u32 l, l, %0;\nsetp.lt.s32 p, l, 0;\n@p bra.uni WAIT_LOOP;\n}" :: "r"(t) : "memory");
}

__device__ __forceinline__ uint32_t check_tile(uint32_t raw, uint32_t full, uint32_t dst, uint32_t lofs, const uint32_t* src, uint32_t bytes, int lane) {
    uint32_t cnt;
    asm volatile("{\n.reg .pred p, e;\n.reg .u32 a, b, c, d;\nmov.u32 %0, 0;\n"
                 "AGAIN:\nand.b32 a, %0, 1;\n"
                 "WAIT:\nmbarrier.try_wait.parity.shared::cta.b64 p, [%1], a;\n@!p bra.uni WAIT;\n"
                 "ld.shared.u32 a, [%4];\nld.shared.u32 b, [%4+4096];\nld.shared.u32 c, [%5+-8192];\nld.shared.u32 d, [%5+-4096];\n"
                 "add.u32 %0, %0, 1;\nmax.u32 a, a, b;\nmax.u32 c, c, d;\nmax.u32 a, a, c;\nsetp.lt.u32 e, %8, 32;\nsetp.eq.and.u32 p, a, 0xFFFFFFFF, e;\n"
                 "vote.sync.any.pred p, p, 0xffffffff;\nsetp.eq.and.u32 e, %8, 0, !p;\n@e mbarrier.arrive.shared::cta.b64 _, [%2];\n"
                 "elect.sync _|e, 0xffffffff;\nand.pred e, e, p;\n"
                 "@e mbarrier.arrive.expect_tx.shared::cta.b64 _, [%1], %7;\n"
                 "@e cp.async.bulk.shared::cluster.global.mbarrier::complete_tx::bytes [%3], [%6], %7, [%1];\n"
                 "@p bra.uni AGAIN;\n}"
                 : "=&r"(cnt) : "r"(raw), "r"(full), "r"(dst), "r"(dst + lofs), "r"(dst + lofs + bytes), "l"(src), "r"(bytes), "r"(lane) : "memory");
    return cnt;
}

template<int ST>
__device__ __forceinline__ void check_tiles(int j, int step, int n, const uint32_t* src, bool small, int lane, bool dry) {
    const uint32_t bytes = small ? 10240 : 14336, nb = small ? NE_SLOTS : NB_SLOTS, lofs = lane * 128 + (lane & 3) * 32 + (lane >> 2) * 4;
    uint32_t sl = j % nb;
    #pragma unroll 1
    for (int inc = dry ? 0 : step; j < n; j += inc, inc = step) {
        const uint32_t c = check_tile(inc ? SB + SM_RAW + 8 * (j + (ST ? 32 * ST - 28 : 0)) : SB + SM_BAR + 8 * B_CLR, SB + SM_BAR + 8 * (j + (ST ? B_FULLB : B_FULLO)),
                                      SB + (ST ? SM_BRING + sl * bytes : SM_QO + max(2 * j - 1, 0) * 8192), lofs, src + (ST ? j * 7168 : max(2 * j - 1, 0) * 2048),
                                      ST ? bytes : j ? 16384 : 8192, inc ? lane : 32);
        sl += inc;
        if (sl >= nb) sl -= nb;
    }
}

__device__ __forceinline__ uint32_t hcol(uint32_t a, int jp) { return (a ^ ((jp & 3) << 5)) + (jp >> 2) * 8192; }

__device__ __forceinline__ uint32_t get_tag() {
    mbar_wait(SB + SM_BAR + 8 * B_CLR, 0);
    uint32_t v; asm volatile("ld.shared.u32 %0, [%1];" : "=r"(v) : "r"(SB + SM_TAG) : "memory"); return v;
}

template<bool USE_SMID>
__global__ void __launch_bounds__(384, 1)
fused_kernel(Scratch* __restrict__ sc, const __nv_bfloat16* __restrict__ wo,
             const __nv_bfloat16* __restrict__ w1, const __nv_bfloat16* __restrict__ b1,
             const __nv_bfloat16* __restrict__ w2, const __nv_bfloat16* __restrict__ b2,
             const __grid_constant__ CUtensorMap tm_x, const __grid_constant__ CUtensorMap tm_wqkv,
             const __grid_constant__ CUtensorMap tm_wo64, const __grid_constant__ CUtensorMap tm_wo48,
             const __grid_constant__ CUtensorMap tm_w1, const __grid_constant__ CUtensorMap tm_w2,
             const __grid_constant__ CUtensorMap tm_xr64, const __grid_constant__ CUtensorMap tm_xr48,
             const __grid_constant__ CUtensorMap tm_out64, const __grid_constant__ CUtensorMap tm_out48) {
    extern __shared__ __align__(1024) uint8_t smem_raw[];
    constexpr uint32_t sb = SB;
    constexpr uint32_t bars = sb + SM_BAR;
    const int tid = threadIdx.x, lane = tid & 31;
    auto get_slot = [&]() {
        int slot;
    if (USE_SMID) {
        asm volatile("{\n.reg .u32 s, t, u, d, a, b, c;\n.reg .pred p, r;\n"
            "mov.u32 s, %%smid;\nshr.u32 t, s, 1;\nsub.u32 u, t, 32;\nmul.lo.u32 d, u, 37;\nshr.u32 d, d, 8;\n"
            "and.b32 a, t, 7;\nshl.b32 a, a, 3;\nshr.u32 c, t, 3;\nadd.u32 a, a, c;\n"
            "mad.lo.u32 b, d, -55, 12;\nshl.b32 c, u, 3;\nadd.u32 b, b, c;\n"
            "setp.lt.u32 p, t, 32;\nselp.u32 a, a, b, p;\n"
            "setp.lt.u32 r, t, 62;\nselp.s32 c, 4, -58, r;\nadd.u32 c, t, c;\nsetp.lt.u32 p, t, 60;\nselp.u32 a, a, c, p;\n"
            "and.b32 s, s, 1;\nshl.b32 a, a, 1;\nadd.u32 %0, a, s;\n}" : "=r"(slot));
    } else slot = blockIdx.x;
        return slot;
    };
    auto load_x = [&](int kb, int row) {
        const uint32_t st = sb + slot_x(kb), bar = bars + 8 * (B_FULLX + kb);
        mbar_expect(bar, 16384);
        tma3d(st, &tm_x, kb * 64, 0, row, bar); tma3d(st + 8192, &tm_x, kb * 64, 1, row, bar);
    };
    const int warp = __shfl_sync(0xffffffffu, tid >> 5, 0);
#define ASSIGN_WORK(s) \
    const int slot = (s), G = slot >> 4, mi = slot & 15; \
    const int tb = 4 * (G >> 1) + (mi >> 2), hp = 2 * (mi & 3) + (G & 1), wcol = (hp * 56) & ~15; \
    const int q = mi & 3, tt2 = 4 * G + (mi >> 2), c64 = 64 * q, c48 = 256 + 48 * q; \
    const int R = (ROLES >> (4 * G)) & 7; \
    const bool early = R < 3; \
    const int ech = R < 2 ? q : 4 + (mi & 1), ft = R == 2 ? mi >> 1 : 4 * (R - !early) + (mi >> 2); \
    const int pr3 = early ? ech >= 3 : q >> 1, col3 = early ? (ech - 3 * pr3) * 9 : (q & 1) * 14;

    if (warp < 8) {
        ASSIGN_WORK(get_slot())
        if (slot >= 128) {
            const uint32_t ep = ld_volatile(&sc->epoch[slot]) + 1;
            if (mi == 0 && warp > 0) {
                const int k = warp % 3;
                uint2* go = (uint2*)(sc->go + 8 * k) + lane;
                if (warp < 4 && lane < 16) st_relaxed2(go, 0, 0);
                while (ld_relaxed(k ? sc->go : sc->hint_k) != ep) __nanosleep(200);
                __nanosleep(warp * 60);
                const uint4* hint = (k ? sc->hint_u : sc->hint_h) + (k == 2 ? 48 + min(lane, 19) : lane) * 2;
                uint2 v[4];
                do {
                    #pragma unroll
                    for (int i = 0; i < 4; i++) v[i] = ld_relaxed2(hint + (k == 0 ? 64 * i : k == 2 ? 40 * i : 32 * (i & 1)));
                } while (!__all_sync(0xffffffffu, v[0].x == ep && v[1].x == ep && v[2].x == ep && v[3].x == ep));
                uint32_t t = later(later(v[0].y, v[1].y), later(v[2].y, v[3].y));
                t = later(t, __shfl_xor_sync(0xffffffffu, t, 1));
                if (k == 1) { t = later(t, __shfl_xor_sync(0xffffffffu, t, 8)); t = later(t, __shfl_xor_sync(0xffffffffu, t, 16)); }
                if (k == 0) {
                    const uint32_t now = gtime32() + 256;
                    t = now - __reduce_min_sync(0xffffffffu, now - t);
                }
                t = __shfl_sync(0xffffffffu, t, 2 * lane);
                if (lane < 16) st_relaxed2(go, ep, t);
            }
            if (mi == 1 && warp >= 4 && ld_volatile(&sc->clean) != ep) {
                for (int l = (tid - 128) / 2; l < sizeof(Tiles) / 128; l += 64) st_relaxed4((uint4*)&sc->tiles[ep & 1] + l * 8 + (lane & 7), EMPTY, EMPTY, EMPTY, EMPTY);
                named_sync(1, 128);
                if (tid == 128) st_release(&sc->clean, ep);
            }
            if (tid == 0) {
                const long long t0 = clock64();
                while (clock64() - t0 < SP_AT) {}
                #pragma unroll 1
                for (int i = 0; i < 7; i++) bulk_prefetch((const char*)wo + (i * 4 + mi) * 14336, 14336);
                uint32_t t = (uint32_t)t0 + PF0_AT;
                #pragma unroll 1
                for (int i = 0; i < PF0_N; i++) {
                    while ((int)(clock32() - t) < 0) {}
                    bulk_prefetch((const char*)w1 + i * 114688 + mi * 14336, 14336);
                    t += PF0_PACE;
                }
                if (mi) {
                    t = (uint32_t)t0 + PF1_AT;
                    #pragma unroll 1
                    for (int i = mi - 1; i < PF1_N; i += 3) {
                        while ((int)(clock32() - t) < 0) {}
                        tma5d_prefetch(&tm_w1, (i & 7) * 64, (i + 48) & 56, (i + 48) >> 6);
                        t += PF1_PACE;
                    }
                    t = (uint32_t)t0 + PF_AT;
                    #pragma unroll 1
                    for (int i = PF_OFS + mi - 1; i < PF_N; i += 3) {
                        while ((int)(clock32() - t) < 0) {}
                        bulk_prefetch((const char*)w2 + (i < 128 ? i * 16384 : i < 288 ? (i - 64 >> 1) * 65536 + (i & 1) * 16384 : (i - 224 >> 1) * 65536 + (i & 1) * 16384 + 32768), 16384);
                        t += PF_PACE;
                    }
                }
                while (ld_relaxed(sc->hint_u + 254) != ep) { __nanosleep(500); if (clock64() - t0 > WD_CLKS) __trap(); }
                sc->epoch[slot] = ep;
                if (mi == 1) sc->clean = ep + 1;
            }
            return;
        }
        {
            const int w = warp & 3, wg = warp >> 2, g = lane >> 2, t = lane & 3;
            if (WARM_AT) { const uint32_t t0 = clock32(); while (clock32() - t0 < WARM_AT) {} __syncwarp(); }
            if (w > 0) post_hint(sc->hint_o + ((2 * tb + (w >> 1)) * 32 + hp * 4 + (w & 1) * 2 + wg) * 2, 0, lane);
            if (wg == 0) {
                if (t < 2) st_relaxed4(sc->stats + tt2 * 256 + q * 64 + 16 * w + g + 8 * t, 0, 0, 0, 0);
            }
        }
        named_sync(0, 288);
        asm volatile("setmaxnreg.inc.sync.aligned.u32 224;");
        int tid; asm volatile("mov.u32 %0, %%tid.x;" : "=r"(tid));
        const int lane = tid & 31, warp = __shfl_sync(0xffffffffu, tid >> 5, 0), wg = warp >> 2;
        uint32_t ep;
        Tiles* tl;
        const int w = warp & 3, g = lane >> 2, t = lane & 3;
        const bool leader = (tid & 127) == 0;
        const uint32_t never = gridDim.y - 1;
        {
            uint32_t a[28][4];
            float accK[28], accV[28], accQ[28];
            const int lrow = 16 * w + (lane & 7) + (lane & 8);
            const uint32_t lbase = sb + wg * 8192 + lrow * 128;
            const uint32_t lx = (lane >> 4) ^ (lane & 7);
            const uint32_t wofs = hp & 1;
            auto pin2 = [&](uint32_t x0, uint32_t x1) {
                asm volatile("{\n.reg .pred p;\nsetp.ne.u32 p, %2, 0;\n@p st.shared.v2.b32 [%0], {%0,%1};\n}" :: "r"(x0), "r"(x1), "r"(never) : "memory");
            };
            float cS[2][4] = {}, cA[2][4] = {}, cB[2][4] = {}, q0, q1, p0, p1;
            auto sq = [&](float& acc, uint32_t v) { const float lo = bf_lo(v), hi = bf_hi(v); acc = fmaf(hi, hi, fmaf(lo, lo, acc)); };
            uint32_t ready = 0;
            #pragma unroll
            for (int kb = 0; kb < 8; kb++) {
                if (kb < 7) {
                    mbar_wait_unless(ready, bars + 8 * (B_FULLX + kb), 0);
                    if (kb == 0 && tid == 0) STAMP(0);
                    if (kb == 6 && tid == 0) STAMP(25);
                    if (kb == 0) FST(0); if (kb == 2) FST(1); if (kb == 4) FST(2); if (kb == 6) FST(3);
                    #pragma unroll
                    for (int s = 4 * kb; s < 4 * kb + 4; s++) ldsm4(a[s], lbase + slot_x(kb) + ((lx ^ (2 * (s & 3))) << 4));
                }
                if (kb > 0 && kb < 6) ready = mbar_test(bars + 8 * (B_FULLX + kb + 1), 0);
                if (kb == 5) named_sync(9 + wg, 160);
                if (kb == NPIPE) continue;
                const int kc = kb < NPIPE ? kb : kb - 1;
                if (kc == NSQ) { p0 = cS[0][0] + cS[1][0]; p1 = cS[0][2] + cS[1][2]; }
                #pragma unroll
                for (int s = 4 * kc; s < 4 * kc + 4; s++) {
                    mma16816(cS[s & 1], a[s][0], a[s][1], a[s][2], a[s][3], 0x3F803F80u, 0x3F803F80u);
                    if (kc < NSQ) {
                        mma1688(cA[0], a[s][0], a[s][1], a[s][0]); mma1688(cA[1], a[s][2], a[s][3], a[s][2]);
                        mma1688(cB[0], a[s][0], a[s][1], a[s][1]); mma1688(cB[1], a[s][2], a[s][3], a[s][3]);
                    }
                }
            }
            const float m0 = (cS[0][0] + cS[1][0]) * (1.f / D_), m1 = (cS[0][2] + cS[1][2]) * (1.f / D_);
            const uint32_t mm0 = pack_bf16(m0, m0), mm1 = pack_bf16(m1, m1);
            if (lane == 0) mbar_arrive(bars + 8 * B_DONEX);
            auto center = [&](int s) { sub_bf16x2(a[s][0], mm0); sub_bf16x2(a[s][1], mm1); sub_bf16x2(a[s][2], mm0); sub_bf16x2(a[s][3], mm1); };
            uint32_t Ka[8], Kb[8], Kc[8], Va[8], Vb[7], Vc[8];
            float r0, r1, ls0, ls1;
            uint32_t pm, zero;
            uint32_t* od;
            uint4* oh;
            auto kpack = [&](uint32_t (&k)[8], int j, int c, float r) {
                const uint32_t v = pack_bf16(accK[4 * j + c] * r, accK[4 * j + c + 1] * r);
                if (j == 3) { k[3] = t < 2 ? v : 0u; k[4] = t < 2 ? 0u : v; } else k[j + (j > 3)] = v;
            };
            auto batch = [&](auto c0, auto c1) {
                constexpr int n0 = c0.value, n1 = c1.value;
                wg_fence();
                static_for<n0, n1>([&](auto nc) {
                    constexpr int n = nc.value;
                    if (n == 4) { center(4); center(5); center(6); center(7); wg_fence(); }
                    const uint64_t desc = mkdesc(sb + (n < 56 ? slot_kv(n >> 3) + (n & 7) * 2048 : SM_QO + (n - 56) * 2048), 8192, 1024, 1) + wofs;
                    wgmma_rs56<1>(n < 28 ? accK : n < 56 ? accV : accQ, a[n % 28], desc, n % 28 != 0);
                });
                wg_commit();
                if (n0 > 0) wg_wait<1>();
            };
            const uint32_t hs = sb + tid * 16 + warp * 512;
            auto hand_over = [&](const uint32_t (&v)[8], int kv) {
                mbar_wait(bars + 8 * (kv ? B_DONE1 + 5 : B_DONEX), 0);
                sts4(hs + (kv ? SM_HALOV : SM_HALOK), v[0], v[1], v[2], v[3]); sts4(hs + (kv ? SM_HALOV : SM_HALOK) + 512, v[4], v[5], v[6], v[7]);
                if (w == 3) named_arrive(6 + kv, 96);
            };
            auto take_over = [&](uint32_t (&v)[8], int kv) {
                if (w == 0) mbar_wait(bars + 8 * (B_HALO + 2 * kv + wg), 0);
                const uint32_t ad = w ? hs + (kv ? SM_HALOV : SM_HALOK) - 1024 : kv ? sb + lane * 16 + wg * 1024 + SM_HALOV + 8192 : halo_kin(wg, lane);
                const uint4 u0 = lds4(ad), u1 = lds4(ad + (w || kv ? 512 : 16));
                v[0] = u0.x; v[1] = u0.y; v[2] = u0.z; v[3] = u0.w; v[4] = u1.x; v[5] = u1.y; v[6] = u1.z; v[7] = u1.w;
            };
            center(0); center(1); center(2); center(3);
            static_for<0, 7>([&](auto pc) {
                constexpr int p = pc.value;
                mbar_wait(bars + 8 * (B_FULLKV + p), 0);
                if (p == 0 && tid == 0) STAMP(26);
                if (p == 3 && tid == 0) STAMP(27);
                FST(4 + p);
                batch(Int<8 * p>(), Int<8 * p + 8>());
                if (p > 0 && leader) mbar_arrive(bars + 8 * (B_DONE1 + p - 1));
                #pragma unroll
                for (int s = 8 * p + 8; s < 8 * p + 16 && s < 28; s++) center(s);
                if (p == 1) {
                    const float c0 = bf_hi(mm0), c1 = bf_hi(mm1);
                    q0 = fmaf(c0, fmaf(c0, 64.f * NSQ, -2.f * p0), (g & 1) ? cA[0][1] + cA[1][1] : cA[0][0] + cA[1][0]) - D_ * (m0 - c0) * (m0 - c0);
                    q1 = fmaf(c1, fmaf(c1, 64.f * NSQ, -2.f * p1), (g & 1) ? cB[0][3] + cB[1][3] : cB[0][2] + cB[1][2]) - D_ * (m1 - c1) * (m1 - c1);
                    asm("" : "+f"(q0), "+f"(q1));
                    q0 = t == (g >> 1) ? q0 : 0.f; q1 = t == (g >> 1) ? q1 : 0.f;
                    pin2(__float_as_uint(q0), __float_as_uint(q1));
                }
                constexpr int PK = NSQ < 5 ? 5 : 4, NR = 28 - 4 * NSQ;
                if (p >= 2 && p < PK) {
                    #pragma unroll
                    for (int s = 4 * NSQ + NR * (p - 2) / (PK - 2); s < 4 * NSQ + NR * (p - 1) / (PK - 2); s++) { sq(q0, a[s][0]); sq(q1, a[s][1]); sq(q0, a[s][2]); sq(q1, a[s][3]); }
                    pin2(__float_as_uint(q0), __float_as_uint(q1));
                }
                if (p == PK - 1) { q0 = quad_sum(q0); q1 = quad_sum(q1); }
                if (p == PK) {
                    r0 = rsqrt_approx(fmaxf(q0 * (1.f / D_), 0.f) + LN_EPS); r1 = rsqrt_approx(fmaxf(q1 * (1.f / D_), 0.f) + LN_EPS);
                    reg_fence(accK);
                    #pragma unroll
                    for (int j = 0; j < 7; j++) kpack(Kc, j, 2, r1);
                    hand_over(Kc, 0);
                }
                if (p == PK + 1) {
                    #pragma unroll
                    for (int j = 0; j < 7; j++) kpack(Kb, j, 0, r0);
                    #pragma unroll
                    for (int j = 0; j < 8; j += 2) pin2(Kb[j], Kb[j + 1]);
                    ls0 = LOG2E_SCALE * r0; ls1 = LOG2E_SCALE * r1;
                    pm = (2 * t <= g ? 0xFFFFu : 0u) | (2 * t + 1 <= g ? 0xFFFF0000u : 0u);
                    zero = never; asm volatile("" : "+r"(zero));
                    pin2(__float_as_uint(ls0), __float_as_uint(ls1)); pin2(pm, zero);
                }
                if (p == 2) ep = get_tag();
                if (p == 6) {
                    tl = &sc->tiles[ep & 1];
                    const int tt = 2 * tb + (w >> 1);
                    od = tl->o + tt * 14336 + (7 * hp) * 256 + (2 * (2 * (w & 1) + wg)) * 32 + lane;
                    oh = sc->hint_o + (tt * 32 + hp * 4 + (w & 1) * 2 + wg) * 2 + (lane & 1);
                    pin2((uint32_t)(uint64_t)od, (uint32_t)((uint64_t)od >> 32));
                    pin2((uint32_t)(uint64_t)oh, (uint32_t)((uint64_t)oh >> 32));
                }
            });
            if (tid == 0) STAMP(1);
            FST(11);
            mbar_wait(bars + 8 * B_FQ, 0);
            batch(Int<56>(), Int<60>());
            reg_fence(accV);
            if (leader) mbar_arrive(bars + 8 * (B_DONE1 + 6));
            if (tid == 0) STAMP(2);
            FST(12);
            #pragma unroll
            for (int j = 0; j < 7; j++) Vc[j] = movtrans(pack_bf16(accV[4 * j + 2] * r1, accV[4 * j + 3] * r1));
            Vc[7] = Vc[6];
            hand_over(Vc, 1);
            batch(Int<60>(), Int<66>());
            #pragma unroll
            for (int j = 0; j < 7; j++) {
                Vb[j] = movtrans(pack_bf16(accV[4 * j] * r0, accV[4 * j + 1] * r0));
                Vc[j] |= zero;
            }
            batch(Int<66>(), Int<72>());
            #pragma unroll
            for (int j = 0; j < 7; j++) pin2(Vb[j], Vc[j]);
            mbar_wait(bars + 8 * (B_FQ + 1), 0);
            FST(13);
            if (w > 0 && lane < 2) { const uint32_t now = gtime32(); st_relaxed4(oh, ep, now, ep, now); }
            batch(Int<72>(), Int<84>());
            FST(14);
            named_sync(1 + wg, 128);
            take_over(Ka, 0);
            if (tid == 0) STAMP(3);
            wg_wait<0>();
            reg_fence(accQ);
            if (tid == 0) STAMP(4);
            FST(15);
            const bool first = (tb == 0 && w == 0);
            uint32_t pA[2], pB0[2], pB1[2], pC[2], z0[2], z1[2];
            float sA[2][4] = {}, sB[2][4] = {}, sC[2][4] = {}, e[2][4], inv[2][2];
            #pragma unroll
            for (int k = 0; k < 2; k++) {
                #pragma unroll
                for (int h = 0; h < 2; h++) {
                    const float* qq = accQ + 12 * h + 8 * k;
                    uint32_t a2 = pack_bf16(qq[4], qq[5]), a3 = pack_bf16(qq[6], qq[7]);
                    if (h == 0 && k == 1) { a2 |= zero; a3 |= zero; }
                    const uint32_t a0 = pack_bf16(qq[0], qq[1]), a1 = pack_bf16(qq[2], qq[3]);
                    mma16816(sB[h], a0, a1, a2, a3, Kb[4 * h + 2 * k], Kb[4 * h + 2 * k + 1]);
                    mma16816(sA[h], a0, a1, a2, a3, Ka[4 * h + 2 * k], Ka[4 * h + 2 * k + 1]);
                    mma16816(sC[h], a0, a1, a2, a3, Kc[4 * h + 2 * k], Kc[4 * h + 2 * k + 1]);
                }
            }
            #pragma unroll
            for (int h = 0; h < 2; h++) {
                const bool n0 = pm & 1, n1 = (int)pm < 0;
                const float l00 = n0 ? sB[h][0] : (first ? -INFINITY : sA[h][0]), l01 = n1 ? sB[h][1] : (first ? -INFINITY : sA[h][1]);
                const float l10 = n0 ? sC[h][2] : sB[h][2], l11 = n1 ? sC[h][3] : sB[h][3];
                const float x0 = -ls0 * quad_max(fmaxf(l00, l01)), x1 = -ls1 * quad_max(fmaxf(l10, l11));
                e[h][0] = ex2(fmaf(l00, ls0, x0)); e[h][1] = ex2(fmaf(l01, ls0, x0)); e[h][2] = ex2(fmaf(l10, ls1, x1)); e[h][3] = ex2(fmaf(l11, ls1, x1));
            }
            pin4(never, e[0][0], e[0][2], e[1][0], e[1][2]);
            take_over(Va, 1);
            #pragma unroll
            for (int h = 0; h < 2; h++) {
                inv[h][0] = rcp_approx(quad_sum(e[h][0] + e[h][1])); inv[h][1] = rcp_approx(quad_sum(e[h][2] + e[h][3]));
                const uint32_t P0 = pack_bf16(e[h][0], e[h][1]), P1 = pack_bf16(e[h][2], e[h][3]);
                pB0[h] = P0 & pm; pA[h] = P0 & ~pm; pC[h] = P1 & pm; pB1[h] = P1 & ~pm; z0[h] = P0 & zero; z1[h] = P1 & zero;
            }
            float o[8][4];
            #pragma unroll
            for (int j = 0; j < 8; j++) {
                o[j][0] = o[j][1] = o[j][2] = o[j][3] = 0.f;
                mma16816(o[j], pB0[j >> 2], pB1[j >> 2], z0[j >> 2], pC[j >> 2], Vb[j - (j >> 2)], Vc[j - (j >> 2)]);
            }
            if (tid == 0) STAMP(12);
            FST(16);
            if (tid == 0) STAMP(16);
            #pragma unroll
            for (int j = 0; j < 8; j++) mma1688(o[j], pA[j >> 2], z1[j >> 2], Va[j - (j >> 2)]);
            #pragma unroll
            for (int j = 0; j < 7; j++) {
                float v[4];
                #pragma unroll
                for (int c = 0; c < 4; c++) {
                    v[c] = j < 3 ? o[j][c] : j > 3 ? o[j + 1][c] : (t < 2 ? o[3][c] : o[4][c]);
                    v[c] *= j < 3 ? inv[0][c >> 1] : j > 3 ? inv[1][c >> 1] : (t < 2 ? inv[0][c >> 1] : inv[1][c >> 1]);
                }
                od[j * 256] = pack_bf16(v[0], v[1]);
                od[j * 256 + 32] = pack_bf16(v[2], v[3]);
            }
            if (lane == 0) mbar_arrive(bars + 8 * B_DONEQ);
            if (tid == 0) STAMP(5);
            FST(17);
        }
        const int z = get_tag() - ep, slot1 = slot + z, tid1 = tid + z, warp1 = warp + z;
        ep += z;
        {
        ASSIGN_WORK(slot1)
        const int tid = tid1, lane = tid & 31, wg = warp1 >> 2, w = warp1 & 3, g = lane >> 2, t = lane & 3;
        tl = &sc->tiles[ep & 1];
        const uint32_t live = wg ^ 1;
        uint32_t rb0, rb1, late[14];
        const unsigned short* pb = (const unsigned short*)(live ? b2 + tt2 * 64 : b1 + ft * 64) + 16 * w + g;
        auto stage_late = [&]() {
            #pragma unroll
            for (int c = 0; c < 14; c++) asm volatile("st.shared.u32 [%0], %1;" :: "r"(sb + SM_H + wg * 8192 + (tid & 127) * 4 + c * 512), "r"(late[c]) : "memory");
            fence_async_smem();
            named_sync(1 + wg, 128);
        };
        auto store_late = [&](bool on, uint32_t* p) {
            #pragma unroll
            for (int c = 0; c < 4; c++)
                if (elect() && on && (c < 3 || w < 2)) bulk_st(p + (4 * c + w) * 256, sb + SM_H + wg * 8192 + (4 * c + w) * 512, 512);
            asm volatile("cp.async.bulk.commit_group;" ::: "memory");
        };
        if (live) {
            float acc[56];
            const int hrow = 32 * (w >> 1) + 2 * ((lane & 7) + (lane & 8)) + (w & 1);
            const uint32_t ha = sb + SM_H + hrow * 128 + (((lane >> 4) ^ (hrow & 7)) << 4);
            uint4* sp = sc->stats + tt2 * 256 + 16 * w + g + 8 * (t & 1);
            uint4* sp_out = sp + q * 64;
            const uint4* sp_in = sp + (t & 2) * 64;
            uint32_t* hd = tl->hn + ((q >> 1) * 32 + (tt2 >> 1)) * 7168 + (q & 1) * 3584 + (tt2 & 1) * 128 + w * 32 + lane;
            pin_ptr(never, sp_out); pin_ptr(never, sp_in); pin_ptr(never, hd);
            float s0 = 0.f, s1 = 0.f, q0 = 0.f, q1 = 0.f, s2 = 0.f, s3 = 0.f, q2 = 0.f, q3 = 0.f;
            auto sums = [&](int j0, int j1) {
                #pragma unroll
                for (int j = j0; j < j1; j++) {
                    s0 += acc[4 * j]; s2 += acc[4 * j + 1]; q0 = fmaf(acc[4 * j], acc[4 * j], q0); q2 = fmaf(acc[4 * j + 1], acc[4 * j + 1], q2);
                    s1 += acc[4 * j + 2]; s3 += acc[4 * j + 3]; q1 = fmaf(acc[4 * j + 2], acc[4 * j + 2], q1); q3 = fmaf(acc[4 * j + 3], acc[4 * j + 3], q3);
                }
            };
            {
                mbar_wait(bars + 8 * B_FULLWO, 0);
                #pragma unroll
                for (int jp = 0; jp < 7; jp++) {
                    uint32_t xx[4];
                    ldsm4(xx, hcol(ha, jp));
                    #pragma unroll
                    for (int r = 0; r < 4; r++) { acc[8 * jp + 2 * r] = bf_lo(xx[r]); acc[8 * jp + 2 * r + 1] = bf_hi(xx[r]); }
                }
                reg_fence(acc);
                named_sync(12, 256);
                spin_mma(bars + 8 * B_FULLX, never);
                auto od_ = [&](int s) { return mkdesc(sb + SM_QO + s * 2048, 1024, 128, 0); };
                auto wd_ = [&](int s) { return mkdesc(sb + slot_wo(s >> 2) + (s & 3) * 2048, 8192, 1024, 1); };
                float accl[32], accr[24];
                #pragma unroll
                for (int i = 0; i < 5; i++) {
                    if (i < 4) mbar_wait(bars + 8 * (B_FULLO + i), 0);
                    if (i == 0 && tid == 0) STAMP(7);
                    if (i == 1) { rb0 = ld_u16(pb); rb1 = ld_u16(pb + 8); }
                    wg_fence();
                    #pragma unroll
                    for (int ss = i ? 0 : 4; ss < 8; ss++) {
                        if (i < 3) wgmma_ss112<0, 1>(acc, od_(8 * i - 4 + ss), wd_(8 * i - 4 + ss));
                        else if (i == 4) wgmma_ss64<0, 1>(accl, od_(20 + ss), wd_(20 + ss));
                        else if (ss == 0) wgmma_ss48<0, 1, 0>(accr, od_(20), wd_(20) + 512);
                        else wgmma_ss48<0, 1>(accr, od_(20 + ss), wd_(20 + ss) + 512);
                    }
                    wg_commit();
                    if (i > 0) {
                        wg_wait<1>();
                        if (i == 3) {
                            reg_fence(acc);
                            #pragma unroll
                            for (int c = 0; c < 32; c++) accl[c] = __uint_as_float(__float_as_uint(acc[c]) | never);
                            reg_fence(accl);
                        }
                        if (i < 4 && leader) mbar_arrive(bars + 8 * (B_DONEO + i - 1));
                    }
                }
                reg_fence(accr);
                #pragma unroll
                for (int c = 0; c < 24; c++) acc[32 + c] += accr[c];
                sums(8, 14);
                pin4(never, s0, s1, s2, s3); pin4(never, q0, q1, q2, q3);
                wg_wait<0>();
                reg_fence(accl);
                #pragma unroll
                for (int c = 0; c < 32; c++) acc[c] = accl[c];
                if (leader) mbar_arrive(bars + 8 * (B_DONEO + 3));
                if (tid == 0) STAMP(8);
            }
            sums(0, 8);
            s0 += s2; s1 += s3; q0 += q2; q1 += q3;
            float sr = ((t & 1) ? s1 : s0) + __shfl_xor_sync(0xffffffffu, (t & 1) ? s0 : s1, 1), qr = ((t & 1) ? q1 : q0) + __shfl_xor_sync(0xffffffffu, (t & 1) ? q0 : q1, 1);
            sr += __shfl_xor_sync(0xffffffffu, sr, 2); qr += __shfl_xor_sync(0xffffffffu, qr, 2);
            st_relaxed4_if(t < 2, sp_out, __float_as_uint(sr), __float_as_uint(qr), ep);
            named_arrive(5, 256);
            if (tid == 0) STAMP(9);
            #pragma unroll
            for (int jp = 0; jp < 7; jp++)
                stsm4(hcol(ha, jp), pack_bf16(acc[8 * jp], acc[8 * jp + 1]), pack_bf16(acc[8 * jp + 2], acc[8 * jp + 3]),
                      pack_bf16(acc[8 * jp + 4], acc[8 * jp + 5]), pack_bf16(acc[8 * jp + 6], acc[8 * jp + 7]));
            uint4 v0, v1;
            do { v0 = ld_relaxed4(sp_in); v1 = ld_relaxed4(sp_in + 64); } while (__any_sync(0xffffffffu, v0.w != ep || v1.w != ep));
            if (tid == 0) STAMP(10);
            sr = __uint_as_float(v0.x) + __uint_as_float(v1.x); qr = __uint_as_float(v0.y) + __uint_as_float(v1.y);
            sr += __shfl_xor_sync(0xffffffffu, sr, 2); qr += __shfl_xor_sync(0xffffffffu, qr, 2);
            const float m = sr * (1.f / D_), var = fmaxf(qr * (1.f / D_) - m * m, 0.f);
            const float r = rsqrt_approx(fmaf(var, 4.f + 4.f * LN_EPS, 4.f * LN_EPS * LN_EPS)), c = -m * r;
            const float r0 = __shfl_sync(0xffffffffu, r, lane & ~1), c0 = __shfl_sync(0xffffffffu, c, lane & ~1);
            const float r1 = __shfl_sync(0xffffffffu, r, lane | 1), c1 = __shfl_sync(0xffffffffu, c, lane | 1);
            #pragma unroll
            for (int j = 0; j < 14; j++) st_global_if(1, hd + j * 256, pack_bf16(fmaf(acc[4 * j], r0, c0), fmaf(acc[4 * j + 1], r0, c0)));
            if (never) mbar_arrive(bars);
            #pragma unroll
            for (int j = 0; j < 14; j++) late[j] = pack_bf16(fmaf(acc[4 * j + 2], r1, c1), fmaf(acc[4 * j + 3], r1, c1));
            if (tid == 0) STAMP(11);
        } else {
            named_arrive(12, 256);
            check_tiles<0>(w, 4, 4, tl->o + tt2 * 14336, false, lane, true);
            rb0 = ld_u16(pb); rb1 = ld_u16(pb + 8);
            auto reset_tiles = [&](int v, int i0, int i1) {
                const int l = slot * 48 + v * 16 + lane / 2;
                #pragma unroll
                for (int i = i0; i < i1; i++)
                    st_relaxed4_if(i < 6 || l < sizeof(Tiles) / 128 - 6 * 6144, (uint4*)&sc->tiles[~ep & 1] + (i * 6144 + l) * 8 + (lane & 7), EMPTY, EMPTY, EMPTY);
            };
            if (CL_N && w < 3) { mbar_wait(bars + 8 * (B_DONEO + CL_P2), 0); reset_tiles(w, 0, CL_N); }
            named_sync(5, 256);
            auto phase3 = [&](auto nc) {
                constexpr int NC = nc.value;
                float acc[4 * NC];
                uint32_t* ud = tl->u + (pr3 * 28 + (ft >> 1) + (NC == 14 ? 4 : 0)) * 7168 + col3 * 256 + (ft & 1) * 128 + w * 32 + lane;
                #pragma unroll
                for (int j = 0; j < 4 * NC; j++) acc[j] = 0.5f * bf_lo((j & 2) ? rb1 : rb0);
                #pragma unroll 1
                for (uint32_t pass = never; pass < 2; pass++) {
                    if (pass) {
                        mix_mainloop<32>(TSVAL acc, leader);
                        if (leader) STAMP(14);
                    }
                    uint32_t pk[NC];
                    #pragma unroll
                    for (int j = 0; j < NC; j++) {
                        const float k = j < GDEP ? GELU_K1 : __uint_as_float(__float_as_uint(GELU_K1) | (pk[j - GDEP] & never));
                        pk[j] = pack_bf16(gelu_half(acc[4 * j], k), gelu_half(acc[4 * j + 1], k));
                        st_global_if(pass, ud + j * 256, pk[j]);
                    }
                }
                if (leader) STAMP(15);
                #pragma unroll
                for (int j = 0; j < NC; j++) late[j] = pack_bf16(gelu_half(acc[4 * j + 2], GELU_K1), gelu_half(acc[4 * j + 3], GELU_K1));
                if (NC == 14) {
                    stage_late();
                    mbar_wait(bars + 8 * (B_FULLB + LATE_AT4), 1);
                    store_late(true, tl->u + (pr3 * 28 + (ft >> 1) + 14) * 7168 + col3 * 256 + (ft & 1) * 128);
                } else {
                    #pragma unroll
                    for (int c = 0; c < NC; c++) st_global_if(1, ud + 4 * 7168 + c * 256, late[c]);
                }
            };
            if (early) phase3(Int<10>()); else phase3(Int<14>());
            if (w) {
                if (early && w == 1) fetch_times(TSVAL sc->go, 1, ep, lane);
                if (CL_N < 7) { mbar_wait(bars + 8 * (B_DONE + CL_AT), 1); reset_tiles(w - 1, CL_N, 7); }
            }
            if (leader) mbar_wait_wd(bars + 8 * B_END, 0);
            return;
        }
        {
            float acc[56];
            const uint32_t ad = sb + SM_H + (16 * w + (lane & 15)) * 128 + (((lane >> 4) ^ (lane & 7)) << 4);
            const float bb0 = bf_lo(rb0), bb1 = bf_lo(rb1);
            named_sync(1, 128);
            #pragma unroll
            for (int jp = 0; jp < 7; jp++) {
                uint32_t hh[4];
                ldsm4(hh, hcol(ad, jp));
                #pragma unroll
                for (int r = 0; r < 4; r++) { acc[8 * jp + 2 * r] = bf_lo(hh[r]) + ((r & 1) ? bb1 : bb0); acc[8 * jp + 2 * r + 1] = bf_hi(hh[r]) + ((r & 1) ? bb1 : bb0); }
            }
            named_sync(1, 128);
            stage_late();
            if (tid == 0) STAMP(39);
            reg_fence(acc);
            spin_mma(bars + 8 * (B_FULLX + 1), never);
            mbar_wait(bars + 8 * (B_FULLB + LATE_AT), 0);
            store_late(true, tl->hn + ((q >> 1) * 32 + 16 + (tt2 >> 1)) * 7168 + (q & 1) * 3584 + (tt2 & 1) * 128);
            check_tiles<1>(CH_H + w, 4, 32, tl->hn + pr3 * 32 * 7168 + col3 * 256, early, lane, false);
            mbar_wait(bars + 8 * (B_DONE + START4), 0);
            mix_mainloop<28>(TSVAL acc, leader);
            if (leader) mbar_arrive(bars + 8 * B_END);
            if (tid == 0) STAMP(18);
            #pragma unroll
            for (int jp = 0; jp < 7; jp++)
                stsm4(hcol(ad, jp), pack_bf16(acc[8 * jp], acc[8 * jp + 1]), pack_bf16(acc[8 * jp + 2], acc[8 * jp + 3]),
                         pack_bf16(acc[8 * jp + 4], acc[8 * jp + 5]), pack_bf16(acc[8 * jp + 6], acc[8 * jp + 7]));
            fence_async_smem();
            __syncwarp();
            if (elect()) {
                tma2d_store(&tm_out64, c64, tt2 * 64 + 16 * w, sb + SM_H + w * 2048);
                tma2d_store(&tm_out48, c48, tt2 * 64 + 16 * w, sb + SM_H + 8192 + w * 2048);
            }
            asm volatile("cp.async.bulk.commit_group;" ::: "memory");
            asm volatile("cp.async.bulk.wait_group.read 0;" ::: "memory");
            if (tid == 0) { sc->epoch[slot] = ep; STAMP(19); }
        }
        }
    } else {
        asm volatile("setmaxnreg.dec.sync.aligned.u32 56;");
        int warp2; asm("mov.u32 %0, %1;" : "=r"(warp2) : "r"(warp));
        if (warp2 > 8) {
            ASSIGN_WORK(get_slot())
            if (slot >= 128) return;
            uint32_t ep, cl;
            uint4* const oh = sc->hint_o + (2 * tb * 32 + hp * 4) * 2 + (lane & 3);
            if (warp == 11) ep = ld_volatile(&sc->epoch[slot]) + 1;
            if (elect()) {
                #pragma unroll
                for (int i = 0; i < 33; i++) mbar_init(bars + 8 * (B_DONEO + i) + (warp - 9) * 264, 1);
                if (warp == 11) {
                    #pragma unroll
                    for (int i = B_DONE1; i < B_DONEO; i++) mbar_init(bars + 8 * i, i < B_DONEX ? 2 : i == B_DONEX ? 8 : 9);
                } else {
                    #pragma unroll
                    for (int i = 0; i < 32; i++) mbar_init(sb + SM_RAW + 8 * i + (warp - 9) * 256, 1);
                }
                asm volatile("fence.mbarrier_init.release.cluster;" ::: "memory");
            }
            __syncwarp();
            if (warp < 11) mbar_expect(sb + SM_RAW + 8 * (tid - 288), tid == 288 ? 8192 : tid < 292 ? 16384 : early && tid < 324 ? 10240 : 14336);
            uint4* const hu = sc->hint_u + (early ? ech * 8 + ft : 40 + q * 20 + ft) * 2;
            if (warp == 10) {
                post_hint(sc->hint_h + (q * 32 + tt2) * 2, 0, lane);
                post_hint(hu, 0, lane);
            }
            if (warp == 11) {
                post_hint(sc->hint_k + (tb * 8 + hp) * 2, 0, lane);
                if (lane < (tb < 15 ? 4 : 0)) st_relaxed4(oh + 128, 0, 0, 0, 0);
                if (lane < (tb ? 0 : 4)) st_relaxed4(oh, 0, 0, 0, 0);
                cl = ld_acquire(&sc->clean);
            }
            named_sync(8, 128);
            if (warp == 9) { named_arrive(4, 64); named_arrive(9, 160); named_arrive(10, 160); }
            if (warp < 11) {
                ep = get_tag();
                mbar_wait(bars + 8 * (B_DONE1 + HALO_AT), 0);
                #pragma unroll 1
                for (int kv = 0; kv < 2; kv++) {
                    uint4 v0 = {}, v1 = {}, v2 = {};
                    if (tb > 0) {
                        const uint4* hg = sc->halo + ((((tb - 1) * 8 + hp) * 2 + warp - 9) * 2 + kv) * 96 + lane;
                        if (kv == 0) while (ld_relaxed(sc->hint_k + ((tb - 1) * 8 + hp) * 2) != ep) {}
                        do { v0 = ld_relaxed4(hg); v1 = ld_relaxed4(hg + 32); v2 = ld_relaxed4(hg + 64); } while (!__all_sync(0xffffffffu, v0.w == ep && v1.w == ep && v2.w == ep));
                    }
                    if (kv) mbar_wait(bars + 8 * (B_DONE1 + 5), 0);
                    const uint32_t hs = kv ? sb + lane * 16 + (warp - 9) * 1024 + SM_HALOV + 8192 : halo_kin(warp - 9, lane);
                    sts4(hs, v0.x, v0.y, v0.z, v1.x); sts4(hs + (kv ? 512 : 16), v1.y, v1.z, v2.x, v2.y);
                    __syncwarp();
                    if (lane == 0) mbar_arrive(bars + 8 * (B_HALO + 2 * kv + warp - 9));
                }
                if (tid == 288) STAMP(21);
            } else {
                const long long t0 = clock64();
                while (__any_sync(0xffffffffu, (int)(cl - ep) < 0)) { cl = ld_acquire(&sc->clean); if (clock64() - t0 > WD_CLKS) __trap(); }
                if (lane == 0) { *(volatile uint32_t*)(smem_raw + SM_TAG) = ep; mbar_arrive(bars + 8 * B_CLR); }
                uint4* hg = sc->halo + (tb * 8 + hp) * 384 + lane;
                #pragma unroll 1
                for (int kv = 0; kv < 2; kv++) {
                    const uint32_t hs = sb + lane * 16 + 3072 + (kv ? SM_HALOV : SM_HALOK);
                    named_sync(6 + kv, 96);
                    #pragma unroll
                    for (int p = 0; p < 2; p++) {
                        const uint4 u0 = lds4(hs + p * 4096), u1 = lds4(hs + p * 4096 + 512);
                        st_relaxed4(hg + p * 192, u0.x, u0.y, u0.z, ep); st_relaxed4(hg + p * 192 + 32, u0.w, u1.x, u1.y, ep); st_relaxed4(hg + p * 192 + 64, u1.z, u1.w, ep, ep);
                    }
                    hg += 96;
                    if (kv == 0) {
                        post_hint(sc->hint_k + (tb * 8 + hp) * 2, ep, lane);
                        #pragma unroll
                        for (int j = 0; j < 6; j++) st_relaxed4(hg + j * 32 + (j / 3) * 96, 0, 0, 0, 0);
                    }
                }
                const uint32_t now = gtime32() - LATE_O;
                if (lane < (tb < 15 ? 4 : 0)) st_relaxed4(oh + 128, ep, now, ep, now);
                if (lane < (tb ? 0 : 4)) st_relaxed4(oh, ep, now, ep, now);
                if (lane == 0) STAMP(23);
                if (lane == 0) mbar_arrive(bars + 8 * B_DONEQ);
            }
            if (warp > 9) {
                const Tiles* const tl = &sc->tiles[ep & 1];
                check_tiles<1>(11 - warp, 2, CH_H, tl->hn + pr3 * 32 * 7168 + col3 * 256, early, lane, true);
                if (warp == 10) {
                    mbar_wait(bars + 8 * (B_DONE + (early ? HINT_E : HINT_U)), 0);
                    post_time(hu, ep, lane);
                }
                if (warp == 11) {
                    mbar_wait(bars + 8 * (B_DONE + (early ? POLL_E : POLL_N)), 0);
                    fetch_times(TSVAL sc->go, 0, ep, lane);
                }
                check_tiles<2>(11 - warp, 2, 28, tl->u + (q >> 1) * 28 * 7168 + (q & 1) * 3584, false, lane, true);
            } else {
                int aslot = 0;
                if (lane == 0) { prefetch_map(&tm_out64); prefetch_map(&tm_out48); }
                #pragma unroll
                for (int i = 0; i < HINT_F; i++) mbar_wait(bars + 8 * (B_FULLO + i), 0);
                post_time(sc->hint_h + (q * 32 + tt2) * 2, ep, lane);
                #pragma unroll 1
                for (int i = 0; i < 30; i++) {
                    if (i == POLL_I && !early) fetch_times(TSVAL sc->go, 1, ep, lane);
                    int d = 2 * i - 11 + (i >= A4_FROM ? A4_DLY : 0);
                    if (early) d = i < 16 ? 1 + (i - NA_SLOTS) * AE_END / 9 : max(d, AE_W2);
                    mbar_wait(bars + 8 * (i < NA_SLOTS ? B_DONEQ + ((A_SCHED >> (4 * i)) & 15) : B_DONE + (d & 31)), d >= 32);
                    if (elect()) {
                        const uint32_t bar = bars + 8 * (B_FULLA + (i & 15)), dst = sb + SM_ARING + aslot * 16384;
                        mbar_expect(bar, 16384);
                        if (i < 16) tma5d(dst, &tm_w1, ft * 64, (i & 7) * 8, i >> 3, bar);
                        else tma5d(dst, &tm_w2, tt2 * 64, 8 * (i < 20 ? i & 1 : i < 25 ? i - 18 : i - 23), i < 20 ? (i >> 1) & 1 : i >= 25, bar);
                    }
                    aslot = aslot == NA_SLOTS - 1 ? 0 : aslot + 1;
                }
            }
        } else {
            const int slot0 = get_slot(), row0 = (slot0 >> 5) * 256 + (slot0 & 12) * 16;
            if (elect()) {
                prefetch_map(&tm_x);
                #pragma unroll
                for (int i = 0; i < 7; i++) mbar_init(bars + 8 * i, 1);
                asm volatile("fence.mbarrier_init.release.cluster;" ::: "memory");
            }
            named_arrive(0, 288);
            if (elect()) {
                #pragma unroll 1
                for (int kb = 0; kb < 7; kb++) {
                    load_x(kb, row0);
                    if (kb == 0) STAMP(22);
                }
                #pragma unroll
                for (int i = 7; i < B_DONE1; i++) mbar_init(bars + 8 * i, 1);
                asm volatile("fence.mbarrier_init.release.cluster;" ::: "memory");
            }
            named_arrive(8, 128);
            ASSIGN_WORK(get_slot())
            if (slot >= 128) return;
            #pragma unroll 1
            for (int kb = 0; kb < 7; kb++) {
                if (kb == 6) { named_sync(4, 64); mbar_wait(bars + 8 * B_DONEX, 0); }
                if (elect()) {
                    const uint32_t st = sb + slot_kv(kb), bar = bars + 8 * (B_FULLKV + kb);
                    mbar_expect(bar, 16384);
                    #pragma unroll
                    for (int i = 0; i < 2; i++) {
                        const int n = 2 * kb + (i ^ (G & 1));
                        tma2d(st + (n & 1) * 8192, &tm_wqkv, (n < 7 ? 448 : 896) + wcol, (n < 7 ? n : n - 7) * 64, bar);
                    }
                }
            }
            if (elect()) {
                mbar_expect(bars + 8 * B_FQ, 32768);
                mbar_expect(bars + 8 * (B_FQ + 1), 24576);
                #pragma unroll 1
                for (int i = 0; i < 7; i++) { const int j = i == 6 ? i : i ^ (G & 1); tma2d(sb + SM_QO + j * 8192, &tm_wqkv, wcol, j * 64, bars + 8 * (B_FQ + (i >> 2))); }
                mbar_expect(bars + 8 * B_FULLWO, 512 * 112 * 2);
            }
            #pragma unroll 1
            for (int i = 0; i < 7; i++) {
                if (i == PFC_AT && elect()) {
                    #pragma unroll 1
                    for (int k = NA_SLOTS + (early ? ech : q); k < (early ? PFC_E : PFC_N); k += early ? 6 : 4) tma5d_prefetch(&tm_w1, ft * 64, (k & 7) * 8, k >> 3);
                }
                if (i == PFW_AT && elect()) {
                    #pragma unroll 1
                    for (int k = PFW_0 + q; k < PFW_N; k += 4) tma5d_prefetch(&tm_w2, tt2 * 64, 8 * (k < 4 ? k & 1 : k < 9 ? k - 2 : k - 7), k < 4 ? k >> 1 : k >= 9);
                }
                const int kb = ((q & 1 ? WO_ORD1 : WO_ORD0) >> (4 * i)) & 7;
                if (kb < 5) mbar_wait(bars + 8 * (B_DONE1 + kb), 0);
                if (elect()) {
                    tma2d(sb + slot_wo(kb), &tm_wo64, c64, kb * 64, bars + 8 * B_FULLWO);
                    tma2d(sb + slot_wo(kb) + 8192, &tm_wo48, c48, kb * 64, bars + 8 * B_FULLWO);
                }
            }
            if (elect()) {
                tma2d(sb + SM_H, &tm_xr64, c64, tt2 * 64, bars + 8 * B_FULLWO);
                tma2d(sb + SM_H + 8192, &tm_xr48, c48, tt2 * 64, bars + 8 * B_FULLWO);
            }
            if (smem_u32(smem_raw) != SB) __trap();
            const uint32_t ep = get_tag();
            const Tiles* const tl = &sc->tiles[ep & 1];
            mbar_wait(bars + 8 * (B_DONE1 + 6), 0);
            const uint32_t t_o = last_hint(TSVAL sc->hint_o + (tt2 * 32 + lane) * 2, ep, 38);
            mbar_wait(bars + 8 * B_DONEQ, 0);
            wait_until(t_o + GO_O);
            if (elect()) {
                #pragma unroll
                for (int i = 0; i < 4; i++) {
                    bulk_ld(sb + SM_QO + max(2 * i - 1, 0) * 8192, tl->o + tt2 * 14336 + max(2 * i - 1, 0) * 2048, i ? 16384 : 8192, sb + SM_RAW + 8 * i);
                }
            }
            if (lane == 0) STAMP(20);
            wait_until(t_o + GO_O + STOP2);
            if (lane == 0) mbar_arrive(bars + 8 * B_FULLX);
            mbar_wait(bars + 8 * (B_DONEO + POLL_H), 0);
            const uint32_t* src = tl->hn + pr3 * 32 * 7168 + col3 * 256;
            uint32_t bytes = early ? 10240 : 14336, dst = sb + SM_BRING, top = dst + (early ? NE_SLOTS * 10240 : NB_SLOTS * 14336), raw = sb + SM_RAW + 32;
            auto issue = [&]() {
                if (elect()) bulk_ld(dst, src, bytes, raw);
                src += 7168; raw += 8; dst += bytes;
                if (dst == top) dst = sb + SM_BRING;
            };
            const uint32_t t_h = last_hint(TSVAL sc->go, ep, 42);
            mbar_wait(bars + 8 * (B_DONEO + 3), 0);
            wait_until(t_h + GO_H);
            STAMP(29);
            #pragma unroll 1
            do {
                issue();
                if (raw == sb + SM_RAW + 40 + 8 * STOP3 && lane == 0) mbar_arrive(bars + 8 * (B_FULLX + 1));
            } while (dst != sb + SM_BRING);
            uint32_t done = bars + 8 * B_DONE;
            #pragma unroll 1
            do { mbar_wait(done, 0); done += 8; issue(); } while (raw != sb + SM_RAW + 288);
            if (early) mbar_wait(bars + 8 * (B_DONE + 31), 0);
            src = tl->u + (q >> 1) * 28 * 7168 + (q & 1) * 3584; bytes = 14336; dst = sb + SM_BRING; top = dst + NB_SLOTS * 14336;
            done = bars + 8 * (B_DONE + 24);
            #pragma unroll 1
            for (uint32_t par = 0; par < 2; par++) {
                mbar_wait(bars + 8 * (B_GO + par), 0);
                const uint32_t ts = *(volatile uint32_t*)(smem_raw + SM_TIME + 128 * par + 4 * lane);
                if (par) done = bars + 8 * B_DONE;
                uint32_t bit = 1, wait = ~1u;
                wait_until(__shfl_sync(0xffffffffu, ts, 0));
                #pragma unroll 1
                do {
                    while (wait & bit) wait = __ballot_sync(0xffffffffu, (int)(gtime32() - ts) < 0);
                    if (bit == 1) STAMP(par ? 36 : 30);
                    mbar_wait(done, par); done += 8;
                    issue();
                    bit *= 2;
                } while (bit != (par ? 1 << 20 : 1 << 8));
            }
        }
    }
}

typedef CUresult (*EncodeFn)(CUtensorMap*, CUtensorMapDataType, cuuint32_t, void*, const cuuint64_t*, const cuuint64_t*, const cuuint32_t*,
                             const cuuint32_t*, CUtensorMapInterleave, CUtensorMapSwizzle, CUtensorMapL2promotion, CUtensorMapFloatOOBfill);

void make_map(EncodeFn fn, CUtensorMap* tm, const void* ptr, int rank, const cuuint64_t* dims, const cuuint64_t* strides, const cuuint32_t* box, CUtensorMapSwizzle sw) {
    cuuint32_t es[5] = {1, 1, 1, 1, 1};
    fn(tm, CU_TENSOR_MAP_DATA_TYPE_BFLOAT16, rank, const_cast<void*>(ptr), dims, strides, box, es, CU_TENSOR_MAP_INTERLEAVE_NONE, sw,
       CU_TENSOR_MAP_L2_PROMOTION_NONE, CU_TENSOR_MAP_FLOAT_OOB_FILL_NONE);
}

}

extern "C" void kernel_launch(void* const* d_in, const int* in_sizes, int n_in, void* d_out, int out_size) {
    const __nv_bfloat16* x = (const __nv_bfloat16*)d_in[0];
    const __nv_bfloat16* wqkv = (const __nv_bfloat16*)d_in[1];
    const __nv_bfloat16* wo = (const __nv_bfloat16*)d_in[2];
    const __nv_bfloat16* w1 = (const __nv_bfloat16*)d_in[4];
    const __nv_bfloat16* b1 = (const __nv_bfloat16*)d_in[5];
    const __nv_bfloat16* w2 = (const __nv_bfloat16*)d_in[6];
    const __nv_bfloat16* b2 = (const __nv_bfloat16*)d_in[7];

    void* fnp = nullptr; cudaDriverEntryPointQueryResult qr;
    cudaGetDriverEntryPoint("cuTensorMapEncodeTiled", &fnp, cudaEnableDefault, &qr);
    EncodeFn fn = (EncodeFn)fnp;
    CUtensorMap tx, twqkv, two64, two48, tw1, tw2, txr64, txr48, tout64, tout48;
    { cuuint64_t d[3] = {448, 2, 1024}, s[2] = {896, 1792}; cuuint32_t b[3] = {64, 1, 64}; make_map(fn, &tx, x, 3, d, s, b, CU_TENSOR_MAP_SWIZZLE_128B); }
    { cuuint64_t d[2] = {1344, 448}, s[1] = {2688}; cuuint32_t b[2] = {64, 64}; make_map(fn, &twqkv, wqkv, 2, d, s, b, CU_TENSOR_MAP_SWIZZLE_128B); }
    { cuuint64_t d[2] = {448, 448}, s[1] = {896}; cuuint32_t b[2] = {64, 64}; make_map(fn, &two64, wo, 2, d, s, b, CU_TENSOR_MAP_SWIZZLE_128B); }
    { cuuint64_t d[2] = {448, 448}, s[1] = {896}; cuuint32_t b[2] = {48, 64}; make_map(fn, &two48, wo, 2, d, s, b, CU_TENSOR_MAP_SWIZZLE_128B); }
    { cuuint64_t d[5] = {1792, 8, 2, 64, 2}, s[4] = {2 * 3584, 3584, 32 * 3584, 16 * 3584}; cuuint32_t b[5] = {64, 8, 2, 8, 1}; make_map(fn, &tw1, w1, 5, d, s, b, CU_TENSOR_MAP_SWIZZLE_128B); }
    { cuuint64_t d[5] = {2048, 8, 2, 56, 2}, s[4] = {4096, 16 * 4096, 32 * 4096, 8 * 4096}; cuuint32_t b[5] = {64, 8, 2, 8, 1}; make_map(fn, &tw2, w2, 5, d, s, b, CU_TENSOR_MAP_SWIZZLE_128B); }
    { cuuint64_t d[2] = {448, 2048}, s[1] = {896}; cuuint32_t b[2] = {64, 64}; make_map(fn, &txr64, x, 2, d, s, b, CU_TENSOR_MAP_SWIZZLE_128B); }
    { cuuint64_t d[2] = {448, 2048}, s[1] = {896}; cuuint32_t b[2] = {48, 64}; make_map(fn, &txr48, x, 2, d, s, b, CU_TENSOR_MAP_SWIZZLE_128B); }
    { cuuint64_t d[2] = {448, 2048}, s[1] = {896}; cuuint32_t b[2] = {64, 16}; make_map(fn, &tout64, d_out, 2, d, s, b, CU_TENSOR_MAP_SWIZZLE_128B); }
    { cuuint64_t d[2] = {448, 2048}, s[1] = {896}; cuuint32_t b[2] = {48, 16}; make_map(fn, &tout48, d_out, 2, d, s, b, CU_TENSOR_MAP_SWIZZLE_128B); }

    void* scv = nullptr;
    cudaGetSymbolAddress(&scv, g_scratch);
    Scratch* scp = (Scratch*)scv;
    int dev = 0, sms = 0;
    cudaGetDevice(&dev);
    cudaDeviceGetAttribute(&sms, cudaDevAttrMultiProcessorCount, dev);
    if (sms == 132) {
        cudaFuncSetAttribute(fused_kernel<true>, cudaFuncAttributeMaxDynamicSharedMemorySize, SM_TOTAL);
        fused_kernel<true><<<132, 384, SM_TOTAL>>>(scp, wo, w1, b1, w2, b2, tx, twqkv, two64, two48, tw1, tw2, txr64, txr48, tout64, tout48);
    } else {
        cudaFuncSetAttribute(fused_kernel<false>, cudaFuncAttributeMaxDynamicSharedMemorySize, SM_TOTAL);
        fused_kernel<false><<<132, 384, SM_TOTAL>>>(scp, wo, w1, b1, w2, b2, tx, twqkv, two64, two48, tw1, tw2, txr64, txr48, tout64, tout48);
    }
}
```
